```python
import torch

def _softmax(x, axis=-1):
    return torch.softmax(x, dim=axis)

def _gelu(x):
    return torch.nn.functional.gelu(x, approximate='tanh')

def _silu(x):
    return torch.nn.functional.silu(x)

def _sigmoid(x):
    return torch.sigmoid(x)

def _layernorm(x, axis=-1, eps=1e-05):
    m = x.mean(dim=axis, keepdim=True)
    v = x.var(dim=axis, keepdim=True, unbiased=False)
    return (x - m) / torch.sqrt(v + eps)

def _scatter_add(tgt, idx, src, axis=0):
    return tgt.clone().index_add_(axis, idx, src)

def _segment_sum(src, seg, n):
    out = torch.zeros((n,) + src.shape[1:], dtype=src.dtype)
    return out.index_add_(0, seg, src)

def _pad(x, pw):
    flat = tuple((v for pair in reversed(pw) for v in pair))
    return torch.nn.functional.pad(x, flat)
kernel_name = 'concat_heads__memory_aug_recurrent_mem_tr__ssm_conv_s4__prompt'

def setup_inputs():

    _w = lambda a: (lambda t: t.to(torch.bfloat16) if t.is_floating_point() else t)(torch.as_tensor(a))

    def _A_setup():
        B, S, Dm = (1, 2048, 1024)
        H, Dh = (32, 128)
        M, seg = (8, 32)
        seg = min(seg, S)
        S = S // seg * seg
        return {'x': _w((lambda *s: torch.randn(*s, dtype=torch.bfloat16) * 0.05)(B, S, Dm)), 'mem0': _w((lambda *s: torch.randn(*s, dtype=torch.bfloat16) * 0.4)(B, M, Dm)), 'Wq': _w((lambda *s: torch.randn(*s, dtype=torch.bfloat16) * 6.4)(Dm, H, Dh) * Dm ** (-0.5)), 'Wk': _w((lambda *s: torch.randn(*s, dtype=torch.bfloat16) * 6.4)(Dm, H, Dh) * Dm ** (-0.5)), 'Wv': _w((lambda *s: torch.randn(*s, dtype=torch.bfloat16) * 0.4)(Dm, H, Dh) * Dm ** (-0.5)), 'Wo': _w((lambda *s: torch.randn(*s, dtype=torch.bfloat16) * 0.4)(H, Dh, Dm) * (H * Dh) ** (-0.5)), 'seg_len': seg}
    _A_in = _A_setup()

    def _B_setup():
        B, L, D, N = (1, 2048, 1024, 128)
        A_re = -(lambda _x: torch.exp(torch.as_tensor(_x)))((lambda *s: torch.randn(*s, dtype=torch.bfloat16) * 6.4)(D, N))
        A_im = torch.pi * (lambda *s: torch.randn(*s, dtype=torch.bfloat16) * 0.05)(D, N)
        B_re = (lambda *s: torch.randn(*s, dtype=torch.bfloat16) * 0.1)(D, N)
        B_im = (lambda *s: torch.randn(*s, dtype=torch.bfloat16) * 0.1)(D, N)
        C_re = (lambda *s: torch.randn(*s, dtype=torch.bfloat16) * 0.1)(D, N)
        C_im = (lambda *s: torch.randn(*s, dtype=torch.bfloat16) * 0.1)(D, N)
        log_dt = (lambda *s: torch.randn(*s, dtype=torch.bfloat16) * 0.05)(D) * 0.5 - 4.0
        Dskip = (lambda *s: torch.randn(*s, dtype=torch.bfloat16) * 0.05)(D)
        return {'u': _w((lambda *s: torch.randn(*s, dtype=torch.bfloat16) * 0.05)(B, L, D)), 'A_re': _w(A_re), 'A_im': _w(A_im), 'B_re': _w(B_re), 'B_im': _w(B_im), 'C_re': _w(C_re), 'C_im': _w(C_im), 'log_dt': _w(log_dt), 'Dskip': _w(Dskip)}
    _B_in = _B_setup()
    return {'A_x': _A_in['x'], 'A_mem0': _A_in['mem0'], 'A_Wq': _A_in['Wq'], 'A_Wk': _A_in['Wk'], 'A_Wv': _A_in['Wv'], 'A_Wo': _A_in['Wo'], 'A_seg_len': _A_in['seg_len'], 'B_u': _B_in['u'], 'B_A_re': _B_in['A_re'], 'B_A_im': _B_in['A_im'], 'B_B_re': _B_in['B_re'], 'B_B_im': _B_in['B_im'], 'B_C_re': _B_in['C_re'], 'B_C_im': _B_in['C_im'], 'B_log_dt': _B_in['log_dt'], 'B_Dskip': _B_in['Dskip']}

def reference(A_x, A_mem0, A_Wq, A_Wk, A_Wv, A_Wo, A_seg_len, B_u, B_A_re, B_A_im, B_B_re, B_B_im, B_C_re, B_C_im, B_log_dt, B_Dskip):

    def _A_ref(x, mem0, Wq, Wk, Wv, Wo, seg_len):
        B, S, Dm = x.shape
        H, Dh = (Wq.shape[1], Wq.shape[2])
        M = mem0.shape[1]
        scale = Dh ** (-0.5)
        n_seg = S // seg_len
        L = M + seg_len
        idx = torch.arange(L)
        mask = (idx[:, None] < M) | (idx[:, None] >= idx[None, :])
        mem = mem0
        outs = []
        for s in range(n_seg):
            xs = x[:, s * seg_len:(s + 1) * seg_len, :].clone()
            h = torch.concatenate([mem, xs], axis=1)
            q = torch.einsum('btd,dhe->bhte', h, Wq)
            k = torch.einsum('btd,dhe->bhte', h, Wk)
            v = torch.einsum('btd,dhe->bhte', h, Wv)
            scores = torch.einsum('bhqe,bhke->bhqk', q, k) * scale
            scores = torch.where(mask[None, None], scores, -1000000000.0)
            p = _softmax(scores, axis=-1)
            o = torch.einsum('bhqk,bhke->bhqe', p, v)
            o = torch.einsum('bhte,hed->btd', o, Wo)
            mem = o[:, :M, :].clone()
            outs.append(o[:, M:, :])
        return torch.concatenate(outs, axis=1)

    def _B_ref(u, A_re, A_im, B_re, B_im, C_re, C_im, log_dt, Dskip):
        Bsz, L, D = u.shape
        dt = torch.exp(log_dt)[:, None]
        A = A_re + 1j * A_im
        Bc = B_re + 1j * B_im
        Cc = C_re + 1j * C_im
        logdA = dt * A
        dB = dt * Bc
        l = (lambda x, dt: x.to(dt))(torch.arange(L), A_re.dtype)
        P = torch.exp(logdA[:, :, None] * l[None, None, :])
        K = torch.einsum('dn,dnl,dn->dl', Cc, P, dB).real
        L2 = 2 * L
        Kp = _pad(K, ((0, 0), (0, L)))
        up = (lambda x, *d: x.permute(*d))(u, 0, 2, 1)
        up = _pad(up, ((0, 0), (0, 0), (0, L)))
        Kf = (lambda x, axes=(-2, -1): torch.fft.rfft2(x.float(), dim=axes))(Kp[:, None, :], axes=(-2, -1))
        Uf = (lambda x, axes=(-2, -1): torch.fft.rfft2(x.float(), dim=axes))(up[:, :, None, :], axes=(-2, -1))
        Yf = Uf * Kf[None, :, :, :]
        y = (lambda x, s, axes=(-2, -1): torch.fft.irfft2(x, s=s, dim=axes).to(torch.bfloat16))(Yf, (1, L2), axes=(-2, -1))[:, :, 0, :L]
        y = (lambda x, *d: x.permute(*d))(y, 0, 2, 1) + u * Dskip[None, None, :]
        return y
    a = _A_ref(A_x, A_mem0, A_Wq, A_Wk, A_Wv, A_Wo, A_seg_len)
    b = _B_ref(B_u, B_A_re, B_A_im, B_B_re, B_B_im, B_C_re, B_C_im, B_log_dt, B_Dskip)
    return torch.concatenate([a, b], axis=-1)
```

```cpp
#include <cuda_runtime.h>
#include <cuda_bf16.h>
#include <cuda.h>
#include <stdint.h>

typedef __nv_bfloat16 bf16;

constexpr int SEQ = 2048, DM = 1024, HD = 4096, NSEG = 64;

__device__ __align__(1024) bf16 g_kv[(size_t)SEQ * 8192];
__device__ __align__(1024) bf16 g_kvm[(size_t)NSEG * 8 * 8192];
__device__ __align__(1024) bf16 g_o[(size_t)SEQ * HD];
__device__ __align__(1024) uint2 g_memx[NSEG * 64 * 32];
__device__ __align__(1024) uint2 g_part[64 * 32 * 32];
__device__ __align__(1024) uint32_t g_flag[256];

__device__ __forceinline__ uint32_t smem_u32(const void* p) { return (uint32_t)__cvta_generic_to_shared(p); }
__device__ __forceinline__ void mbar_init(uint32_t bar, uint32_t cnt) {
    asm volatile("mbarrier.init.shared::cta.b64 [%0], %1;" ::"r"(bar), "r"(cnt) : "memory");
}
__device__ __forceinline__ void mbar_expect_tx(uint32_t bar, uint32_t bytes) {
    asm volatile("mbarrier.arrive.expect_tx.shared::cta.b64 _, [%0], %1;" ::"r"(bar), "r"(bytes) : "memory");
}
__device__ __forceinline__ void mbar_arrive(uint32_t bar) {
    asm volatile("mbarrier.arrive.shared::cta.b64 _, [%0];" ::"r"(bar) : "memory");
}
__device__ __forceinline__ bool mbar_try(uint32_t bar, uint32_t parity) {
    uint32_t ok;
    asm volatile("{\n.reg .pred p;\nmbarrier.try_wait.parity.shared::cta.b64 p, [%1], %2;\nselp.u32 %0, 1, 0, p;\n}"
                 : "=r"(ok) : "r"(bar), "r"(parity) : "memory");
    return ok;
}
__device__ __forceinline__ bool mbar_try_cluster(uint32_t bar, uint32_t parity) {
    uint32_t ok;
    asm volatile("{\n.reg .pred p;\nmbarrier.try_wait.parity.acquire.cluster.shared::cta.b64 p, [%1], %2;\nselp.u32 %0, 1, 0, p;\n}"
                 : "=r"(ok) : "r"(bar), "r"(parity) : "memory");
    return ok;
}
constexpr int SPIN_LIMIT = 1 << 20;
__device__ __forceinline__ void mbar_wait(uint32_t bar, uint32_t parity) {
    int n = 0;
    while (!mbar_try(bar, parity)) { if (++n > SPIN_LIMIT) __trap(); }
}
__device__ __forceinline__ void mbar_wait_cluster(uint32_t bar, uint32_t parity) {
    int n = 0;
    while (!mbar_try_cluster(bar, parity)) { if (++n > SPIN_LIMIT) __trap(); }
}
__device__ __forceinline__ void tma2d(uint32_t dst, const CUtensorMap* m, int c0, int c1, uint32_t bar) {
    asm volatile("cp.async.bulk.tensor.2d.shared::cluster.global.mbarrier::complete_tx::bytes [%0], [%1, {%3, %4}], [%2];"
                 ::"r"(dst), "l"(m), "r"(bar), "r"(c0), "r"(c1) : "memory");
}
__device__ __forceinline__ void tma3d(uint32_t dst, const CUtensorMap* m, int c0, int c1, int c2, uint32_t bar) {
    asm volatile("cp.async.bulk.tensor.3d.shared::cluster.global.mbarrier::complete_tx::bytes [%0], [%1, {%3, %4, %5}], [%2];"
                 ::"r"(dst), "l"(m), "r"(bar), "r"(c0), "r"(c1), "r"(c2) : "memory");
}
__device__ __forceinline__ uint32_t pack2(float lo, float hi) {
    uint32_t r;
    asm("cvt.rn.bf16x2.f32 %0, %1, %2;" : "=r"(r) : "f"(hi), "f"(lo));
    return r;
}
__device__ __forceinline__ float bf_lo(uint32_t v) { return __uint_as_float(v << 16); }
__device__ __forceinline__ float bf_hi(uint32_t v) { return __uint_as_float(v & 0xffff0000u); }
__device__ __forceinline__ float bf_round(float x) { return bf_lo(pack2(x, 0.f)); }
__device__ __forceinline__ float ex2(float x) { float y; asm("ex2.approx.ftz.f32 %0, %1;" : "=f"(y) : "f"(x)); return y; }
__device__ __forceinline__ void mma16816(float (&c)[4], uint32_t a0, uint32_t a1, uint32_t a2, uint32_t a3, uint32_t b0, uint32_t b1) {
    asm volatile("mma.sync.aligned.m16n8k16.row.col.f32.bf16.bf16.f32 {%0,%1,%2,%3}, {%4,%5,%6,%7}, {%8,%9}, {%0,%1,%2,%3};"
                 : "+f"(c[0]), "+f"(c[1]), "+f"(c[2]), "+f"(c[3]) : "r"(a0), "r"(a1), "r"(a2), "r"(a3), "r"(b0), "r"(b1));
}
__device__ __forceinline__ void mma1688(float (&c)[4], uint32_t a0, uint32_t a1, uint32_t b0) {
    asm volatile("mma.sync.aligned.m16n8k8.row.col.f32.bf16.bf16.f32 {%0,%1,%2,%3}, {%4,%5}, {%6}, {%0,%1,%2,%3};"
                 : "+f"(c[0]), "+f"(c[1]), "+f"(c[2]), "+f"(c[3]) : "r"(a0), "r"(a1), "r"(b0));
}
__device__ __forceinline__ void ldsm4(uint32_t (&r)[4], uint32_t a) {
    asm volatile("ldmatrix.sync.aligned.m8n8.x4.shared.b16 {%0,%1,%2,%3}, [%4];"
                 : "=r"(r[0]), "=r"(r[1]), "=r"(r[2]), "=r"(r[3]) : "r"(a) : "memory");
}
__device__ __forceinline__ void ldsm4t(uint32_t (&r)[4], uint32_t a) {
    asm volatile("ldmatrix.sync.aligned.m8n8.x4.trans.shared.b16 {%0,%1,%2,%3}, [%4];"
                 : "=r"(r[0]), "=r"(r[1]), "=r"(r[2]), "=r"(r[3]) : "r"(a) : "memory");
}
__device__ __forceinline__ void ldsm2t(uint32_t& r0, uint32_t& r1, uint32_t a) {
    asm volatile("ldmatrix.sync.aligned.m8n8.x2.trans.shared.b16 {%0,%1}, [%2];" : "=r"(r0), "=r"(r1) : "r"(a) : "memory");
}
__device__ __forceinline__ void stsm4t(uint32_t a, uint32_t r0, uint32_t r1, uint32_t r2, uint32_t r3) {
    asm volatile("stmatrix.sync.aligned.m8n8.x4.trans.shared.b16 [%0], {%1,%2,%3,%4};"
                 ::"r"(a), "r"(r0), "r"(r1), "r"(r2), "r"(r3) : "memory");
}
__device__ __forceinline__ void lds128(uint32_t (&r)[4], uint32_t a) {
    asm volatile("ld.shared.v4.u32 {%0,%1,%2,%3}, [%4];" : "=r"(r[0]), "=r"(r[1]), "=r"(r[2]), "=r"(r[3]) : "r"(a) : "memory");
}
__device__ __forceinline__ float4 lds128f(uint32_t a) {
    float4 v;
    asm volatile("ld.shared.v4.f32 {%0,%1,%2,%3}, [%4];" : "=f"(v.x), "=f"(v.y), "=f"(v.z), "=f"(v.w) : "r"(a) : "memory");
    return v;
}
__device__ __forceinline__ float2 lds64f(uint32_t a) {
    float2 v;
    asm volatile("ld.shared.v2.f32 {%0,%1}, [%2];" : "=f"(v.x), "=f"(v.y) : "r"(a) : "memory");
    return v;
}
__device__ __forceinline__ uint32_t lds32(uint32_t a) {
    uint32_t v;
    asm volatile("ld.shared.u32 %0, [%1];" : "=r"(v) : "r"(a) : "memory");
    return v;
}
__device__ __forceinline__ void sts128(uint32_t a, uint32_t r0, uint32_t r1, uint32_t r2, uint32_t r3) {
    asm volatile("st.shared.v4.u32 [%0], {%1,%2,%3,%4};" ::"r"(a), "r"(r0), "r"(r1), "r"(r2), "r"(r3) : "memory");
}
__device__ __forceinline__ void sts128f(uint32_t a, float r0, float r1, float r2, float r3) {
    asm volatile("st.shared.v4.f32 [%0], {%1,%2,%3,%4};" ::"r"(a), "f"(r0), "f"(r1), "f"(r2), "f"(r3) : "memory");
}
__device__ __forceinline__ void sts64(uint32_t a, uint32_t r0, uint32_t r1) {
    asm volatile("st.shared.v2.u32 [%0], {%1,%2};" ::"r"(a), "r"(r0), "r"(r1) : "memory");
}
__device__ __forceinline__ void sts64f(uint32_t a, float r0, float r1) {
    asm volatile("st.shared.v2.f32 [%0], {%1,%2};" ::"r"(a), "f"(r0), "f"(r1) : "memory");
}
__device__ __forceinline__ void sts32f(uint32_t a, float r0) {
    asm volatile("st.shared.f32 [%0], %1;" ::"r"(a), "f"(r0) : "memory");
}
__device__ __forceinline__ uint2 ld_rlx64(const uint2* p) {
    uint2 v;
    asm volatile("{\n.reg .b64 t;\nld.relaxed.gpu.global.b64 t, [%2];\nmov.b64 {%0,%1}, t;\n}" : "=r"(v.x), "=r"(v.y) : "l"(p) : "memory");
    return v;
}
__device__ __forceinline__ void st_rlx64(uint2* p, uint32_t x, uint32_t y) {
    asm volatile("{\n.reg .b64 t;\nmov.b64 t, {%1,%2};\nst.relaxed.gpu.global.b64 [%0], t;\n}" ::"l"(p), "r"(x), "r"(y) : "memory");
}
__device__ __forceinline__ uint32_t ld_acq32(const uint32_t* p) {
    uint32_t v;
    asm volatile("ld.acquire.gpu.global.u32 %0, [%1];" : "=r"(v) : "l"(p) : "memory");
    return v;
}
__device__ __forceinline__ void wait_flag(const uint32_t* p, uint32_t need) {
    int n = 0;
    while (ld_acq32(p) < need) { __nanosleep(200); if (++n > SPIN_LIMIT) __trap(); }
}
__device__ __forceinline__ void bar_sync(int id, int n) { asm volatile("bar.sync %0, %1;" ::"r"(id), "r"(n) : "memory"); }
__device__ __forceinline__ void wg_fence() { asm volatile("wgmma.fence.sync.aligned;" ::: "memory"); }
__device__ __forceinline__ void wg_commit() { asm volatile("wgmma.commit_group.sync.aligned;" ::: "memory"); }
template <int N> __device__ __forceinline__ void wg_wait() { asm volatile("wgmma.wait_group.sync.aligned %0;" ::"n"(N) : "memory"); }
__device__ __forceinline__ uint64_t desc_sw128(uint32_t addr, uint32_t lbo, uint32_t sbo) {
    return (uint64_t)((addr & 0x3FFFF) >> 4) | ((uint64_t)(lbo >> 4) << 16) | ((uint64_t)(sbo >> 4) << 32) | (1ull << 62);
}
__device__ __forceinline__ void quad_transpose(uint32_t& r0, uint32_t& r1, uint32_t& r2, uint32_t& r3, int t) {
    const bool o = t & 1, h = t & 2;
    uint32_t s0 = __shfl_xor_sync(~0u, o ? r0 : r1, 1), s1 = __shfl_xor_sync(~0u, o ? r2 : r3, 1);
    uint32_t a0 = o ? s0 : r0, a1 = o ? r1 : s0, a2 = o ? s1 : r2, a3 = o ? r3 : s1;
    s0 = __shfl_xor_sync(~0u, h ? a0 : a2, 2); s1 = __shfl_xor_sync(~0u, h ? a1 : a3, 2);
    r0 = h ? s0 : a0; r1 = h ? s1 : a1; r2 = h ? a2 : s0; r3 = h ? a3 : s1;
}

__device__ __forceinline__ void wgmma_n256(float (&d)[128], uint64_t da, uint64_t db, int sd) {
    asm volatile("{\n.reg .pred p;\nsetp.ne.b32 p, %130, 0;\n"
        "wgmma.mma_async.sync.aligned.m64n256k16.f32.bf16.bf16 "
        "{%0,%1,%2,%3,%4,%5,%6,%7,%8,%9,%10,%11,%12,%13,%14,%15,"
        "%16,%17,%18,%19,%20,%21,%22,%23,%24,%25,%26,%27,%28,%29,%30,%31,"
        "%32,%33,%34,%35,%36,%37,%38,%39,%40,%41,%42,%43,%44,%45,%46,%47,"
        "%48,%49,%50,%51,%52,%53,%54,%55,%56,%57,%58,%59,%60,%61,%62,%63,"
        "%64,%65,%66,%67,%68,%69,%70,%71,%72,%73,%74,%75,%76,%77,%78,%79,"
        "%80,%81,%82,%83,%84,%85,%86,%87,%88,%89,%90,%91,%92,%93,%94,%95,"
        "%96,%97,%98,%99,%100,%101,%102,%103,%104,%105,%106,%107,%108,%109,%110,%111,"
        "%112,%113,%114,%115,%116,%117,%118,%119,%120,%121,%122,%123,%124,%125,%126,%127}, %128, %129, p, 1, 1, 0, 1;\n}\n"
        : "+f"(d[0]), "+f"(d[1]), "+f"(d[2]), "+f"(d[3]), "+f"(d[4]), "+f"(d[5]), "+f"(d[6]), "+f"(d[7]),
          "+f"(d[8]), "+f"(d[9]), "+f"(d[10]), "+f"(d[11]), "+f"(d[12]), "+f"(d[13]), "+f"(d[14]), "+f"(d[15]),
          "+f"(d[16]), "+f"(d[17]), "+f"(d[18]), "+f"(d[19]), "+f"(d[20]), "+f"(d[21]), "+f"(d[22]), "+f"(d[23]),
          "+f"(d[24]), "+f"(d[25]), "+f"(d[26]), "+f"(d[27]), "+f"(d[28]), "+f"(d[29]), "+f"(d[30]), "+f"(d[31]),
          "+f"(d[32]), "+f"(d[33]), "+f"(d[34]), "+f"(d[35]), "+f"(d[36]), "+f"(d[37]), "+f"(d[38]), "+f"(d[39]),
          "+f"(d[40]), "+f"(d[41]), "+f"(d[42]), "+f"(d[43]), "+f"(d[44]), "+f"(d[45]), "+f"(d[46]), "+f"(d[47]),
          "+f"(d[48]), "+f"(d[49]), "+f"(d[50]), "+f"(d[51]), "+f"(d[52]), "+f"(d[53]), "+f"(d[54]), "+f"(d[55]),
          "+f"(d[56]), "+f"(d[57]), "+f"(d[58]), "+f"(d[59]), "+f"(d[60]), "+f"(d[61]), "+f"(d[62]), "+f"(d[63]),
          "+f"(d[64]), "+f"(d[65]), "+f"(d[66]), "+f"(d[67]), "+f"(d[68]), "+f"(d[69]), "+f"(d[70]), "+f"(d[71]),
          "+f"(d[72]), "+f"(d[73]), "+f"(d[74]), "+f"(d[75]), "+f"(d[76]), "+f"(d[77]), "+f"(d[78]), "+f"(d[79]),
          "+f"(d[80]), "+f"(d[81]), "+f"(d[82]), "+f"(d[83]), "+f"(d[84]), "+f"(d[85]), "+f"(d[86]), "+f"(d[87]),
          "+f"(d[88]), "+f"(d[89]), "+f"(d[90]), "+f"(d[91]), "+f"(d[92]), "+f"(d[93]), "+f"(d[94]), "+f"(d[95]),
          "+f"(d[96]), "+f"(d[97]), "+f"(d[98]), "+f"(d[99]), "+f"(d[100]), "+f"(d[101]), "+f"(d[102]), "+f"(d[103]),
          "+f"(d[104]), "+f"(d[105]), "+f"(d[106]), "+f"(d[107]), "+f"(d[108]), "+f"(d[109]), "+f"(d[110]), "+f"(d[111]),
          "+f"(d[112]), "+f"(d[113]), "+f"(d[114]), "+f"(d[115]), "+f"(d[116]), "+f"(d[117]), "+f"(d[118]), "+f"(d[119]),
          "+f"(d[120]), "+f"(d[121]), "+f"(d[122]), "+f"(d[123]), "+f"(d[124]), "+f"(d[125]), "+f"(d[126]), "+f"(d[127])
        : "l"(da), "l"(db), "r"(sd));
}

__device__ __forceinline__ void wgmma_n128(float (&d)[64], uint64_t da, uint64_t db, int sd) {
    asm volatile("{\n.reg .pred p;\nsetp.ne.b32 p, %66, 0;\n"
        "wgmma.mma_async.sync.aligned.m64n128k16.f32.bf16.bf16 "
        "{%0,%1,%2,%3,%4,%5,%6,%7,%8,%9,%10,%11,%12,%13,%14,%15,"
        "%16,%17,%18,%19,%20,%21,%22,%23,%24,%25,%26,%27,%28,%29,%30,%31,"
        "%32,%33,%34,%35,%36,%37,%38,%39,%40,%41,%42,%43,%44,%45,%46,%47,"
        "%48,%49,%50,%51,%52,%53,%54,%55,%56,%57,%58,%59,%60,%61,%62,%63}, %64, %65, p, 1, 1, 0, 1;\n}\n"
        : "+f"(d[0]), "+f"(d[1]), "+f"(d[2]), "+f"(d[3]), "+f"(d[4]), "+f"(d[5]), "+f"(d[6]), "+f"(d[7]),
          "+f"(d[8]), "+f"(d[9]), "+f"(d[10]), "+f"(d[11]), "+f"(d[12]), "+f"(d[13]), "+f"(d[14]), "+f"(d[15]),
          "+f"(d[16]), "+f"(d[17]), "+f"(d[18]), "+f"(d[19]), "+f"(d[20]), "+f"(d[21]), "+f"(d[22]), "+f"(d[23]),
          "+f"(d[24]), "+f"(d[25]), "+f"(d[26]), "+f"(d[27]), "+f"(d[28]), "+f"(d[29]), "+f"(d[30]), "+f"(d[31]),
          "+f"(d[32]), "+f"(d[33]), "+f"(d[34]), "+f"(d[35]), "+f"(d[36]), "+f"(d[37]), "+f"(d[38]), "+f"(d[39]),
          "+f"(d[40]), "+f"(d[41]), "+f"(d[42]), "+f"(d[43]), "+f"(d[44]), "+f"(d[45]), "+f"(d[46]), "+f"(d[47]),
          "+f"(d[48]), "+f"(d[49]), "+f"(d[50]), "+f"(d[51]), "+f"(d[52]), "+f"(d[53]), "+f"(d[54]), "+f"(d[55]),
          "+f"(d[56]), "+f"(d[57]), "+f"(d[58]), "+f"(d[59]), "+f"(d[60]), "+f"(d[61]), "+f"(d[62]), "+f"(d[63])
        : "l"(da), "l"(db), "r"(sd));
}

constexpr int STAGE_BYTES = 49152, NSTAGE = 4;
constexpr int GEMM_SMEM = NSTAGE * STAGE_BYTES + 1024 + 128;

struct GemmSmem { uint32_t st, full, empty; };
__device__ __forceinline__ GemmSmem gemm_setup(uint8_t* raw) {
    GemmSmem g;
    uint32_t base = smem_u32(raw);
    g.st = (base + 127 + 1024) & ~1023u;
    g.full = base; g.empty = base + 64;
    if (threadIdx.x == 0) {
        for (int s = 0; s < NSTAGE; s++) { mbar_init(g.full + 8 * s, 1); mbar_init(g.empty + 8 * s, 2); }
        asm volatile("fence.mbarrier_init.release.cluster;" ::: "memory");
        asm volatile("fence.proxy.async.shared::cta;" ::: "memory");
    }
    __syncthreads();
    return g;
}
template <int BN, typename ACC>
__device__ __forceinline__ void gemm_kblock(ACC& acc, uint32_t stage, int wg, bool first) {
    const uint64_t da = desc_sw128(stage + wg * 8192, 16, 1024);
    const uint64_t db = desc_sw128(stage + 16384, 8192, 1024);
    wg_fence();
#pragma unroll
    for (int k = 0; k < 4; k++) {
        if constexpr (BN == 256) wgmma_n256(acc, da + k * 2, db + k * 128, first && k == 0 ? 0 : 1);
        else wgmma_n128(acc, da + k * 2, db + k * 128, first && k == 0 ? 0 : 1);
    }
    wg_commit();
}

__device__ __forceinline__ void kv_store_unit(const uint32_t (&pk)[64], int u, bf16* dst, int t) {
    const int G = (u >> 2) * 2 + (u & 1), hh = (u >> 1) & 1;
    uint32_t r0 = pk[(4 * G + 0) * 2 + hh], r1 = pk[(4 * G + 1) * 2 + hh], r2 = pk[(4 * G + 2) * 2 + hh], r3 = pk[(4 * G + 3) * 2 + hh];
    quad_transpose(r0, r1, r2, r3, t);
    *reinterpret_cast<uint4*>(dst + (size_t)hh * 8 * 8192 + G * 32) = make_uint4(r0, r1, r2, r3);
}

__global__ void __launch_bounds__(384, 1)
k_kv(const __grid_constant__ CUtensorMap mx, const __grid_constant__ CUtensorMap mwk, const __grid_constant__ CUtensorMap mwv) {
    extern __shared__ uint8_t smem_raw[];
    const int c = blockIdx.x;
    if (c >= 128) {
        const int i0 = (c - 128) * 384 + threadIdx.x;
        const uint4 ones = make_uint4(~0u, ~0u, ~0u, ~0u);
        for (int i = i0; i < NSEG * 64 * 32 / 2; i += 4 * 384) reinterpret_cast<uint4*>(g_memx)[i] = ones;
        for (int i = i0; i < 64 * 32 * 32 / 2; i += 4 * 384) reinterpret_cast<uint4*>(g_part)[i] = ones;
        if (i0 < 256) g_flag[i0] = 0;
        return;
    }
    GemmSmem g = gemm_setup(smem_raw);
    const int m0 = (c & 15) * 128, nb0 = c >> 4;
    const int wg = threadIdx.x >> 7;
    if (wg == 0) {
        asm volatile("setmaxnreg.dec.sync.aligned.u32 40;");
        if (threadIdx.x == 0) {
            for (int it = 0; it < 64; it++) {
                const int s = it & 3, tile = it >> 4, kb = it & 15;
                mbar_wait(g.empty + 8 * s, ((it >> 2) & 1) ^ 1);
                mbar_expect_tx(g.full + 8 * s, STAGE_BYTES);
                const int nb = nb0 + 8 * tile;
                tma2d(g.st + s * STAGE_BYTES, &mx, kb * 64, m0, g.full + 8 * s);
                tma3d(g.st + s * STAGE_BYTES + 16384, nb < 16 ? &mwk : &mwv, 0, kb * 64, (nb & 15) * 4, g.full + 8 * s);
            }
        }
    } else {
        asm volatile("setmaxnreg.inc.sync.aligned.u32 232;");
        const int cw = wg - 1, lane = threadIdx.x & 31, t = lane & 3;
        const int row = m0 + cw * 64 + ((threadIdx.x >> 5) & 3) * 16 + (lane >> 2);
        bf16* dst = g_kv + (size_t)row * 8192 + nb0 * 256 + t * 8;
        float acc[128];
        uint32_t pk[64];
#pragma unroll 1
        for (int tile = 0; tile < 4; tile++) {
#pragma unroll
            for (int kb = 0; kb < 16; kb++) {
                mbar_wait(g.full + 8 * (kb & 3), (kb >> 2) & 1);
                gemm_kblock<256>(acc, g.st + (kb & 3) * STAGE_BYTES, cw, kb == 0);
                if (tile > 0) kv_store_unit(pk, kb, dst + (tile - 1) * 2048, t);
                if (kb > 0) {
                    wg_wait<1>();
                    if ((threadIdx.x & 127) == 0) mbar_arrive(g.empty + 8 * ((kb - 1) & 3));
                }
            }
            wg_wait<0>();
            if ((threadIdx.x & 127) == 0) mbar_arrive(g.empty + 8 * 3);
#pragma unroll
            for (int i = 0; i < 64; i++) pk[i] = pack2(acc[2 * i], acc[2 * i + 1]);
        }
#pragma unroll
        for (int u = 0; u < 16; u++) kv_store_unit(pk, u, dst + 3 * 2048, t);
    }
}

constexpr int NSM = 16;
constexpr int C_W1 = 0;
constexpr int C_W2 = C_W1 + 8 * NSM * 512;
constexpr int C_KV = C_W2 + 22 * 8 * 512;
constexpr int C_RED = C_KV + 16384;
constexpr int C_R3 = C_RED + 32768;
constexpr int C_QKV = C_R3 + 5120;
constexpr int C_SC = C_QKV + 3 * 8 * 272;
constexpr int C_OB = C_SC + 2 * 8 * 52 * 4;
constexpr int C_BAR = C_OB + 2048;
constexpr int CHAIN_SMEM = C_BAR + 64 + 1024;

__global__ void __cluster_dims__(3, 1, 1) __launch_bounds__(256, 1)
k_chain(const bf16* __restrict__ mem0, const bf16* __restrict__ Wq, const bf16* __restrict__ Wk, const bf16* __restrict__ Wv,
        const bf16* __restrict__ Wo, const __grid_constant__ CUtensorMap mkv) {
    extern __shared__ uint8_t smem_raw[];
    const uint32_t sb = (smem_u32(smem_raw) + 1023) & ~1023u;
    const int tid = threadIdx.x, w = tid >> 5, lane = tid & 31, g = lane >> 2, t = lane & 3;
    const int h = blockIdx.x / 3, r = blockIdx.x - 3 * h;
    const uint32_t bar_x = sb + C_BAR, bar_kv = sb + C_BAR + 8;
    asm volatile("griddepcontrol.launch_dependents;");
    if (tid == 0) {
        mbar_init(bar_x, 8); mbar_init(bar_kv, 1);
        asm volatile("fence.mbarrier_init.release.cluster;" ::: "memory");
        asm volatile("fence.proxy.async.shared::cta;" ::: "memory");
        mbar_expect_tx(bar_kv, 16384);
        tma3d(sb + C_KV, &mkv, 0, 0, 2 * h, bar_kv);
        tma3d(sb + C_KV + 8192, &mkv, 0, 0, 64 + 2 * h, bar_kv);
    }
    const int tile0 = r == 0 ? 0 : 1 + 21 * r, ntile = r == 0 ? 22 : 21;
    {
        const bf16* wo = Wo + (size_t)h * 128 * DM + 2 * g;
#pragma unroll 1
        for (int i = w; i < ntile; i += 8) {
#pragma unroll
            for (int ks = 0; ks < 8; ks++) {
                const bf16* p = wo + (size_t)(16 * ks + 2 * t) * DM + (tile0 + i) * 16;
                uint32_t x0 = __ldg((const uint32_t*)p), x1 = __ldg((const uint32_t*)(p + DM));
                uint32_t x2 = __ldg((const uint32_t*)(p + 8 * DM)), x3 = __ldg((const uint32_t*)(p + 9 * DM));
                sts128(sb + C_W2 + (i * 8 + ks) * 512 + lane * 16, __byte_perm(x0, x1, 0x5410), __byte_perm(x0, x1, 0x7632),
                       __byte_perm(x2, x3, 0x5410), __byte_perm(x2, x3, 0x7632));
            }
        }
    }
    uint32_t wr[6][8][4];
    {
        const bf16* W = (r == 0 ? Wq : r == 1 ? Wk : Wv) + (size_t)(128 * w + 4 * t) * HD + h * 128 + 8 * g;
#pragma unroll
        for (int ks = 0; ks < 8; ks++) {
            uint4 x[4][2];
#pragma unroll
            for (int i = 0; i < 4; i++) {
                x[i][0] = __ldg((const uint4*)(W + (size_t)(16 * ks + i) * HD));
                x[i][1] = __ldg((const uint4*)(W + (size_t)(16 * ks + i) * HD + 64));
            }
#pragma unroll
            for (int j = 0; j < 8; j++) {
                const uint32_t sel = (j & 1) ? 0x7632 : 0x5410;
                uint32_t a[4];
#pragma unroll
                for (int q = 0; q < 4; q++) {
                    const uint4 &lo = x[(q >> 1) * 2][q & 1], &hi = x[(q >> 1) * 2 + 1][q & 1];
                    const uint32_t l = (j >> 1) == 0 ? lo.x : (j >> 1) == 1 ? lo.y : (j >> 1) == 2 ? lo.z : lo.w;
                    const uint32_t u = (j >> 1) == 0 ? hi.x : (j >> 1) == 1 ? hi.y : (j >> 1) == 2 ? hi.z : hi.w;
                    a[q] = __byte_perm(l, u, sel);
                }
                if (ks < 2) sts128(sb + C_W1 + ((w * 2 + ks) * 8 + j) * 512 + lane * 16, a[0], a[1], a[2], a[3]);
                else { wr[ks - 2][j][0] = a[0]; wr[ks - 2][j][1] = a[1]; wr[ks - 2][j][2] = a[2]; wr[ks - 2][j][3] = a[3]; }
            }
        }
    }
    asm volatile("barrier.cluster.arrive.aligned;\nbarrier.cluster.wait.aligned;" ::: "memory");

    const float sl2e = 0.08838834764831845f * 1.4426950408889634f;
#pragma unroll 1
    for (int s = 0; s < NSEG; s++) {
        uint2 bm[8];
        if (s == 0) {
#pragma unroll
            for (int ks = 0; ks < 8; ks++) bm[ks] = __ldg((const uint2*)(mem0 + g * DM + (8 * w + ks) * 16 + 4 * t));
        } else {
            const uint2* src = g_memx + (s * 64 + 8 * w) * 32 + lane;
            int n = 0;
            while (true) {
#pragma unroll
                for (int ks = 0; ks < 8; ks++) bm[ks] = ld_rlx64(src + ks * 32);
                bool bad = false;
#pragma unroll
                for (int ks = 0; ks < 8; ks++) bad |= bm[ks].x == 0xffffffffu;
                if (!__any_sync(~0u, bad)) break;
                if (++n > SPIN_LIMIT) __trap();
            }
        }
        const uint32_t f = (t & 1) | ((t & 2) << 1);
#pragma unroll
        for (int q = 0; q < 2; q++) {
            float acc[4][4];
#pragma unroll
            for (int j = 0; j < 4; j++) { acc[j][0] = acc[j][1] = acc[j][2] = acc[j][3] = 0.f; }
#pragma unroll
            for (int kk = 0; kk < 8; kk++) {
                const int ks = kk == 3 ? 0 : kk == 7 ? 1 : kk < 3 ? kk + 2 : kk + 1;
#pragma unroll
                for (int j = 0; j < 4; j++) {
                    if (ks < 2) {
                        uint32_t a[4];
                        lds128(a, sb + C_W1 + ((w * 2 + ks) * 8 + q * 4 + j) * 512 + lane * 16);
                        mma16816(acc[j], a[0], a[1], a[2], a[3], bm[ks].x, bm[ks].y);
                    } else {
                        const uint32_t(&a)[4] = wr[ks - 2][q * 4 + j];
                        mma16816(acc[j], a[0], a[1], a[2], a[3], bm[ks].x, bm[ks].y);
                    }
                }
            }
#pragma unroll
            for (int c = 0; c < 4; c++)
                sts128f(sb + C_RED + w * 4096 + (2 * t + (c & 1)) * 512 + ((16 * (c >> 1) + 2 * g + q) ^ f) * 16,
                        acc[0][c], acc[1][c], acc[2][c], acc[3][c]);
        }
        __syncthreads();
        {
            const uint32_t fw = ((w >> 1) & 1) | (w & 4);
            const uint32_t a = sb + C_RED + w * 512 + (lane ^ fw) * 16;
            float4 v[8];
#pragma unroll
            for (int i = 0; i < 8; i++) v[i] = lds128f(a + i * 4096);
#pragma unroll
            for (int o = 4; o; o >>= 1)
#pragma unroll
                for (int i = 0; i < o; i++) { v[i].x += v[i + o].x; v[i].y += v[i + o].y; v[i].z += v[i + o].z; v[i].w += v[i + o].w; }
            const uint32_t p0 = pack2(v[0].x, v[0].y), p1 = pack2(v[0].z, v[0].w);
            const uint32_t dst = sb + C_QKV + (r * 8 + w) * 272 + lane * 8;
#pragma unroll
            for (int i = 1; i < 3; i++) {
                const uint32_t peer = r + i >= 3 ? r + i - 3 : r + i;
                uint32_t rd, rb;
                asm("mapa.shared::cluster.u32 %0, %1, %2;" : "=r"(rd) : "r"(dst), "r"(peer));
                asm("mapa.shared::cluster.u32 %0, %1, %2;" : "=r"(rb) : "r"(bar_x), "r"(peer));
                asm volatile("st.async.weak.shared::cluster.mbarrier::complete_tx::bytes.v2.b32 [%0], {%1,%2}, [%3];"
                             ::"r"(rd), "r"(p0), "r"(p1), "r"(rb) : "memory");
            }
            sts64(dst, p0, p1);
            __syncwarp();
            if (lane == 0) { if (w == 0) mbar_expect_tx(bar_x, 4096); else mbar_arrive(bar_x); }
        }
        const bool last = s == NSEG - 1;
        if (!last) {
            mbar_wait(bar_kv, s & 1);
            uint32_t ka[4][4], vb[2][4];
            if (w < 4) {
                const int row = (w >> 1) * 16 + (lane & 15);
#pragma unroll
                for (int ks = 0; ks < 4; ks++)
                    ldsm4(ka[ks], sb + C_KV + (w & 1) * 4096 + row * 128 + (((2 * ks + (lane >> 4)) ^ (row & 7)) << 4));
            }
            {
                const int key = 8 * ((lane & 7) >> 1) + 2 * (lane >> 3) + (lane & 1);
#pragma unroll
                for (int i = 0; i < 2; i++)
                    ldsm4t(vb[i], sb + C_KV + 8192 + (w >> 2) * 4096 + key * 128 + ((((2 * w + i) & 7) ^ (key & 7)) << 4));
            }
            mbar_wait_cluster(bar_x, s & 1);
            if (w < 6) {
                const uint32_t off = (lane & 7) * 272 + (w & 1) * 128 + (lane >> 3) * 16;
                uint32_t qb[2][4];
                ldsm4(qb[0], sb + C_QKV + off);
                ldsm4(qb[1], sb + C_QKV + off + 64);
                if (w >= 4) {
                    uint32_t km[2][4];
                    ldsm4(km[0], sb + C_QKV + 8 * 272 + off);
                    ldsm4(km[1], sb + C_QKV + 8 * 272 + off + 64);
#pragma unroll
                    for (int ks = 0; ks < 4; ks++) {
                        ka[ks][0] = km[ks >> 1][(ks & 1) * 2]; ka[ks][2] = km[ks >> 1][(ks & 1) * 2 + 1];
                        ka[ks][1] = 0; ka[ks][3] = 0;
                    }
                }
                float c0[4] = {0.f, 0.f, 0.f, 0.f}, c1[4] = {0.f, 0.f, 0.f, 0.f};
                mma16816(c0, ka[0][0], ka[0][1], ka[0][2], ka[0][3], qb[0][0], qb[0][1]);
                mma16816(c1, ka[2][0], ka[2][1], ka[2][2], ka[2][3], qb[1][0], qb[1][1]);
                mma16816(c0, ka[1][0], ka[1][1], ka[1][2], ka[1][3], qb[0][2], qb[0][3]);
                mma16816(c1, ka[3][0], ka[3][1], ka[3][2], ka[3][3], qb[1][2], qb[1][3]);
                const uint32_t a = sb + C_SC + (w & 1) * (8 * 52 * 4) + (2 * t * 52 + (w >> 1) * 16 + g) * 4;
                sts32f(a, c0[0] + c1[0]);
                sts32f(a + 208, c0[1] + c1[1]);
                sts32f(a + 32, c0[2] + c1[2]);
                sts32f(a + 240, c0[3] + c1[3]);
            }
            uint32_t vm0, vm1;
            ldsm2t(vm0, vm1, sb + C_QKV + 16 * 272 + (lane & 7) * 272 + w * 32 + ((lane >> 3) & 1) * 16);
            __syncthreads();
            {
                const uint32_t a = sb + C_SC + (g * 52 + 8 * t) * 4;
                float4 x0 = lds128f(a), x1 = lds128f(a + 16), y0 = lds128f(a + 1664), y1 = lds128f(a + 1680);
                float2 x2 = lds64f(a + 128 - 24 * t), y2 = lds64f(a + 1664 + 128 - 24 * t);
                float p[10] = {x0.x + y0.x, x0.y + y0.y, x0.z + y0.z, x0.w + y0.w, x1.x + y1.x,
                               x1.y + y1.y, x1.z + y1.z, x1.w + y1.w, x2.x + y2.x, x2.y + y2.y};
                float m = fmaxf(fmaxf(fmaxf(p[0], p[1]), fmaxf(p[2], p[3])), fmaxf(fmaxf(p[4], p[5]), fmaxf(p[6], p[7])));
                m = fmaxf(m, fmaxf(p[8], p[9]));
                m = fmaxf(m, __shfl_xor_sync(~0u, m, 1));
                m = fmaxf(m, __shfl_xor_sync(~0u, m, 2));
                const float ms = m * sl2e;
#pragma unroll
                for (int i = 0; i < 10; i++) p[i] = ex2(fmaf(p[i], sl2e, -ms));
                const uint32_t a0 = pack2(p[0], p[1]), a1 = pack2(p[2], p[3]), a2 = pack2(p[4], p[5]), a3 = pack2(p[6], p[7]), a4 = pack2(p[8], p[9]);
                float o0[4] = {0.f, 0.f, 0.f, 0.f}, o1[4] = {0.f, 0.f, 0.f, 0.f}, o2[4] = {0.f, 0.f, 0.f, 0.f}, o3[4] = {0.f, 0.f, 0.f, 0.f};
                mma16816(o0, a0, 0, a1, 0, vb[0][0], vb[0][1]);
                mma16816(o1, a0, 0, a1, 0, vb[1][0], vb[1][1]);
                mma16816(o2, a2, 0, a3, 0, vb[0][2], vb[0][3]);
                mma16816(o3, a2, 0, a3, 0, vb[1][2], vb[1][3]);
                mma1688(o0, a4, 0, vm0);
                mma1688(o1, a4, 0, vm1);
                float sum = ((p[0] + p[1]) + (p[2] + p[3])) + ((p[4] + p[5]) + (p[6] + p[7])) + (p[8] + p[9]);
                sum += __shfl_xor_sync(~0u, sum, 1);
                sum += __shfl_xor_sync(~0u, sum, 2);
                const float inv = __frcp_rn(sum);
                sts64(sb + C_OB + (w >> 1) * 512 + lane * 16 + (w & 1) * 8, pack2((o0[0] + o2[0]) * inv, (o0[1] + o2[1]) * inv),
                      pack2((o1[0] + o3[0]) * inv, (o1[1] + o3[1]) * inv));
            }
            __syncthreads();
            if (tid == 0 && s + 1 < NSEG - 1) {
                mbar_expect_tx(bar_kv, 16384);
                tma3d(sb + C_KV, &mkv, 0, (s + 1) * 32, 2 * h, bar_kv);
                tma3d(sb + C_KV + 8192, &mkv, 0, (s + 1) * 32, 64 + 2 * h, bar_kv);
            }
            {
                uint32_t ob[4][4];
#pragma unroll
                for (int i = 0; i < 4; i++) lds128(ob[i], sb + C_OB + i * 512 + lane * 16);
                const uint32_t tag = s & 1;
#pragma unroll
                for (int i = 0; i < 3; i++) {
                    const int tl = w + 8 * i;
                    if (i < 2 || tl < ntile) {
                        float c0[4] = {0.f, 0.f, 0.f, 0.f}, c1[4] = {0.f, 0.f, 0.f, 0.f};
#pragma unroll
                        for (int ks = 0; ks < 8; ks++) {
                            uint32_t a[4];
                            lds128(a, sb + C_W2 + (tl * 8 + ks) * 512 + lane * 16);
                            mma16816((ks & 1) ? c1 : c0, a[0], a[1], a[2], a[3], ob[ks >> 1][(ks & 1) * 2], ob[ks >> 1][(ks & 1) * 2 + 1]);
                        }
                        const uint32_t p0 = pack2(c0[0] + c1[0], c0[2] + c1[2]), p1 = pack2(c0[1] + c1[1], c0[3] + c1[3]);
                        st_rlx64(g_part + ((tile0 + tl) * 32 + h) * 32 + lane, (p0 & ~1u) | tag, p1);
                    }
                }
            }
        } else {
            mbar_wait_cluster(bar_x, s & 1);
        }
        if (r == 0) {
            uint32_t v[4];
            lds128(v, sb + C_QKV + (8 + (tid >> 4)) * 272 + (tid & 15) * 16);
            *reinterpret_cast<uint4*>(g_kvm + (size_t)(s * 8 + ((tid >> 4) & 7)) * 8192 + (tid >> 7) * HD + h * 128 + (tid & 15) * 8) =
                make_uint4(v[0], v[1], v[2], v[3]);
            if ((s & 3) == 3) {
                __syncthreads();
                if (tid == 0) asm volatile("fence.acq_rel.gpu;\nst.relaxed.gpu.global.u32 [%0], %1;" ::"l"(g_flag + h), "r"(s + 1) : "memory");
            }
        } else if (!last) {
            const int j = 2 * h + r - 1;
            const uint2* src = g_part + (j * 32 + 4 * w) * 32 + lane;
            const uint32_t tag = s & 1;
            uint2 v[4];
            int n = 0;
            while (true) {
#pragma unroll
                for (int i = 0; i < 4; i++) v[i] = ld_rlx64(src + i * 32);
                const uint32_t bad = ((v[0].x ^ tag) | (v[1].x ^ tag) | (v[2].x ^ tag) | (v[3].x ^ tag)) & 1;
                if (!__any_sync(~0u, bad)) break;
                if (++n > SPIN_LIMIT) __trap();
            }
            const uint32_t a = sb + C_R3 + w * 640 + t * 160 + g * 8;
            sts64f(a, (bf_lo(v[0].x) + bf_lo(v[1].x)) + (bf_lo(v[2].x) + bf_lo(v[3].x)),
                   (bf_hi(v[0].x) + bf_hi(v[1].x)) + (bf_hi(v[2].x) + bf_hi(v[3].x)));
            sts64f(a + 80, (bf_lo(v[0].y) + bf_lo(v[1].y)) + (bf_lo(v[2].y) + bf_lo(v[3].y)),
                   (bf_hi(v[0].y) + bf_hi(v[1].y)) + (bf_hi(v[2].y) + bf_hi(v[3].y)));
            __syncthreads();
            if (w == 0) {
                float4 u[8];
#pragma unroll
                for (int i = 0; i < 8; i++) u[i] = lds128f(sb + C_R3 + i * 640 + g * 80 + t * 16);
#pragma unroll
                for (int o = 4; o; o >>= 1)
#pragma unroll
                    for (int i = 0; i < o; i++) { u[i].x += u[i + o].x; u[i].y += u[i + o].y; u[i].z += u[i + o].z; u[i].w += u[i + o].w; }
                st_rlx64(g_memx + ((s + 1) * 64 + j) * 32 + lane, pack2(u[0].x, u[0].y), pack2(u[0].z, u[0].w));
            }
        }
    }
    asm volatile("barrier.cluster.arrive.aligned;\nbarrier.cluster.wait.aligned;" ::: "memory");
}

constexpr int S4_US = 4368;
constexpr int S4_PS = 8336;
constexpr int S4_KS = 1296;
constexpr int S4_U = 0, S4_P = 16 * S4_US, S4_K = S4_P + 16 * S4_PS;
constexpr int S4_SMEM = S4_K + 16 * S4_KS;

__device__ __forceinline__ void csq(float& a, float& b) { const float t = a * b; a = fmaf(a, a, -b * b); b = t + t; }
__device__ __forceinline__ uint32_t cmulpack(float cr, float ci, float a, float b) {
    return pack2(fmaf(cr, a, -ci * b), -fmaf(cr, b, ci * a));
}
__device__ __forceinline__ void cexp(float& re, float& im, float l2, float turns) {
    const float mag = ex2(l2), fr = (turns - rintf(turns)) * 6.283185307179586f;
    re = mag * __cosf(fr); im = mag * __sinf(fr);
}
__device__ __forceinline__ int s4_idx(int l) {
    const int r = l < 256 ? 0 : 24 - __clz(l);
    const int m = r == 0 ? l : (l + (1 << (r - 1)) - 1 + ((l >> r) & 1)) >> r;
    return 128 * r + m;
}

__global__ void __launch_bounds__(512, 1)
k_s4(const bf16* __restrict__ u, const bf16* __restrict__ Are, const bf16* __restrict__ Aim, const bf16* __restrict__ Bre,
     const bf16* __restrict__ Bim, const bf16* __restrict__ Cre, const bf16* __restrict__ Cim, const bf16* __restrict__ logdt,
     const bf16* __restrict__ Dsk, bf16* __restrict__ out) {
    extern __shared__ __align__(16) uint8_t smem_raw[];
    const uint32_t sb = smem_u32(smem_raw);
    asm volatile("griddepcontrol.launch_dependents;");
    const int tid = threadIdx.x, w = tid >> 5, lane = tid & 31, g = lane >> 2, t = lane & 3;
    const int d0 = blockIdx.x * 16;
    const int d = d0 + (w & 1) + ((w >> 1) & 3) * 4 + (w >> 3) * 2;
    const uint32_t tr_off = (lane & 15), tr_l = (lane >> 4) * 16;
    {
        const bf16* src = u + (size_t)(w * 128 + g) * DM + d0 + 4 * t;
        uint2 v[16];
#pragma unroll
        for (int i = 0; i < 16; i++) v[i] = __ldg((const uint2*)(src + (size_t)i * 8 * DM));
        if (lane < 16) sts128(sb + S4_U + w * S4_US + lane * 16, 0, 0, 0, 0);
#pragma unroll
        for (int i = 0; i < 8; i++)
            stsm4t(sb + S4_U + tr_off * S4_US + 256 + (w * 128 + i * 16) * 2 + tr_l, v[2 * i].x, v[2 * i].y, v[2 * i + 1].x, v[2 * i + 1].y);
    }
    const uint32_t pk = sb + S4_P + w * S4_PS, kd = sb + S4_K + w * S4_KS;
    {
        const float dt = bf_round(expf(__bfloat162float(logdt[d])));
        const int o = d * 128 + lane * 4;
        const uint2 ar = __ldg((const uint2*)(Are + o)), ai = __ldg((const uint2*)(Aim + o)), br = __ldg((const uint2*)(Bre + o));
        const uint2 bi = __ldg((const uint2*)(Bim + o)), cr = __ldg((const uint2*)(Cre + o)), ci = __ldg((const uint2*)(Cim + o));
#pragma unroll
        for (int i = 0; i < 4; i++) {
            auto pick = [&](const uint2& v) { const uint32_t x = i < 2 ? v.x : v.y; return (i & 1) ? bf_hi(x) : bf_lo(x); };
            const float dbr = dt * pick(br), dbi = dt * pick(bi), c_r = pick(cr), c_i = pick(ci);
            sts128f(pk + (lane * 4 + i) * 16, dt * pick(ar) * 1.4426950408889634f, dt * pick(ai) * 0.15915494309189535f,
                    fmaf(c_r, dbr, -c_i * dbi), fmaf(c_r, dbi, c_i * dbr));
        }
    }
    __syncwarp();
    {
        float T[5][4];
#pragma unroll
        for (int i = 0; i < 5; i++) T[i][0] = T[i][1] = T[i][2] = T[i][3] = 0.f;
        float klast = 0.f;
        const float g0 = (float)g, g8 = (float)(g + 8);
#pragma unroll 1
        for (int ks = 0; ks < 16; ks++) {
            uint32_t A[4][4], B[5][2];
#pragma unroll
            for (int hf = 0; hf < 2; hf++) {
                const float4 p = lds128f(pk + (ks * 8 + hf * 4 + t) * 16);
                float ur, ui, wr_, wi;
                cexp(ur, ui, p.x * g0, p.y * g0);
                cexp(wr_, wi, p.x * g8, p.y * g8);
#pragma unroll
                for (int r = 0; r < 4; r++) {
                    A[r][hf * 2] = pack2(ur, ui); A[r][hf * 2 + 1] = pack2(wr_, wi);
                    csq(ur, ui); csq(wr_, wi);
                }
                B[0][hf] = cmulpack(p.z, p.w, ur, ui);
#pragma unroll
                for (int r = 1; r < 5; r++) { B[r][hf] = cmulpack(p.z, p.w, wr_, wi); csq(wr_, wi); }
                klast += fmaf(p.z, wr_, -p.w * wi);
            }
            mma16816(T[0], A[0][0], A[0][1], A[0][2], A[0][3], B[0][0], B[0][1]);
#pragma unroll
            for (int r = 0; r < 4; r++) mma16816(T[r + 1], A[r][0], A[r][1], A[r][2], A[r][3], B[r + 1][0], B[r + 1][1]);
        }
        klast += __shfl_xor_sync(~0u, klast, 1);
        klast += __shfl_xor_sync(~0u, klast, 2);
        const uint32_t a = kd + (lane & 7) * 32 + ((lane >> 3) & 1) * 16 + (lane >> 4) * 256;
        stsm4t(a, pack2(T[0][0], T[0][1]), pack2(T[0][2], T[0][3]), pack2(T[1][0], T[1][1]), pack2(T[1][2], T[1][3]));
        stsm4t(a + 512, pack2(T[2][0], T[2][1]), pack2(T[2][2], T[2][3]), pack2(T[3][0], T[3][1]), pack2(T[3][2], T[3][3]));
        asm volatile("stmatrix.sync.aligned.m8n8.x2.trans.shared.b16 [%0], {%1,%2};"
                     ::"r"(a + 1024), "r"(pack2(T[4][0], T[4][1])), "r"(pack2(T[4][2], T[4][3])) : "memory");
        if (lane == 0) asm volatile("st.shared.u16 [%0], %1;" ::"r"(kd + 1280), "h"((unsigned short)pack2(klast, 0.f)) : "memory");
    }
    __syncwarp();
    {
        if (lane < 4) sts128(pk + lane * 16, 0, 0, 0, 0);
#pragma unroll 2
        for (int i = 0; i < 16; i++) {
            const int x = i * 128 + lane * 4;
            uint32_t v[5];
#pragma unroll
            for (int j = 0; j < 5; j++) {
                unsigned short hv;
                asm volatile("ld.shared.u16 %0, [%1];" : "=h"(hv) : "r"(kd + 2 * s4_idx(max(x + j - 1, 0))) : "memory");
                v[j] = hv;
            }
            if (x == 0) v[0] = 0;
            sts128(pk + 64 + x * 4, v[1] | (v[0] << 16), v[2] | (v[1] << 16), v[3] | (v[2] << 16), v[4] | (v[3] << 16));
        }
    }
    __syncthreads();
    {
        float acc[16][4];
#pragma unroll
        for (int i = 0; i < 16; i++) acc[i][0] = acc[i][1] = acc[i][2] = acc[i][3] = 0.f;
        const uint32_t ub = sb + S4_U + w * S4_US + 256 + (lane & 7) * 32 + ((lane >> 3) & 1) * 16 + (lane >> 4) * 256;
        const uint32_t kb = pk + 64 + (g - 2 * t) * 4;
#pragma unroll 1
        for (int j0 = 0; j0 < 8; j0++) {
            uint32_t B[8][4];
#pragma unroll
            for (int i = 0; i < 8; i++) ldsm4(B[i], ub + i * 512 - j0 * 32);
#pragma unroll
            for (int J = 0; J < 16; J++) {
                const uint32_t a = kb + j0 * 64 + J * 512;
                const uint32_t rm = lds32(a - 32), r0 = lds32(a), rp = lds32(a + 32);
#pragma unroll
                for (int I = J; I < 16; I++)
                    mma16816(acc[I], r0, rp, rm, r0, B[(I - J) >> 1][((I - J) & 1) * 2], B[(I - J) >> 1][((I - J) & 1) * 2 + 1]);
            }
        }
        __syncwarp();
        const uint32_t yb = pk + (lane & 7) * 32 + ((lane >> 3) & 1) * 16 + (lane >> 4) * 256;
#pragma unroll
        for (int i = 0; i < 8; i++)
            stsm4t(yb + i * 512, pack2(acc[2 * i][0], acc[2 * i][1]), pack2(acc[2 * i][2], acc[2 * i][3]),
                   pack2(acc[2 * i + 1][0], acc[2 * i + 1][1]), pack2(acc[2 * i + 1][2], acc[2 * i + 1][3]));
    }
    __syncthreads();
    {
        const uint2 dv = __ldg((const uint2*)(Dsk + d0 + 4 * t));
        bf16* dst = out + (size_t)(w * 128 + g) * 2048 + 1024 + d0 + 4 * t;
#pragma unroll
        for (int i = 0; i < 8; i++) {
            uint32_t y[4], x[4], o[4];
            ldsm4t(y, sb + S4_P + tr_off * S4_PS + (w * 128 + i * 16) * 2 + tr_l);
            ldsm4t(x, sb + S4_U + tr_off * S4_US + 256 + (w * 128 + i * 16) * 2 + tr_l);
#pragma unroll
            for (int j = 0; j < 4; j++) {
                const uint32_t dd = (j & 1) ? dv.y : dv.x;
                const uint32_t sk = pack2(bf_lo(x[j]) * bf_lo(dd), bf_hi(x[j]) * bf_hi(dd));
                o[j] = pack2(bf_lo(y[j]) + bf_lo(sk), bf_hi(y[j]) + bf_hi(sk));
            }
            *reinterpret_cast<uint2*>(dst + (size_t)(i * 16) * 2048) = make_uint2(o[0], o[1]);
            *reinterpret_cast<uint2*>(dst + (size_t)(i * 16 + 8) * 2048) = make_uint2(o[2], o[3]);
        }
    }
}

constexpr int WO_BN = 128, WO_PER = DM / WO_BN;
constexpr int BG_ITEMS = 16 * (16 + WO_PER);

template <int BN, typename ACC>
__device__ __forceinline__ void gemm_mainloop(ACC& acc, const GemmSmem& g, int cw, int nk) {
#pragma unroll 1
    for (int k0 = 0; k0 < nk; k0 += 4) {
#pragma unroll
        for (int s = 0; s < 4; s++) {
            mbar_wait(g.full + 8 * s, (k0 >> 2) & 1);
            gemm_kblock<BN>(acc, g.st + s * STAGE_BYTES, cw, s == 0 && k0 == 0);
            wg_wait<1>();
            if ((threadIdx.x & 127) == 0 && (s > 0 || k0 > 0)) mbar_arrive(g.empty + 8 * ((s + 3) & 3));
        }
    }
    wg_wait<0>();
    if ((threadIdx.x & 127) == 0) mbar_arrive(g.empty + 8 * 3);
}

__global__ void __launch_bounds__(384, 1)
k_bg(const __grid_constant__ CUtensorMap mx, const __grid_constant__ CUtensorMap mwq, const __grid_constant__ CUtensorMap mkv4,
     const __grid_constant__ CUtensorMap mkvm, const __grid_constant__ CUtensorMap mo, const __grid_constant__ CUtensorMap mwo,
     bf16* __restrict__ out) {
    extern __shared__ uint8_t smem_raw[];
    int blk, idx; bool is_qa;
    {
        const int it = blockIdx.x;
        if (it < 16) { blk = 0; idx = it; is_qa = true; }
        else {
            const int q = (it - 16) / (16 + WO_PER), rr = (it - 16) - q * (16 + WO_PER);
            if (q == 15) { blk = 15; idx = rr; is_qa = false; }
            else if (rr < 16) { blk = q + 1; idx = rr; is_qa = true; }
            else { blk = q; idx = rr - 16; is_qa = false; }
        }
    }
    GemmSmem g = gemm_setup(smem_raw);
    const int m0 = blk * 128, wg = threadIdx.x >> 7;
    if (wg == 0) {
        asm volatile("setmaxnreg.dec.sync.aligned.u32 40;");
        if (threadIdx.x == 0) {
            if (is_qa) {
                for (int it = 0; it < 20; it++) {
                    const int s = it & 3;
                    const uint32_t st = g.st + s * STAGE_BYTES, fb = g.full + 8 * s;
                    mbar_wait(g.empty + 8 * s, ((it >> 2) & 1) ^ 1);
                    if (it < 16) {
                        mbar_expect_tx(fb, STAGE_BYTES);
                        tma2d(st, &mx, it * 64, m0, fb);
                        tma3d(st + 16384, &mwq, 0, it * 64, idx * 4, fb);
                    } else {
                        mbar_expect_tx(fb, 40960);
                        tma3d(st, &mkv4, 0, m0 + s * 32, idx * 4, fb);
                        tma3d(st + 16384, &mkv4, 0, m0 + s * 32, 64 + idx * 4, fb);
                    }
                }
                wait_flag(g_flag + 2 * idx, 4 * blk + 4);
                wait_flag(g_flag + 2 * idx + 1, 4 * blk + 4);
                asm volatile("fence.proxy.async.global;" ::: "memory");
                for (int s = 0; s < 4; s++) {
                    const uint32_t st = g.st + s * STAGE_BYTES, fb = g.full + 8 * s;
                    tma3d(st + 32768, &mkvm, 0, (blk * 4 + s) * 8, idx * 4, fb);
                    tma3d(st + 36864, &mkvm, 0, (blk * 4 + s) * 8, 64 + idx * 4, fb);
                }
            } else {
                wait_flag(g_flag + 64 + blk, 16);
                asm volatile("fence.proxy.async.global;" ::: "memory");
                for (int it = 0; it < 64; it++) {
                    const int s = it & 3;
                    const uint32_t st = g.st + s * STAGE_BYTES, fb = g.full + 8 * s;
                    mbar_wait(g.empty + 8 * s, ((it >> 2) & 1) ^ 1);
                    mbar_expect_tx(fb, 16384 + WO_BN * 128);
                    tma2d(st, &mo, it * 64, m0, fb);
                    tma3d(st + 16384, &mwo, 0, it * 64, idx * (WO_BN / 64), fb);
                }
            }
        }
    } else {
        asm volatile("setmaxnreg.inc.sync.aligned.u32 232;");
        const int cw = wg - 1, ww = (threadIdx.x >> 5) & 3, lane = threadIdx.x & 31, gq = lane >> 2, t = lane & 3;
        const int row = m0 + cw * 64 + ww * 16 + gq;
        if (is_qa) {
            uint32_t q[64];
            {
                float acc[128];
                gemm_mainloop<256>(acc, g, cw, 16);
#pragma unroll
                for (int i = 0; i < 64; i++) q[i] = pack2(acc[2 * i], acc[2 * i + 1]);
            }
            const int sg = cw * 2 + (ww >> 1), hf = ww & 1;
            const uint32_t st = g.st + sg * STAGE_BYTES;
            mbar_wait(g.full + 8 * sg, 0);
            const float scale = 0.08838834764831845f, l2e = 1.4426950408889634f;
            const int r8 = lane & 7, m4 = lane >> 3;
#pragma unroll
            for (int hh = 0; hh < 2; hh++) {
                float sc[5][4];
#pragma unroll
                for (int nt = 0; nt < 5; nt++) {
                    sc[nt][0] = sc[nt][1] = sc[nt][2] = sc[nt][3] = 0.f;
                    if (nt < 3 || hf) {
#pragma unroll
                        for (int kp = 0; kp < 4; kp++) {
                            const int nb = hh * 2 + (kp >> 1);
                            const uint32_t base = nt == 0 ? st + 32768 + nb * 1024 : st + nb * 4096 + (nt - 1) * 1024;
                            uint32_t b[4];
                            ldsm4(b, base + r8 * 128 + ((((kp & 1) * 4 + m4) ^ r8) << 4));
                            const int j = (hh * 16 + kp * 4) * 2;
                            mma16816(sc[nt], q[j], q[j + 1], q[j + 2], q[j + 3], b[0], b[1]);
                            mma16816(sc[nt], q[j + 4], q[j + 5], q[j + 6], q[j + 7], b[2], b[3]);
                        }
                    }
                }
                float mx[2] = {-3.0e38f, -3.0e38f};
#pragma unroll
                for (int nt = 0; nt < 5; nt++)
#pragma unroll
                    for (int c = 0; c < 4; c++) {
                        float v = bf_round(bf_round(sc[nt][c]) * scale);
                        if (nt > 0 && (nt - 1) * 8 + 2 * t + (c & 1) > hf * 16 + gq + (c >> 1) * 8) v = -1.0e9f;
                        sc[nt][c] = v;
                        mx[c >> 1] = fmaxf(mx[c >> 1], v);
                    }
                float sum[2] = {0.f, 0.f};
#pragma unroll
                for (int i = 0; i < 2; i++) {
                    mx[i] = fmaxf(mx[i], __shfl_xor_sync(~0u, mx[i], 1));
                    mx[i] = fmaxf(mx[i], __shfl_xor_sync(~0u, mx[i], 2));
                }
#pragma unroll
                for (int nt = 0; nt < 5; nt++)
#pragma unroll
                    for (int c = 0; c < 4; c++) {
                        sc[nt][c] = ex2((sc[nt][c] - mx[c >> 1]) * l2e);
                        sum[c >> 1] += sc[nt][c];
                    }
#pragma unroll
                for (int i = 0; i < 2; i++) {
                    sum[i] += __shfl_xor_sync(~0u, sum[i], 1);
                    sum[i] += __shfl_xor_sync(~0u, sum[i], 2);
                    sum[i] = __frcp_rn(sum[i]);
                }
                uint32_t p[5][2];
#pragma unroll
                for (int nt = 0; nt < 5; nt++) {
                    p[nt][0] = pack2(sc[nt][0] * sum[0], sc[nt][1] * sum[0]);
                    p[nt][1] = pack2(sc[nt][2] * sum[1], sc[nt][3] * sum[1]);
                }
                bf16* dst = g_o + (size_t)row * HD + idx * 256 + hh * 128 + t * 8;
#pragma unroll
                for (int G = 0; G < 4; G++) {
                    const int nb = hh * 2 + (G >> 1), c0 = (G & 1) * 4;
                    float o[4][4];
#pragma unroll
                    for (int i = 0; i < 4; i++) o[i][0] = o[i][1] = o[i][2] = o[i][3] = 0.f;
                    uint32_t b[4];
                    ldsm4t(b, st + 36864 + nb * 1024 + r8 * 128 + (((c0 + m4) ^ r8) << 4));
#pragma unroll
                    for (int i = 0; i < 4; i++) mma1688(o[i], p[0][0], p[0][1], b[i]);
#pragma unroll
                    for (int kk = 0; kk < 2; kk++) {
                        if (kk == 0 || hf) {
#pragma unroll
                            for (int i = 0; i < 2; i++) {
                                ldsm4t(b, st + 16384 + nb * 4096 + (kk * 16 + (m4 & 1) * 8 + r8) * 128 + (((c0 + 2 * i + (m4 >> 1)) ^ r8) << 4));
                                mma16816(o[2 * i], p[1 + 2 * kk][0], p[1 + 2 * kk][1], p[2 + 2 * kk][0], p[2 + 2 * kk][1], b[0], b[1]);
                                mma16816(o[2 * i + 1], p[1 + 2 * kk][0], p[1 + 2 * kk][1], p[2 + 2 * kk][0], p[2 + 2 * kk][1], b[2], b[3]);
                            }
                        }
                    }
#pragma unroll
                    for (int rr = 0; rr < 2; rr++) {
                        uint32_t r0 = pack2(o[0][2 * rr], o[0][2 * rr + 1]), r1 = pack2(o[1][2 * rr], o[1][2 * rr + 1]);
                        uint32_t r2 = pack2(o[2][2 * rr], o[2][2 * rr + 1]), r3 = pack2(o[3][2 * rr], o[3][2 * rr + 1]);
                        quad_transpose(r0, r1, r2, r3, t);
                        *reinterpret_cast<uint4*>(dst + (size_t)rr * 8 * HD + G * 32) = make_uint4(r0, r1, r2, r3);
                    }
                }
            }
            bar_sync(1, 256);
            if (threadIdx.x == 128)
                asm volatile("fence.acq_rel.gpu;\nred.relaxed.gpu.global.add.u32 [%0], 1;" ::"l"(g_flag + 64 + blk) : "memory");
        } else {
            float acc[WO_BN / 2];
            gemm_mainloop<WO_BN>(acc, g, cw, 64);
            bf16* dst = out + (size_t)row * 2048 + idx * WO_BN + t * 8;
#pragma unroll
            for (int G = 0; G < WO_BN / 32; G++)
#pragma unroll
                for (int rr = 0; rr < 2; rr++) {
                    uint32_t r0 = pack2(acc[16 * G + 2 * rr], acc[16 * G + 2 * rr + 1]), r1 = pack2(acc[16 * G + 4 + 2 * rr], acc[16 * G + 5 + 2 * rr]);
                    uint32_t r2 = pack2(acc[16 * G + 8 + 2 * rr], acc[16 * G + 9 + 2 * rr]), r3 = pack2(acc[16 * G + 12 + 2 * rr], acc[16 * G + 13 + 2 * rr]);
                    quad_transpose(r0, r1, r2, r3, t);
                    *reinterpret_cast<uint4*>(dst + (size_t)rr * 8 * 2048 + G * 32) = make_uint4(r0, r1, r2, r3);
                }
        }
    }
}

typedef CUresult (*EncodeFn)(CUtensorMap*, CUtensorMapDataType, cuuint32_t, void*, const cuuint64_t*, const cuuint64_t*,
                             const cuuint32_t*, const cuuint32_t*, CUtensorMapInterleave, CUtensorMapSwizzle,
                             CUtensorMapL2promotion, CUtensorMapFloatOOBfill);

static void map2d(EncodeFn enc, CUtensorMap* m, const void* p, int rows, int cols, int box_rows) {
    cuuint64_t dim[2] = {(cuuint64_t)cols, (cuuint64_t)rows}, str[1] = {(cuuint64_t)cols * 2};
    cuuint32_t box[2] = {64, (cuuint32_t)box_rows}, es[2] = {1, 1};
    enc(m, CU_TENSOR_MAP_DATA_TYPE_BFLOAT16, 2, (void*)p, dim, str, box, es, CU_TENSOR_MAP_INTERLEAVE_NONE,
        CU_TENSOR_MAP_SWIZZLE_128B, CU_TENSOR_MAP_L2_PROMOTION_L2_256B, CU_TENSOR_MAP_FLOAT_OOB_FILL_NONE);
}
static void map3d(EncodeFn enc, CUtensorMap* m, const void* p, int rows, int cols, int box_rows, int nblk) {
    cuuint64_t dim[3] = {64, (cuuint64_t)rows, (cuuint64_t)cols / 64}, str[2] = {(cuuint64_t)cols * 2, 128};
    cuuint32_t box[3] = {64, (cuuint32_t)box_rows, (cuuint32_t)nblk}, es[3] = {1, 1, 1};
    enc(m, CU_TENSOR_MAP_DATA_TYPE_BFLOAT16, 3, (void*)p, dim, str, box, es, CU_TENSOR_MAP_INTERLEAVE_NONE,
        CU_TENSOR_MAP_SWIZZLE_128B, CU_TENSOR_MAP_L2_PROMOTION_L2_256B, CU_TENSOR_MAP_FLOAT_OOB_FILL_NONE);
}

#define USE_PDL 1

extern "C" void kernel_launch(void* const* d_in, const int* in_sizes, int n_in, void* d_out, int out_size) {
    const bf16 *x = (const bf16*)d_in[0], *mem0 = (const bf16*)d_in[1], *Wq = (const bf16*)d_in[2], *Wk = (const bf16*)d_in[3];
    const bf16 *Wv = (const bf16*)d_in[4], *Wo = (const bf16*)d_in[5];
    const bf16 *u = (const bf16*)d_in[7], *Are = (const bf16*)d_in[8], *Aim = (const bf16*)d_in[9], *Bre = (const bf16*)d_in[10];
    const bf16 *Bim = (const bf16*)d_in[11], *Cre = (const bf16*)d_in[12], *Cim = (const bf16*)d_in[13];
    const bf16 *logdt = (const bf16*)d_in[14], *Dsk = (const bf16*)d_in[15];
    bf16* out = (bf16*)d_out;

    void* fn = nullptr;
    cudaDriverEntryPointQueryResult qr;
    cudaGetDriverEntryPoint("cuTensorMapEncodeTiled", &fn, cudaEnableDefault, &qr);
    EncodeFn enc = (EncodeFn)fn;
    void *kv, *kvm, *o;
    cudaGetSymbolAddress(&kv, g_kv);
    cudaGetSymbolAddress(&kvm, g_kvm);
    cudaGetSymbolAddress(&o, g_o);
    CUtensorMap mx, mwq, mwk, mwv, mwo, mkv2, mkv4, mkvm, mo;
    map2d(enc, &mx, x, SEQ, DM, 128);
    map2d(enc, &mo, o, SEQ, HD, 128);
    map3d(enc, &mwq, Wq, DM, HD, 64, 4);
    map3d(enc, &mwk, Wk, DM, HD, 64, 4);
    map3d(enc, &mwv, Wv, DM, HD, 64, 4);
    map3d(enc, &mwo, Wo, HD, DM, 64, WO_BN / 64);
    map3d(enc, &mkv2, kv, SEQ, 8192, 32, 2);
    map3d(enc, &mkv4, kv, SEQ, 8192, 32, 4);
    map3d(enc, &mkvm, kvm, NSEG * 8, 8192, 8, 4);
    cudaFuncSetAttribute(k_kv, cudaFuncAttributeMaxDynamicSharedMemorySize, GEMM_SMEM);
    cudaFuncSetAttribute(k_bg, cudaFuncAttributeMaxDynamicSharedMemorySize, GEMM_SMEM);
    cudaFuncSetAttribute(k_chain, cudaFuncAttributeMaxDynamicSharedMemorySize, CHAIN_SMEM);
    cudaFuncSetAttribute(k_s4, cudaFuncAttributeMaxDynamicSharedMemorySize, S4_SMEM);

    cudaStream_t st = cudaStreamPerThread;
    k_kv<<<132, 384, GEMM_SMEM, st>>>(mx, mwk, mwv);
    k_chain<<<96, 256, CHAIN_SMEM, st>>>(mem0, Wq, Wk, Wv, Wo, mkv2);
    cudaLaunchAttribute pdl[1];
    pdl[0].id = cudaLaunchAttributeProgrammaticStreamSerialization;
    pdl[0].val.programmaticStreamSerializationAllowed = 1;
    cudaLaunchConfig_t cfg = {};
    cfg.stream = st; cfg.attrs = pdl; cfg.numAttrs = USE_PDL;
    cfg.gridDim = dim3(64); cfg.blockDim = dim3(512); cfg.dynamicSmemBytes = S4_SMEM;
    cudaLaunchKernelEx(&cfg, k_s4, u, Are, Aim, Bre, Bim, Cre, Cim, logdt, Dsk, out);
    cfg.gridDim = dim3(BG_ITEMS); cfg.blockDim = dim3(384); cfg.dynamicSmemBytes = GEMM_SMEM;
    cudaLaunchKernelEx(&cfg, k_bg, mx, mwq, mkv4, mkvm, mo, mwo, out);
}
```

```cpp
#include <cuda_runtime.h>
#include <cuda_bf16.h>
#include <cuda.h>
#include <stdint.h>

typedef __nv_bfloat16 bf16;

constexpr int SEQ = 2048, DM = 1024, HD = 4096, NSEG = 64;

__device__ __align__(1024) bf16 g_kv[(size_t)SEQ * 8192];
__device__ __align__(1024) bf16 g_kvm[(size_t)NSEG * 8 * 8192];
__device__ __align__(1024) bf16 g_o[(size_t)SEQ * HD];
__device__ __align__(1024) uint2 g_memx[NSEG * 64 * 32];
__device__ __align__(1024) uint2 g_part[64 * 32 * 32];
__device__ __align__(1024) uint32_t g_flag[256];

__device__ __forceinline__ uint32_t smem_u32(const void* p) { return (uint32_t)__cvta_generic_to_shared(p); }
__device__ __forceinline__ void mbar_init(uint32_t bar, uint32_t cnt) {
    asm volatile("mbarrier.init.shared::cta.b64 [%0], %1;" ::"r"(bar), "r"(cnt) : "memory");
}
__device__ __forceinline__ void mbar_expect_tx(uint32_t bar, uint32_t bytes) {
    asm volatile("mbarrier.arrive.expect_tx.shared::cta.b64 _, [%0], %1;" ::"r"(bar), "r"(bytes) : "memory");
}
__device__ __forceinline__ void mbar_arrive(uint32_t bar) {
    asm volatile("mbarrier.arrive.shared::cta.b64 _, [%0];" ::"r"(bar) : "memory");
}
__device__ __forceinline__ bool mbar_try(uint32_t bar, uint32_t parity) {
    uint32_t ok;
    asm volatile("{\n.reg .pred p;\nmbarrier.try_wait.parity.shared::cta.b64 p, [%1], %2;\nselp.u32 %0, 1, 0, p;\n}"
                 : "=r"(ok) : "r"(bar), "r"(parity) : "memory");
    return ok;
}
__device__ __forceinline__ bool mbar_try_cluster(uint32_t bar, uint32_t parity) {
    uint32_t ok;
    asm volatile("{\n.reg .pred p;\nmbarrier.try_wait.parity.acquire.cluster.shared::cta.b64 p, [%1], %2;\nselp.u32 %0, 1, 0, p;\n}"
                 : "=r"(ok) : "r"(bar), "r"(parity) : "memory");
    return ok;
}
constexpr int SPIN_LIMIT = 1 << 20;
__device__ __forceinline__ void mbar_wait(uint32_t bar, uint32_t parity) {
    int n = 0;
    while (!mbar_try(bar, parity)) { if (++n > SPIN_LIMIT) __trap(); }
}
__device__ __forceinline__ void mbar_wait_cluster(uint32_t bar, uint32_t parity) {
    int n = 0;
    while (!mbar_try_cluster(bar, parity)) { if (++n > SPIN_LIMIT) __trap(); }
}
__device__ __forceinline__ void tma2d(uint32_t dst, const CUtensorMap* m, int c0, int c1, uint32_t bar) {
    asm volatile("cp.async.bulk.tensor.2d.shared::cluster.global.mbarrier::complete_tx::bytes [%0], [%1, {%3, %4}], [%2];"
                 ::"r"(dst), "l"(m), "r"(bar), "r"(c0), "r"(c1) : "memory");
}
__device__ __forceinline__ void tma3d(uint32_t dst, const CUtensorMap* m, int c0, int c1, int c2, uint32_t bar) {
    asm volatile("cp.async.bulk.tensor.3d.shared::cluster.global.mbarrier::complete_tx::bytes [%0], [%1, {%3, %4, %5}], [%2];"
                 ::"r"(dst), "l"(m), "r"(bar), "r"(c0), "r"(c1), "r"(c2) : "memory");
}
__device__ __forceinline__ uint32_t pack2(float lo, float hi) {
    uint32_t r;
    asm("cvt.rn.bf16x2.f32 %0, %1, %2;" : "=r"(r) : "f"(hi), "f"(lo));
    return r;
}
__device__ __forceinline__ float bf_lo(uint32_t v) { return __uint_as_float(v << 16); }
__device__ __forceinline__ float bf_hi(uint32_t v) { return __uint_as_float(v & 0xffff0000u); }
__device__ __forceinline__ float bf_round(float x) { return bf_lo(pack2(x, 0.f)); }
__device__ __forceinline__ float ex2(float x) { float y; asm("ex2.approx.ftz.f32 %0, %1;" : "=f"(y) : "f"(x)); return y; }
__device__ __forceinline__ void mma16816(float (&c)[4], uint32_t a0, uint32_t a1, uint32_t a2, uint32_t a3, uint32_t b0, uint32_t b1) {
    asm volatile("mma.sync.aligned.m16n8k16.row.col.f32.bf16.bf16.f32 {%0,%1,%2,%3}, {%4,%5,%6,%7}, {%8,%9}, {%0,%1,%2,%3};"
                 : "+f"(c[0]), "+f"(c[1]), "+f"(c[2]), "+f"(c[3]) : "r"(a0), "r"(a1), "r"(a2), "r"(a3), "r"(b0), "r"(b1));
}
__device__ __forceinline__ void mma1688(float (&c)[4], uint32_t a0, uint32_t a1, uint32_t b0) {
    asm volatile("mma.sync.aligned.m16n8k8.row.col.f32.bf16.bf16.f32 {%0,%1,%2,%3}, {%4,%5}, {%6}, {%0,%1,%2,%3};"
                 : "+f"(c[0]), "+f"(c[1]), "+f"(c[2]), "+f"(c[3]) : "r"(a0), "r"(a1), "r"(b0));
}
__device__ __forceinline__ void ldsm4(uint32_t (&r)[4], uint32_t a) {
    asm volatile("ldmatrix.sync.aligned.m8n8.x4.shared.b16 {%0,%1,%2,%3}, [%4];"
                 : "=r"(r[0]), "=r"(r[1]), "=r"(r[2]), "=r"(r[3]) : "r"(a) : "memory");
}
__device__ __forceinline__ void ldsm4t(uint32_t (&r)[4], uint32_t a) {
    asm volatile("ldmatrix.sync.aligned.m8n8.x4.trans.shared.b16 {%0,%1,%2,%3}, [%4];"
                 : "=r"(r[0]), "=r"(r[1]), "=r"(r[2]), "=r"(r[3]) : "r"(a) : "memory");
}
__device__ __forceinline__ void ldsm2t(uint32_t& r0, uint32_t& r1, uint32_t a) {
    asm volatile("ldmatrix.sync.aligned.m8n8.x2.trans.shared.b16 {%0,%1}, [%2];" : "=r"(r0), "=r"(r1) : "r"(a) : "memory");
}
__device__ __forceinline__ void stsm4t(uint32_t a, uint32_t r0, uint32_t r1, uint32_t r2, uint32_t r3) {
    asm volatile("stmatrix.sync.aligned.m8n8.x4.trans.shared.b16 [%0], {%1,%2,%3,%4};"
                 ::"r"(a), "r"(r0), "r"(r1), "r"(r2), "r"(r3) : "memory");
}
__device__ __forceinline__ void lds128(uint32_t (&r)[4], uint32_t a) {
    asm volatile("ld.shared.v4.u32 {%0,%1,%2,%3}, [%4];" : "=r"(r[0]), "=r"(r[1]), "=r"(r[2]), "=r"(r[3]) : "r"(a) : "memory");
}
__device__ __forceinline__ float4 lds128f(uint32_t a) {
    float4 v;
    asm volatile("ld.shared.v4.f32 {%0,%1,%2,%3}, [%4];" : "=f"(v.x), "=f"(v.y), "=f"(v.z), "=f"(v.w) : "r"(a) : "memory");
    return v;
}
__device__ __forceinline__ float2 lds64f(uint32_t a) {
    float2 v;
    asm volatile("ld.shared.v2.f32 {%0,%1}, [%2];" : "=f"(v.x), "=f"(v.y) : "r"(a) : "memory");
    return v;
}
__device__ __forceinline__ uint32_t lds32(uint32_t a) {
    uint32_t v;
    asm volatile("ld.shared.u32 %0, [%1];" : "=r"(v) : "r"(a) : "memory");
    return v;
}
__device__ __forceinline__ void sts128(uint32_t a, uint32_t r0, uint32_t r1, uint32_t r2, uint32_t r3) {
    asm volatile("st.shared.v4.u32 [%0], {%1,%2,%3,%4};" ::"r"(a), "r"(r0), "r"(r1), "r"(r2), "r"(r3) : "memory");
}
__device__ __forceinline__ void sts128f(uint32_t a, float r0, float r1, float r2, float r3) {
    asm volatile("st.shared.v4.f32 [%0], {%1,%2,%3,%4};" ::"r"(a), "f"(r0), "f"(r1), "f"(r2), "f"(r3) : "memory");
}
__device__ __forceinline__ void sts64(uint32_t a, uint32_t r0, uint32_t r1) {
    asm volatile("st.shared.v2.u32 [%0], {%1,%2};" ::"r"(a), "r"(r0), "r"(r1) : "memory");
}
__device__ __forceinline__ void sts64f(uint32_t a, float r0, float r1) {
    asm volatile("st.shared.v2.f32 [%0], {%1,%2};" ::"r"(a), "f"(r0), "f"(r1) : "memory");
}
__device__ __forceinline__ void sts32f(uint32_t a, float r0) {
    asm volatile("st.shared.f32 [%0], %1;" ::"r"(a), "f"(r0) : "memory");
}
__device__ __forceinline__ uint2 ld_rlx64(const uint2* p) {
    uint2 v;
    asm volatile("{\n.reg .b64 t;\nld.relaxed.gpu.global.b64 t, [%2];\nmov.b64 {%0,%1}, t;\n}" : "=r"(v.x), "=r"(v.y) : "l"(p) : "memory");
    return v;
}
__device__ __forceinline__ void st_rlx64(uint2* p, uint32_t x, uint32_t y) {
    asm volatile("{\n.reg .b64 t;\nmov.b64 t, {%1,%2};\nst.relaxed.gpu.global.b64 [%0], t;\n}" ::"l"(p), "r"(x), "r"(y) : "memory");
}
__device__ __forceinline__ uint32_t ld_acq32(const uint32_t* p) {
    uint32_t v;
    asm volatile("ld.acquire.gpu.global.u32 %0, [%1];" : "=r"(v) : "l"(p) : "memory");
    return v;
}
__device__ __forceinline__ void wait_flag(const uint32_t* p, uint32_t need) {
    int n = 0;
    while (ld_acq32(p) < need) { __nanosleep(200); if (++n > SPIN_LIMIT) __trap(); }
}
__device__ __forceinline__ void bar_sync(int id, int n) { asm volatile("bar.sync %0, %1;" ::"r"(id), "r"(n) : "memory"); }
__device__ __forceinline__ void wg_fence() { asm volatile("wgmma.fence.sync.aligned;" ::: "memory"); }
__device__ __forceinline__ void wg_commit() { asm volatile("wgmma.commit_group.sync.aligned;" ::: "memory"); }
template <int N> __device__ __forceinline__ void wg_wait() { asm volatile("wgmma.wait_group.sync.aligned %0;" ::"n"(N) : "memory"); }
__device__ __forceinline__ uint64_t desc_sw128(uint32_t addr, uint32_t lbo, uint32_t sbo) {
    return (uint64_t)((addr & 0x3FFFF) >> 4) | ((uint64_t)(lbo >> 4) << 16) | ((uint64_t)(sbo >> 4) << 32) | (1ull << 62);
}
__device__ __forceinline__ void quad_transpose(uint32_t& r0, uint32_t& r1, uint32_t& r2, uint32_t& r3, int t) {
    const bool o = t & 1, h = t & 2;
    uint32_t s0 = __shfl_xor_sync(~0u, o ? r0 : r1, 1), s1 = __shfl_xor_sync(~0u, o ? r2 : r3, 1);
    uint32_t a0 = o ? s0 : r0, a1 = o ? r1 : s0, a2 = o ? s1 : r2, a3 = o ? r3 : s1;
    s0 = __shfl_xor_sync(~0u, h ? a0 : a2, 2); s1 = __shfl_xor_sync(~0u, h ? a1 : a3, 2);
    r0 = h ? s0 : a0; r1 = h ? s1 : a1; r2 = h ? a2 : s0; r3 = h ? a3 : s1;
}

__device__ __forceinline__ void wgmma_n256(float (&d)[128], uint64_t da, uint64_t db, int sd) {
    asm volatile("{\n.reg .pred p;\nsetp.ne.b32 p, %130, 0;\n"
        "wgmma.mma_async.sync.aligned.m64n256k16.f32.bf16.bf16 "
        "{%0,%1,%2,%3,%4,%5,%6,%7,%8,%9,%10,%11,%12,%13,%14,%15,"
        "%16,%17,%18,%19,%20,%21,%22,%23,%24,%25,%26,%27,%28,%29,%30,%31,"
        "%32,%33,%34,%35,%36,%37,%38,%39,%40,%41,%42,%43,%44,%45,%46,%47,"
        "%48,%49,%50,%51,%52,%53,%54,%55,%56,%57,%58,%59,%60,%61,%62,%63,"
        "%64,%65,%66,%67,%68,%69,%70,%71,%72,%73,%74,%75,%76,%77,%78,%79,"
        "%80,%81,%82,%83,%84,%85,%86,%87,%88,%89,%90,%91,%92,%93,%94,%95,"
        "%96,%97,%98,%99,%100,%101,%102,%103,%104,%105,%106,%107,%108,%109,%110,%111,"
        "%112,%113,%114,%115,%116,%117,%118,%119,%120,%121,%122,%123,%124,%125,%126,%127}, %128, %129, p, 1, 1, 0, 1;\n}\n"
        : "+f"(d[0]), "+f"(d[1]), "+f"(d[2]), "+f"(d[3]), "+f"(d[4]), "+f"(d[5]), "+f"(d[6]), "+f"(d[7]),
          "+f"(d[8]), "+f"(d[9]), "+f"(d[10]), "+f"(d[11]), "+f"(d[12]), "+f"(d[13]), "+f"(d[14]), "+f"(d[15]),
          "+f"(d[16]), "+f"(d[17]), "+f"(d[18]), "+f"(d[19]), "+f"(d[20]), "+f"(d[21]), "+f"(d[22]), "+f"(d[23]),
          "+f"(d[24]), "+f"(d[25]), "+f"(d[26]), "+f"(d[27]), "+f"(d[28]), "+f"(d[29]), "+f"(d[30]), "+f"(d[31]),
          "+f"(d[32]), "+f"(d[33]), "+f"(d[34]), "+f"(d[35]), "+f"(d[36]), "+f"(d[37]), "+f"(d[38]), "+f"(d[39]),
          "+f"(d[40]), "+f"(d[41]), "+f"(d[42]), "+f"(d[43]), "+f"(d[44]), "+f"(d[45]), "+f"(d[46]), "+f"(d[47]),
          "+f"(d[48]), "+f"(d[49]), "+f"(d[50]), "+f"(d[51]), "+f"(d[52]), "+f"(d[53]), "+f"(d[54]), "+f"(d[55]),
          "+f"(d[56]), "+f"(d[57]), "+f"(d[58]), "+f"(d[59]), "+f"(d[60]), "+f"(d[61]), "+f"(d[62]), "+f"(d[63]),
          "+f"(d[64]), "+f"(d[65]), "+f"(d[66]), "+f"(d[67]), "+f"(d[68]), "+f"(d[69]), "+f"(d[70]), "+f"(d[71]),
          "+f"(d[72]), "+f"(d[73]), "+f"(d[74]), "+f"(d[75]), "+f"(d[76]), "+f"(d[77]), "+f"(d[78]), "+f"(d[79]),
          "+f"(d[80]), "+f"(d[81]), "+f"(d[82]), "+f"(d[83]), "+f"(d[84]), "+f"(d[85]), "+f"(d[86]), "+f"(d[87]),
          "+f"(d[88]), "+f"(d[89]), "+f"(d[90]), "+f"(d[91]), "+f"(d[92]), "+f"(d[93]), "+f"(d[94]), "+f"(d[95]),
          "+f"(d[96]), "+f"(d[97]), "+f"(d[98]), "+f"(d[99]), "+f"(d[100]), "+f"(d[101]), "+f"(d[102]), "+f"(d[103]),
          "+f"(d[104]), "+f"(d[105]), "+f"(d[106]), "+f"(d[107]), "+f"(d[108]), "+f"(d[109]), "+f"(d[110]), "+f"(d[111]),
          "+f"(d[112]), "+f"(d[113]), "+f"(d[114]), "+f"(d[115]), "+f"(d[116]), "+f"(d[117]), "+f"(d[118]), "+f"(d[119]),
          "+f"(d[120]), "+f"(d[121]), "+f"(d[122]), "+f"(d[123]), "+f"(d[124]), "+f"(d[125]), "+f"(d[126]), "+f"(d[127])
        : "l"(da), "l"(db), "r"(sd));
}

__device__ __forceinline__ void wgmma_n128(float (&d)[64], uint64_t da, uint64_t db, int sd) {
    asm volatile("{\n.reg .pred p;\nsetp.ne.b32 p, %66, 0;\n"
        "wgmma.mma_async.sync.aligned.m64n128k16.f32.bf16.bf16 "
        "{%0,%1,%2,%3,%4,%5,%6,%7,%8,%9,%10,%11,%12,%13,%14,%15,"
        "%16,%17,%18,%19,%20,%21,%22,%23,%24,%25,%26,%27,%28,%29,%30,%31,"
        "%32,%33,%34,%35,%36,%37,%38,%39,%40,%41,%42,%43,%44,%45,%46,%47,"
        "%48,%49,%50,%51,%52,%53,%54,%55,%56,%57,%58,%59,%60,%61,%62,%63}, %64, %65, p, 1, 1, 0, 1;\n}\n"
        : "+f"(d[0]), "+f"(d[1]), "+f"(d[2]), "+f"(d[3]), "+f"(d[4]), "+f"(d[5]), "+f"(d[6]), "+f"(d[7]),
          "+f"(d[8]), "+f"(d[9]), "+f"(d[10]), "+f"(d[11]), "+f"(d[12]), "+f"(d[13]), "+f"(d[14]), "+f"(d[15]),
          "+f"(d[16]), "+f"(d[17]), "+f"(d[18]), "+f"(d[19]), "+f"(d[20]), "+f"(d[21]), "+f"(d[22]), "+f"(d[23]),
          "+f"(d[24]), "+f"(d[25]), "+f"(d[26]), "+f"(d[27]), "+f"(d[28]), "+f"(d[29]), "+f"(d[30]), "+f"(d[31]),
          "+f"(d[32]), "+f"(d[33]), "+f"(d[34]), "+f"(d[35]), "+f"(d[36]), "+f"(d[37]), "+f"(d[38]), "+f"(d[39]),
          "+f"(d[40]), "+f"(d[41]), "+f"(d[42]), "+f"(d[43]), "+f"(d[44]), "+f"(d[45]), "+f"(d[46]), "+f"(d[47]),
          "+f"(d[48]), "+f"(d[49]), "+f"(d[50]), "+f"(d[51]), "+f"(d[52]), "+f"(d[53]), "+f"(d[54]), "+f"(d[55]),
          "+f"(d[56]), "+f"(d[57]), "+f"(d[58]), "+f"(d[59]), "+f"(d[60]), "+f"(d[61]), "+f"(d[62]), "+f"(d[63])
        : "l"(da), "l"(db), "r"(sd));
}

constexpr int STAGE_BYTES = 49152, NSTAGE = 4;
constexpr int GEMM_SMEM = NSTAGE * STAGE_BYTES + 1024 + 128;

struct GemmSmem { uint32_t st, full, empty; };
__device__ __forceinline__ GemmSmem gemm_setup(uint8_t* raw) {
    GemmSmem g;
    uint32_t base = smem_u32(raw);
    g.st = (base + 127 + 1024) & ~1023u;
    g.full = base; g.empty = base + 64;
    if (threadIdx.x == 0) {
        for (int s = 0; s < NSTAGE; s++) { mbar_init(g.full + 8 * s, 1); mbar_init(g.empty + 8 * s, 2); }
        asm volatile("fence.mbarrier_init.release.cluster;" ::: "memory");
        asm volatile("fence.proxy.async.shared::cta;" ::: "memory");
    }
    __syncthreads();
    return g;
}
template <int BN, typename ACC>
__device__ __forceinline__ void gemm_kblock(ACC& acc, uint32_t stage, int wg, bool first) {
    const uint64_t da = desc_sw128(stage + wg * 8192, 16, 1024);
    const uint64_t db = desc_sw128(stage + 16384, 8192, 1024);
    wg_fence();
#pragma unroll
    for (int k = 0; k < 4; k++) {
        if constexpr (BN == 256) wgmma_n256(acc, da + k * 2, db + k * 128, first && k == 0 ? 0 : 1);
        else wgmma_n128(acc, da + k * 2, db + k * 128, first && k == 0 ? 0 : 1);
    }
    wg_commit();
}

__device__ __forceinline__ void kv_store_unit(const uint32_t (&pk)[64], int u, bf16* dst, int t) {
    const int G = (u >> 2) * 2 + (u & 1), hh = (u >> 1) & 1;
    uint32_t r0 = pk[(4 * G + 0) * 2 + hh], r1 = pk[(4 * G + 1) * 2 + hh], r2 = pk[(4 * G + 2) * 2 + hh], r3 = pk[(4 * G + 3) * 2 + hh];
    quad_transpose(r0, r1, r2, r3, t);
    *reinterpret_cast<uint4*>(dst + (size_t)hh * 8 * 8192 + G * 32) = make_uint4(r0, r1, r2, r3);
}

__global__ void __launch_bounds__(384, 1)
k_kv(const __grid_constant__ CUtensorMap mx, const __grid_constant__ CUtensorMap mwk, const __grid_constant__ CUtensorMap mwv) {
    extern __shared__ uint8_t smem_raw[];
    const int c = blockIdx.x;
    if (c >= 128) {
        const int i0 = (c - 128) * 384 + threadIdx.x;
        const uint4 ones = make_uint4(~0u, ~0u, ~0u, ~0u);
        for (int i = i0; i < NSEG * 64 * 32 / 2; i += 4 * 384) reinterpret_cast<uint4*>(g_memx)[i] = ones;
        for (int i = i0; i < 64 * 32 * 32 / 2; i += 4 * 384) reinterpret_cast<uint4*>(g_part)[i] = ones;
        if (i0 < 256) g_flag[i0] = 0;
        return;
    }
    GemmSmem g = gemm_setup(smem_raw);
    const int m0 = (c & 15) * 128, nb0 = c >> 4;
    const int wg = threadIdx.x >> 7;
    if (wg == 0) {
        asm volatile("setmaxnreg.dec.sync.aligned.u32 40;");
        if (threadIdx.x == 0) {
            for (int it = 0; it < 64; it++) {
                const int s = it & 3, tile = it >> 4, kb = it & 15;
                mbar_wait(g.empty + 8 * s, ((it >> 2) & 1) ^ 1);
                mbar_expect_tx(g.full + 8 * s, STAGE_BYTES);
                const int nb = nb0 + 8 * tile;
                tma2d(g.st + s * STAGE_BYTES, &mx, kb * 64, m0, g.full + 8 * s);
                tma3d(g.st + s * STAGE_BYTES + 16384, nb < 16 ? &mwk : &mwv, 0, kb * 64, (nb & 15) * 4, g.full + 8 * s);
            }
        }
    } else {
        asm volatile("setmaxnreg.inc.sync.aligned.u32 232;");
        const int cw = wg - 1, lane = threadIdx.x & 31, t = lane & 3;
        const int row = m0 + cw * 64 + ((threadIdx.x >> 5) & 3) * 16 + (lane >> 2);
        bf16* dst = g_kv + (size_t)row * 8192 + nb0 * 256 + t * 8;
        float acc[128];
        uint32_t pk[64];
#pragma unroll 1
        for (int tile = 0; tile < 4; tile++) {
#pragma unroll
            for (int kb = 0; kb < 16; kb++) {
                mbar_wait(g.full + 8 * (kb & 3), (kb >> 2) & 1);
                gemm_kblock<256>(acc, g.st + (kb & 3) * STAGE_BYTES, cw, kb == 0);
                if (tile > 0) kv_store_unit(pk, kb, dst + (tile - 1) * 2048, t);
                if (kb > 0) {
                    wg_wait<1>();
                    if ((threadIdx.x & 127) == 0) mbar_arrive(g.empty + 8 * ((kb - 1) & 3));
                }
            }
            wg_wait<0>();
            if ((threadIdx.x & 127) == 0) mbar_arrive(g.empty + 8 * 3);
#pragma unroll
            for (int i = 0; i < 64; i++) pk[i] = pack2(acc[2 * i], acc[2 * i + 1]);
        }
#pragma unroll
        for (int u = 0; u < 16; u++) kv_store_unit(pk, u, dst + 3 * 2048, t);
    }
}

#define NS1 22
#define PF1 8
#define PF2 8
constexpr int C_W1 = 0;
constexpr int C_W2 = C_W1 + 8 * NS1 * 512;
constexpr int C_KV = C_W2 + 22 * 8 * 512;
constexpr int C_RED = C_KV + 16384;
constexpr int C_R3 = C_RED + 16384;
constexpr int C_QKV = C_R3 + 2560;
constexpr int C_SC = C_QKV + 3 * 8 * 272;
constexpr int C_OB = C_SC + 2 * 8 * 52 * 4;
constexpr int C_BAR = C_OB + 2048;
#define MID1 28
__host__ __device__ constexpr int smem_idx(int p) {
    return p < PF1 ? p : p >= 64 - PF1 ? NS1 - (64 - p) : (p >= MID1 && p < MID1 + NS1 - 2 * PF1) ? PF1 + p - MID1 : -1;
}
constexpr int CHAIN_SMEM = C_BAR + 64 + 1024;
#define TS(i)

#define DLY3 400
#define DLY1 200
#define DLY0 0
template <int N> __device__ __forceinline__ void idle() {
    if (N > 0) {
        uint32_t t0, t1;
        asm volatile("mov.u32 %0, %%clock;" : "=r"(t0)::"memory");
        do { asm volatile("mov.u32 %0, %%clock;" : "=r"(t1)::"memory"); } while (t1 - t0 < N);
    }
}
__device__ __forceinline__ uint32_t pin(uint32_t x) { asm volatile("mov.b32 %0, %0;" : "+r"(x)); return x; }
template <typename T> __device__ __forceinline__ T* pin(T* x) { asm volatile("mov.b64 %0, %0;" : "+l"(x)); return x; }
__device__ __forceinline__ uint2 lds64(uint32_t a) {
    uint2 v;
    asm volatile("ld.shared.v2.u32 {%0,%1}, [%2];" : "=r"(v.x), "=r"(v.y) : "r"(a) : "memory");
    return v;
}
__device__ __forceinline__ void sum8(float (&c)[4], const uint2 (&v)[8], uint32_t idn) {
    float d[4] = {0.f, 0.f, 0.f, 0.f};
    c[0] = c[1] = c[2] = c[3] = 0.f;
    mma16816(c, v[0].x, v[0].y, v[1].x, v[1].y, idn, idn);
    mma16816(d, v[2].x, v[2].y, v[3].x, v[3].y, idn, idn);
    mma16816(c, v[4].x, v[4].y, v[5].x, v[5].y, idn, idn);
    mma16816(d, v[6].x, v[6].y, v[7].x, v[7].y, idn, idn);
    c[0] += d[0]; c[1] += d[1]; c[2] += d[2]; c[3] += d[3];
}

__global__ void __cluster_dims__(3, 1, 1) __launch_bounds__(256, 1)
k_chain(const bf16* __restrict__ mem0, const bf16* __restrict__ Wq, const bf16* __restrict__ Wk, const bf16* __restrict__ Wv,
        const bf16* __restrict__ Wo, const __grid_constant__ CUtensorMap mkv) {
    extern __shared__ uint8_t smem_raw[];
    const uint32_t sb = (smem_u32(smem_raw) + 1023) & ~1023u;
    const int tid = __shfl_sync(~0u, threadIdx.x, threadIdx.x & 31), w = tid >> 5, lane = tid & 31, g = lane >> 2, t = lane & 3;
    const int h = blockIdx.x / 3, r = blockIdx.x - 3 * h;
    const uint32_t bar_x = sb + C_BAR, bar_kv = sb + C_BAR + 8, bar_go = sb + C_BAR + 16;
    asm volatile("griddepcontrol.launch_dependents;");
    if (tid == 0) {
        mbar_init(bar_x, 8); mbar_init(bar_kv, 1); mbar_init(bar_go, 1);
        asm volatile("fence.mbarrier_init.release.cluster;" ::: "memory");
        asm volatile("fence.proxy.async.shared::cta;" ::: "memory");
        mbar_expect_tx(bar_kv, 16384);
        tma3d(sb + C_KV, &mkv, 0, 0, 2 * h, bar_kv);
        tma3d(sb + C_KV + 8192, &mkv, 0, 0, 64 + 2 * h, bar_kv);
    }
    const int tile0 = r == 0 ? 0 : 1 + 21 * r, ntile = r == 0 ? 22 : 21;
    const bool three = w + 16 < ntile;
    const uint32_t wa = pin(sb + tid * 16);
#define W1A(i) (wa + C_W1 + (i) * 4096)
#define W2A(x) (wa + C_W2 + ((x) < 16 ? (x) * 4096 : 65536 + ((x) - 16) * 3072))
    {
        const bf16* wo = Wo + (size_t)h * 128 * DM + 2 * g + (size_t)(2 * t) * DM + (tile0 + w) * 16;
        uint32_t x[3][8][4];
#pragma unroll
        for (int i = 0; i < 3; i++)
#pragma unroll
            for (int ks = 0; ks < 8; ks++) {
                const bf16* p = wo + (size_t)(16 * ks) * DM + ((i < 2 || three) ? i * 128 : 0);
                x[i][ks][0] = __ldg((const uint32_t*)p); x[i][ks][1] = __ldg((const uint32_t*)(p + DM));
                x[i][ks][2] = __ldg((const uint32_t*)(p + 8 * DM)); x[i][ks][3] = __ldg((const uint32_t*)(p + 9 * DM));
            }
#pragma unroll
        for (int i = 0; i < 3; i++)
            if (i < 2 || three) {
#pragma unroll
                for (int ks = 0; ks < 8; ks++)
                    sts128(W2A(i * 8 + ks), __byte_perm(x[i][ks][0], x[i][ks][1], 0x5410), __byte_perm(x[i][ks][0], x[i][ks][1], 0x7632),
                           __byte_perm(x[i][ks][2], x[i][ks][3], 0x5410), __byte_perm(x[i][ks][2], x[i][ks][3], 0x7632));
            }
    }
    uint32_t wr[64][4];
    {
        const bf16* W = (r == 0 ? Wq : r == 1 ? Wk : Wv) + (size_t)(128 * w + 4 * t) * HD + h * 128 + 8 * g;
#pragma unroll
        for (int ks = 0; ks < 8; ks++) {
            uint4 x[4][2];
#pragma unroll
            for (int i = 0; i < 4; i++) {
                x[i][0] = __ldg((const uint4*)(W + (size_t)(16 * ks + i) * HD));
                x[i][1] = __ldg((const uint4*)(W + (size_t)(16 * ks + i) * HD + 64));
            }
#pragma unroll
            for (int j = 0; j < 8; j++) {
                const uint32_t sel = (j & 1) ? 0x7632 : 0x5410;
                uint32_t a[4];
#pragma unroll
                for (int q = 0; q < 4; q++) {
                    const uint4 &lo = x[(q >> 1) * 2][q & 1], &hi = x[(q >> 1) * 2 + 1][q & 1];
                    const uint32_t l = (j >> 1) == 0 ? lo.x : (j >> 1) == 1 ? lo.y : (j >> 1) == 2 ? lo.z : lo.w;
                    const uint32_t u = (j >> 1) == 0 ? hi.x : (j >> 1) == 1 ? hi.y : (j >> 1) == 2 ? hi.z : hi.w;
                    a[q] = __byte_perm(l, u, sel);
                }
                const int p = 32 * (j >> 2) + 4 * ks + (j & 3);
                if (smem_idx(p) >= 0) sts128(W1A(smem_idx(p)), a[0], a[1], a[2], a[3]);
                else { wr[p][0] = a[0]; wr[p][1] = a[1]; wr[p][2] = a[2]; wr[p][3] = a[3]; }
            }
        }
    }
    asm volatile("barrier.cluster.arrive.aligned;\nbarrier.cluster.wait.aligned;" ::: "memory");

    const float sl2e = 0.08838834764831845f * 1.4426950408889634f;
    const uint32_t idn = pin(g == 2 * t ? 0x00003f80u : g == 2 * t + 1 ? 0x3f800000u : 0u);
#pragma unroll 1
    for (int s = 0; s < NSEG; s++) {
        uint32_t buf[PF1][4];
#pragma unroll
        for (int i = 0; i < PF1; i++) lds128(buf[i], W1A(i));
        uint2 bm[8];
        const uint32_t ra = pin(sb + C_RED + w * 2048 + t * 512 + (((2 * g) ^ ((t & 1) | ((t & 2) << 2))) << 3));
        TS(0);
        if (s == 0) {
#pragma unroll
            for (int ks = 0; ks < 8; ks++) bm[ks] = __ldg((const uint2*)(mem0 + g * DM + (8 * w + ks) * 16 + 4 * t));
        } else {
            const uint2* src = pin(g_memx + (s * 64 + 8 * w) * 32 + lane);
            if (r == 0) { mbar_wait(bar_go, (s - 1) & 1); idle<DLY0>(); } else idle<DLY1>();
#pragma unroll
            for (int ks = 0; ks < 8; ks++) bm[ks] = ld_rlx64(src + ks * 32);
            int n = 0;
            while (max(max(max(bm[0].x, bm[1].x), max(bm[2].x, bm[3].x)), max(max(bm[4].x, bm[5].x), max(bm[6].x, bm[7].x))) == 0xffffffffu) {
#pragma unroll
                for (int ks = 0; ks < 8; ks++) if (bm[ks].x == 0xffffffffu) bm[ks] = ld_rlx64(src + ks * 32);
                if (++n > SPIN_LIMIT) __trap();
            }
            __syncwarp();
        }
        TS(1);
        {
#pragma unroll
            for (int q = 0; q < 2; q++) {
                float acc[4][4];
#pragma unroll
                for (int j = 0; j < 4; j++) { acc[j][0] = acc[j][1] = acc[j][2] = acc[j][3] = 0.f; }
#pragma unroll
                for (int ks = 0; ks < 8; ks++)
#pragma unroll
                    for (int j = 0; j < 4; j++) {
                        const int p = 32 * q + 4 * ks + j, i = smem_idx(p);
                        if (i >= 0) {
                            uint32_t(&a)[4] = buf[i % PF1];
                            mma16816(acc[j], a[0], a[1], a[2], a[3], bm[ks].x, bm[ks].y);
                            if (i + PF1 < NS1) { lds128(a, W1A(i + PF1)); if (j == 3) __syncwarp(); }
                        } else {
                            const uint32_t(&a)[4] = wr[p];
                            mma16816(acc[j], a[0], a[1], a[2], a[3], bm[ks].x, bm[ks].y);
                        }
                    }
#pragma unroll
                for (int c = 0; c < 4; c++)
                    sts64((ra ^ (q * 8)) + (c & 1) * 256 + (c >> 1) * 128, pack2(acc[0][c], acc[1][c]), pack2(acc[2][c], acc[3][c]));
            }
        }
        {
            const uint32_t a = pin(sb + C_RED + w * 256 + ((lane ^ (((w >> 1) & 1) | ((w & 4) << 1))) << 3));
            TS(2);
            __syncthreads();
            TS(3);
            uint2 v[8];
#pragma unroll
            for (int i = 0; i < 8; i++) v[i] = lds64(a + i * 2048);
            float c[4];
            sum8(c, v, idn);
            const uint32_t p0 = pack2(c[0], c[1]), p1 = pack2(c[2], c[3]);
            const uint32_t dst = sb + C_QKV + (r * 8 + w) * 272 + lane * 8;
#pragma unroll
            for (int i = 1; i < 3; i++) {
                const uint32_t peer = r + i >= 3 ? r + i - 3 : r + i;
                uint32_t rd, rb;
                asm("mapa.shared::cluster.u32 %0, %1, %2;" : "=r"(rd) : "r"(dst), "r"(peer));
                asm("mapa.shared::cluster.u32 %0, %1, %2;" : "=r"(rb) : "r"(bar_x), "r"(peer));
                asm volatile("st.async.weak.shared::cluster.mbarrier::complete_tx::bytes.v2.b32 [%0], {%1,%2}, [%3];"
                             ::"r"(rd), "r"(p0), "r"(p1), "r"(rb) : "memory");
            }
            sts64(dst, p0, p1);
            __syncwarp();
            if (lane == 0) { if (w == 0) mbar_expect_tx(bar_x, 4096); else mbar_arrive(bar_x); }
        }
        TS(4);
        const bool last = s == NSEG - 1;
        if (!last) {
            mbar_wait(bar_kv, s & 1);
            uint32_t ka[4][4], vb[2][4], wb[PF2][4];
            {
                const int row = ((w >> 1) & 1) * 16 + (lane & 15);
#pragma unroll
                for (int ks = 0; ks < 4; ks++)
                    ldsm4(ka[ks], sb + C_KV + (w & 1) * 4096 + row * 128 + (((2 * ks + (lane >> 4)) ^ (row & 7)) << 4));
                const int key = 8 * ((lane & 7) >> 1) + 2 * (lane >> 3) + (lane & 1);
#pragma unroll
                for (int i = 0; i < 2; i++)
                    ldsm4t(vb[i], sb + C_KV + 8192 + (w >> 2) * 4096 + key * 128 + ((((2 * w + i) & 7) ^ (key & 7)) << 4));
#pragma unroll
                for (int i = 0; i < PF2; i++) lds128(wb[i], W2A(i));
            }
            const uint32_t qa = pin(sb + C_QKV + (lane & 7) * 272 + (lane >> 3) * 16 + (w & 1) * 128);
            const uint32_t va = pin(sb + C_QKV + (lane & 7) * 272 + (lane >> 3) * 16 + 16 * 272 + w * 32);
            const uint32_t sa = pin(sb + C_SC + (w & 1) * (8 * 52 * 4) + (2 * t * 52 + (w >> 1) * 16 + g) * 4);
            const uint32_t a = pin(sb + C_SC + (g * 52 + 8 * t) * 4), a2 = pin(sb + C_SC + (g * 52 + 32 + 2 * t) * 4);
            const uint32_t kma = pin(sb + C_QKV + 8 * 272 + (lane & 7) * 272 + (lane >> 4) * 16 + (w & 1) * 128);
            TS(5);
            mbar_wait(bar_x, s & 1);
            TS(6);
            if (w < 6) {
                uint32_t qb[2][4];
                ldsm4(qb[0], qa);
                ldsm4(qb[1], qa + 64);
                if (w >= 4) {
#pragma unroll
                    for (int ks = 0; ks < 4; ks++) ldsm4(ka[ks], kma + ks * 32);
                }
                float c0[4] = {0.f, 0.f, 0.f, 0.f}, c1[4] = {0.f, 0.f, 0.f, 0.f};
                mma16816(c0, ka[0][0], ka[0][1], ka[0][2], ka[0][3], qb[0][0], qb[0][1]);
                mma16816(c1, ka[2][0], ka[2][1], ka[2][2], ka[2][3], qb[1][0], qb[1][1]);
                mma16816(c0, ka[1][0], ka[1][1], ka[1][2], ka[1][3], qb[0][2], qb[0][3]);
                mma16816(c1, ka[3][0], ka[3][1], ka[3][2], ka[3][3], qb[1][2], qb[1][3]);
                sts32f(sa, c0[0] + c1[0]);
                sts32f(sa + 208, c0[1] + c1[1]);
                sts32f(sa + 32, c0[2] + c1[2]);
                sts32f(sa + 240, c0[3] + c1[3]);
            }
            uint32_t vm0, vm1;
            ldsm2t(vm0, vm1, va);
            __syncthreads();
            TS(7);
            {
                float4 x0 = lds128f(a), y0 = lds128f(a + 1664), x1 = lds128f(a + 16), y1 = lds128f(a + 1680);
                float2 x2 = lds64f(a2), y2 = lds64f(a2 + 1664);
                const uint32_t ow = pin(sb + C_OB + lane * 16 + (w >> 1) * 512 + (w & 1) * 8);
                float p[10] = {x0.x + y0.x, x0.y + y0.y, x0.z + y0.z, x0.w + y0.w, x1.x + y1.x,
                               x1.y + y1.y, x1.z + y1.z, x1.w + y1.w, x2.x + y2.x, x2.y + y2.y};
                float m = fmaxf(fmaxf(fmaxf(p[0], p[1]), fmaxf(p[2], p[3])), fmaxf(fmaxf(p[4], p[5]), fmaxf(p[6], p[7])));
                m = fmaxf(m, fmaxf(p[8], p[9]));
                const float m1 = __shfl_xor_sync(~0u, m, 1), m2 = __shfl_xor_sync(~0u, m, 2), m3 = __shfl_xor_sync(~0u, m, 3);
                m = fmaxf(fmaxf(m, m1), fmaxf(m2, m3));
                const float ms = m * sl2e;
#pragma unroll
                for (int i = 0; i < 10; i++) p[i] = ex2(fmaf(p[i], sl2e, -ms));
                const uint32_t a0 = pack2(p[0], p[1]), a1 = pack2(p[2], p[3]), a2 = pack2(p[4], p[5]), a3 = pack2(p[6], p[7]), a4 = pack2(p[8], p[9]);
                float o0[4] = {0.f, 0.f, 0.f, 0.f}, o1[4] = {0.f, 0.f, 0.f, 0.f}, o2[4] = {0.f, 0.f, 0.f, 0.f}, o3[4] = {0.f, 0.f, 0.f, 0.f};
                mma16816(o0, a0, a0, a1, a1, vb[0][0], vb[0][1]);
                mma16816(o1, a0, a0, a1, a1, vb[1][0], vb[1][1]);
                mma16816(o2, a2, a2, a3, a3, vb[0][2], vb[0][3]);
                mma16816(o3, a2, a2, a3, a3, vb[1][2], vb[1][3]);
                mma1688(o0, a4, a4, vm0);
                mma1688(o1, a4, a4, vm1);
                float sum = ((p[0] + p[1]) + (p[2] + p[3])) + ((p[4] + p[5]) + (p[6] + p[7])) + (p[8] + p[9]);
                const float s1 = __shfl_xor_sync(~0u, sum, 1), s2 = __shfl_xor_sync(~0u, sum, 2), s3 = __shfl_xor_sync(~0u, sum, 3);
                sum = (sum + s1) + (s2 + s3);
                float inv;
                asm("rcp.approx.ftz.f32 %0, %1;" : "=f"(inv) : "f"(sum));
                sts64(ow, pack2((o0[0] + o2[0]) * inv, (o0[1] + o2[1]) * inv),
                      pack2((o1[0] + o3[0]) * inv, (o1[1] + o3[1]) * inv));
            }
            uint2* pdst = pin(g_part + ((tile0 + w) * 32 + h) * 32 + lane);
            const uint32_t oa = pin(sb + C_OB + lane * 16);
            TS(8);
            __syncthreads();
            TS(9);
            {
                uint32_t ob[4][4];
#pragma unroll
                for (int i = 0; i < 4; i++) lds128(ob[i], oa + i * 512);
                const uint32_t tag = s & 1;
                float c[3][2][4];
#pragma unroll
                for (int x = 0; x < 24; x++) {
                    const int i = x >> 3, ks = x & 7;
                    if (ks < 2) c[i][ks][0] = c[i][ks][1] = c[i][ks][2] = c[i][ks][3] = 0.f;
                    uint32_t(&a)[4] = wb[x % PF2];
                    mma16816(c[i][ks & 1], a[0], a[1], a[2], a[3], ob[ks >> 1][(ks & 1) * 2], ob[ks >> 1][(ks & 1) * 2 + 1]);
                    if (x + PF2 < 16) lds128(a, W2A(x + PF2));
                    else if (x + PF2 < 24) { if (three) lds128(a, W2A(x + PF2)); }
                    if (ks == 7) {
                        const uint32_t p0 = pack2(c[i][0][0] + c[i][1][0], c[i][0][2] + c[i][1][2]);
                        const uint32_t p1 = pack2(c[i][0][1] + c[i][1][1], c[i][0][3] + c[i][1][3]);
                        if (i < 2 || three) st_rlx64(pdst + i * 8192, (p0 & ~1u) | tag, p1);
                    }
                }
            }
            if (tid == 224 && s + 1 < NSEG - 1) {
                mbar_expect_tx(bar_kv, 16384);
                tma3d(sb + C_KV, &mkv, 0, (s + 1) * 32, 2 * h, bar_kv);
                tma3d(sb + C_KV + 8192, &mkv, 0, (s + 1) * 32, 64 + 2 * h, bar_kv);
            }
        } else {
            mbar_wait(bar_x, s & 1);
        }
        TS(10);
        if (r == 0) {
            TS(11); TS(12);
            uint32_t v[4];
            lds128(v, sb + C_QKV + (8 + (tid >> 4)) * 272 + (tid & 15) * 16);
            *reinterpret_cast<uint4*>(g_kvm + (size_t)(s * 8 + ((tid >> 4) & 7)) * 8192 + (tid >> 7) * HD + h * 128 + (tid & 15) * 8) =
                make_uint4(v[0], v[1], v[2], v[3]);
            if ((s & 3) == 3) {
                __syncthreads();
                if (tid == 0) asm volatile("fence.acq_rel.gpu;\nst.relaxed.gpu.global.u32 [%0], %1;" ::"l"(g_flag + h), "r"(s + 1) : "memory");
            }
        } else if (!last) {
            const int j = 2 * h + r - 1;
            uint2* mdst = pin(g_memx + ((s + 1) * 64 + j) * 32 + lane);
            const uint32_t a2 = pin(sb + C_R3 + g * 80 + t * 16);
            if (w < 4) {
                const uint2* src = pin(g_part + (j * 32 + 8 * w) * 32 + lane);
                const uint32_t a = pin(sb + C_R3 + w * 640 + t * 160 + g * 8);
                const uint32_t tag = s & 1;
                uint2 v[8];
                idle<DLY3>();
#pragma unroll
                for (int i = 0; i < 8; i++) v[i] = ld_rlx64(src + i * 32);
                int n = 0;
                while (true) {
                    const uint32_t o = (v[0].x | v[1].x | v[2].x) | (v[3].x | v[4].x | v[5].x) | (v[6].x | v[7].x);
                    const uint32_t an = (v[0].x & v[1].x & v[2].x) & (v[3].x & v[4].x & v[5].x) & (v[6].x & v[7].x);
                    if ((((o ^ tag) | (an ^ tag)) & 1) == 0) break;
#pragma unroll
                    for (int i = 0; i < 8; i++) if ((v[i].x ^ tag) & 1) v[i] = ld_rlx64(src + i * 32);
                    if (++n > SPIN_LIMIT) __trap();
                }
                __syncwarp();
                TS(11);
                float c[4];
                sum8(c, v, idn);
                sts64f(a, c[0], c[1]);
                sts64f(a + 80, c[2], c[3]);
            } else { TS(11); }
            __syncthreads();
            TS(12);
            if (w == 0) {
                const float4 u0 = lds128f(a2), u1 = lds128f(a2 + 640), u2 = lds128f(a2 + 1280), u3 = lds128f(a2 + 1920);
                st_rlx64(mdst, pack2((u0.x + u1.x) + (u2.x + u3.x), (u0.y + u1.y) + (u2.y + u3.y)),
                         pack2((u0.z + u1.z) + (u2.z + u3.z), (u0.w + u1.w) + (u2.w + u3.w)));
            } else if (tid == 32 && r == 1) {
                uint32_t rb;
                asm("mapa.shared::cluster.u32 %0, %1, 0;" : "=r"(rb) : "r"(bar_go));
                asm volatile("mbarrier.arrive.relaxed.cluster.shared::cluster.b64 _, [%0];" ::"r"(rb) : "memory");
            }
        }
    }
    asm volatile("barrier.cluster.arrive.aligned;\nbarrier.cluster.wait.aligned;" ::: "memory");
}

constexpr int S4_US = 4368;
constexpr int S4_PS = 8336;
constexpr int S4_KS = 1296;
constexpr int S4_U = 0, S4_P = 16 * S4_US, S4_K = S4_P + 16 * S4_PS;
constexpr int S4_SMEM = S4_K + 16 * S4_KS;

__device__ __forceinline__ void csq(float& a, float& b) { const float t = a * b; a = fmaf(a, a, -b * b); b = t + t; }
__device__ __forceinline__ uint32_t cmulpack(float cr, float ci, float a, float b) {
    return pack2(fmaf(cr, a, -ci * b), -fmaf(cr, b, ci * a));
}
__device__ __forceinline__ void cexp(float& re, float& im, float l2, float turns) {
    const float mag = ex2(l2), fr = (turns - rintf(turns)) * 6.283185307179586f;
    re = mag * __cosf(fr); im = mag * __sinf(fr);
}
__device__ __forceinline__ int s4_idx(int l) {
    const int r = l < 256 ? 0 : 24 - __clz(l);
    const int m = r == 0 ? l : (l + (1 << (r - 1)) - 1 + ((l >> r) & 1)) >> r;
    return 128 * r + m;
}

__global__ void __launch_bounds__(512, 1)
k_s4(const bf16* __restrict__ u, const bf16* __restrict__ Are, const bf16* __restrict__ Aim, const bf16* __restrict__ Bre,
     const bf16* __restrict__ Bim, const bf16* __restrict__ Cre, const bf16* __restrict__ Cim, const bf16* __restrict__ logdt,
     const bf16* __restrict__ Dsk, bf16* __restrict__ out) {
    extern __shared__ __align__(16) uint8_t smem_raw[];
    const uint32_t sb = smem_u32(smem_raw);
    asm volatile("griddepcontrol.launch_dependents;");
    const int tid = threadIdx.x, w = tid >> 5, lane = tid & 31, g = lane >> 2, t = lane & 3;
    const int d0 = blockIdx.x * 16;
    const int d = d0 + (w & 1) + ((w >> 1) & 3) * 4 + (w >> 3) * 2;
    const uint32_t tr_off = (lane & 15), tr_l = (lane >> 4) * 16;
    {
        const bf16* src = u + (size_t)(w * 128 + g) * DM + d0 + 4 * t;
        uint2 v[16];
#pragma unroll
        for (int i = 0; i < 16; i++) v[i] = __ldg((const uint2*)(src + (size_t)i * 8 * DM));
        if (lane < 16) sts128(sb + S4_U + w * S4_US + lane * 16, 0, 0, 0, 0);
#pragma unroll
        for (int i = 0; i < 8; i++)
            stsm4t(sb + S4_U + tr_off * S4_US + 256 + (w * 128 + i * 16) * 2 + tr_l, v[2 * i].x, v[2 * i].y, v[2 * i + 1].x, v[2 * i + 1].y);
    }
    const uint32_t pk = sb + S4_P + w * S4_PS, kd = sb + S4_K + w * S4_KS;
    {
        const float dt = bf_round(expf(__bfloat162float(logdt[d])));
        const int o = d * 128 + lane * 4;
        const uint2 ar = __ldg((const uint2*)(Are + o)), ai = __ldg((const uint2*)(Aim + o)), br = __ldg((const uint2*)(Bre + o));
        const uint2 bi = __ldg((const uint2*)(Bim + o)), cr = __ldg((const uint2*)(Cre + o)), ci = __ldg((const uint2*)(Cim + o));
#pragma unroll
        for (int i = 0; i < 4; i++) {
            auto pick = [&](const uint2& v) { const uint32_t x = i < 2 ? v.x : v.y; return (i & 1) ? bf_hi(x) : bf_lo(x); };
            const float dbr = dt * pick(br), dbi = dt * pick(bi), c_r = pick(cr), c_i = pick(ci);
            sts128f(pk + (lane * 4 + i) * 16, dt * pick(ar) * 1.4426950408889634f, dt * pick(ai) * 0.15915494309189535f,
                    fmaf(c_r, dbr, -c_i * dbi), fmaf(c_r, dbi, c_i * dbr));
        }
    }
    __syncwarp();
    {
        float T[5][4];
#pragma unroll
        for (int i = 0; i < 5; i++) T[i][0] = T[i][1] = T[i][2] = T[i][3] = 0.f;
        float klast = 0.f;
        const float g0 = (float)g, g8 = (float)(g + 8);
#pragma unroll 1
        for (int ks = 0; ks < 16; ks++) {
            uint32_t A[4][4], B[5][2];
#pragma unroll
            for (int hf = 0; hf < 2; hf++) {
                const float4 p = lds128f(pk + (ks * 8 + hf * 4 + t) * 16);
                float ur, ui, wr_, wi;
                cexp(ur, ui, p.x * g0, p.y * g0);
                cexp(wr_, wi, p.x * g8, p.y * g8);
#pragma unroll
                for (int r = 0; r < 4; r++) {
                    A[r][hf * 2] = pack2(ur, ui); A[r][hf * 2 + 1] = pack2(wr_, wi);
                    csq(ur, ui); csq(wr_, wi);
                }
                B[0][hf] = cmulpack(p.z, p.w, ur, ui);
#pragma unroll
                for (int r = 1; r < 5; r++) { B[r][hf] = cmulpack(p.z, p.w, wr_, wi); csq(wr_, wi); }
                klast += fmaf(p.z, wr_, -p.w * wi);
            }
            mma16816(T[0], A[0][0], A[0][1], A[0][2], A[0][3], B[0][0], B[0][1]);
#pragma unroll
            for (int r = 0; r < 4; r++) mma16816(T[r + 1], A[r][0], A[r][1], A[r][2], A[r][3], B[r + 1][0], B[r + 1][1]);
        }
        klast += __shfl_xor_sync(~0u, klast, 1);
        klast += __shfl_xor_sync(~0u, klast, 2);
        const uint32_t a = kd + (lane & 7) * 32 + ((lane >> 3) & 1) * 16 + (lane >> 4) * 256;
        stsm4t(a, pack2(T[0][0], T[0][1]), pack2(T[0][2], T[0][3]), pack2(T[1][0], T[1][1]), pack2(T[1][2], T[1][3]));
        stsm4t(a + 512, pack2(T[2][0], T[2][1]), pack2(T[2][2], T[2][3]), pack2(T[3][0], T[3][1]), pack2(T[3][2], T[3][3]));
        asm volatile("stmatrix.sync.aligned.m8n8.x2.trans.shared.b16 [%0], {%1,%2};"
                     ::"r"(a + 1024), "r"(pack2(T[4][0], T[4][1])), "r"(pack2(T[4][2], T[4][3])) : "memory");
        if (lane == 0) asm volatile("st.shared.u16 [%0], %1;" ::"r"(kd + 1280), "h"((unsigned short)pack2(klast, 0.f)) : "memory");
    }
    __syncwarp();
    {
        if (lane < 4) sts128(pk + lane * 16, 0, 0, 0, 0);
#pragma unroll 2
        for (int i = 0; i < 16; i++) {
            const int x = i * 128 + lane * 4;
            uint32_t v[5];
#pragma unroll
            for (int j = 0; j < 5; j++) {
                unsigned short hv;
                asm volatile("ld.shared.u16 %0, [%1];" : "=h"(hv) : "r"(kd + 2 * s4_idx(max(x + j - 1, 0))) : "memory");
                v[j] = hv;
            }
            if (x == 0) v[0] = 0;
            sts128(pk + 64 + x * 4, v[1] | (v[0] << 16), v[2] | (v[1] << 16), v[3] | (v[2] << 16), v[4] | (v[3] << 16));
        }
    }
    __syncthreads();
    {
        float acc[16][4];
#pragma unroll
        for (int i = 0; i < 16; i++) acc[i][0] = acc[i][1] = acc[i][2] = acc[i][3] = 0.f;
        const uint32_t ub = sb + S4_U + w * S4_US + 256 + (lane & 7) * 32 + ((lane >> 3) & 1) * 16 + (lane >> 4) * 256;
        const uint32_t kb = pk + 64 + (g - 2 * t) * 4;
#pragma unroll 1
        for (int j0 = 0; j0 < 8; j0++) {
            uint32_t B[8][4];
#pragma unroll
            for (int i = 0; i < 8; i++) ldsm4(B[i], ub + i * 512 - j0 * 32);
#pragma unroll
            for (int J = 0; J < 16; J++) {
                const uint32_t a = kb + j0 * 64 + J * 512;
                const uint32_t rm = lds32(a - 32), r0 = lds32(a), rp = lds32(a + 32);
#pragma unroll
                for (int I = J; I < 16; I++)
                    mma16816(acc[I], r0, rp, rm, r0, B[(I - J) >> 1][((I - J) & 1) * 2], B[(I - J) >> 1][((I - J) & 1) * 2 + 1]);
            }
        }
        __syncwarp();
        const uint32_t yb = pk + (lane & 7) * 32 + ((lane >> 3) & 1) * 16 + (lane >> 4) * 256;
#pragma unroll
        for (int i = 0; i < 8; i++)
            stsm4t(yb + i * 512, pack2(acc[2 * i][0], acc[2 * i][1]), pack2(acc[2 * i][2], acc[2 * i][3]),
                   pack2(acc[2 * i + 1][0], acc[2 * i + 1][1]), pack2(acc[2 * i + 1][2], acc[2 * i + 1][3]));
    }
    __syncthreads();
    {
        const uint2 dv = __ldg((const uint2*)(Dsk + d0 + 4 * t));
        bf16* dst = out + (size_t)(w * 128 + g) * 2048 + 1024 + d0 + 4 * t;
#pragma unroll
        for (int i = 0; i < 8; i++) {
            uint32_t y[4], x[4], o[4];
            ldsm4t(y, sb + S4_P + tr_off * S4_PS + (w * 128 + i * 16) * 2 + tr_l);
            ldsm4t(x, sb + S4_U + tr_off * S4_US + 256 + (w * 128 + i * 16) * 2 + tr_l);
#pragma unroll
            for (int j = 0; j < 4; j++) {
                const uint32_t dd = (j & 1) ? dv.y : dv.x;
                const uint32_t sk = pack2(bf_lo(x[j]) * bf_lo(dd), bf_hi(x[j]) * bf_hi(dd));
                o[j] = pack2(bf_lo(y[j]) + bf_lo(sk), bf_hi(y[j]) + bf_hi(sk));
            }
            *reinterpret_cast<uint2*>(dst + (size_t)(i * 16) * 2048) = make_uint2(o[0], o[1]);
            *reinterpret_cast<uint2*>(dst + (size_t)(i * 16 + 8) * 2048) = make_uint2(o[2], o[3]);
        }
    }
}

constexpr int WO_BN = 128, WO_PER = DM / WO_BN;
constexpr int BG_ITEMS = 16 * (16 + WO_PER);

template <int BN, typename ACC>
__device__ __forceinline__ void gemm_mainloop(ACC& acc, const GemmSmem& g, int cw, int nk) {
#pragma unroll 1
    for (int k0 = 0; k0 < nk; k0 += 4) {
#pragma unroll
        for (int s = 0; s < 4; s++) {
            mbar_wait(g.full + 8 * s, (k0 >> 2) & 1);
            gemm_kblock<BN>(acc, g.st + s * STAGE_BYTES, cw, s == 0 && k0 == 0);
            wg_wait<1>();
            if ((threadIdx.x & 127) == 0 && (s > 0 || k0 > 0)) mbar_arrive(g.empty + 8 * ((s + 3) & 3));
        }
    }
    wg_wait<0>();
    if ((threadIdx.x & 127) == 0) mbar_arrive(g.empty + 8 * 3);
}

__global__ void __launch_bounds__(384, 1)
k_bg(const __grid_constant__ CUtensorMap mx, const __grid_constant__ CUtensorMap mwq, const __grid_constant__ CUtensorMap mkv4,
     const __grid_constant__ CUtensorMap mkvm, const __grid_constant__ CUtensorMap mo, const __grid_constant__ CUtensorMap mwo,
     bf16* __restrict__ out) {
    extern __shared__ uint8_t smem_raw[];
    int blk, idx; bool is_qa;
    {
        const int it = blockIdx.x;
        if (it < 16) { blk = 0; idx = it; is_qa = true; }
        else {
            const int q = (it - 16) / (16 + WO_PER), rr = (it - 16) - q * (16 + WO_PER);
            if (q == 15) { blk = 15; idx = rr; is_qa = false; }
            else if (rr < 16) { blk = q + 1; idx = rr; is_qa = true; }
            else { blk = q; idx = rr - 16; is_qa = false; }
        }
    }
    GemmSmem g = gemm_setup(smem_raw);
    const int m0 = blk * 128, wg = threadIdx.x >> 7;
    if (wg == 0) {
        asm volatile("setmaxnreg.dec.sync.aligned.u32 40;");
        if (threadIdx.x == 0) {
            if (is_qa) {
                for (int it = 0; it < 20; it++) {
                    const int s = it & 3;
                    const uint32_t st = g.st + s * STAGE_BYTES, fb = g.full + 8 * s;
                    mbar_wait(g.empty + 8 * s, ((it >> 2) & 1) ^ 1);
                    if (it < 16) {
                        mbar_expect_tx(fb, STAGE_BYTES);
                        tma2d(st, &mx, it * 64, m0, fb);
                        tma3d(st + 16384, &mwq, 0, it * 64, idx * 4, fb);
                    } else {
                        mbar_expect_tx(fb, 40960);
                        tma3d(st, &mkv4, 0, m0 + s * 32, idx * 4, fb);
                        tma3d(st + 16384, &mkv4, 0, m0 + s * 32, 64 + idx * 4, fb);
                    }
                }
                wait_flag(g_flag + 2 * idx, 4 * blk + 4);
                wait_flag(g_flag + 2 * idx + 1, 4 * blk + 4);
                asm volatile("fence.proxy.async.global;" ::: "memory");
                for (int s = 0; s < 4; s++) {
                    const uint32_t st = g.st + s * STAGE_BYTES, fb = g.full + 8 * s;
                    tma3d(st + 32768, &mkvm, 0, (blk * 4 + s) * 8, idx * 4, fb);
                    tma3d(st + 36864, &mkvm, 0, (blk * 4 + s) * 8, 64 + idx * 4, fb);
                }
            } else {
                wait_flag(g_flag + 64 + blk, 16);
                asm volatile("fence.proxy.async.global;" ::: "memory");
                for (int it = 0; it < 64; it++) {
                    const int s = it & 3;
                    const uint32_t st = g.st + s * STAGE_BYTES, fb = g.full + 8 * s;
                    mbar_wait(g.empty + 8 * s, ((it >> 2) & 1) ^ 1);
                    mbar_expect_tx(fb, 16384 + WO_BN * 128);
                    tma2d(st, &mo, it * 64, m0, fb);
                    tma3d(st + 16384, &mwo, 0, it * 64, idx * (WO_BN / 64), fb);
                }
            }
        }
    } else {
        asm volatile("setmaxnreg.inc.sync.aligned.u32 232;");
        const int cw = wg - 1, ww = (threadIdx.x >> 5) & 3, lane = threadIdx.x & 31, gq = lane >> 2, t = lane & 3;
        const int row = m0 + cw * 64 + ww * 16 + gq;
        if (is_qa) {
            uint32_t q[64];
            {
                float acc[128];
                gemm_mainloop<256>(acc, g, cw, 16);
#pragma unroll
                for (int i = 0; i < 64; i++) q[i] = pack2(acc[2 * i], acc[2 * i + 1]);
            }
            const int sg = cw * 2 + (ww >> 1), hf = ww & 1;
            const uint32_t st = g.st + sg * STAGE_BYTES;
            mbar_wait(g.full + 8 * sg, 0);
            const float scale = 0.08838834764831845f, l2e = 1.4426950408889634f;
            const int r8 = lane & 7, m4 = lane >> 3;
#pragma unroll
            for (int hh = 0; hh < 2; hh++) {
                float sc[5][4];
#pragma unroll
                for (int nt = 0; nt < 5; nt++) {
                    sc[nt][0] = sc[nt][1] = sc[nt][2] = sc[nt][3] = 0.f;
                    if (nt < 3 || hf) {
#pragma unroll
                        for (int kp = 0; kp < 4; kp++) {
                            const int nb = hh * 2 + (kp >> 1);
                            const uint32_t base = nt == 0 ? st + 32768 + nb * 1024 : st + nb * 4096 + (nt - 1) * 1024;
                            uint32_t b[4];
                            ldsm4(b, base + r8 * 128 + ((((kp & 1) * 4 + m4) ^ r8) << 4));
                            const int j = (hh * 16 + kp * 4) * 2;
                            mma16816(sc[nt], q[j], q[j + 1], q[j + 2], q[j + 3], b[0], b[1]);
                            mma16816(sc[nt], q[j + 4], q[j + 5], q[j + 6], q[j + 7], b[2], b[3]);
                        }
                    }
                }
                float mx[2] = {-3.0e38f, -3.0e38f};
#pragma unroll
                for (int nt = 0; nt < 5; nt++)
#pragma unroll
                    for (int c = 0; c < 4; c++) {
                        float v = bf_round(bf_round(sc[nt][c]) * scale);
                        if (nt > 0 && (nt - 1) * 8 + 2 * t + (c & 1) > hf * 16 + gq + (c >> 1) * 8) v = -1.0e9f;
                        sc[nt][c] = v;
                        mx[c >> 1] = fmaxf(mx[c >> 1], v);
                    }
                float sum[2] = {0.f, 0.f};
#pragma unroll
                for (int i = 0; i < 2; i++) {
                    mx[i] = fmaxf(mx[i], __shfl_xor_sync(~0u, mx[i], 1));
                    mx[i] = fmaxf(mx[i], __shfl_xor_sync(~0u, mx[i], 2));
                }
#pragma unroll
                for (int nt = 0; nt < 5; nt++)
#pragma unroll
                    for (int c = 0; c < 4; c++) {
                        sc[nt][c] = ex2((sc[nt][c] - mx[c >> 1]) * l2e);
                        sum[c >> 1] += sc[nt][c];
                    }
#pragma unroll
                for (int i = 0; i < 2; i++) {
                    sum[i] += __shfl_xor_sync(~0u, sum[i], 1);
                    sum[i] += __shfl_xor_sync(~0u, sum[i], 2);
                    sum[i] = __frcp_rn(sum[i]);
                }
                uint32_t p[5][2];
#pragma unroll
                for (int nt = 0; nt < 5; nt++) {
                    p[nt][0] = pack2(sc[nt][0] * sum[0], sc[nt][1] * sum[0]);
                    p[nt][1] = pack2(sc[nt][2] * sum[1], sc[nt][3] * sum[1]);
                }
                bf16* dst = g_o + (size_t)row * HD + idx * 256 + hh * 128 + t * 8;
#pragma unroll
                for (int G = 0; G < 4; G++) {
                    const int nb = hh * 2 + (G >> 1), c0 = (G & 1) * 4;
                    float o[4][4];
#pragma unroll
                    for (int i = 0; i < 4; i++) o[i][0] = o[i][1] = o[i][2] = o[i][3] = 0.f;
                    uint32_t b[4];
                    ldsm4t(b, st + 36864 + nb * 1024 + r8 * 128 + (((c0 + m4) ^ r8) << 4));
#pragma unroll
                    for (int i = 0; i < 4; i++) mma1688(o[i], p[0][0], p[0][1], b[i]);
#pragma unroll
                    for (int kk = 0; kk < 2; kk++) {
                        if (kk == 0 || hf) {
#pragma unroll
                            for (int i = 0; i < 2; i++) {
                                ldsm4t(b, st + 16384 + nb * 4096 + (kk * 16 + (m4 & 1) * 8 + r8) * 128 + (((c0 + 2 * i + (m4 >> 1)) ^ r8) << 4));
                                mma16816(o[2 * i], p[1 + 2 * kk][0], p[1 + 2 * kk][1], p[2 + 2 * kk][0], p[2 + 2 * kk][1], b[0], b[1]);
                                mma16816(o[2 * i + 1], p[1 + 2 * kk][0], p[1 + 2 * kk][1], p[2 + 2 * kk][0], p[2 + 2 * kk][1], b[2], b[3]);
                            }
                        }
                    }
#pragma unroll
                    for (int rr = 0; rr < 2; rr++) {
                        uint32_t r0 = pack2(o[0][2 * rr], o[0][2 * rr + 1]), r1 = pack2(o[1][2 * rr], o[1][2 * rr + 1]);
                        uint32_t r2 = pack2(o[2][2 * rr], o[2][2 * rr + 1]), r3 = pack2(o[3][2 * rr], o[3][2 * rr + 1]);
                        quad_transpose(r0, r1, r2, r3, t);
                        *reinterpret_cast<uint4*>(dst + (size_t)rr * 8 * HD + G * 32) = make_uint4(r0, r1, r2, r3);
                    }
                }
            }
            bar_sync(1, 256);
            if (threadIdx.x == 128)
                asm volatile("fence.acq_rel.gpu;\nred.relaxed.gpu.global.add.u32 [%0], 1;" ::"l"(g_flag + 64 + blk) : "memory");
        } else {
            float acc[WO_BN / 2];
            gemm_mainloop<WO_BN>(acc, g, cw, 64);
            bf16* dst = out + (size_t)row * 2048 + idx * WO_BN + t * 8;
#pragma unroll
            for (int G = 0; G < WO_BN / 32; G++)
#pragma unroll
                for (int rr = 0; rr < 2; rr++) {
                    uint32_t r0 = pack2(acc[16 * G + 2 * rr], acc[16 * G + 2 * rr + 1]), r1 = pack2(acc[16 * G + 4 + 2 * rr], acc[16 * G + 5 + 2 * rr]);
                    uint32_t r2 = pack2(acc[16 * G + 8 + 2 * rr], acc[16 * G + 9 + 2 * rr]), r3 = pack2(acc[16 * G + 12 + 2 * rr], acc[16 * G + 13 + 2 * rr]);
                    quad_transpose(r0, r1, r2, r3, t);
                    *reinterpret_cast<uint4*>(dst + (size_t)rr * 8 * 2048 + G * 32) = make_uint4(r0, r1, r2, r3);
                }
        }
    }
}

typedef CUresult (*EncodeFn)(CUtensorMap*, CUtensorMapDataType, cuuint32_t, void*, const cuuint64_t*, const cuuint64_t*,
                             const cuuint32_t*, const cuuint32_t*, CUtensorMapInterleave, CUtensorMapSwizzle,
                             CUtensorMapL2promotion, CUtensorMapFloatOOBfill);

static void map2d(EncodeFn enc, CUtensorMap* m, const void* p, int rows, int cols, int box_rows) {
    cuuint64_t dim[2] = {(cuuint64_t)cols, (cuuint64_t)rows}, str[1] = {(cuuint64_t)cols * 2};
    cuuint32_t box[2] = {64, (cuuint32_t)box_rows}, es[2] = {1, 1};
    enc(m, CU_TENSOR_MAP_DATA_TYPE_BFLOAT16, 2, (void*)p, dim, str, box, es, CU_TENSOR_MAP_INTERLEAVE_NONE,
        CU_TENSOR_MAP_SWIZZLE_128B, CU_TENSOR_MAP_L2_PROMOTION_L2_256B, CU_TENSOR_MAP_FLOAT_OOB_FILL_NONE);
}
static void map3d(EncodeFn enc, CUtensorMap* m, const void* p, int rows, int cols, int box_rows, int nblk) {
    cuuint64_t dim[3] = {64, (cuuint64_t)rows, (cuuint64_t)cols / 64}, str[2] = {(cuuint64_t)cols * 2, 128};
    cuuint32_t box[3] = {64, (cuuint32_t)box_rows, (cuuint32_t)nblk}, es[3] = {1, 1, 1};
    enc(m, CU_TENSOR_MAP_DATA_TYPE_BFLOAT16, 3, (void*)p, dim, str, box, es, CU_TENSOR_MAP_INTERLEAVE_NONE,
        CU_TENSOR_MAP_SWIZZLE_128B, CU_TENSOR_MAP_L2_PROMOTION_L2_256B, CU_TENSOR_MAP_FLOAT_OOB_FILL_NONE);
}

#define USE_PDL 1

extern "C" void kernel_launch(void* const* d_in, const int* in_sizes, int n_in, void* d_out, int out_size) {
    const bf16 *x = (const bf16*)d_in[0], *mem0 = (const bf16*)d_in[1], *Wq = (const bf16*)d_in[2], *Wk = (const bf16*)d_in[3];
    const bf16 *Wv = (const bf16*)d_in[4], *Wo = (const bf16*)d_in[5];
    const bf16 *u = (const bf16*)d_in[7], *Are = (const bf16*)d_in[8], *Aim = (const bf16*)d_in[9], *Bre = (const bf16*)d_in[10];
    const bf16 *Bim = (const bf16*)d_in[11], *Cre = (const bf16*)d_in[12], *Cim = (const bf16*)d_in[13];
    const bf16 *logdt = (const bf16*)d_in[14], *Dsk = (const bf16*)d_in[15];
    bf16* out = (bf16*)d_out;

    void* fn = nullptr;
    cudaDriverEntryPointQueryResult qr;
    cudaGetDriverEntryPoint("cuTensorMapEncodeTiled", &fn, cudaEnableDefault, &qr);
    EncodeFn enc = (EncodeFn)fn;
    void *kv, *kvm, *o;
    cudaGetSymbolAddress(&kv, g_kv);
    cudaGetSymbolAddress(&kvm, g_kvm);
    cudaGetSymbolAddress(&o, g_o);
    CUtensorMap mx, mwq, mwk, mwv, mwo, mkv2, mkv4, mkvm, mo;
    map2d(enc, &mx, x, SEQ, DM, 128);
    map2d(enc, &mo, o, SEQ, HD, 128);
    map3d(enc, &mwq, Wq, DM, HD, 64, 4);
    map3d(enc, &mwk, Wk, DM, HD, 64, 4);
    map3d(enc, &mwv, Wv, DM, HD, 64, 4);
    map3d(enc, &mwo, Wo, HD, DM, 64, WO_BN / 64);
    map3d(enc, &mkv2, kv, SEQ, 8192, 32, 2);
    map3d(enc, &mkv4, kv, SEQ, 8192, 32, 4);
    map3d(enc, &mkvm, kvm, NSEG * 8, 8192, 8, 4);
    cudaFuncSetAttribute(k_kv, cudaFuncAttributeMaxDynamicSharedMemorySize, GEMM_SMEM);
    cudaFuncSetAttribute(k_bg, cudaFuncAttributeMaxDynamicSharedMemorySize, GEMM_SMEM);
    cudaFuncSetAttribute(k_chain, cudaFuncAttributeMaxDynamicSharedMemorySize, CHAIN_SMEM);
    cudaFuncSetAttribute(k_s4, cudaFuncAttributeMaxDynamicSharedMemorySize, S4_SMEM);

    cudaStream_t st = cudaStreamPerThread;
    k_kv<<<132, 384, GEMM_SMEM, st>>>(mx, mwk, mwv);
    k_chain<<<96, 256, CHAIN_SMEM, st>>>(mem0, Wq, Wk, Wv, Wo, mkv2);
    cudaLaunchAttribute pdl[1];
    pdl[0].id = cudaLaunchAttributeProgrammaticStreamSerialization;
    pdl[0].val.programmaticStreamSerializationAllowed = 1;
    cudaLaunchConfig_t cfg = {};
    cfg.stream = st; cfg.attrs = pdl; cfg.numAttrs = USE_PDL;
    cfg.gridDim = dim3(64); cfg.blockDim = dim3(512); cfg.dynamicSmemBytes = S4_SMEM;
    cudaLaunchKernelEx(&cfg, k_s4, u, Are, Aim, Bre, Bim, Cre, Cim, logdt, Dsk, out);
    cfg.gridDim = dim3(BG_ITEMS); cfg.blockDim = dim3(384); cfg.dynamicSmemBytes = GEMM_SMEM;
    cudaLaunchKernelEx(&cfg, k_bg, mx, mwq, mkv4, mkvm, mo, mwo, out);
}
```

```cpp
#include <cuda_runtime.h>
#include <cuda_bf16.h>
#include <cuda.h>
#include <stdint.h>

typedef __nv_bfloat16 bf16;

constexpr int SEQ = 2048, DM = 1024, HD = 4096, NSEG = 64;

__device__ __align__(1024) bf16 g_kv[(size_t)SEQ * 8192];
__device__ __align__(1024) bf16 g_kvm[(size_t)NSEG * 8 * 8192];
__device__ __align__(1024) bf16 g_o[(size_t)SEQ * HD];
__device__ __align__(1024) uint2 g_memx[NSEG * 64 * 32];
__device__ __align__(1024) uint2 g_part[64 * 32 * 32];
__device__ __align__(1024) uint32_t g_flag[256];

__device__ __forceinline__ uint32_t smem_u32(const void* p) { return (uint32_t)__cvta_generic_to_shared(p); }
__device__ __forceinline__ void mbar_init(uint32_t bar, uint32_t cnt) {
    asm volatile("mbarrier.init.shared::cta.b64 [%0], %1;" ::"r"(bar), "r"(cnt) : "memory");
}
__device__ __forceinline__ void mbar_expect_tx(uint32_t bar, uint32_t bytes) {
    asm volatile("mbarrier.arrive.expect_tx.shared::cta.b64 _, [%0], %1;" ::"r"(bar), "r"(bytes) : "memory");
}
__device__ __forceinline__ void mbar_arrive(uint32_t bar) {
    asm volatile("mbarrier.arrive.shared::cta.b64 _, [%0];" ::"r"(bar) : "memory");
}
__device__ __forceinline__ bool mbar_try(uint32_t bar, uint32_t parity) {
    uint32_t ok;
    asm volatile("{\n.reg .pred p;\nmbarrier.try_wait.parity.shared::cta.b64 p, [%1], %2;\nselp.u32 %0, 1, 0, p;\n}"
                 : "=r"(ok) : "r"(bar), "r"(parity) : "memory");
    return ok;
}
__device__ __forceinline__ bool mbar_try_cluster(uint32_t bar, uint32_t parity) {
    uint32_t ok;
    asm volatile("{\n.reg .pred p;\nmbarrier.try_wait.parity.acquire.cluster.shared::cta.b64 p, [%1], %2;\nselp.u32 %0, 1, 0, p;\n}"
                 : "=r"(ok) : "r"(bar), "r"(parity) : "memory");
    return ok;
}
constexpr int SPIN_LIMIT = 1 << 20;
__device__ __forceinline__ void mbar_wait(uint32_t bar, uint32_t parity) {
    int n = 0;
    while (!mbar_try(bar, parity)) { if (++n > SPIN_LIMIT) __trap(); }
}
__device__ __forceinline__ void mbar_wait_cluster(uint32_t bar, uint32_t parity) {
    int n = 0;
    while (!mbar_try_cluster(bar, parity)) { if (++n > SPIN_LIMIT) __trap(); }
}
__device__ __forceinline__ void tma2d(uint32_t dst, const CUtensorMap* m, int c0, int c1, uint32_t bar) {
    asm volatile("cp.async.bulk.tensor.2d.shared::cluster.global.mbarrier::complete_tx::bytes [%0], [%1, {%3, %4}], [%2];"
                 ::"r"(dst), "l"(m), "r"(bar), "r"(c0), "r"(c1) : "memory");
}
__device__ __forceinline__ void tma3d(uint32_t dst, const CUtensorMap* m, int c0, int c1, int c2, uint32_t bar) {
    asm volatile("cp.async.bulk.tensor.3d.shared::cluster.global.mbarrier::complete_tx::bytes [%0], [%1, {%3, %4, %5}], [%2];"
                 ::"r"(dst), "l"(m), "r"(bar), "r"(c0), "r"(c1), "r"(c2) : "memory");
}
__device__ __forceinline__ uint32_t pack2(float lo, float hi) {
    uint32_t r;
    asm("cvt.rn.bf16x2.f32 %0, %1, %2;" : "=r"(r) : "f"(hi), "f"(lo));
    return r;
}
__device__ __forceinline__ float bf_lo(uint32_t v) { return __uint_as_float(v << 16); }
__device__ __forceinline__ float bf_hi(uint32_t v) { return __uint_as_float(v & 0xffff0000u); }
__device__ __forceinline__ float bf_round(float x) { return bf_lo(pack2(x, 0.f)); }
__device__ __forceinline__ float ex2(float x) { float y; asm("ex2.approx.ftz.f32 %0, %1;" : "=f"(y) : "f"(x)); return y; }
__device__ __forceinline__ void mma16816(float (&c)[4], uint32_t a0, uint32_t a1, uint32_t a2, uint32_t a3, uint32_t b0, uint32_t b1) {
    asm volatile("mma.sync.aligned.m16n8k16.row.col.f32.bf16.bf16.f32 {%0,%1,%2,%3}, {%4,%5,%6,%7}, {%8,%9}, {%0,%1,%2,%3};"
                 : "+f"(c[0]), "+f"(c[1]), "+f"(c[2]), "+f"(c[3]) : "r"(a0), "r"(a1), "r"(a2), "r"(a3), "r"(b0), "r"(b1));
}
__device__ __forceinline__ void mma1688(float (&c)[4], uint32_t a0, uint32_t a1, uint32_t b0) {
    asm volatile("mma.sync.aligned.m16n8k8.row.col.f32.bf16.bf16.f32 {%0,%1,%2,%3}, {%4,%5}, {%6}, {%0,%1,%2,%3};"
                 : "+f"(c[0]), "+f"(c[1]), "+f"(c[2]), "+f"(c[3]) : "r"(a0), "r"(a1), "r"(b0));
}
__device__ __forceinline__ void ldsm4(uint32_t (&r)[4], uint32_t a) {
    asm volatile("ldmatrix.sync.aligned.m8n8.x4.shared.b16 {%0,%1,%2,%3}, [%4];"
                 : "=r"(r[0]), "=r"(r[1]), "=r"(r[2]), "=r"(r[3]) : "r"(a) : "memory");
}
__device__ __forceinline__ void ldsm4t(uint32_t (&r)[4], uint32_t a) {
    asm volatile("ldmatrix.sync.aligned.m8n8.x4.trans.shared.b16 {%0,%1,%2,%3}, [%4];"
                 : "=r"(r[0]), "=r"(r[1]), "=r"(r[2]), "=r"(r[3]) : "r"(a) : "memory");
}
__device__ __forceinline__ void ldsm2t(uint32_t& r0, uint32_t& r1, uint32_t a) {
    asm volatile("ldmatrix.sync.aligned.m8n8.x2.trans.shared.b16 {%0,%1}, [%2];" : "=r"(r0), "=r"(r1) : "r"(a) : "memory");
}
__device__ __forceinline__ void stsm4t(uint32_t a, uint32_t r0, uint32_t r1, uint32_t r2, uint32_t r3) {
    asm volatile("stmatrix.sync.aligned.m8n8.x4.trans.shared.b16 [%0], {%1,%2,%3,%4};"
                 ::"r"(a), "r"(r0), "r"(r1), "r"(r2), "r"(r3) : "memory");
}
__device__ __forceinline__ void lds128(uint32_t (&r)[4], uint32_t a) {
    asm volatile("ld.shared.v4.u32 {%0,%1,%2,%3}, [%4];" : "=r"(r[0]), "=r"(r[1]), "=r"(r[2]), "=r"(r[3]) : "r"(a) : "memory");
}
__device__ __forceinline__ float4 lds128f(uint32_t a) {
    float4 v;
    asm volatile("ld.shared.v4.f32 {%0,%1,%2,%3}, [%4];" : "=f"(v.x), "=f"(v.y), "=f"(v.z), "=f"(v.w) : "r"(a) : "memory");
    return v;
}
__device__ __forceinline__ float2 lds64f(uint32_t a) {
    float2 v;
    asm volatile("ld.shared.v2.f32 {%0,%1}, [%2];" : "=f"(v.x), "=f"(v.y) : "r"(a) : "memory");
    return v;
}
__device__ __forceinline__ uint32_t lds32(uint32_t a) {
    uint32_t v;
    asm volatile("ld.shared.u32 %0, [%1];" : "=r"(v) : "r"(a) : "memory");
    return v;
}
__device__ __forceinline__ void sts128(uint32_t a, uint32_t r0, uint32_t r1, uint32_t r2, uint32_t r3) {
    asm volatile("st.shared.v4.u32 [%0], {%1,%2,%3,%4};" ::"r"(a), "r"(r0), "r"(r1), "r"(r2), "r"(r3) : "memory");
}
__device__ __forceinline__ void sts128f(uint32_t a, float r0, float r1, float r2, float r3) {
    asm volatile("st.shared.v4.f32 [%0], {%1,%2,%3,%4};" ::"r"(a), "f"(r0), "f"(r1), "f"(r2), "f"(r3) : "memory");
}
__device__ __forceinline__ void sts64(uint32_t a, uint32_t r0, uint32_t r1) {
    asm volatile("st.shared.v2.u32 [%0], {%1,%2};" ::"r"(a), "r"(r0), "r"(r1) : "memory");
}
__device__ __forceinline__ void sts64f(uint32_t a, float r0, float r1) {
    asm volatile("st.shared.v2.f32 [%0], {%1,%2};" ::"r"(a), "f"(r0), "f"(r1) : "memory");
}
__device__ __forceinline__ void sts32f(uint32_t a, float r0) {
    asm volatile("st.shared.f32 [%0], %1;" ::"r"(a), "f"(r0) : "memory");
}
__device__ __forceinline__ uint2 ld_rlx64(const uint2* p) {
    uint2 v;
    asm volatile("{\n.reg .b64 t;\nld.relaxed.gpu.global.b64 t, [%2];\nmov.b64 {%0,%1}, t;\n}" : "=r"(v.x), "=r"(v.y) : "l"(p) : "memory");
    return v;
}
__device__ __forceinline__ void st_rlx64(uint2* p, uint32_t x, uint32_t y) {
    asm volatile("{\n.reg .b64 t;\nmov.b64 t, {%1,%2};\nst.relaxed.gpu.global.b64 [%0], t;\n}" ::"l"(p), "r"(x), "r"(y) : "memory");
}
__device__ __forceinline__ uint32_t ld_acq32(const uint32_t* p) {
    uint32_t v;
    asm volatile("ld.acquire.gpu.global.u32 %0, [%1];" : "=r"(v) : "l"(p) : "memory");
    return v;
}
__device__ __forceinline__ void wait_flag(const uint32_t* p, uint32_t need) {
    int n = 0;
    while (ld_acq32(p) < need) { __nanosleep(200); if (++n > SPIN_LIMIT) __trap(); }
}
__device__ __forceinline__ void bar_sync(int id, int n) { asm volatile("bar.sync %0, %1;" ::"r"(id), "r"(n) : "memory"); }
__device__ __forceinline__ void wg_fence() { asm volatile("wgmma.fence.sync.aligned;" ::: "memory"); }
__device__ __forceinline__ void wg_commit() { asm volatile("wgmma.commit_group.sync.aligned;" ::: "memory"); }
template <int N> __device__ __forceinline__ void wg_wait() { asm volatile("wgmma.wait_group.sync.aligned %0;" ::"n"(N) : "memory"); }
__device__ __forceinline__ uint64_t desc_sw128(uint32_t addr, uint32_t lbo, uint32_t sbo) {
    return (uint64_t)((addr & 0x3FFFF) >> 4) | ((uint64_t)(lbo >> 4) << 16) | ((uint64_t)(sbo >> 4) << 32) | (1ull << 62);
}
__device__ __forceinline__ void quad_transpose(uint32_t& r0, uint32_t& r1, uint32_t& r2, uint32_t& r3, int t) {
    const bool o = t & 1, h = t & 2;
    uint32_t s0 = __shfl_xor_sync(~0u, o ? r0 : r1, 1), s1 = __shfl_xor_sync(~0u, o ? r2 : r3, 1);
    uint32_t a0 = o ? s0 : r0, a1 = o ? r1 : s0, a2 = o ? s1 : r2, a3 = o ? r3 : s1;
    s0 = __shfl_xor_sync(~0u, h ? a0 : a2, 2); s1 = __shfl_xor_sync(~0u, h ? a1 : a3, 2);
    r0 = h ? s0 : a0; r1 = h ? s1 : a1; r2 = h ? a2 : s0; r3 = h ? a3 : s1;
}

__device__ __forceinline__ void wgmma_n256(float (&d)[128], uint64_t da, uint64_t db, int sd) {
    asm volatile("{\n.reg .pred p;\nsetp.ne.b32 p, %130, 0;\n"
        "wgmma.mma_async.sync.aligned.m64n256k16.f32.bf16.bf16 "
        "{%0,%1,%2,%3,%4,%5,%6,%7,%8,%9,%10,%11,%12,%13,%14,%15,"
        "%16,%17,%18,%19,%20,%21,%22,%23,%24,%25,%26,%27,%28,%29,%30,%31,"
        "%32,%33,%34,%35,%36,%37,%38,%39,%40,%41,%42,%43,%44,%45,%46,%47,"
        "%48,%49,%50,%51,%52,%53,%54,%55,%56,%57,%58,%59,%60,%61,%62,%63,"
        "%64,%65,%66,%67,%68,%69,%70,%71,%72,%73,%74,%75,%76,%77,%78,%79,"
        "%80,%81,%82,%83,%84,%85,%86,%87,%88,%89,%90,%91,%92,%93,%94,%95,"
        "%96,%97,%98,%99,%100,%101,%102,%103,%104,%105,%106,%107,%108,%109,%110,%111,"
        "%112,%113,%114,%115,%116,%117,%118,%119,%120,%121,%122,%123,%124,%125,%126,%127}, %128, %129, p, 1, 1, 0, 1;\n}\n"
        : "+f"(d[0]), "+f"(d[1]), "+f"(d[2]), "+f"(d[3]), "+f"(d[4]), "+f"(d[5]), "+f"(d[6]), "+f"(d[7]),
          "+f"(d[8]), "+f"(d[9]), "+f"(d[10]), "+f"(d[11]), "+f"(d[12]), "+f"(d[13]), "+f"(d[14]), "+f"(d[15]),
          "+f"(d[16]), "+f"(d[17]), "+f"(d[18]), "+f"(d[19]), "+f"(d[20]), "+f"(d[21]), "+f"(d[22]), "+f"(d[23]),
          "+f"(d[24]), "+f"(d[25]), "+f"(d[26]), "+f"(d[27]), "+f"(d[28]), "+f"(d[29]), "+f"(d[30]), "+f"(d[31]),
          "+f"(d[32]), "+f"(d[33]), "+f"(d[34]), "+f"(d[35]), "+f"(d[36]), "+f"(d[37]), "+f"(d[38]), "+f"(d[39]),
          "+f"(d[40]), "+f"(d[41]), "+f"(d[42]), "+f"(d[43]), "+f"(d[44]), "+f"(d[45]), "+f"(d[46]), "+f"(d[47]),
          "+f"(d[48]), "+f"(d[49]), "+f"(d[50]), "+f"(d[51]), "+f"(d[52]), "+f"(d[53]), "+f"(d[54]), "+f"(d[55]),
          "+f"(d[56]), "+f"(d[57]), "+f"(d[58]), "+f"(d[59]), "+f"(d[60]), "+f"(d[61]), "+f"(d[62]), "+f"(d[63]),
          "+f"(d[64]), "+f"(d[65]), "+f"(d[66]), "+f"(d[67]), "+f"(d[68]), "+f"(d[69]), "+f"(d[70]), "+f"(d[71]),
          "+f"(d[72]), "+f"(d[73]), "+f"(d[74]), "+f"(d[75]), "+f"(d[76]), "+f"(d[77]), "+f"(d[78]), "+f"(d[79]),
          "+f"(d[80]), "+f"(d[81]), "+f"(d[82]), "+f"(d[83]), "+f"(d[84]), "+f"(d[85]), "+f"(d[86]), "+f"(d[87]),
          "+f"(d[88]), "+f"(d[89]), "+f"(d[90]), "+f"(d[91]), "+f"(d[92]), "+f"(d[93]), "+f"(d[94]), "+f"(d[95]),
          "+f"(d[96]), "+f"(d[97]), "+f"(d[98]), "+f"(d[99]), "+f"(d[100]), "+f"(d[101]), "+f"(d[102]), "+f"(d[103]),
          "+f"(d[104]), "+f"(d[105]), "+f"(d[106]), "+f"(d[107]), "+f"(d[108]), "+f"(d[109]), "+f"(d[110]), "+f"(d[111]),
          "+f"(d[112]), "+f"(d[113]), "+f"(d[114]), "+f"(d[115]), "+f"(d[116]), "+f"(d[117]), "+f"(d[118]), "+f"(d[119]),
          "+f"(d[120]), "+f"(d[121]), "+f"(d[122]), "+f"(d[123]), "+f"(d[124]), "+f"(d[125]), "+f"(d[126]), "+f"(d[127])
        : "l"(da), "l"(db), "r"(sd));
}

__device__ __forceinline__ void wgmma_n128(float (&d)[64], uint64_t da, uint64_t db, int sd) {
    asm volatile("{\n.reg .pred p;\nsetp.ne.b32 p, %66, 0;\n"
        "wgmma.mma_async.sync.aligned.m64n128k16.f32.bf16.bf16 "
        "{%0,%1,%2,%3,%4,%5,%6,%7,%8,%9,%10,%11,%12,%13,%14,%15,"
        "%16,%17,%18,%19,%20,%21,%22,%23,%24,%25,%26,%27,%28,%29,%30,%31,"
        "%32,%33,%34,%35,%36,%37,%38,%39,%40,%41,%42,%43,%44,%45,%46,%47,"
        "%48,%49,%50,%51,%52,%53,%54,%55,%56,%57,%58,%59,%60,%61,%62,%63}, %64, %65, p, 1, 1, 0, 1;\n}\n"
        : "+f"(d[0]), "+f"(d[1]), "+f"(d[2]), "+f"(d[3]), "+f"(d[4]), "+f"(d[5]), "+f"(d[6]), "+f"(d[7]),
          "+f"(d[8]), "+f"(d[9]), "+f"(d[10]), "+f"(d[11]), "+f"(d[12]), "+f"(d[13]), "+f"(d[14]), "+f"(d[15]),
          "+f"(d[16]), "+f"(d[17]), "+f"(d[18]), "+f"(d[19]), "+f"(d[20]), "+f"(d[21]), "+f"(d[22]), "+f"(d[23]),
          "+f"(d[24]), "+f"(d[25]), "+f"(d[26]), "+f"(d[27]), "+f"(d[28]), "+f"(d[29]), "+f"(d[30]), "+f"(d[31]),
          "+f"(d[32]), "+f"(d[33]), "+f"(d[34]), "+f"(d[35]), "+f"(d[36]), "+f"(d[37]), "+f"(d[38]), "+f"(d[39]),
          "+f"(d[40]), "+f"(d[41]), "+f"(d[42]), "+f"(d[43]), "+f"(d[44]), "+f"(d[45]), "+f"(d[46]), "+f"(d[47]),
          "+f"(d[48]), "+f"(d[49]), "+f"(d[50]), "+f"(d[51]), "+f"(d[52]), "+f"(d[53]), "+f"(d[54]), "+f"(d[55]),
          "+f"(d[56]), "+f"(d[57]), "+f"(d[58]), "+f"(d[59]), "+f"(d[60]), "+f"(d[61]), "+f"(d[62]), "+f"(d[63])
        : "l"(da), "l"(db), "r"(sd));
}

constexpr int STAGE_BYTES = 49152, NSTAGE = 4;
constexpr int GEMM_SMEM = NSTAGE * STAGE_BYTES + 1024 + 128;

struct GemmSmem { uint32_t st, full, empty; };
__device__ __forceinline__ GemmSmem gemm_setup(uint8_t* raw) {
    GemmSmem g;
    uint32_t base = smem_u32(raw);
    g.st = (base + 127 + 1024) & ~1023u;
    g.full = base; g.empty = base + 64;
    if (threadIdx.x == 0) {
        for (int s = 0; s < NSTAGE; s++) { mbar_init(g.full + 8 * s, 1); mbar_init(g.empty + 8 * s, 2); }
        asm volatile("fence.mbarrier_init.release.cluster;" ::: "memory");
        asm volatile("fence.proxy.async.shared::cta;" ::: "memory");
    }
    __syncthreads();
    return g;
}
template <int BN, typename ACC>
__device__ __forceinline__ void gemm_kblock(ACC& acc, uint32_t stage, int wg, bool first) {
    const uint64_t da = desc_sw128(stage + wg * 8192, 16, 1024);
    const uint64_t db = desc_sw128(stage + 16384, 8192, 1024);
    wg_fence();
#pragma unroll
    for (int k = 0; k < 4; k++) {
        if constexpr (BN == 256) wgmma_n256(acc, da + k * 2, db + k * 128, first && k == 0 ? 0 : 1);
        else wgmma_n128(acc, da + k * 2, db + k * 128, first && k == 0 ? 0 : 1);
    }
    wg_commit();
}

__device__ __forceinline__ void kv_store_unit(const uint32_t (&pk)[64], int u, bf16* dst, int t) {
    const int G = (u >> 2) * 2 + (u & 1), hh = (u >> 1) & 1;
    uint32_t r0 = pk[(4 * G + 0) * 2 + hh], r1 = pk[(4 * G + 1) * 2 + hh], r2 = pk[(4 * G + 2) * 2 + hh], r3 = pk[(4 * G + 3) * 2 + hh];
    quad_transpose(r0, r1, r2, r3, t);
#define KVST ".cs"
    asm volatile("st.global" KVST ".v4.u32 [%0], {%1,%2,%3,%4};" ::"l"(dst + (size_t)hh * 8 * 8192 + G * 32), "r"(r0), "r"(r1), "r"(r2), "r"(r3) : "memory");
}

__global__ void __launch_bounds__(384, 1)
k_kv(const __grid_constant__ CUtensorMap mx, const __grid_constant__ CUtensorMap mwk, const __grid_constant__ CUtensorMap mwv,
     const bf16* __restrict__ Wq, const bf16* __restrict__ Wo) {
    extern __shared__ uint8_t smem_raw[];
    const int c = blockIdx.x;
    if (c >= 128) {
        const int i0 = (c - 128) * 384 + threadIdx.x;
        const uint4 ones = make_uint4(~0u, ~0u, ~0u, ~0u);
        for (int i = i0; i < NSEG * 64 * 32 / 2; i += 4 * 384) reinterpret_cast<uint4*>(g_memx)[i] = ones;
        for (int i = i0; i < 64 * 32 * 32 / 2; i += 4 * 384) reinterpret_cast<uint4*>(g_part)[i] = ones;
        if (i0 < 256) g_flag[i0] = 0;
        if (threadIdx.x == 0) {
            const char* p = (const char*)(c < 130 ? Wq : Wo) + (size_t)(c & 1) * (4 << 20);
            for (int i = 0; i < 256; i++) {
                asm volatile("cp.async.bulk.prefetch.L2.global [%0], 16384;" ::"l"(p + i * 16384) : "memory");
                __nanosleep(40);
            }
        }
        return;
    }
    GemmSmem g = gemm_setup(smem_raw);
    const int m0 = (c & 15) * 128, nb0 = c >> 4;
    const int wg = threadIdx.x >> 7;
    if (wg == 0) {
        asm volatile("setmaxnreg.dec.sync.aligned.u32 40;");
        if (threadIdx.x == 0) {
            for (int it = 0; it < 64; it++) {
                const int s = it & 3, tile = it >> 4, kb = it & 15;
                mbar_wait(g.empty + 8 * s, ((it >> 2) & 1) ^ 1);
                mbar_expect_tx(g.full + 8 * s, STAGE_BYTES);
                const int nb = nb0 + 8 * tile;
                tma2d(g.st + s * STAGE_BYTES, &mx, kb * 64, m0, g.full + 8 * s);
                tma3d(g.st + s * STAGE_BYTES + 16384, nb < 16 ? &mwk : &mwv, 0, kb * 64, (nb & 15) * 4, g.full + 8 * s);
            }
        }
    } else {
        asm volatile("setmaxnreg.inc.sync.aligned.u32 232;");
        const int cw = wg - 1, lane = threadIdx.x & 31, t = lane & 3;
        const int row = m0 + cw * 64 + ((threadIdx.x >> 5) & 3) * 16 + (lane >> 2);
        bf16* dst = g_kv + (size_t)row * 8192 + nb0 * 256 + t * 8;
        float acc[128];
        uint32_t pk[64];
#pragma unroll 1
        for (int tile = 0; tile < 4; tile++) {
#pragma unroll
            for (int kb = 0; kb < 16; kb++) {
                mbar_wait(g.full + 8 * (kb & 3), (kb >> 2) & 1);
                gemm_kblock<256>(acc, g.st + (kb & 3) * STAGE_BYTES, cw, kb == 0);
                if (tile > 0) kv_store_unit(pk, kb, dst + (tile - 1) * 2048, t);
                if (kb > 0) {
                    wg_wait<1>();
                    if ((threadIdx.x & 127) == 0) mbar_arrive(g.empty + 8 * ((kb - 1) & 3));
                }
            }
            wg_wait<0>();
            if ((threadIdx.x & 127) == 0) mbar_arrive(g.empty + 8 * 3);
#pragma unroll
            for (int i = 0; i < 64; i++) pk[i] = pack2(acc[2 * i], acc[2 * i + 1]);
        }
#pragma unroll
        for (int u = 0; u < 16; u++) kv_store_unit(pk, u, dst + 3 * 2048, t);
    }
}

constexpr int NS1 = 30;
#define RB1 4
#define PFC 4
constexpr int C_W1 = 0;
constexpr int C_W2 = C_W1 + 8 * NS1 * 512;
constexpr int C_KV = C_W2 + 14 * 8 * 512;
constexpr int C_RED = C_KV + 16384;
constexpr int C_R3 = C_RED + 64 * 272;
constexpr int C_QKV = C_R3 + 2560;
constexpr int C_SC = C_QKV + 3 * 8 * 272;
constexpr int C_OB = C_SC + 2 * 8 * 52 * 4;
constexpr int C_BAR = C_OB + 8 * 272;
__host__ __device__ constexpr int smem_idx(int ks, int j) {
    return ks == 0 ? j : ks == 1 ? (j < 4 ? 8 + j : -1) : (j < 3 ? 6 + 3 * ks + j : -1);
}
constexpr int CHAIN_SMEM = C_BAR + 64;
#define TS(i)

#define DLY3 3
#define DLY1 16
#define DLY0 8
#define DLYW 3
template <int N> __device__ __forceinline__ uint32_t delayed(uint32_t x, int lane) {
#pragma unroll
    for (int i = 0; i < N; i++) asm volatile("shfl.sync.idx.b32 %0, %0, %1, 31, -1;" : "+r"(x) : "r"(lane) : "memory");
    return x;
}
__device__ __forceinline__ void lds128v(uint32_t (&r)[4], uint32_t a) {
    asm volatile("ld.volatile.shared.v4.u32 {%0,%1,%2,%3}, [%4];" : "=r"(r[0]), "=r"(r[1]), "=r"(r[2]), "=r"(r[3]) : "r"(a) : "memory");
}
__device__ __forceinline__ uint2 lds64(uint32_t a) {
    uint2 v;
    asm volatile("ld.shared.v2.u32 {%0,%1}, [%2];" : "=r"(v.x), "=r"(v.y) : "r"(a) : "memory");
    return v;
}
#define LDQ ".L1::no_allocate"
__device__ __forceinline__ uint4 ldw128(const void* p) {
    uint4 v;
    asm volatile("ld.global.nc" LDQ ".v4.u32 {%0,%1,%2,%3}, [%4];" : "=r"(v.x), "=r"(v.y), "=r"(v.z), "=r"(v.w) : "l"(p));
    return v;
}
__device__ __forceinline__ void mbar_wait_u(uint32_t bar, uint32_t parity) {
    asm volatile("{\n.reg .pred p;\n.reg .u32 n;\n"
                 "mbarrier.try_wait.parity.shared::cta.b64 p, [%0], %1;\n@p bra.uni DONE;\nmov.u32 n, 0;\n"
                 "AGAIN:\nmbarrier.try_wait.parity.shared::cta.b64 p, [%0], %1;\n@p bra.uni DONE;\n"
                 "add.u32 n, n, 1;\nsetp.lt.u32 p, n, 0x100000;\n@p bra.uni AGAIN;\ntrap;\nDONE:\n}"
                 ::"r"(bar), "r"(parity) : "memory");
}
__device__ __forceinline__ void fetch8(uint64_t (&d)[8], const void* src) {
#define P8_LD(i) "ld.relaxed.gpu.global.b64 %" #i ", [%8 + " #i " * 256];\n"
    asm volatile(P8_LD(0) P8_LD(1) P8_LD(2) P8_LD(3) P8_LD(4) P8_LD(5) P8_LD(6) P8_LD(7)
                 : "=&l"(d[0]), "=&l"(d[1]), "=&l"(d[2]), "=&l"(d[3]), "=&l"(d[4]), "=&l"(d[5]), "=&l"(d[6]), "=&l"(d[7]) : "l"(src) : "memory");
}
template <bool TAG> __device__ __forceinline__ void settle8(uint2 (&v)[8], uint64_t (&d)[8], const void* src, uint32_t tag) {
#define P8_X(i) "mov.b64 {x" #i ", _}, %" #i ";\n"
#define P8_HEAD "{\n.reg .pred p, q;\n.reg .u32 n, x0, x1, x2, x3, x4, x5, x6, x7, m0, m1;\nmov.u32 n, 0;\nCHECK:\n" \
                P8_X(0) P8_X(1) P8_X(2) P8_X(3) P8_X(4) P8_X(5) P8_X(6) P8_X(7)
#define P8_VOTE "vote.sync.all.pred p, p, -1;\n@p bra.uni DONE;\n"
#define P8_TAIL "add.u32 n, n, 1;\nsetp.lt.u32 p, n, 0x100000;\n@p bra.uni CHECK;\ntrap;\nDONE:\n}"
#define P8_OPS : "+l"(d[0]), "+l"(d[1]), "+l"(d[2]), "+l"(d[3]), "+l"(d[4]), "+l"(d[5]), "+l"(d[6]), "+l"(d[7]) : "l"(src), "r"(tag) : "memory"
#define P8_RT(i) "lop3.b32 m0, x" #i ", %9, 1, 0x28;\nsetp.ne.u32 q, m0, 0;\n@q " P8_LD(i)
#define P8_RS(i) "setp.eq.u32 q, x" #i ", 0xffffffff;\n@q " P8_LD(i)
    if (TAG)
        asm volatile(P8_HEAD "lop3.b32 m0, x0, x1, %9, 0x7e;\nlop3.b32 m1, x2, x3, %9, 0x7e;\nlop3.b32 m0, m0, x4, %9, 0xf6;\n"
                     "lop3.b32 m1, m1, x5, %9, 0xf6;\nlop3.b32 m0, m0, x6, %9, 0xf6;\nlop3.b32 m1, m1, x7, %9, 0xf6;\n"
                     "lop3.b32 m0, m0, m1, 1, 0xa8;\nsetp.eq.u32 p, m0, 0;\n" P8_VOTE
                     P8_RT(0) P8_RT(1) P8_RT(2) P8_RT(3) P8_RT(4) P8_RT(5) P8_RT(6) P8_RT(7) P8_TAIL P8_OPS);
    else
        asm volatile(P8_HEAD "max.u32 m0, x0, x1;\nmax.u32 m0, m0, x2;\nmax.u32 m1, x3, x4;\nmax.u32 m1, m1, x5;\nmax.u32 m0, m0, x6;\n"
                     "max.u32 m0, m0, x7;\nmax.u32 m0, m0, m1;\nsetp.ne.u32 p, m0, 0xffffffff;\n" P8_VOTE
                     P8_RS(0) P8_RS(1) P8_RS(2) P8_RS(3) P8_RS(4) P8_RS(5) P8_RS(6) P8_RS(7) P8_TAIL P8_OPS);
#pragma unroll
    for (int i = 0; i < 8; i++) { v[i].x = (uint32_t)d[i]; v[i].y = (uint32_t)(d[i] >> 32); }
}
__device__ __forceinline__ void sum8(float (&c)[4], const uint2 (&v)[8], uint32_t idn) {
    float d[4] = {0.f, 0.f, 0.f, 0.f};
    c[0] = c[1] = c[2] = c[3] = 0.f;
    mma16816(c, v[0].x, v[0].y, v[1].x, v[1].y, idn, idn);
    mma16816(d, v[2].x, v[2].y, v[3].x, v[3].y, idn, idn);
    mma16816(c, v[4].x, v[4].y, v[5].x, v[5].y, idn, idn);
    mma16816(d, v[6].x, v[6].y, v[7].x, v[7].y, idn, idn);
    c[0] += d[0]; c[1] += d[1]; c[2] += d[2]; c[3] += d[3];
}

__global__ void __cluster_dims__(3, 1, 1) __launch_bounds__(256, 1)
k_chain(const bf16* __restrict__ mem0, const bf16* __restrict__ Wq, const bf16* __restrict__ Wk, const bf16* __restrict__ Wv,
        const bf16* __restrict__ Wo, const __grid_constant__ CUtensorMap mkv) {
    extern __shared__ __align__(1024) uint8_t smem_chain[];
    const uint32_t sb = smem_u32(smem_chain);
    if (sb & 1023) __trap();
    const int w = __shfl_sync(~0u, threadIdx.x >> 5, 0), lane = __shfl_sync(~0u, threadIdx.x & 31, threadIdx.x & 31);
    const int tid = w * 32 + lane, g = lane >> 2, t = lane & 3;
    auto pin = [&](uint32_t x) { return delayed<1>(x, lane); };
    const int h = blockIdx.x / 3, r = blockIdx.x - 3 * h;
    const uint32_t bar_x = sb + C_BAR, bar_kv = sb + C_BAR + 8, bar_go = sb + C_BAR + 16, bar_w = sb + C_BAR + 24;
    asm volatile("griddepcontrol.launch_dependents;");
    const int tbase = r == 0 ? 0 : 1 + 21 * r, ntile = r == 0 ? 22 : 21;
    if (tid == 0) {
        mbar_init(bar_x, 8); mbar_init(bar_kv, 1); mbar_init(bar_go, 1); mbar_init(bar_w, 1);
        asm volatile("fence.mbarrier_init.release.cluster;" ::: "memory");
        asm volatile("fence.proxy.async.shared::cta;" ::: "memory");
        mbar_expect_tx(bar_w, 128 * 32 * ntile);
    }
    __syncthreads();
    asm volatile("barrier.cluster.arrive.relaxed.aligned;" ::: "memory");
    if (tid < 128)
        asm volatile("cp.async.bulk.shared::cluster.global.mbarrier::complete_tx::bytes [%0], [%1], %2, [%3];"
                     ::"r"(sb + C_W1 + tid * 720), "l"(Wo + (size_t)(h * 128 + tid) * DM + tbase * 16), "r"(32 * ntile), "r"(bar_w) : "memory");
    const int tile0 = tbase + 7 - w;
    const bool three = w >= (r == 0 ? 2 : 3);
    const uint32_t wa = pin(sb + tid * 16);
#define W1A(i) (wa + C_W1 + (i) * 4096)
#define W2A(x) (wa + C_W2 + ((x) < 8 ? (x) * 4096 : 32768 - 1024 + ((x) - 8) * 3072))
    uint32_t wo0[8][4], wr[64][4];
    {
        const bf16* W = (r == 0 ? Wq : r == 1 ? Wk : Wv) + (size_t)(128 * w + (lane >> 4)) * HD + h * 128 + 8 * (lane & 15);
        uint4 raw[8][8];
        auto fetch = [&](int ks) {
#pragma unroll
            for (int i = 0; i < 8; i++) raw[ks][i] = ldw128(W + (size_t)(16 * ks + 2 * i) * HD);
        };
        fetch(0); fetch(1); fetch(2); fetch(3);
        mbar_wait_u(bar_w, 0);
        const uint32_t p = sb + C_W1 + ((lane & 7) + (lane >> 4) * 8) * 720 + (7 - w) * 32 + ((lane >> 3) & 1) * 16;
#pragma unroll
        for (int ks = 0; ks < 8; ks++) {
            uint32_t a[4];
            ldsm4t(wo0[ks], p + ks * 16 * 720);
            ldsm4t(a, p + ks * 16 * 720 + 256);
            sts128(W2A(ks), a[0], a[1], a[2], a[3]);
            if (three) { ldsm4t(a, p + ks * 16 * 720 + 512); sts128(W2A(8 + ks), a[0], a[1], a[2], a[3]); }
        }
        __syncthreads();
        const uint32_t stg = sb + C_KV + w * 4096;
        const uint32_t rd = stg + ((lane & 6) + 8 * (lane & 1) + (lane >> 4)) * 256 + ((((lane >> 3) & 1) ^ (lane & 7)) << 4);
#pragma unroll
        for (int ks = 0; ks < 8; ks++) {
#pragma unroll
            for (int i = 0; i < 8; i++)
                sts128(stg + (2 * i + (lane >> 4)) * 256 + (((lane & 15) ^ (((2 * i) & 6) | (i >> 2))) << 4),
                       raw[ks][i].x, raw[ks][i].y, raw[ks][i].z, raw[ks][i].w);
            if (ks < 2) fetch(ks + 4);
            if (ks == 3 || ks == 5) fetch(ks / 2 + 5);
            __syncwarp();
#pragma unroll
            for (int j = 0; j < 8; j++) {
                if (smem_idx(ks, j) >= 0) {
                    uint32_t a[4];
                    ldsm4t(a, rd ^ (j << 5));
                    sts128(W1A(smem_idx(ks, j)), a[0], a[1], a[2], a[3]);
                } else ldsm4t(wr[8 * ks + j], rd ^ (j << 5));
            }
            __syncwarp();
        }
    }
    asm volatile("fence.proxy.async.shared::cta;" ::: "memory");
    __syncthreads();
    if (tid == 0) {
        mbar_expect_tx(bar_kv, 16384);
        tma3d(sb + C_KV, &mkv, 0, 0, 2 * h, bar_kv);
        tma3d(sb + C_KV + 8192, &mkv, 0, 0, 64 + 2 * h, bar_kv);
    }
    asm volatile("barrier.cluster.wait.aligned;" ::: "memory");

    auto publish_kvm = [&](int s) {
        uint32_t v[4];
        lds128(v, sb + C_QKV + (8 + (tid >> 4)) * 272 + (tid & 15) * 16);
        asm volatile("st.global.v4.u32 [%0], {%1,%2,%3,%4};"
                     ::"l"(g_kvm + (size_t)(s * 8 + ((tid >> 4) & 7)) * 8192 + (tid >> 7) * HD + h * 128 + (tid & 15) * 8),
                       "r"(v[0]), "r"(v[1]), "r"(v[2]), "r"(v[3]) : "memory");
        if ((s & 3) == 3) {
            __syncthreads();
            if (w == 7) asm volatile("{\n.reg .pred p;\nsetp.eq.u32 p, %2, 0;\nfence.acq_rel.gpu;\n@p st.relaxed.gpu.global.u32 [%0], %1;\n}"
                                     ::"l"(g_flag + h), "r"(s + 1), "r"(lane) : "memory");
        }
    };
    const float sl2e = 0.08838834764831845f * 1.4426950408889634f;
    const uint32_t idn = pin(g == 2 * t ? 0x00003f80u : g == 2 * t + 1 ? 0x3f800000u : 0u);
    const uint32_t lm = pin(sb + (lane & 7) * 272 + (lane >> 3) * 16);
    const uint32_t sa = pin(sb + C_SC + (w & 1) * (8 * 52 * 4) + (2 * t * 52 + (w < 4 ? 32 : (w & 2) * 8) + g) * 4);
    const uint32_t sr = pin(sb + C_SC + (g * 52 + 8 * t) * 4), sr2 = pin(sb + C_SC + (g * 52 + 32 + 2 * t) * 4);
    uint32_t kva;
    {
        const int pos = (w & 2) * 8 + (lane & 15), row = (pos & 24) + ((pos + (pos >> 2 & 6)) & 7);
        const int key = 4 * (lane & 6) + (((lane & 7) + 2 * (lane >> 4)) & 7);
        kva = pin(w >= 4 ? sb + C_KV + (w & 1) * 4096 + row * 128 + (((lane >> 4) ^ (row & 7)) << 4)
                         : sb + C_KV + 8192 + (w >> 1) * 4096 + key * 128 + ((((w & 1) * 4 + ((lane >> 3) & 1)) ^ (key & 7)) << 4));
    }
    uint32_t buf0[8][4], ring[RB1][4];
    auto stage_w1 = [&]() {
#pragma unroll
        for (int i = 0; i < 8; i++) lds128v(buf0[i], W1A(i));
#pragma unroll
        for (int i = 0; i < RB1; i++) lds128v(ring[i], W1A(8 + i));
    };
    stage_w1();
    if (r > 0 && w < 2) asm volatile("prefetch.global.L2 [%0];" ::"l"(g_memx + ((w + 1) * 64 + 2 * h + r - 1) * 32 + lane) : "memory");
    if (r > 0) asm volatile("prefetch.global.L2 [%0];" ::"l"(g_part + (2 * h + r - 1) * 1024 + tid * 4) : "memory");
    uint2 bm[8];
#pragma unroll
    for (int ks = 0; ks < 8; ks++) {
        const uint32_t* p = (const uint32_t*)(mem0 + g * DM + (8 * w + ks) * 16) + t;
        const uint32_t x = __ldg(p), y = __ldg(p + 4);
        bm[ks] = make_uint2(__byte_perm(x, y, 0x5410), __byte_perm(x, y, 0x7632));
    }
#pragma unroll 1
    for (int s = 0;; s++) {
        TS(1);
        {
            float acc[8][4];
#pragma unroll
            for (int ks = 0; ks < 8; ks++) {
#pragma unroll
                for (int j = 0; j < 8; j++) {
                    const int i = smem_idx(ks, j) - 8;
                    if (ks == 0) {
                        acc[j][0] = acc[j][1] = acc[j][2] = acc[j][3] = 0.f;
                        mma16816(acc[j], buf0[j][0], buf0[j][1], buf0[j][2], buf0[j][3], bm[ks].x, bm[ks].y);
                    } else if (i >= 0) {
                        uint32_t(&a)[4] = ring[i % RB1];
                        mma16816(acc[j], a[0], a[1], a[2], a[3], bm[ks].x, bm[ks].y);
                        if (8 + i + RB1 < NS1) lds128v(a, W1A(8 + i + RB1));
                    } else {
                        const uint32_t(&a)[4] = wr[8 * ks + j];
                        mma16816(acc[j], a[0], a[1], a[2], a[3], bm[ks].x, bm[ks].y);
                    }
                }
            }
#pragma unroll
            for (int c = 0; c < 4; c++)
                stsm4t(lm + C_RED + w * 2176 + c * 64, pack2(acc[2 * c][0], acc[2 * c][1]), pack2(acc[2 * c][2], acc[2 * c][3]),
                       pack2(acc[2 * c + 1][0], acc[2 * c + 1][1]), pack2(acc[2 * c + 1][2], acc[2 * c + 1][3]));
        }
        {
            const uint32_t a = sb + C_RED + w * 272 + lane * 8;
            if (s < NSEG - 1) mbar_wait_u(bar_kv, s & 1);
            TS(2);
            __syncthreads();
            TS(3);
            uint2 v[8];
#pragma unroll
            for (int i = 0; i < 8; i++) v[i] = lds64(a + i * 2176);
            float c[4];
            sum8(c, v, idn);
            const uint32_t p0 = pack2(c[0], c[1]), p1 = pack2(c[2], c[3]);
            const uint32_t dst = sb + C_QKV + (r * 8 + w) * 272 + lane * 8;
#pragma unroll
            for (int i = 1; i < 3; i++) {
                const uint32_t peer = r + i >= 3 ? r + i - 3 : r + i;
                uint32_t rd, rb;
                asm("mapa.shared::cluster.u32 %0, %1, %2;" : "=r"(rd) : "r"(dst), "r"(peer));
                asm("mapa.shared::cluster.u32 %0, %1, %2;" : "=r"(rb) : "r"(bar_x), "r"(peer));
                asm volatile("st.async.weak.shared::cluster.mbarrier::complete_tx::bytes.v2.b32 [%0], {%1,%2}, [%3];"
                             ::"r"(rd), "r"(p0), "r"(p1), "r"(rb) : "memory");
            }
            sts64(dst, p0, p1);
            __syncwarp();
            asm volatile("{\n.reg .pred p;\nsetp.eq.u32 p, %1, 0;\n@p mbarrier.arrive.expect_tx.shared::cta.b64 _, [%0], 512;\n}"
                         ::"r"(bar_x), "r"(lane) : "memory");
        }
        TS(4);
        if (s == NSEG - 1) break;
        uint32_t wb[8][4], wc[8][4];
        const uint32_t po = ((tile0 * 32 + h) * 32 + lane) * 8;
        const uint32_t tag = s & 1;
        auto project = [&](const uint32_t(&wt)[8][4], const uint32_t(&ob)[4][4], int i) {
            float c0[4] = {0.f, 0.f, 0.f, 0.f}, c1[4] = {0.f, 0.f, 0.f, 0.f};
#pragma unroll
            for (int ks = 0; ks < 8; ks++)
                mma16816((ks & 1) ? c1 : c0, wt[ks][0], wt[ks][1], wt[ks][2], wt[ks][3], ob[ks >> 1][(ks & 1) * 2], ob[ks >> 1][(ks & 1) * 2 + 1]);
            st_rlx64((uint2*)((char*)g_part + po) + i * 8192, (pack2(c0[0] + c1[0], c0[2] + c1[2]) & ~1u) | tag, pack2(c0[1] + c1[1], c0[3] + c1[3]));
        };
        if (w >= 4) {
            uint32_t ka[4][4];
#pragma unroll
            for (int ks = 0; ks < 4; ks++) ldsm4(ka[ks], kva ^ (ks << 5));
            const uint32_t qa = lm + C_QKV + (w & 1) * 128;
            TS(5);
            mbar_wait_u(bar_x, s & 1);
            TS(6);
            {
                uint32_t qb[2][4];
                ldsm4(qb[0], qa);
                ldsm4(qb[1], qa + 64);
                float c0[4] = {0.f, 0.f, 0.f, 0.f}, c1[4] = {0.f, 0.f, 0.f, 0.f};
                mma16816(c0, ka[0][0], ka[0][1], ka[0][2], ka[0][3], qb[0][0], qb[0][1]);
                mma16816(c1, ka[1][0], ka[1][1], ka[1][2], ka[1][3], qb[0][2], qb[0][3]);
                mma16816(c0, ka[2][0], ka[2][1], ka[2][2], ka[2][3], qb[1][0], qb[1][1]);
                mma16816(c1, ka[3][0], ka[3][1], ka[3][2], ka[3][3], qb[1][2], qb[1][3]);
                sts32f(sa, c0[0] + c1[0]);
                sts32f(sa + 208, c0[1] + c1[1]);
                sts32f(sa + 32, c0[2] + c1[2]);
                sts32f(sa + 240, c0[3] + c1[3]);
            }
            __syncthreads();
            TS(7);
            if (w == 7 && s + 1 < NSEG - 1) {
                if (lane == 0) {
                    mbar_expect_tx(bar_kv, 16384);
                    tma3d(sb + C_KV, &mkv, 0, (s + 1) * 32, 2 * h, bar_kv);
                    tma3d(sb + C_KV + 8192, &mkv, 0, (s + 1) * 32, 64 + 2 * h, bar_kv);
                }
                __syncwarp();
            }
            const uint32_t wd = delayed<DLYW>(wa, lane);
#pragma unroll
            for (int i = 0; i < 8; i++) lds128(wb[i], wd + C_W2 + i * 4096);
#pragma unroll
            for (int i = 0; i < PFC; i++) lds128(wc[i], wd + C_W2 + 32768 - 1024 + i * 3072);
            TS(8);
            __syncthreads();
            TS(9);
            uint32_t ob[4][4];
#pragma unroll
            for (int i = 0; i < 4; i++) ldsm4(ob[i], lm + C_OB + i * 64);
#pragma unroll
            for (int i = PFC; i < 8; i++) lds128v(wc[i], W2A(8 + i));
            project(wb, ob, 1);
            project(wo0, ob, 0);
            project(wc, ob, 2);
        } else {
            uint32_t va[4][4];
#pragma unroll
            for (int i = 0; i < 4; i++) ldsm4t(va[i], kva ^ (((i >> 1) << 5) | ((i & 1) * 0x240)));
#pragma unroll
            for (int i = 0; i < 8; i++) lds128(wb[i], W2A(i));
            const uint32_t qa = lm + C_QKV + (w & 1) * 128, oa = lm + w * 64;
            TS(5);
            mbar_wait_u(bar_x, s & 1);
            TS(6);
            if (w < 2) {
                uint32_t qb[2][4], km[2][4];
                ldsm4(qb[0], qa);
                ldsm4(km[0], qa + 8 * 272);
                ldsm4(qb[1], qa + 64);
                ldsm4(km[1], qa + 8 * 272 + 64);
                float c0[4] = {0.f, 0.f, 0.f, 0.f}, c1[4] = {0.f, 0.f, 0.f, 0.f};
                mma16816(c0, km[0][0], km[0][1], km[0][2], km[0][3], qb[0][0], qb[0][2]);
                mma16816(c1, km[0][0], km[0][1], km[0][2], km[0][3], qb[0][1], qb[0][3]);
                mma16816(c0, km[1][0], km[1][1], km[1][2], km[1][3], qb[1][0], qb[1][2]);
                mma16816(c1, km[1][0], km[1][1], km[1][2], km[1][3], qb[1][1], qb[1][3]);
                sts32f(sa, c0[0] + c1[2]);
                sts32f(sa + 208, c0[1] + c1[3]);
            }
            __syncthreads();
            TS(7);
            {
                float4 x0 = lds128f(sr), y0 = lds128f(sr + 1664), x1 = lds128f(sr + 16), y1 = lds128f(sr + 1680);
                float2 x2 = lds64f(sr2), y2 = lds64f(sr2 + 1664);
                float p[10] = {x0.x + y0.x, x0.y + y0.y, x0.z + y0.z, x0.w + y0.w, x1.x + y1.x,
                               x1.y + y1.y, x1.z + y1.z, x1.w + y1.w, x2.x + y2.x, x2.y + y2.y};
                float m = fmaxf(fmaxf(fmaxf(p[0], p[1]), fmaxf(p[2], p[3])), fmaxf(fmaxf(fmaxf(p[4], p[5]), fmaxf(p[6], p[7])), fmaxf(p[8], p[9])));
                const float m1 = __shfl_xor_sync(~0u, m, 1), m2 = __shfl_xor_sync(~0u, m, 2), m3 = __shfl_xor_sync(~0u, m, 3);
                uint32_t vm[4];
                ldsm4t(vm, oa + C_QKV + 16 * 272);
                m = fmaxf(fmaxf(m, m1), fmaxf(m2, m3));
                const float ms = m * sl2e;
#pragma unroll
                for (int i = 0; i < 10; i++) p[i] = ex2(fmaf(p[i], sl2e, -ms));
                const uint32_t b0 = pack2(p[0], p[1]), b1 = pack2(p[2], p[3]), b2 = pack2(p[4], p[5]), b3 = pack2(p[6], p[7]), b4 = pack2(p[8], p[9]);
                const uint32_t one = 0x3f803f80u;
                float o0[4] = {0.f, 0.f, 0.f, 0.f}, o1[4] = {0.f, 0.f, 0.f, 0.f}, sm[4] = {0.f, 0.f, 0.f, 0.f};
                mma16816(sm, one, one, one, one, b0, b1);
                mma16816(o0, va[0][0], va[0][1], va[0][2], va[0][3], b0, b1);
                mma16816(o1, va[2][0], va[2][1], va[2][2], va[2][3], b0, b1);
                mma16816(sm, one, one, one, one, b2, b3);
                mma16816(o0, va[1][0], va[1][1], va[1][2], va[1][3], b2, b3);
                mma16816(o1, va[3][0], va[3][1], va[3][2], va[3][3], b2, b3);
                mma1688(sm, one, one, b4);
                mma1688(o0, vm[0], vm[1], b4);
                mma1688(o1, vm[2], vm[3], b4);
                float i0, i1;
                asm("rcp.approx.ftz.f32 %0, %1;" : "=f"(i0) : "f"(sm[0]));
                asm("rcp.approx.ftz.f32 %0, %1;" : "=f"(i1) : "f"(sm[1]));
                stsm4t(oa + C_OB, pack2(o0[0] * i0, o0[1] * i1), pack2(o0[2] * i0, o0[3] * i1),
                       pack2(o1[0] * i0, o1[1] * i1), pack2(o1[2] * i0, o1[3] * i1));
            }
            TS(8);
            __syncthreads();
            TS(9);
            uint32_t ob[4][4];
#pragma unroll
            for (int i = 0; i < 4; i++) ldsm4(ob[i], lm + C_OB + i * 64);
            if (three) {
#pragma unroll
                for (int i = 0; i < 8; i++) lds128v(wc[i], W2A(8 + i));
                project(wb, ob, 1);
                project(wo0, ob, 0);
                project(wc, ob, 2);
            } else {
                project(wb, ob, 1);
                project(wo0, ob, 0);
            }
        }
        TS(10);
        __syncthreads();
        uint32_t eo = (((s + 1) * 64 + 8 * w) * 32 + lane) * 8;
        uint64_t d[8];
        if (r == 0) {
            TS(11); TS(12);
            stage_w1();
            publish_kvm(s);
            mbar_wait_u(bar_go, s & 1);
            eo = delayed<DLY0>(eo, lane);
        } else {
            const int j = 2 * h + r - 1;
            if (w < 4) {
                const char* src = (const char*)g_part + delayed<DLY3>(((j * 32 + 8 * w) * 32 + lane) * 8, lane);
                fetch8(d, src);
                const uint32_t a = pin(sb + C_R3 + w * 640 + t * 160 + g * 8), a2 = pin(sb + C_R3 + g * 80 + t * 16);
                stage_w1();
                uint2 v[8];
                settle8<true>(v, d, src, tag);
                TS(11);
                float c[4];
                sum8(c, v, idn);
                sts64f(a, c[0], c[1]);
                sts64f(a + 80, c[2], c[3]);
                __syncthreads();
                TS(12);
                if (w == 0) {
                    const float4 u0 = lds128f(a2), u1 = lds128f(a2 + 640), u2 = lds128f(a2 + 1280), u3 = lds128f(a2 + 1920);
                    st_rlx64((uint2*)((char*)g_memx + eo) + j * 32, pack2((u0.x + u1.x) + (u2.x + u3.x), (u0.y + u1.y) + (u2.y + u3.y)),
                             pack2((u0.z + u1.z) + (u2.z + u3.z), (u0.w + u1.w) + (u2.w + u3.w)));
                }
            } else {
                if (w == 5 && s + 3 < NSEG)
                    asm volatile("prefetch.global.L2 [%0];" ::"l"(g_memx + ((s + 3) * 64 + j) * 32 + lane) : "memory");
                stage_w1();
                TS(11);
                __syncthreads();
                TS(12);
                if (w == 4 && r == 1)
                    asm volatile("{\n.reg .pred p;\n.reg .u32 a;\nelect.sync _|p, -1;\nmapa.shared::cluster.u32 a, %0, 0;\n"
                                 "@p mbarrier.arrive.relaxed.cluster.shared::cluster.b64 _, [a];\n}" ::"r"(bar_go) : "memory");
            }
            eo = delayed<DLY1>(eo, lane);
        }
        { const int s_ = s; { const int s = s_ + 1; TS(0); } }
        fetch8(d, (const char*)g_memx + eo);
        settle8<false>(bm, d, (const char*)g_memx + eo, 0);
    }
    mbar_wait_u(bar_x, (NSEG - 1) & 1);
    if (r == 0) publish_kvm(NSEG - 1);
    asm volatile("barrier.cluster.arrive.relaxed.aligned;\nbarrier.cluster.wait.aligned;" ::: "memory");
}

constexpr int S4_US = 4368;
constexpr int S4_PS = 8336;
constexpr int S4_KS = 1296;
constexpr int S4_U = 0, S4_P = 16 * S4_US, S4_K = S4_P + 16 * S4_PS;
constexpr int S4_SMEM = S4_K + 16 * S4_KS;

__device__ __forceinline__ void csq(float& a, float& b) { const float t = a * b; a = fmaf(a, a, -b * b); b = t + t; }
__device__ __forceinline__ uint32_t cmulpack(float cr, float ci, float a, float b) {
    return pack2(fmaf(cr, a, -ci * b), -fmaf(cr, b, ci * a));
}
__device__ __forceinline__ void cexp(float& re, float& im, float l2, float turns) {
    const float mag = ex2(l2), fr = (turns - rintf(turns)) * 6.283185307179586f;
    re = mag * __cosf(fr); im = mag * __sinf(fr);
}
__device__ __forceinline__ int s4_idx(int l) {
    const int r = l < 256 ? 0 : 24 - __clz(l);
    const int m = r == 0 ? l : (l + (1 << (r - 1)) - 1 + ((l >> r) & 1)) >> r;
    return 128 * r + m;
}

__global__ void __launch_bounds__(512, 1)
k_s4(const bf16* __restrict__ u, const bf16* __restrict__ Are, const bf16* __restrict__ Aim, const bf16* __restrict__ Bre,
     const bf16* __restrict__ Bim, const bf16* __restrict__ Cre, const bf16* __restrict__ Cim, const bf16* __restrict__ logdt,
     const bf16* __restrict__ Dsk, bf16* __restrict__ out) {
    extern __shared__ __align__(16) uint8_t smem_raw[];
    const uint32_t sb = smem_u32(smem_raw);
    asm volatile("griddepcontrol.launch_dependents;");
    const int tid = threadIdx.x, w = tid >> 5, lane = tid & 31, g = lane >> 2, t = lane & 3;
    const int d0 = blockIdx.x * 16;
    const int d = d0 + (w & 1) + ((w >> 1) & 3) * 4 + (w >> 3) * 2;
    const uint32_t tr_off = (lane & 15), tr_l = (lane >> 4) * 16;
    {
        const bf16* src = u + (size_t)(w * 128 + g) * DM + d0 + 4 * t;
        uint2 v[16];
#pragma unroll
        for (int i = 0; i < 16; i++) v[i] = __ldg((const uint2*)(src + (size_t)i * 8 * DM));
        if (lane < 16) sts128(sb + S4_U + w * S4_US + lane * 16, 0, 0, 0, 0);
#pragma unroll
        for (int i = 0; i < 8; i++)
            stsm4t(sb + S4_U + tr_off * S4_US + 256 + (w * 128 + i * 16) * 2 + tr_l, v[2 * i].x, v[2 * i].y, v[2 * i + 1].x, v[2 * i + 1].y);
    }
    const uint32_t pk = sb + S4_P + w * S4_PS, kd = sb + S4_K + w * S4_KS;
    {
        const float dt = bf_round(expf(__bfloat162float(logdt[d])));
        const int o = d * 128 + lane * 4;
        const uint2 ar = __ldg((const uint2*)(Are + o)), ai = __ldg((const uint2*)(Aim + o)), br = __ldg((const uint2*)(Bre + o));
        const uint2 bi = __ldg((const uint2*)(Bim + o)), cr = __ldg((const uint2*)(Cre + o)), ci = __ldg((const uint2*)(Cim + o));
#pragma unroll
        for (int i = 0; i < 4; i++) {
            auto pick = [&](const uint2& v) { const uint32_t x = i < 2 ? v.x : v.y; return (i & 1) ? bf_hi(x) : bf_lo(x); };
            const float dbr = dt * pick(br), dbi = dt * pick(bi), c_r = pick(cr), c_i = pick(ci);
            sts128f(pk + (lane * 4 + i) * 16, dt * pick(ar) * 1.4426950408889634f, dt * pick(ai) * 0.15915494309189535f,
                    fmaf(c_r, dbr, -c_i * dbi), fmaf(c_r, dbi, c_i * dbr));
        }
    }
    __syncwarp();
    {
        float T[5][4];
#pragma unroll
        for (int i = 0; i < 5; i++) T[i][0] = T[i][1] = T[i][2] = T[i][3] = 0.f;
        float klast = 0.f;
        const float g0 = (float)g, g8 = (float)(g + 8);
#pragma unroll 1
        for (int ks = 0; ks < 16; ks++) {
            uint32_t A[4][4], B[5][2];
#pragma unroll
            for (int hf = 0; hf < 2; hf++) {
                const float4 p = lds128f(pk + (ks * 8 + hf * 4 + t) * 16);
                float ur, ui, wr_, wi;
                cexp(ur, ui, p.x * g0, p.y * g0);
                cexp(wr_, wi, p.x * g8, p.y * g8);
#pragma unroll
                for (int r = 0; r < 4; r++) {
                    A[r][hf * 2] = pack2(ur, ui); A[r][hf * 2 + 1] = pack2(wr_, wi);
                    csq(ur, ui); csq(wr_, wi);
                }
                B[0][hf] = cmulpack(p.z, p.w, ur, ui);
#pragma unroll
                for (int r = 1; r < 5; r++) { B[r][hf] = cmulpack(p.z, p.w, wr_, wi); csq(wr_, wi); }
                klast += fmaf(p.z, wr_, -p.w * wi);
            }
            mma16816(T[0], A[0][0], A[0][1], A[0][2], A[0][3], B[0][0], B[0][1]);
#pragma unroll
            for (int r = 0; r < 4; r++) mma16816(T[r + 1], A[r][0], A[r][1], A[r][2], A[r][3], B[r + 1][0], B[r + 1][1]);
        }
        klast += __shfl_xor_sync(~0u, klast, 1);
        klast += __shfl_xor_sync(~0u, klast, 2);
        const uint32_t a = kd + (lane & 7) * 32 + ((lane >> 3) & 1) * 16 + (lane >> 4) * 256;
        stsm4t(a, pack2(T[0][0], T[0][1]), pack2(T[0][2], T[0][3]), pack2(T[1][0], T[1][1]), pack2(T[1][2], T[1][3]));
        stsm4t(a + 512, pack2(T[2][0], T[2][1]), pack2(T[2][2], T[2][3]), pack2(T[3][0], T[3][1]), pack2(T[3][2], T[3][3]));
        asm volatile("stmatrix.sync.aligned.m8n8.x2.trans.shared.b16 [%0], {%1,%2};"
                     ::"r"(a + 1024), "r"(pack2(T[4][0], T[4][1])), "r"(pack2(T[4][2], T[4][3])) : "memory");
        if (lane == 0) asm volatile("st.shared.u16 [%0], %1;" ::"r"(kd + 1280), "h"((unsigned short)pack2(klast, 0.f)) : "memory");
    }
    __syncwarp();
    {
        if (lane < 4) sts128(pk + lane * 16, 0, 0, 0, 0);
#pragma unroll 2
        for (int i = 0; i < 16; i++) {
            const int x = i * 128 + lane * 4;
            uint32_t v[5];
#pragma unroll
            for (int j = 0; j < 5; j++) {
                unsigned short hv;
                asm volatile("ld.shared.u16 %0, [%1];" : "=h"(hv) : "r"(kd + 2 * s4_idx(max(x + j - 1, 0))) : "memory");
                v[j] = hv;
            }
            if (x == 0) v[0] = 0;
            sts128(pk + 64 + x * 4, v[1] | (v[0] << 16), v[2] | (v[1] << 16), v[3] | (v[2] << 16), v[4] | (v[3] << 16));
        }
    }
    __syncthreads();
    {
        float acc[16][4];
#pragma unroll
        for (int i = 0; i < 16; i++) acc[i][0] = acc[i][1] = acc[i][2] = acc[i][3] = 0.f;
        const uint32_t ub = sb + S4_U + w * S4_US + 256 + (lane & 7) * 32 + ((lane >> 3) & 1) * 16 + (lane >> 4) * 256;
        const uint32_t kb = pk + 64 + (g - 2 * t) * 4;
#pragma unroll 1
        for (int j0 = 0; j0 < 8; j0++) {
            uint32_t B[8][4];
#pragma unroll
            for (int i = 0; i < 8; i++) ldsm4(B[i], ub + i * 512 - j0 * 32);
#pragma unroll
            for (int J = 0; J < 16; J++) {
                const uint32_t a = kb + j0 * 64 + J * 512;
                const uint32_t rm = lds32(a - 32), r0 = lds32(a), rp = lds32(a + 32);
#pragma unroll
                for (int I = J; I < 16; I++)
                    mma16816(acc[I], r0, rp, rm, r0, B[(I - J) >> 1][((I - J) & 1) * 2], B[(I - J) >> 1][((I - J) & 1) * 2 + 1]);
            }
        }
        __syncwarp();
        const uint32_t yb = pk + (lane & 7) * 32 + ((lane >> 3) & 1) * 16 + (lane >> 4) * 256;
#pragma unroll
        for (int i = 0; i < 8; i++)
            stsm4t(yb + i * 512, pack2(acc[2 * i][0], acc[2 * i][1]), pack2(acc[2 * i][2], acc[2 * i][3]),
                   pack2(acc[2 * i + 1][0], acc[2 * i + 1][1]), pack2(acc[2 * i + 1][2], acc[2 * i + 1][3]));
    }
    __syncthreads();
    {
        const uint2 dv = __ldg((const uint2*)(Dsk + d0 + 4 * t));
        bf16* dst = out + (size_t)(w * 128 + g) * 2048 + 1024 + d0 + 4 * t;
#pragma unroll
        for (int i = 0; i < 8; i++) {
            uint32_t y[4], x[4], o[4];
            ldsm4t(y, sb + S4_P + tr_off * S4_PS + (w * 128 + i * 16) * 2 + tr_l);
            ldsm4t(x, sb + S4_U + tr_off * S4_US + 256 + (w * 128 + i * 16) * 2 + tr_l);
#pragma unroll
            for (int j = 0; j < 4; j++) {
                const uint32_t dd = (j & 1) ? dv.y : dv.x;
                const uint32_t sk = pack2(bf_lo(x[j]) * bf_lo(dd), bf_hi(x[j]) * bf_hi(dd));
                o[j] = pack2(bf_lo(y[j]) + bf_lo(sk), bf_hi(y[j]) + bf_hi(sk));
            }
            *reinterpret_cast<uint2*>(dst + (size_t)(i * 16) * 2048) = make_uint2(o[0], o[1]);
            *reinterpret_cast<uint2*>(dst + (size_t)(i * 16 + 8) * 2048) = make_uint2(o[2], o[3]);
        }
    }
}

constexpr int WO_BN = 128, WO_PER = DM / WO_BN;
constexpr int BG_ITEMS = 16 * (16 + WO_PER);

template <int BN, typename ACC>
__device__ __forceinline__ void gemm_mainloop(ACC& acc, const GemmSmem& g, int cw, int nk) {
#pragma unroll 1
    for (int k0 = 0; k0 < nk; k0 += 4) {
#pragma unroll
        for (int s = 0; s < 4; s++) {
            mbar_wait(g.full + 8 * s, (k0 >> 2) & 1);
            gemm_kblock<BN>(acc, g.st + s * STAGE_BYTES, cw, s == 0 && k0 == 0);
            wg_wait<1>();
            if ((threadIdx.x & 127) == 0 && (s > 0 || k0 > 0)) mbar_arrive(g.empty + 8 * ((s + 3) & 3));
        }
    }
    wg_wait<0>();
    if ((threadIdx.x & 127) == 0) mbar_arrive(g.empty + 8 * 3);
}

__global__ void __launch_bounds__(384, 1)
k_bg(const __grid_constant__ CUtensorMap mx, const __grid_constant__ CUtensorMap mwq, const __grid_constant__ CUtensorMap mkv4,
     const __grid_constant__ CUtensorMap mkvm, const __grid_constant__ CUtensorMap mo, const __grid_constant__ CUtensorMap mwo,
     bf16* __restrict__ out) {
    extern __shared__ uint8_t smem_raw[];
    int blk, idx; bool is_qa;
    {
        const int it = blockIdx.x;
        if (it < 16) { blk = 0; idx = it; is_qa = true; }
        else {
            const int q = (it - 16) / (16 + WO_PER), rr = (it - 16) - q * (16 + WO_PER);
            if (q == 15) { blk = 15; idx = rr; is_qa = false; }
            else if (rr < 16) { blk = q + 1; idx = rr; is_qa = true; }
            else { blk = q; idx = rr - 16; is_qa = false; }
        }
    }
    GemmSmem g = gemm_setup(smem_raw);
    const int m0 = blk * 128, wg = threadIdx.x >> 7;
    if (wg == 0) {
        asm volatile("setmaxnreg.dec.sync.aligned.u32 40;");
        if (threadIdx.x == 0) {
            if (is_qa) {
                for (int it = 0; it < 20; it++) {
                    const int s = it & 3;
                    const uint32_t st = g.st + s * STAGE_BYTES, fb = g.full + 8 * s;
                    mbar_wait(g.empty + 8 * s, ((it >> 2) & 1) ^ 1);
                    if (it < 16) {
                        mbar_expect_tx(fb, STAGE_BYTES);
                        tma2d(st, &mx, it * 64, m0, fb);
                        tma3d(st + 16384, &mwq, 0, it * 64, idx * 4, fb);
                    } else {
                        mbar_expect_tx(fb, 40960);
                        tma3d(st, &mkv4, 0, m0 + s * 32, idx * 4, fb);
                        tma3d(st + 16384, &mkv4, 0, m0 + s * 32, 64 + idx * 4, fb);
                    }
                }
                wait_flag(g_flag + 2 * idx, 4 * blk + 4);
                wait_flag(g_flag + 2 * idx + 1, 4 * blk + 4);
                asm volatile("fence.proxy.async.global;" ::: "memory");
                for (int s = 0; s < 4; s++) {
                    const uint32_t st = g.st + s * STAGE_BYTES, fb = g.full + 8 * s;
                    tma3d(st + 32768, &mkvm, 0, (blk * 4 + s) * 8, idx * 4, fb);
                    tma3d(st + 36864, &mkvm, 0, (blk * 4 + s) * 8, 64 + idx * 4, fb);
                }
            } else {
                wait_flag(g_flag + 64 + blk, 16);
                asm volatile("fence.proxy.async.global;" ::: "memory");
                for (int it = 0; it < 64; it++) {
                    const int s = it & 3;
                    const uint32_t st = g.st + s * STAGE_BYTES, fb = g.full + 8 * s;
                    mbar_wait(g.empty + 8 * s, ((it >> 2) & 1) ^ 1);
                    mbar_expect_tx(fb, 16384 + WO_BN * 128);
                    tma2d(st, &mo, it * 64, m0, fb);
                    tma3d(st + 16384, &mwo, 0, it * 64, idx * (WO_BN / 64), fb);
                }
            }
        }
    } else {
        asm volatile("setmaxnreg.inc.sync.aligned.u32 232;");
        const int cw = wg - 1, ww = (threadIdx.x >> 5) & 3, lane = threadIdx.x & 31, gq = lane >> 2, t = lane & 3;
        const int row = m0 + cw * 64 + ww * 16 + gq;
        if (is_qa) {
            uint32_t q[64];
            {
                float acc[128];
                gemm_mainloop<256>(acc, g, cw, 16);
#pragma unroll
                for (int i = 0; i < 64; i++) q[i] = pack2(acc[2 * i], acc[2 * i + 1]);
            }
            const int sg = cw * 2 + (ww >> 1), hf = ww & 1;
            const uint32_t st = g.st + sg * STAGE_BYTES;
            mbar_wait(g.full + 8 * sg, 0);
            const float scale = 0.08838834764831845f, l2e = 1.4426950408889634f;
            const int r8 = lane & 7, m4 = lane >> 3;
#pragma unroll
            for (int hh = 0; hh < 2; hh++) {
                float sc[5][4];
#pragma unroll
                for (int nt = 0; nt < 5; nt++) {
                    sc[nt][0] = sc[nt][1] = sc[nt][2] = sc[nt][3] = 0.f;
                    if (nt < 3 || hf) {
#pragma unroll
                        for (int kp = 0; kp < 4; kp++) {
                            const int nb = hh * 2 + (kp >> 1);
                            const uint32_t base = nt == 0 ? st + 32768 + nb * 1024 : st + nb * 4096 + (nt - 1) * 1024;
                            uint32_t b[4];
                            ldsm4(b, base + r8 * 128 + ((((kp & 1) * 4 + m4) ^ r8) << 4));
                            const int j = (hh * 16 + kp * 4) * 2;
                            mma16816(sc[nt], q[j], q[j + 1], q[j + 2], q[j + 3], b[0], b[1]);
                            mma16816(sc[nt], q[j + 4], q[j + 5], q[j + 6], q[j + 7], b[2], b[3]);
                        }
                    }
                }
                float mx[2] = {-3.0e38f, -3.0e38f};
#pragma unroll
                for (int nt = 0; nt < 5; nt++)
#pragma unroll
                    for (int c = 0; c < 4; c++) {
                        float v = bf_round(bf_round(sc[nt][c]) * scale);
                        if (nt > 0 && (nt - 1) * 8 + 2 * t + (c & 1) > hf * 16 + gq + (c >> 1) * 8) v = -1.0e9f;
                        sc[nt][c] = v;
                        mx[c >> 1] = fmaxf(mx[c >> 1], v);
                    }
                float sum[2] = {0.f, 0.f};
#pragma unroll
                for (int i = 0; i < 2; i++) {
                    mx[i] = fmaxf(mx[i], __shfl_xor_sync(~0u, mx[i], 1));
                    mx[i] = fmaxf(mx[i], __shfl_xor_sync(~0u, mx[i], 2));
                }
#pragma unroll
                for (int nt = 0; nt < 5; nt++)
#pragma unroll
                    for (int c = 0; c < 4; c++) {
                        sc[nt][c] = ex2((sc[nt][c] - mx[c >> 1]) * l2e);
                        sum[c >> 1] += sc[nt][c];
                    }
#pragma unroll
                for (int i = 0; i < 2; i++) {
                    sum[i] += __shfl_xor_sync(~0u, sum[i], 1);
                    sum[i] += __shfl_xor_sync(~0u, sum[i], 2);
                    sum[i] = __frcp_rn(sum[i]);
                }
                uint32_t p[5][2];
#pragma unroll
                for (int nt = 0; nt < 5; nt++) {
                    p[nt][0] = pack2(sc[nt][0] * sum[0], sc[nt][1] * sum[0]);
                    p[nt][1] = pack2(sc[nt][2] * sum[1], sc[nt][3] * sum[1]);
                }
                bf16* dst = g_o + (size_t)row * HD + idx * 256 + hh * 128 + t * 8;
#pragma unroll
                for (int G = 0; G < 4; G++) {
                    const int nb = hh * 2 + (G >> 1), c0 = (G & 1) * 4;
                    float o[4][4];
#pragma unroll
                    for (int i = 0; i < 4; i++) o[i][0] = o[i][1] = o[i][2] = o[i][3] = 0.f;
                    uint32_t b[4];
                    ldsm4t(b, st + 36864 + nb * 1024 + r8 * 128 + (((c0 + m4) ^ r8) << 4));
#pragma unroll
                    for (int i = 0; i < 4; i++) mma1688(o[i], p[0][0], p[0][1], b[i]);
#pragma unroll
                    for (int kk = 0; kk < 2; kk++) {
                        if (kk == 0 || hf) {
#pragma unroll
                            for (int i = 0; i < 2; i++) {
                                ldsm4t(b, st + 16384 + nb * 4096 + (kk * 16 + (m4 & 1) * 8 + r8) * 128 + (((c0 + 2 * i + (m4 >> 1)) ^ r8) << 4));
                                mma16816(o[2 * i], p[1 + 2 * kk][0], p[1 + 2 * kk][1], p[2 + 2 * kk][0], p[2 + 2 * kk][1], b[0], b[1]);
                                mma16816(o[2 * i + 1], p[1 + 2 * kk][0], p[1 + 2 * kk][1], p[2 + 2 * kk][0], p[2 + 2 * kk][1], b[2], b[3]);
                            }
                        }
                    }
#pragma unroll
                    for (int rr = 0; rr < 2; rr++) {
                        uint32_t r0 = pack2(o[0][2 * rr], o[0][2 * rr + 1]), r1 = pack2(o[1][2 * rr], o[1][2 * rr + 1]);
                        uint32_t r2 = pack2(o[2][2 * rr], o[2][2 * rr + 1]), r3 = pack2(o[3][2 * rr], o[3][2 * rr + 1]);
                        quad_transpose(r0, r1, r2, r3, t);
                        *reinterpret_cast<uint4*>(dst + (size_t)rr * 8 * HD + G * 32) = make_uint4(r0, r1, r2, r3);
                    }
                }
            }
            bar_sync(1, 256);
            if (threadIdx.x == 128)
                asm volatile("fence.acq_rel.gpu;\nred.relaxed.gpu.global.add.u32 [%0], 1;" ::"l"(g_flag + 64 + blk) : "memory");
        } else {
            float acc[WO_BN / 2];
            gemm_mainloop<WO_BN>(acc, g, cw, 64);
            bf16* dst = out + (size_t)row * 2048 + idx * WO_BN + t * 8;
#pragma unroll
            for (int G = 0; G < WO_BN / 32; G++)
#pragma unroll
                for (int rr = 0; rr < 2; rr++) {
                    uint32_t r0 = pack2(acc[16 * G + 2 * rr], acc[16 * G + 2 * rr + 1]), r1 = pack2(acc[16 * G + 4 + 2 * rr], acc[16 * G + 5 + 2 * rr]);
                    uint32_t r2 = pack2(acc[16 * G + 8 + 2 * rr], acc[16 * G + 9 + 2 * rr]), r3 = pack2(acc[16 * G + 12 + 2 * rr], acc[16 * G + 13 + 2 * rr]);
                    quad_transpose(r0, r1, r2, r3, t);
                    *reinterpret_cast<uint4*>(dst + (size_t)rr * 8 * 2048 + G * 32) = make_uint4(r0, r1, r2, r3);
                }
        }
    }
}

typedef CUresult (*EncodeFn)(CUtensorMap*, CUtensorMapDataType, cuuint32_t, void*, const cuuint64_t*, const cuuint64_t*,
                             const cuuint32_t*, const cuuint32_t*, CUtensorMapInterleave, CUtensorMapSwizzle,
                             CUtensorMapL2promotion, CUtensorMapFloatOOBfill);

static void map2d(EncodeFn enc, CUtensorMap* m, const void* p, int rows, int cols, int box_rows) {
    cuuint64_t dim[2] = {(cuuint64_t)cols, (cuuint64_t)rows}, str[1] = {(cuuint64_t)cols * 2};
    cuuint32_t box[2] = {64, (cuuint32_t)box_rows}, es[2] = {1, 1};
    enc(m, CU_TENSOR_MAP_DATA_TYPE_BFLOAT16, 2, (void*)p, dim, str, box, es, CU_TENSOR_MAP_INTERLEAVE_NONE,
        CU_TENSOR_MAP_SWIZZLE_128B, CU_TENSOR_MAP_L2_PROMOTION_L2_256B, CU_TENSOR_MAP_FLOAT_OOB_FILL_NONE);
}
static void map3d(EncodeFn enc, CUtensorMap* m, const void* p, int rows, int cols, int box_rows, int nblk) {
    cuuint64_t dim[3] = {64, (cuuint64_t)rows, (cuuint64_t)cols / 64}, str[2] = {(cuuint64_t)cols * 2, 128};
    cuuint32_t box[3] = {64, (cuuint32_t)box_rows, (cuuint32_t)nblk}, es[3] = {1, 1, 1};
    enc(m, CU_TENSOR_MAP_DATA_TYPE_BFLOAT16, 3, (void*)p, dim, str, box, es, CU_TENSOR_MAP_INTERLEAVE_NONE,
        CU_TENSOR_MAP_SWIZZLE_128B, CU_TENSOR_MAP_L2_PROMOTION_L2_256B, CU_TENSOR_MAP_FLOAT_OOB_FILL_NONE);
}

#define USE_PDL 1

extern "C" void kernel_launch(void* const* d_in, const int* in_sizes, int n_in, void* d_out, int out_size) {
    const bf16 *x = (const bf16*)d_in[0], *mem0 = (const bf16*)d_in[1], *Wq = (const bf16*)d_in[2], *Wk = (const bf16*)d_in[3];
    const bf16 *Wv = (const bf16*)d_in[4], *Wo = (const bf16*)d_in[5];
    const bf16 *u = (const bf16*)d_in[7], *Are = (const bf16*)d_in[8], *Aim = (const bf16*)d_in[9], *Bre = (const bf16*)d_in[10];
    const bf16 *Bim = (const bf16*)d_in[11], *Cre = (const bf16*)d_in[12], *Cim = (const bf16*)d_in[13];
    const bf16 *logdt = (const bf16*)d_in[14], *Dsk = (const bf16*)d_in[15];
    bf16* out = (bf16*)d_out;

    void* fn = nullptr;
    cudaDriverEntryPointQueryResult qr;
    cudaGetDriverEntryPoint("cuTensorMapEncodeTiled", &fn, cudaEnableDefault, &qr);
    EncodeFn enc = (EncodeFn)fn;
    void *kv, *kvm, *o;
    cudaGetSymbolAddress(&kv, g_kv);
    cudaGetSymbolAddress(&kvm, g_kvm);
    cudaGetSymbolAddress(&o, g_o);
    CUtensorMap mx, mwq, mwk, mwv, mwo, mkv2, mkv4, mkvm, mo;
    map2d(enc, &mx, x, SEQ, DM, 128);
    map2d(enc, &mo, o, SEQ, HD, 128);
    map3d(enc, &mwq, Wq, DM, HD, 64, 4);
    map3d(enc, &mwk, Wk, DM, HD, 64, 4);
    map3d(enc, &mwv, Wv, DM, HD, 64, 4);
    map3d(enc, &mwo, Wo, HD, DM, 64, WO_BN / 64);
    map3d(enc, &mkv2, kv, SEQ, 8192, 32, 2);
    map3d(enc, &mkv4, kv, SEQ, 8192, 32, 4);
    map3d(enc, &mkvm, kvm, NSEG * 8, 8192, 8, 4);
    cudaFuncSetAttribute(k_kv, cudaFuncAttributeMaxDynamicSharedMemorySize, GEMM_SMEM);
    cudaFuncSetAttribute(k_bg, cudaFuncAttributeMaxDynamicSharedMemorySize, GEMM_SMEM);
    cudaFuncSetAttribute(k_chain, cudaFuncAttributeMaxDynamicSharedMemorySize, CHAIN_SMEM);
    cudaFuncSetAttribute(k_s4, cudaFuncAttributeMaxDynamicSharedMemorySize, S4_SMEM);

    cudaStream_t st = cudaStreamPerThread;
    k_kv<<<132, 384, GEMM_SMEM, st>>>(mx, mwk, mwv, Wq, Wo);
    k_chain<<<96, 256, CHAIN_SMEM, st>>>(mem0, Wq, Wk, Wv, Wo, mkv2);
    cudaLaunchAttribute pdl[1];
    pdl[0].id = cudaLaunchAttributeProgrammaticStreamSerialization;
    pdl[0].val.programmaticStreamSerializationAllowed = 1;
    cudaLaunchConfig_t cfg = {};
    cfg.stream = st; cfg.attrs = pdl; cfg.numAttrs = USE_PDL;
    cfg.gridDim = dim3(64); cfg.blockDim = dim3(512); cfg.dynamicSmemBytes = S4_SMEM;
    cudaLaunchKernelEx(&cfg, k_s4, u, Are, Aim, Bre, Bim, Cre, Cim, logdt, Dsk, out);
    cfg.gridDim = dim3(BG_ITEMS); cfg.blockDim = dim3(384); cfg.dynamicSmemBytes = GEMM_SMEM;
    cudaLaunchKernelEx(&cfg, k_bg, mx, mwq, mkv4, mkvm, mo, mwo, out);
}
```

```cpp
#include <cuda_runtime.h>
#include <cuda_bf16.h>
#include <cuda.h>
#include <stdint.h>

typedef __nv_bfloat16 bf16;

constexpr int SEQ = 2048, DM = 1024, HD = 4096, NSEG = 64;

__device__ __align__(1024) bf16 g_kv[(size_t)SEQ * 8192];
__device__ __align__(1024) bf16 g_kvm[(size_t)NSEG * 8 * 8192];
__device__ __align__(1024) bf16 g_o[(size_t)SEQ * HD];
__device__ __align__(1024) uint2 g_memx[NSEG * 64 * 32];
__device__ __align__(1024) uint2 g_part[64 * 32 * 32];
__device__ __align__(1024) uint32_t g_flag[256];

#define TL(kern, slot)

__device__ __forceinline__ uint32_t smem_u32(const void* p) { return (uint32_t)__cvta_generic_to_shared(p); }
__device__ __forceinline__ void mbar_init(uint32_t bar, uint32_t cnt) {
    asm volatile("mbarrier.init.shared::cta.b64 [%0], %1;" ::"r"(bar), "r"(cnt) : "memory");
}
__device__ __forceinline__ void mbar_expect_tx(uint32_t bar, uint32_t bytes) {
    asm volatile("mbarrier.arrive.expect_tx.shared::cta.b64 _, [%0], %1;" ::"r"(bar), "r"(bytes) : "memory");
}
__device__ __forceinline__ void mbar_arrive(uint32_t bar) {
    asm volatile("mbarrier.arrive.shared::cta.b64 _, [%0];" ::"r"(bar) : "memory");
}
__device__ __forceinline__ bool mbar_try(uint32_t bar, uint32_t parity) {
    uint32_t ok;
    asm volatile("{\n.reg .pred p;\nmbarrier.try_wait.parity.shared::cta.b64 p, [%1], %2;\nselp.u32 %0, 1, 0, p;\n}"
                 : "=r"(ok) : "r"(bar), "r"(parity) : "memory");
    return ok;
}
constexpr int SPIN_LIMIT = 1 << 20;
__device__ __forceinline__ void mbar_wait(uint32_t bar, uint32_t parity) {
    int n = 0;
    while (!mbar_try(bar, parity)) { if (++n > SPIN_LIMIT) __trap(); }
}
__device__ __forceinline__ void mbar_wait_u(uint32_t bar, uint32_t parity) {
    asm volatile("{\n.reg .pred p;\n.reg .u32 n;\n"
                 "mbarrier.try_wait.parity.shared::cta.b64 p, [%0], %1;\n@p bra.uni DONE;\nmov.u32 n, 0;\n"
                 "AGAIN:\nmbarrier.try_wait.parity.shared::cta.b64 p, [%0], %1;\n@p bra.uni DONE;\n"
                 "add.u32 n, n, 1;\nsetp.lt.u32 p, n, 0x100000;\n@p bra.uni AGAIN;\ntrap;\nDONE:\n}"
                 ::"r"(bar), "r"(parity) : "memory");
}
__device__ __forceinline__ void tma2d(uint32_t dst, const CUtensorMap* m, int c0, int c1, uint32_t bar) {
    asm volatile("cp.async.bulk.tensor.2d.shared::cluster.global.mbarrier::complete_tx::bytes [%0], [%1, {%3, %4}], [%2];"
                 ::"r"(dst), "l"(m), "r"(bar), "r"(c0), "r"(c1) : "memory");
}
__device__ __forceinline__ void tma3d(uint32_t dst, const CUtensorMap* m, int c0, int c1, int c2, uint32_t bar) {
    asm volatile("cp.async.bulk.tensor.3d.shared::cluster.global.mbarrier::complete_tx::bytes [%0], [%1, {%3, %4, %5}], [%2];"
                 ::"r"(dst), "l"(m), "r"(bar), "r"(c0), "r"(c1), "r"(c2) : "memory");
}
__device__ __forceinline__ uint32_t pack2(float lo, float hi) {
    uint32_t r;
    asm("cvt.rn.bf16x2.f32 %0, %1, %2;" : "=r"(r) : "f"(hi), "f"(lo));
    return r;
}
__device__ __forceinline__ float bf_lo(uint32_t v) { return __uint_as_float(v << 16); }
__device__ __forceinline__ float bf_hi(uint32_t v) { return __uint_as_float(v & 0xffff0000u); }
__device__ __forceinline__ float bf_round(float x) { return bf_lo(pack2(x, 0.f)); }
__device__ __forceinline__ float ex2(float x) { float y; asm("ex2.approx.ftz.f32 %0, %1;" : "=f"(y) : "f"(x)); return y; }
__device__ __forceinline__ void mma16816(float (&c)[4], uint32_t a0, uint32_t a1, uint32_t a2, uint32_t a3, uint32_t b0, uint32_t b1) {
    asm volatile("mma.sync.aligned.m16n8k16.row.col.f32.bf16.bf16.f32 {%0,%1,%2,%3}, {%4,%5,%6,%7}, {%8,%9}, {%0,%1,%2,%3};"
                 : "+f"(c[0]), "+f"(c[1]), "+f"(c[2]), "+f"(c[3]) : "r"(a0), "r"(a1), "r"(a2), "r"(a3), "r"(b0), "r"(b1));
}
__device__ __forceinline__ void mma1688(float (&c)[4], uint32_t a0, uint32_t a1, uint32_t b0) {
    asm volatile("mma.sync.aligned.m16n8k8.row.col.f32.bf16.bf16.f32 {%0,%1,%2,%3}, {%4,%5}, {%6}, {%0,%1,%2,%3};"
                 : "+f"(c[0]), "+f"(c[1]), "+f"(c[2]), "+f"(c[3]) : "r"(a0), "r"(a1), "r"(b0));
}
__device__ __forceinline__ void ldsm4(uint32_t (&r)[4], uint32_t a) {
    asm volatile("ldmatrix.sync.aligned.m8n8.x4.shared.b16 {%0,%1,%2,%3}, [%4];"
                 : "=r"(r[0]), "=r"(r[1]), "=r"(r[2]), "=r"(r[3]) : "r"(a) : "memory");
}
__device__ __forceinline__ void ldsm4t(uint32_t (&r)[4], uint32_t a) {
    asm volatile("ldmatrix.sync.aligned.m8n8.x4.trans.shared.b16 {%0,%1,%2,%3}, [%4];"
                 : "=r"(r[0]), "=r"(r[1]), "=r"(r[2]), "=r"(r[3]) : "r"(a) : "memory");
}
__device__ __forceinline__ void ldsm2t(uint32_t& r0, uint32_t& r1, uint32_t a) {
    asm volatile("ldmatrix.sync.aligned.m8n8.x2.trans.shared.b16 {%0,%1}, [%2];" : "=r"(r0), "=r"(r1) : "r"(a) : "memory");
}
__device__ __forceinline__ void stsm4t(uint32_t a, uint32_t r0, uint32_t r1, uint32_t r2, uint32_t r3) {
    asm volatile("stmatrix.sync.aligned.m8n8.x4.trans.shared.b16 [%0], {%1,%2,%3,%4};"
                 ::"r"(a), "r"(r0), "r"(r1), "r"(r2), "r"(r3) : "memory");
}
__device__ __forceinline__ void lds128(uint32_t (&r)[4], uint32_t a) {
    asm volatile("ld.shared.v4.u32 {%0,%1,%2,%3}, [%4];" : "=r"(r[0]), "=r"(r[1]), "=r"(r[2]), "=r"(r[3]) : "r"(a) : "memory");
}
__device__ __forceinline__ float4 lds128f(uint32_t a) {
    float4 v;
    asm volatile("ld.shared.v4.f32 {%0,%1,%2,%3}, [%4];" : "=f"(v.x), "=f"(v.y), "=f"(v.z), "=f"(v.w) : "r"(a) : "memory");
    return v;
}
__device__ __forceinline__ float2 lds64f(uint32_t a) {
    float2 v;
    asm volatile("ld.shared.v2.f32 {%0,%1}, [%2];" : "=f"(v.x), "=f"(v.y) : "r"(a) : "memory");
    return v;
}
__device__ __forceinline__ uint32_t lds32(uint32_t a) {
    uint32_t v;
    asm volatile("ld.shared.u32 %0, [%1];" : "=r"(v) : "r"(a) : "memory");
    return v;
}
__device__ __forceinline__ void sts128(uint32_t a, uint32_t r0, uint32_t r1, uint32_t r2, uint32_t r3) {
    asm volatile("st.shared.v4.u32 [%0], {%1,%2,%3,%4};" ::"r"(a), "r"(r0), "r"(r1), "r"(r2), "r"(r3) : "memory");
}
__device__ __forceinline__ void sts128f(uint32_t a, float r0, float r1, float r2, float r3) {
    asm volatile("st.shared.v4.f32 [%0], {%1,%2,%3,%4};" ::"r"(a), "f"(r0), "f"(r1), "f"(r2), "f"(r3) : "memory");
}
__device__ __forceinline__ void sts64(uint32_t a, uint32_t r0, uint32_t r1) {
    asm volatile("st.shared.v2.u32 [%0], {%1,%2};" ::"r"(a), "r"(r0), "r"(r1) : "memory");
}
__device__ __forceinline__ void sts64f(uint32_t a, float r0, float r1) {
    asm volatile("st.shared.v2.f32 [%0], {%1,%2};" ::"r"(a), "f"(r0), "f"(r1) : "memory");
}
__device__ __forceinline__ void sts32f(uint32_t a, float r0) {
    asm volatile("st.shared.f32 [%0], %1;" ::"r"(a), "f"(r0) : "memory");
}
__device__ __forceinline__ uint2 ld_rlx64(const uint2* p) {
    uint2 v;
    asm volatile("{\n.reg .b64 t;\nld.relaxed.gpu.global.b64 t, [%2];\nmov.b64 {%0,%1}, t;\n}" : "=r"(v.x), "=r"(v.y) : "l"(p) : "memory");
    return v;
}
__device__ __forceinline__ void st_rlx64(uint2* p, uint32_t x, uint32_t y) {
    asm volatile("{\n.reg .b64 t;\nmov.b64 t, {%1,%2};\nst.relaxed.gpu.global.b64 [%0], t;\n}" ::"l"(p), "r"(x), "r"(y) : "memory");
}
__device__ __forceinline__ uint32_t ld_acq32(const uint32_t* p) {
    uint32_t v;
    asm volatile("ld.acquire.gpu.global.u32 %0, [%1];" : "=r"(v) : "l"(p) : "memory");
    return v;
}
__device__ __forceinline__ void wait_flag(const uint32_t* p, uint32_t need) {
    int n = 0;
    while (ld_acq32(p) < need) { __nanosleep(200); if (++n > SPIN_LIMIT) __trap(); }
}
__device__ __forceinline__ void bar_sync(int id, int n) { asm volatile("bar.sync %0, %1;" ::"r"(id), "r"(n) : "memory"); }
__device__ __forceinline__ void wg_fence() { asm volatile("wgmma.fence.sync.aligned;" ::: "memory"); }
__device__ __forceinline__ void wg_commit() { asm volatile("wgmma.commit_group.sync.aligned;" ::: "memory"); }
template <int N> __device__ __forceinline__ void wg_wait() { asm volatile("wgmma.wait_group.sync.aligned %0;" ::"n"(N) : "memory"); }
__device__ __forceinline__ uint64_t desc_sw128(uint32_t addr, uint32_t lbo, uint32_t sbo) {
    return (uint64_t)((addr & 0x3FFFF) >> 4) | ((uint64_t)(lbo >> 4) << 16) | ((uint64_t)(sbo >> 4) << 32) | (1ull << 62);
}
__device__ __forceinline__ void quad_transpose(uint32_t& r0, uint32_t& r1, uint32_t& r2, uint32_t& r3, int t) {
    const bool o = t & 1, h = t & 2;
    uint32_t s0 = __shfl_xor_sync(~0u, o ? r0 : r1, 1), s1 = __shfl_xor_sync(~0u, o ? r2 : r3, 1);
    uint32_t a0 = o ? s0 : r0, a1 = o ? r1 : s0, a2 = o ? s1 : r2, a3 = o ? r3 : s1;
    s0 = __shfl_xor_sync(~0u, h ? a0 : a2, 2); s1 = __shfl_xor_sync(~0u, h ? a1 : a3, 2);
    r0 = h ? s0 : a0; r1 = h ? s1 : a1; r2 = h ? a2 : s0; r3 = h ? a3 : s1;
}

__device__ __forceinline__ void wgmma_n256(float (&d)[128], uint64_t da, uint64_t db, int sd) {
    asm volatile("{\n.reg .pred p;\nsetp.ne.b32 p, %130, 0;\n"
        "wgmma.mma_async.sync.aligned.m64n256k16.f32.bf16.bf16 "
        "{%0,%1,%2,%3,%4,%5,%6,%7,%8,%9,%10,%11,%12,%13,%14,%15,"
        "%16,%17,%18,%19,%20,%21,%22,%23,%24,%25,%26,%27,%28,%29,%30,%31,"
        "%32,%33,%34,%35,%36,%37,%38,%39,%40,%41,%42,%43,%44,%45,%46,%47,"
        "%48,%49,%50,%51,%52,%53,%54,%55,%56,%57,%58,%59,%60,%61,%62,%63,"
        "%64,%65,%66,%67,%68,%69,%70,%71,%72,%73,%74,%75,%76,%77,%78,%79,"
        "%80,%81,%82,%83,%84,%85,%86,%87,%88,%89,%90,%91,%92,%93,%94,%95,"
        "%96,%97,%98,%99,%100,%101,%102,%103,%104,%105,%106,%107,%108,%109,%110,%111,"
        "%112,%113,%114,%115,%116,%117,%118,%119,%120,%121,%122,%123,%124,%125,%126,%127}, %128, %129, p, 1, 1, 0, 1;\n}\n"
        : "+f"(d[0]), "+f"(d[1]), "+f"(d[2]), "+f"(d[3]), "+f"(d[4]), "+f"(d[5]), "+f"(d[6]), "+f"(d[7]),
          "+f"(d[8]), "+f"(d[9]), "+f"(d[10]), "+f"(d[11]), "+f"(d[12]), "+f"(d[13]), "+f"(d[14]), "+f"(d[15]),
          "+f"(d[16]), "+f"(d[17]), "+f"(d[18]), "+f"(d[19]), "+f"(d[20]), "+f"(d[21]), "+f"(d[22]), "+f"(d[23]),
          "+f"(d[24]), "+f"(d[25]), "+f"(d[26]), "+f"(d[27]), "+f"(d[28]), "+f"(d[29]), "+f"(d[30]), "+f"(d[31]),
          "+f"(d[32]), "+f"(d[33]), "+f"(d[34]), "+f"(d[35]), "+f"(d[36]), "+f"(d[37]), "+f"(d[38]), "+f"(d[39]),
          "+f"(d[40]), "+f"(d[41]), "+f"(d[42]), "+f"(d[43]), "+f"(d[44]), "+f"(d[45]), "+f"(d[46]), "+f"(d[47]),
          "+f"(d[48]), "+f"(d[49]), "+f"(d[50]), "+f"(d[51]), "+f"(d[52]), "+f"(d[53]), "+f"(d[54]), "+f"(d[55]),
          "+f"(d[56]), "+f"(d[57]), "+f"(d[58]), "+f"(d[59]), "+f"(d[60]), "+f"(d[61]), "+f"(d[62]), "+f"(d[63]),
          "+f"(d[64]), "+f"(d[65]), "+f"(d[66]), "+f"(d[67]), "+f"(d[68]), "+f"(d[69]), "+f"(d[70]), "+f"(d[71]),
          "+f"(d[72]), "+f"(d[73]), "+f"(d[74]), "+f"(d[75]), "+f"(d[76]), "+f"(d[77]), "+f"(d[78]), "+f"(d[79]),
          "+f"(d[80]), "+f"(d[81]), "+f"(d[82]), "+f"(d[83]), "+f"(d[84]), "+f"(d[85]), "+f"(d[86]), "+f"(d[87]),
          "+f"(d[88]), "+f"(d[89]), "+f"(d[90]), "+f"(d[91]), "+f"(d[92]), "+f"(d[93]), "+f"(d[94]), "+f"(d[95]),
          "+f"(d[96]), "+f"(d[97]), "+f"(d[98]), "+f"(d[99]), "+f"(d[100]), "+f"(d[101]), "+f"(d[102]), "+f"(d[103]),
          "+f"(d[104]), "+f"(d[105]), "+f"(d[106]), "+f"(d[107]), "+f"(d[108]), "+f"(d[109]), "+f"(d[110]), "+f"(d[111]),
          "+f"(d[112]), "+f"(d[113]), "+f"(d[114]), "+f"(d[115]), "+f"(d[116]), "+f"(d[117]), "+f"(d[118]), "+f"(d[119]),
          "+f"(d[120]), "+f"(d[121]), "+f"(d[122]), "+f"(d[123]), "+f"(d[124]), "+f"(d[125]), "+f"(d[126]), "+f"(d[127])
        : "l"(da), "l"(db), "r"(sd));
}

__device__ __forceinline__ void wgmma_n128(float (&d)[64], uint64_t da, uint64_t db, int sd) {
    asm volatile("{\n.reg .pred p;\nsetp.ne.b32 p, %66, 0;\n"
        "wgmma.mma_async.sync.aligned.m64n128k16.f32.bf16.bf16 "
        "{%0,%1,%2,%3,%4,%5,%6,%7,%8,%9,%10,%11,%12,%13,%14,%15,"
        "%16,%17,%18,%19,%20,%21,%22,%23,%24,%25,%26,%27,%28,%29,%30,%31,"
        "%32,%33,%34,%35,%36,%37,%38,%39,%40,%41,%42,%43,%44,%45,%46,%47,"
        "%48,%49,%50,%51,%52,%53,%54,%55,%56,%57,%58,%59,%60,%61,%62,%63}, %64, %65, p, 1, 1, 0, 1;\n}\n"
        : "+f"(d[0]), "+f"(d[1]), "+f"(d[2]), "+f"(d[3]), "+f"(d[4]), "+f"(d[5]), "+f"(d[6]), "+f"(d[7]),
          "+f"(d[8]), "+f"(d[9]), "+f"(d[10]), "+f"(d[11]), "+f"(d[12]), "+f"(d[13]), "+f"(d[14]), "+f"(d[15]),
          "+f"(d[16]), "+f"(d[17]), "+f"(d[18]), "+f"(d[19]), "+f"(d[20]), "+f"(d[21]), "+f"(d[22]), "+f"(d[23]),
          "+f"(d[24]), "+f"(d[25]), "+f"(d[26]), "+f"(d[27]), "+f"(d[28]), "+f"(d[29]), "+f"(d[30]), "+f"(d[31]),
          "+f"(d[32]), "+f"(d[33]), "+f"(d[34]), "+f"(d[35]), "+f"(d[36]), "+f"(d[37]), "+f"(d[38]), "+f"(d[39]),
          "+f"(d[40]), "+f"(d[41]), "+f"(d[42]), "+f"(d[43]), "+f"(d[44]), "+f"(d[45]), "+f"(d[46]), "+f"(d[47]),
          "+f"(d[48]), "+f"(d[49]), "+f"(d[50]), "+f"(d[51]), "+f"(d[52]), "+f"(d[53]), "+f"(d[54]), "+f"(d[55]),
          "+f"(d[56]), "+f"(d[57]), "+f"(d[58]), "+f"(d[59]), "+f"(d[60]), "+f"(d[61]), "+f"(d[62]), "+f"(d[63])
        : "l"(da), "l"(db), "r"(sd));
}

constexpr int STAGE_BYTES = 49152, NSTAGE = 4;
constexpr int GEMM_SMEM = NSTAGE * STAGE_BYTES + 128;

struct GemmSmem { uint32_t st, full, empty; };
__device__ __forceinline__ GemmSmem gemm_setup(uint8_t* raw) {
    GemmSmem g;
    g.st = smem_u32(raw);
    if (g.st & 1023) __trap();
    g.full = g.st + NSTAGE * STAGE_BYTES; g.empty = g.full + 64;
    if (threadIdx.x == 0) {
        for (int s = 0; s < NSTAGE; s++) { mbar_init(g.full + 8 * s, 1); mbar_init(g.empty + 8 * s, 2); }
        asm volatile("fence.mbarrier_init.release.cluster;" ::: "memory");
        asm volatile("fence.proxy.async.shared::cta;" ::: "memory");
    }
    __syncthreads();
    return g;
}
__device__ __forceinline__ void mbar_arrive_one(uint32_t bar, uint32_t who) {
    asm volatile("{\n.reg .pred p;\nsetp.eq.u32 p, %1, 0;\n@p mbarrier.arrive.shared::cta.b64 _, [%0];\n}" ::"r"(bar), "r"(who) : "memory");
}
template <int BN, typename ACC>
__device__ __forceinline__ void gemm_kblock(ACC& acc, uint32_t stage, int wg, bool first) {
    const uint64_t da = desc_sw128(stage + wg * 8192, 16, 1024);
    const uint64_t db = desc_sw128(stage + 16384, 8192, 1024);
    wg_fence();
#pragma unroll
    for (int k = 0; k < 4; k++) {
        if constexpr (BN == 256) wgmma_n256(acc, da + k * 2, db + k * 128, first && k == 0 ? 0 : 1);
        else wgmma_n128(acc, da + k * 2, db + k * 128, first && k == 0 ? 0 : 1);
    }
    wg_commit();
}

__device__ __forceinline__ void kv_store_unit(const uint32_t (&pk)[64], int u, bf16* dst, int t) {
    const int G = (u >> 2) * 2 + (u & 1), hh = (u >> 1) & 1;
    uint32_t r0 = pk[(4 * G + 0) * 2 + hh], r1 = pk[(4 * G + 1) * 2 + hh], r2 = pk[(4 * G + 2) * 2 + hh], r3 = pk[(4 * G + 3) * 2 + hh];
    quad_transpose(r0, r1, r2, r3, t);
#define KVST ".cs"
    asm volatile("st.global" KVST ".v4.u32 [%0], {%1,%2,%3,%4};" ::"l"(dst + (size_t)hh * 8 * 8192 + G * 32), "r"(r0), "r"(r1), "r"(r2), "r"(r3) : "memory");
}

__global__ void __launch_bounds__(384, 1)
k_kv(const __grid_constant__ CUtensorMap mx, const __grid_constant__ CUtensorMap mwk, const __grid_constant__ CUtensorMap mwv,
     const bf16* __restrict__ Wq, const bf16* __restrict__ Wo) {
    extern __shared__ __align__(1024) uint8_t smem_gemm[];
    const int c = blockIdx.x;
    if (threadIdx.x == 0) TL(0, 0);
    if (c >= 128) {
        const int i0 = (c - 128) * 384 + threadIdx.x;
        const uint4 ones = make_uint4(~0u, ~0u, ~0u, ~0u);
        for (int i = i0; i < NSEG * 64 * 32 / 2; i += 4 * 384) reinterpret_cast<uint4*>(g_memx)[i] = ones;
        for (int i = i0; i < 64 * 32 * 32 / 2; i += 4 * 384) reinterpret_cast<uint4*>(g_part)[i] = ones;
        if (i0 < 256) g_flag[i0] = 0;
        if (threadIdx.x == 0) {
            const char* p = (const char*)(c < 130 ? Wq : Wo) + (size_t)(c & 1) * (4 << 20);
            for (int i = 0; i < 256; i++) {
                asm volatile("cp.async.bulk.prefetch.L2.global [%0], 16384;" ::"l"(p + i * 16384) : "memory");
                __nanosleep(40);
            }
        }
        if (threadIdx.x == 0) TL(0, 1);
        return;
    }
    GemmSmem g = gemm_setup(smem_gemm);
    const int m0 = (c & 15) * 128, nb0 = c >> 4;
    const int wg = __shfl_sync(~0u, threadIdx.x >> 7, 0);
    if (wg == 0) {
        asm volatile("setmaxnreg.dec.sync.aligned.u32 40;");
        if (threadIdx.x == 0) {
            for (int it = 0; it < 64; it++) {
                const int s = it & 3, tile = it >> 4, kb = it & 15;
                mbar_wait(g.empty + 8 * s, ((it >> 2) & 1) ^ 1);
                mbar_expect_tx(g.full + 8 * s, STAGE_BYTES);
                const int nb = nb0 + 8 * tile;
                tma2d(g.st + s * STAGE_BYTES, &mx, kb * 64, m0, g.full + 8 * s);
                tma3d(g.st + s * STAGE_BYTES + 16384, nb < 16 ? &mwk : &mwv, 0, kb * 64, (nb & 15) * 4, g.full + 8 * s);
            }
        }
    } else {
        asm volatile("setmaxnreg.inc.sync.aligned.u32 232;");
        const int cw = wg - 1, lane = threadIdx.x & 31, t = lane & 3;
        const int row = m0 + cw * 64 + ((threadIdx.x >> 5) & 3) * 16 + (lane >> 2);
        bf16* dst = g_kv + (size_t)row * 8192 + nb0 * 256 + t * 8;
        float acc[128];
        uint32_t pk[64];
#pragma unroll 1
        for (int tile = 0; tile < 4; tile++) {
#pragma unroll
            for (int kb = 0; kb < 16; kb++) {
                mbar_wait_u(g.full + 8 * (kb & 3), (kb >> 2) & 1);
                gemm_kblock<256>(acc, g.st + (kb & 3) * STAGE_BYTES, cw, kb == 0);
                if (tile > 0) kv_store_unit(pk, kb, dst + (tile - 1) * 2048, t);
                if (kb > 0) {
                    wg_wait<1>();
                    mbar_arrive_one(g.empty + 8 * ((kb - 1) & 3), threadIdx.x & 127);
                }
            }
            wg_wait<0>();
            mbar_arrive_one(g.empty + 8 * 3, threadIdx.x & 127);
#pragma unroll
            for (int i = 0; i < 64; i++) pk[i] = pack2(acc[2 * i], acc[2 * i + 1]);
        }
        if (threadIdx.x == 128) TL(0, 2);
#pragma unroll
        for (int u = 0; u < 16; u++) kv_store_unit(pk, u, dst + 3 * 2048, t);
        if (threadIdx.x == 128) TL(0, 1);
    }
}

constexpr int NS1 = 30;
#define RB1 4
#define PFC 4
constexpr int C_W1 = 0;
constexpr int C_W2 = C_W1 + 8 * NS1 * 512;
constexpr int C_KV = C_W2 + 14 * 8 * 512;
constexpr int C_RED = C_KV + 16384;
constexpr int C_R3 = C_RED + 64 * 272;
constexpr int C_QKV = C_R3 + 2560;
constexpr int C_SC = C_QKV + 3 * 8 * 272;
constexpr int C_OB = C_SC + 2 * 8 * 52 * 4;
constexpr int C_BAR = C_OB + 8 * 272;
__host__ __device__ constexpr int smem_idx(int ks, int j) {
    return ks == 0 ? j : ks == 1 ? (j < 4 ? 8 + j : -1) : (j < 3 ? 6 + 3 * ks + j : -1);
}
constexpr int CHAIN_SMEM = C_BAR + 64;
#define TS(i)

#define DLY3 3
#define DLY1 16
#define DLY0 8
#define DLYW 3
template <int N> __device__ __forceinline__ uint32_t delayed(uint32_t x, int lane) {
#pragma unroll
    for (int i = 0; i < N; i++) asm volatile("shfl.sync.idx.b32 %0, %0, %1, 31, -1;" : "+r"(x) : "r"(lane) : "memory");
    return x;
}
__device__ __forceinline__ void lds128v(uint32_t (&r)[4], uint32_t a) {
    asm volatile("ld.volatile.shared.v4.u32 {%0,%1,%2,%3}, [%4];" : "=r"(r[0]), "=r"(r[1]), "=r"(r[2]), "=r"(r[3]) : "r"(a) : "memory");
}
__device__ __forceinline__ uint2 lds64(uint32_t a) {
    uint2 v;
    asm volatile("ld.shared.v2.u32 {%0,%1}, [%2];" : "=r"(v.x), "=r"(v.y) : "r"(a) : "memory");
    return v;
}
#define LDQ ".L1::no_allocate"
__device__ __forceinline__ uint4 ldw128(const void* p) {
    uint4 v;
    asm volatile("ld.global.nc" LDQ ".v4.u32 {%0,%1,%2,%3}, [%4];" : "=r"(v.x), "=r"(v.y), "=r"(v.z), "=r"(v.w) : "l"(p));
    return v;
}
__device__ __forceinline__ void fetch8(uint64_t (&d)[8], const void* src) {
#define P8_LD(i) "ld.relaxed.gpu.global.b64 %" #i ", [%8 + " #i " * 256];\n"
    asm volatile(P8_LD(0) P8_LD(1) P8_LD(2) P8_LD(3) P8_LD(4) P8_LD(5) P8_LD(6) P8_LD(7)
                 : "=&l"(d[0]), "=&l"(d[1]), "=&l"(d[2]), "=&l"(d[3]), "=&l"(d[4]), "=&l"(d[5]), "=&l"(d[6]), "=&l"(d[7]) : "l"(src) : "memory");
}
template <bool TAG> __device__ __forceinline__ void settle8(uint2 (&v)[8], uint64_t (&d)[8], const void* src, uint32_t tag) {
#define P8_X(i) "mov.b64 {x" #i ", _}, %" #i ";\n"
#define P8_HEAD "{\n.reg .pred p, q;\n.reg .u32 n, x0, x1, x2, x3, x4, x5, x6, x7, m0, m1;\nmov.u32 n, 0;\nCHECK:\n" \
                P8_X(0) P8_X(1) P8_X(2) P8_X(3) P8_X(4) P8_X(5) P8_X(6) P8_X(7)
#define P8_VOTE "vote.sync.all.pred p, p, -1;\n@p bra.uni DONE;\n"
#define P8_TAIL "add.u32 n, n, 1;\nsetp.lt.u32 p, n, 0x100000;\n@p bra.uni CHECK;\ntrap;\nDONE:\n}"
#define P8_OPS : "+l"(d[0]), "+l"(d[1]), "+l"(d[2]), "+l"(d[3]), "+l"(d[4]), "+l"(d[5]), "+l"(d[6]), "+l"(d[7]) : "l"(src), "r"(tag) : "memory"
#define P8_RT(i) "lop3.b32 m0, x" #i ", %9, 1, 0x28;\nsetp.ne.u32 q, m0, 0;\n@q " P8_LD(i)
#define P8_RS(i) "setp.eq.u32 q, x" #i ", 0xffffffff;\n@q " P8_LD(i)
    if (TAG)
        asm volatile(P8_HEAD "lop3.b32 m0, x0, x1, %9, 0x7e;\nlop3.b32 m1, x2, x3, %9, 0x7e;\nlop3.b32 m0, m0, x4, %9, 0xf6;\n"
                     "lop3.b32 m1, m1, x5, %9, 0xf6;\nlop3.b32 m0, m0, x6, %9, 0xf6;\nlop3.b32 m1, m1, x7, %9, 0xf6;\n"
                     "lop3.b32 m0, m0, m1, 1, 0xa8;\nsetp.eq.u32 p, m0, 0;\n" P8_VOTE
                     P8_RT(0) P8_RT(1) P8_RT(2) P8_RT(3) P8_RT(4) P8_RT(5) P8_RT(6) P8_RT(7) P8_TAIL P8_OPS);
    else
        asm volatile(P8_HEAD "max.u32 m0, x0, x1;\nmax.u32 m0, m0, x2;\nmax.u32 m1, x3, x4;\nmax.u32 m1, m1, x5;\nmax.u32 m0, m0, x6;\n"
                     "max.u32 m0, m0, x7;\nmax.u32 m0, m0, m1;\nsetp.ne.u32 p, m0, 0xffffffff;\n" P8_VOTE
                     P8_RS(0) P8_RS(1) P8_RS(2) P8_RS(3) P8_RS(4) P8_RS(5) P8_RS(6) P8_RS(7) P8_TAIL P8_OPS);
#pragma unroll
    for (int i = 0; i < 8; i++) { v[i].x = (uint32_t)d[i]; v[i].y = (uint32_t)(d[i] >> 32); }
}
__device__ __forceinline__ void sum8(float (&c)[4], const uint2 (&v)[8], uint32_t idn) {
    float d[4] = {0.f, 0.f, 0.f, 0.f};
    c[0] = c[1] = c[2] = c[3] = 0.f;
    mma16816(c, v[0].x, v[0].y, v[1].x, v[1].y, idn, idn);
    mma16816(d, v[2].x, v[2].y, v[3].x, v[3].y, idn, idn);
    mma16816(c, v[4].x, v[4].y, v[5].x, v[5].y, idn, idn);
    mma16816(d, v[6].x, v[6].y, v[7].x, v[7].y, idn, idn);
    c[0] += d[0]; c[1] += d[1]; c[2] += d[2]; c[3] += d[3];
}

__global__ void __cluster_dims__(3, 1, 1) __launch_bounds__(256, 1)
k_chain(const bf16* __restrict__ mem0, const bf16* __restrict__ Wq, const bf16* __restrict__ Wk, const bf16* __restrict__ Wv,
        const bf16* __restrict__ Wo, const __grid_constant__ CUtensorMap mkv) {
    extern __shared__ __align__(1024) uint8_t smem_chain[];
    const uint32_t sb = smem_u32(smem_chain);
    if (sb & 1023) __trap();
    const int w = __shfl_sync(~0u, threadIdx.x >> 5, 0), lane = __shfl_sync(~0u, threadIdx.x & 31, threadIdx.x & 31);
    const int tid = w * 32 + lane, g = lane >> 2, t = lane & 3;
    auto pin = [&](uint32_t x) { return delayed<1>(x, lane); };
    const int h = blockIdx.x / 3, r = blockIdx.x - 3 * h;
    const uint32_t bar_x = sb + C_BAR, bar_kv = sb + C_BAR + 8, bar_go = sb + C_BAR + 16, bar_w = sb + C_BAR + 24;
    asm volatile("griddepcontrol.launch_dependents;");
    const int tbase = r == 0 ? 0 : 1 + 21 * r, ntile = r == 0 ? 22 : 21;
    if (tid == 0) {
        mbar_init(bar_x, 8); mbar_init(bar_kv, 1); mbar_init(bar_go, 1); mbar_init(bar_w, 1);
        asm volatile("fence.mbarrier_init.release.cluster;" ::: "memory");
        asm volatile("fence.proxy.async.shared::cta;" ::: "memory");
        mbar_expect_tx(bar_w, 128 * 32 * ntile);
    }
    __syncthreads();
    asm volatile("barrier.cluster.arrive.relaxed.aligned;" ::: "memory");
    if (tid < 128)
        asm volatile("cp.async.bulk.shared::cluster.global.mbarrier::complete_tx::bytes [%0], [%1], %2, [%3];"
                     ::"r"(sb + C_W1 + tid * 720), "l"(Wo + (size_t)(h * 128 + tid) * DM + tbase * 16), "r"(32 * ntile), "r"(bar_w) : "memory");
    const int tile0 = tbase + 7 - w;
    const bool three = w >= (r == 0 ? 2 : 3);
    const uint32_t wa = pin(sb + tid * 16);
#define W1A(i) (wa + C_W1 + (i) * 4096)
#define W2A(x) (wa + C_W2 + ((x) < 8 ? (x) * 4096 : 32768 - 1024 + ((x) - 8) * 3072))
    uint32_t wo0[8][4], wr[64][4];
    {
        const bf16* W = (r == 0 ? Wq : r == 1 ? Wk : Wv) + (size_t)(128 * w + (lane >> 4)) * HD + h * 128 + 8 * (lane & 15);
        uint4 raw[8][8];
        auto fetch = [&](int ks) {
#pragma unroll
            for (int i = 0; i < 8; i++) raw[ks][i] = ldw128(W + (size_t)(16 * ks + 2 * i) * HD);
        };
        fetch(0); fetch(1); fetch(2); fetch(3);
        mbar_wait_u(bar_w, 0);
        const uint32_t p = sb + C_W1 + ((lane & 7) + (lane >> 4) * 8) * 720 + (7 - w) * 32 + ((lane >> 3) & 1) * 16;
#pragma unroll
        for (int ks = 0; ks < 8; ks++) {
            uint32_t a[4];
            ldsm4t(wo0[ks], p + ks * 16 * 720);
            ldsm4t(a, p + ks * 16 * 720 + 256);
            sts128(W2A(ks), a[0], a[1], a[2], a[3]);
            if (three) { ldsm4t(a, p + ks * 16 * 720 + 512); sts128(W2A(8 + ks), a[0], a[1], a[2], a[3]); }
        }
        __syncthreads();
        const uint32_t stg = sb + C_KV + w * 4096;
        const uint32_t rd = stg + ((lane & 6) + 8 * (lane & 1) + (lane >> 4)) * 256 + ((((lane >> 3) & 1) ^ (lane & 7)) << 4);
#pragma unroll
        for (int ks = 0; ks < 8; ks++) {
#pragma unroll
            for (int i = 0; i < 8; i++)
                sts128(stg + (2 * i + (lane >> 4)) * 256 + (((lane & 15) ^ (((2 * i) & 6) | (i >> 2))) << 4),
                       raw[ks][i].x, raw[ks][i].y, raw[ks][i].z, raw[ks][i].w);
            if (ks < 2) fetch(ks + 4);
            if (ks == 3 || ks == 5) fetch(ks / 2 + 5);
            __syncwarp();
#pragma unroll
            for (int j = 0; j < 8; j++) {
                if (smem_idx(ks, j) >= 0) {
                    uint32_t a[4];
                    ldsm4t(a, rd ^ (j << 5));
                    sts128(W1A(smem_idx(ks, j)), a[0], a[1], a[2], a[3]);
                } else ldsm4t(wr[8 * ks + j], rd ^ (j << 5));
            }
            __syncwarp();
        }
    }
    asm volatile("fence.proxy.async.shared::cta;" ::: "memory");
    __syncthreads();
    if (tid == 0) {
        mbar_expect_tx(bar_kv, 16384);
        tma3d(sb + C_KV, &mkv, 0, 0, 2 * h, bar_kv);
        tma3d(sb + C_KV + 8192, &mkv, 0, 0, 64 + 2 * h, bar_kv);
    }
    asm volatile("barrier.cluster.wait.aligned;" ::: "memory");

    auto publish_kvm = [&](int s) {
        uint32_t v[4];
        lds128(v, sb + C_QKV + (8 + (tid >> 4)) * 272 + (tid & 15) * 16);
        asm volatile("st.global.v4.u32 [%0], {%1,%2,%3,%4};"
                     ::"l"(g_kvm + (size_t)(s * 8 + ((tid >> 4) & 7)) * 8192 + (tid >> 7) * HD + h * 128 + (tid & 15) * 8),
                       "r"(v[0]), "r"(v[1]), "r"(v[2]), "r"(v[3]) : "memory");
        if ((s & 3) == 3) {
            __syncthreads();
            if (w == 7) asm volatile("{\n.reg .pred p;\nsetp.eq.u32 p, %2, 0;\nfence.acq_rel.gpu;\n@p st.relaxed.gpu.global.u32 [%0], %1;\n}"
                                     ::"l"(g_flag + h), "r"(s + 1), "r"(lane) : "memory");
        }
    };
    const float sl2e = 0.08838834764831845f * 1.4426950408889634f;
    const uint32_t idn = pin(g == 2 * t ? 0x00003f80u : g == 2 * t + 1 ? 0x3f800000u : 0u);
    const uint32_t lm = pin(sb + (lane & 7) * 272 + (lane >> 3) * 16);
    const uint32_t sa = pin(sb + C_SC + (w & 1) * (8 * 52 * 4) + (2 * t * 52 + (w < 4 ? 32 : (w & 2) * 8) + g) * 4);
    const uint32_t sr = pin(sb + C_SC + (g * 52 + 8 * t) * 4), sr2 = pin(sb + C_SC + (g * 52 + 32 + 2 * t) * 4);
    uint32_t kva;
    {
        const int pos = (w & 2) * 8 + (lane & 15), row = (pos & 24) + ((pos + (pos >> 2 & 6)) & 7);
        const int key = 4 * (lane & 6) + (((lane & 7) + 2 * (lane >> 4)) & 7);
        kva = pin(w >= 4 ? sb + C_KV + (w & 1) * 4096 + row * 128 + (((lane >> 4) ^ (row & 7)) << 4)
                         : sb + C_KV + 8192 + (w >> 1) * 4096 + key * 128 + ((((w & 1) * 4 + ((lane >> 3) & 1)) ^ (key & 7)) << 4));
    }
    uint32_t buf0[8][4], ring[RB1][4];
    auto stage_w1 = [&]() {
#pragma unroll
        for (int i = 0; i < 8; i++) lds128v(buf0[i], W1A(i));
#pragma unroll
        for (int i = 0; i < RB1; i++) lds128v(ring[i], W1A(8 + i));
    };
    stage_w1();
    if (r > 0 && w < 2) asm volatile("prefetch.global.L2 [%0];" ::"l"(g_memx + ((w + 1) * 64 + 2 * h + r - 1) * 32 + lane) : "memory");
    if (r > 0) asm volatile("prefetch.global.L2 [%0];" ::"l"(g_part + (2 * h + r - 1) * 1024 + tid * 4) : "memory");
    uint2 bm[8];
#pragma unroll
    for (int ks = 0; ks < 8; ks++) {
        const uint32_t* p = (const uint32_t*)(mem0 + g * DM + (8 * w + ks) * 16) + t;
        const uint32_t x = __ldg(p), y = __ldg(p + 4);
        bm[ks] = make_uint2(__byte_perm(x, y, 0x5410), __byte_perm(x, y, 0x7632));
    }
#pragma unroll 1
    for (int s = 0;; s++) {
        TS(1);
        {
            float acc[8][4];
#pragma unroll
            for (int ks = 0; ks < 8; ks++) {
#pragma unroll
                for (int j = 0; j < 8; j++) {
                    const int i = smem_idx(ks, j) - 8;
                    if (ks == 0) {
                        acc[j][0] = acc[j][1] = acc[j][2] = acc[j][3] = 0.f;
                        mma16816(acc[j], buf0[j][0], buf0[j][1], buf0[j][2], buf0[j][3], bm[ks].x, bm[ks].y);
                    } else if (i >= 0) {
                        uint32_t(&a)[4] = ring[i % RB1];
                        mma16816(acc[j], a[0], a[1], a[2], a[3], bm[ks].x, bm[ks].y);
                        if (8 + i + RB1 < NS1) lds128v(a, W1A(8 + i + RB1));
                    } else {
                        const uint32_t(&a)[4] = wr[8 * ks + j];
                        mma16816(acc[j], a[0], a[1], a[2], a[3], bm[ks].x, bm[ks].y);
                    }
                }
            }
#pragma unroll
            for (int c = 0; c < 4; c++)
                stsm4t(lm + C_RED + w * 2176 + c * 64, pack2(acc[2 * c][0], acc[2 * c][1]), pack2(acc[2 * c][2], acc[2 * c][3]),
                       pack2(acc[2 * c + 1][0], acc[2 * c + 1][1]), pack2(acc[2 * c + 1][2], acc[2 * c + 1][3]));
        }
        {
            const uint32_t a = sb + C_RED + w * 272 + lane * 8;
            if (s < NSEG - 1) mbar_wait_u(bar_kv, s & 1);
            TS(2);
            __syncthreads();
            TS(3);
            uint2 v[8];
#pragma unroll
            for (int i = 0; i < 8; i++) v[i] = lds64(a + i * 2176);
            float c[4];
            sum8(c, v, idn);
            const uint32_t p0 = pack2(c[0], c[1]), p1 = pack2(c[2], c[3]);
            const uint32_t dst = sb + C_QKV + (r * 8 + w) * 272 + lane * 8;
#pragma unroll
            for (int i = 1; i < 3; i++) {
                const uint32_t peer = r + i >= 3 ? r + i - 3 : r + i;
                uint32_t rd, rb;
                asm("mapa.shared::cluster.u32 %0, %1, %2;" : "=r"(rd) : "r"(dst), "r"(peer));
                asm("mapa.shared::cluster.u32 %0, %1, %2;" : "=r"(rb) : "r"(bar_x), "r"(peer));
                asm volatile("st.async.weak.shared::cluster.mbarrier::complete_tx::bytes.v2.b32 [%0], {%1,%2}, [%3];"
                             ::"r"(rd), "r"(p0), "r"(p1), "r"(rb) : "memory");
            }
            sts64(dst, p0, p1);
            __syncwarp();
            asm volatile("{\n.reg .pred p;\nsetp.eq.u32 p, %1, 0;\n@p mbarrier.arrive.expect_tx.shared::cta.b64 _, [%0], 512;\n}"
                         ::"r"(bar_x), "r"(lane) : "memory");
        }
        TS(4);
        if (s == NSEG - 1) break;
        uint32_t wb[8][4], wc[8][4];
        const uint32_t po = ((tile0 * 32 + h) * 32 + lane) * 8;
        const uint32_t tag = s & 1;
        auto project = [&](const uint32_t(&wt)[8][4], const uint32_t(&ob)[4][4], int i) {
            float c0[4] = {0.f, 0.f, 0.f, 0.f}, c1[4] = {0.f, 0.f, 0.f, 0.f};
#pragma unroll
            for (int ks = 0; ks < 8; ks++)
                mma16816((ks & 1) ? c1 : c0, wt[ks][0], wt[ks][1], wt[ks][2], wt[ks][3], ob[ks >> 1][(ks & 1) * 2], ob[ks >> 1][(ks & 1) * 2 + 1]);
            st_rlx64((uint2*)((char*)g_part + po) + i * 8192, (pack2(c0[0] + c1[0], c0[2] + c1[2]) & ~1u) | tag, pack2(c0[1] + c1[1], c0[3] + c1[3]));
        };
        if (w >= 4) {
            uint32_t ka[4][4];
#pragma unroll
            for (int ks = 0; ks < 4; ks++) ldsm4(ka[ks], kva ^ (ks << 5));
            const uint32_t qa = lm + C_QKV + (w & 1) * 128;
            TS(5);
            mbar_wait_u(bar_x, s & 1);
            TS(6);
            {
                uint32_t qb[2][4];
                ldsm4(qb[0], qa);
                ldsm4(qb[1], qa + 64);
                float c0[4] = {0.f, 0.f, 0.f, 0.f}, c1[4] = {0.f, 0.f, 0.f, 0.f};
                mma16816(c0, ka[0][0], ka[0][1], ka[0][2], ka[0][3], qb[0][0], qb[0][1]);
                mma16816(c1, ka[1][0], ka[1][1], ka[1][2], ka[1][3], qb[0][2], qb[0][3]);
                mma16816(c0, ka[2][0], ka[2][1], ka[2][2], ka[2][3], qb[1][0], qb[1][1]);
                mma16816(c1, ka[3][0], ka[3][1], ka[3][2], ka[3][3], qb[1][2], qb[1][3]);
                sts32f(sa, c0[0] + c1[0]);
                sts32f(sa + 208, c0[1] + c1[1]);
                sts32f(sa + 32, c0[2] + c1[2]);
                sts32f(sa + 240, c0[3] + c1[3]);
            }
            __syncthreads();
            TS(7);
            if (w == 7 && s + 1 < NSEG - 1) {
                if (lane == 0) {
                    mbar_expect_tx(bar_kv, 16384);
                    tma3d(sb + C_KV, &mkv, 0, (s + 1) * 32, 2 * h, bar_kv);
                    tma3d(sb + C_KV + 8192, &mkv, 0, (s + 1) * 32, 64 + 2 * h, bar_kv);
                }
                __syncwarp();
            }
            const uint32_t wd = delayed<DLYW>(wa, lane);
#pragma unroll
            for (int i = 0; i < 8; i++) lds128(wb[i], wd + C_W2 + i * 4096);
#pragma unroll
            for (int i = 0; i < PFC; i++) lds128(wc[i], wd + C_W2 + 32768 - 1024 + i * 3072);
            TS(8);
            __syncthreads();
            TS(9);
            uint32_t ob[4][4];
#pragma unroll
            for (int i = 0; i < 4; i++) ldsm4(ob[i], lm + C_OB + i * 64);
#pragma unroll
            for (int i = PFC; i < 8; i++) lds128v(wc[i], W2A(8 + i));
            project(wb, ob, 1);
            project(wo0, ob, 0);
            project(wc, ob, 2);
        } else {
            uint32_t va[4][4];
#pragma unroll
            for (int i = 0; i < 4; i++) ldsm4t(va[i], kva ^ (((i >> 1) << 5) | ((i & 1) * 0x240)));
#pragma unroll
            for (int i = 0; i < 8; i++) lds128(wb[i], W2A(i));
            const uint32_t qa = lm + C_QKV + (w & 1) * 128, oa = lm + w * 64;
            TS(5);
            mbar_wait_u(bar_x, s & 1);
            TS(6);
            if (w < 2) {
                uint32_t qb[2][4], km[2][4];
                ldsm4(qb[0], qa);
                ldsm4(km[0], qa + 8 * 272);
                ldsm4(qb[1], qa + 64);
                ldsm4(km[1], qa + 8 * 272 + 64);
                float c0[4] = {0.f, 0.f, 0.f, 0.f}, c1[4] = {0.f, 0.f, 0.f, 0.f};
                mma16816(c0, km[0][0], km[0][1], km[0][2], km[0][3], qb[0][0], qb[0][2]);
                mma16816(c1, km[0][0], km[0][1], km[0][2], km[0][3], qb[0][1], qb[0][3]);
                mma16816(c0, km[1][0], km[1][1], km[1][2], km[1][3], qb[1][0], qb[1][2]);
                mma16816(c1, km[1][0], km[1][1], km[1][2], km[1][3], qb[1][1], qb[1][3]);
                sts32f(sa, c0[0] + c1[2]);
                sts32f(sa + 208, c0[1] + c1[3]);
            }
            __syncthreads();
            TS(7);
            {
                float4 x0 = lds128f(sr), y0 = lds128f(sr + 1664), x1 = lds128f(sr + 16), y1 = lds128f(sr + 1680);
                float2 x2 = lds64f(sr2), y2 = lds64f(sr2 + 1664);
                float p[10] = {x0.x + y0.x, x0.y + y0.y, x0.z + y0.z, x0.w + y0.w, x1.x + y1.x,
                               x1.y + y1.y, x1.z + y1.z, x1.w + y1.w, x2.x + y2.x, x2.y + y2.y};
                float m = fmaxf(fmaxf(fmaxf(p[0], p[1]), fmaxf(p[2], p[3])), fmaxf(fmaxf(fmaxf(p[4], p[5]), fmaxf(p[6], p[7])), fmaxf(p[8], p[9])));
                const float m1 = __shfl_xor_sync(~0u, m, 1), m2 = __shfl_xor_sync(~0u, m, 2), m3 = __shfl_xor_sync(~0u, m, 3);
                uint32_t vm[4];
                ldsm4t(vm, oa + C_QKV + 16 * 272);
                m = fmaxf(fmaxf(m, m1), fmaxf(m2, m3));
                const float ms = m * sl2e;
#pragma unroll
                for (int i = 0; i < 10; i++) p[i] = ex2(fmaf(p[i], sl2e, -ms));
                const uint32_t b0 = pack2(p[0], p[1]), b1 = pack2(p[2], p[3]), b2 = pack2(p[4], p[5]), b3 = pack2(p[6], p[7]), b4 = pack2(p[8], p[9]);
                const uint32_t one = 0x3f803f80u;
                float o0[4] = {0.f, 0.f, 0.f, 0.f}, o1[4] = {0.f, 0.f, 0.f, 0.f}, sm[4] = {0.f, 0.f, 0.f, 0.f};
                mma16816(sm, one, one, one, one, b0, b1);
                mma16816(o0, va[0][0], va[0][1], va[0][2], va[0][3], b0, b1);
                mma16816(o1, va[2][0], va[2][1], va[2][2], va[2][3], b0, b1);
                mma16816(sm, one, one, one, one, b2, b3);
                mma16816(o0, va[1][0], va[1][1], va[1][2], va[1][3], b2, b3);
                mma16816(o1, va[3][0], va[3][1], va[3][2], va[3][3], b2, b3);
                mma1688(sm, one, one, b4);
                mma1688(o0, vm[0], vm[1], b4);
                mma1688(o1, vm[2], vm[3], b4);
                float i0, i1;
                asm("rcp.approx.ftz.f32 %0, %1;" : "=f"(i0) : "f"(sm[0]));
                asm("rcp.approx.ftz.f32 %0, %1;" : "=f"(i1) : "f"(sm[1]));
                stsm4t(oa + C_OB, pack2(o0[0] * i0, o0[1] * i1), pack2(o0[2] * i0, o0[3] * i1),
                       pack2(o1[0] * i0, o1[1] * i1), pack2(o1[2] * i0, o1[3] * i1));
            }
            TS(8);
            __syncthreads();
            TS(9);
            uint32_t ob[4][4];
#pragma unroll
            for (int i = 0; i < 4; i++) ldsm4(ob[i], lm + C_OB + i * 64);
            if (three) {
#pragma unroll
                for (int i = 0; i < 8; i++) lds128v(wc[i], W2A(8 + i));
                project(wb, ob, 1);
                project(wo0, ob, 0);
                project(wc, ob, 2);
            } else {
                project(wb, ob, 1);
                project(wo0, ob, 0);
            }
        }
        TS(10);
        __syncthreads();
        uint32_t eo = (((s + 1) * 64 + 8 * w) * 32 + lane) * 8;
        uint64_t d[8];
        if (r == 0) {
            TS(11); TS(12);
            stage_w1();
            publish_kvm(s);
            mbar_wait_u(bar_go, s & 1);
            eo = delayed<DLY0>(eo, lane);
        } else {
            const int j = 2 * h + r - 1;
            if (w < 4) {
                const char* src = (const char*)g_part + delayed<DLY3>(((j * 32 + 8 * w) * 32 + lane) * 8, lane);
                fetch8(d, src);
                const uint32_t a = pin(sb + C_R3 + w * 640 + t * 160 + g * 8), a2 = pin(sb + C_R3 + g * 80 + t * 16);
                stage_w1();
                uint2 v[8];
                settle8<true>(v, d, src, tag);
                TS(11);
                float c[4];
                sum8(c, v, idn);
                sts64f(a, c[0], c[1]);
                sts64f(a + 80, c[2], c[3]);
                __syncthreads();
                TS(12);
                if (w == 0) {
                    const float4 u0 = lds128f(a2), u1 = lds128f(a2 + 640), u2 = lds128f(a2 + 1280), u3 = lds128f(a2 + 1920);
                    st_rlx64((uint2*)((char*)g_memx + eo) + j * 32, pack2((u0.x + u1.x) + (u2.x + u3.x), (u0.y + u1.y) + (u2.y + u3.y)),
                             pack2((u0.z + u1.z) + (u2.z + u3.z), (u0.w + u1.w) + (u2.w + u3.w)));
                }
            } else {
                if (w == 5 && s + 3 < NSEG)
                    asm volatile("prefetch.global.L2 [%0];" ::"l"(g_memx + ((s + 3) * 64 + j) * 32 + lane) : "memory");
                stage_w1();
                TS(11);
                __syncthreads();
                TS(12);
                if (w == 4 && r == 1)
                    asm volatile("{\n.reg .pred p;\n.reg .u32 a;\nelect.sync _|p, -1;\nmapa.shared::cluster.u32 a, %0, 0;\n"
                                 "@p mbarrier.arrive.relaxed.cluster.shared::cluster.b64 _, [a];\n}" ::"r"(bar_go) : "memory");
            }
            eo = delayed<DLY1>(eo, lane);
        }
        { const int s_ = s; { const int s = s_ + 1; TS(0); } }
        fetch8(d, (const char*)g_memx + eo);
        settle8<false>(bm, d, (const char*)g_memx + eo, 0);
    }
    mbar_wait_u(bar_x, (NSEG - 1) & 1);
    if (r == 0) publish_kvm(NSEG - 1);
    asm volatile("barrier.cluster.arrive.relaxed.aligned;\nbarrier.cluster.wait.aligned;" ::: "memory");
}

constexpr int S4_US = 4368;
constexpr int S4_RS = 8848;
constexpr int S4_KS = 1296;
constexpr int S4_U = 0, S4_R = 16 * S4_US, S4_K = S4_R + 16 * S4_RS;
constexpr int S4_SMEM = S4_K + 16 * S4_KS;
constexpr int S4_SIG = 3104, S4_PK = 2 * S4_SIG;

struct cf { float r, i; };
__device__ __forceinline__ cf cmul(cf a, cf b) { return {fmaf(a.r, b.r, -a.i * b.i), fmaf(a.r, b.i, a.i * b.r)}; }
__device__ __forceinline__ cf cmulc(cf a, cf b) { return {fmaf(a.r, b.r, a.i * b.i), fmaf(a.i, b.r, -a.r * b.i)}; }
__device__ __forceinline__ cf csq(cf a) { const float t = a.r * a.i; return {fmaf(a.r, a.r, -a.i * a.i), t + t}; }
__device__ __forceinline__ cf cexp(float l2, float turns) {
    const float mag = ex2(l2), fr = (turns - rintf(turns)) * 6.283185307179586f;
    return {mag * __cosf(fr), mag * __sinf(fr)};
}
__device__ __forceinline__ void sts32(uint32_t a, uint32_t v) { asm volatile("st.shared.u32 [%0], %1;" ::"r"(a), "r"(v) : "memory"); }
__device__ __forceinline__ uint32_t lds16(uint32_t a) {
    uint32_t v;
    asm volatile("ld.shared.u16 %0, [%1];" : "=r"(v) : "r"(a) : "memory");
    return v;
}

template <int M0, int NQ>
__device__ __forceinline__ void s4_class(float (&acc)[16][4], uint32_t sig, uint32_t taps, int x0) {
    constexpr int D0 = M0 / 8, D1 = M0 == 32 ? 9 : 15;
    uint32_t R[D1 - D0 + 2];
#pragma unroll
    for (int D = D0 - 1; D <= D1; D++) {
        if (D < D0 || 8 * D - 7 >= 2 * M0) { R[D - D0 + 1] = 0; continue; }
        const int m = 8 * D + x0;
        uint32_t lo = lds16(taps + m * (2 * NQ)), hi = lds16(taps + (m - 1) * (2 * NQ));
        if (D == D0) { lo = m >= M0 ? lo : 0; hi = m > M0 ? hi : 0; }
        if (D == 2 * D0) { lo = m < 2 * M0 ? lo : 0; hi = m <= 2 * M0 ? hi : 0; }
        R[D - D0 + 1] = lo | (hi << 16);
    }
#pragma unroll
    for (int J = 0; 2 * J + D0 < 16; J++) {
        uint32_t a[4];
        ldsm4t(a, sig + J * 512);
#pragma unroll
        for (int D = D0; D <= D1; D++)
            if (2 * J + D < 16) mma16816(acc[2 * J + D], a[0], a[1], a[2], a[3], R[D - D0 + 1], R[D - D0]);
    }
}

__global__ void __launch_bounds__(512, 1)
k_s4(const bf16* __restrict__ u, const bf16* __restrict__ Are, const bf16* __restrict__ Aim, const bf16* __restrict__ Bre,
     const bf16* __restrict__ Bim, const bf16* __restrict__ Cre, const bf16* __restrict__ Cim, const bf16* __restrict__ logdt,
     const bf16* __restrict__ Dsk, bf16* __restrict__ out) {
    extern __shared__ __align__(16) uint8_t smem_s4[];
    const uint32_t sb = smem_u32(smem_s4);
    asm volatile("griddepcontrol.launch_dependents;");
    const int tid = threadIdx.x, w = __shfl_sync(~0u, tid >> 5, 0), lane = tid & 31, g = lane >> 2, t = lane & 3;
    if (tid == 0) TL(2, 0);
    const int d0 = blockIdx.x * 16;
    const int d = d0 + (w & 1) + ((w >> 1) & 3) * 4 + (w >> 3) * 2;
    const uint32_t tr_off = (lane & 15), tr_l = (lane >> 4) * 16;
    const uint32_t ur = sb + S4_U + w * S4_US, rs = sb + S4_R + w * S4_RS, kd = sb + S4_K + w * S4_KS;
    if (lane < 16) sts128(ur + lane * 16, 0, 0, 0, 0);
    {
        const int o = d * 128 + lane * 4;
        const uint2 ar = __ldg((const uint2*)(Are + o)), ai = __ldg((const uint2*)(Aim + o)), br = __ldg((const uint2*)(Bre + o));
        const uint2 bi = __ldg((const uint2*)(Bim + o)), cr = __ldg((const uint2*)(Cre + o)), ci = __ldg((const uint2*)(Cim + o));
        const float dt = bf_round(expf(__bfloat162float(logdt[d])));
        const bf16* src = u + (size_t)(w * 128 + g) * DM + d0 + 4 * t;
        float T[5][4];
#pragma unroll
        for (int i = 0; i < 5; i++) T[i][0] = T[i][1] = T[i][2] = T[i][3] = 0.f;
        float klast = 0.f;
        const uint32_t wr_ = rs + lane * 4;
        const uint32_t ra = rs + (lane & 15) * 144 + (lane >> 4) * 16, rb = rs + (16 + (lane & 7)) * 144 + (lane >> 3) * 16;
#pragma unroll 1
        for (int c = 0; c < 4; c++) {
            uint2 v[4];
#pragma unroll
            for (int i = 0; i < 4; i++) v[i] = __ldg((const uint2*)(src + (size_t)(c * 32 + i * 8) * DM));
            auto pick = [&](const uint2& x) { const uint32_t y = c < 2 ? x.x : x.y; return (c & 1) ? bf_hi(y) : bf_lo(y); };
            auto put = [&](int row, cf x) { sts32(wr_ + row * 144, pack2(x.r, x.i)); };
            const float l2 = dt * pick(ar) * 1.4426950408889634f, tu = dt * pick(ai) * 0.15915494309189535f;
            const cf z1 = cexp(l2, tu), z2 = csq(z1), z4 = csq(z2), z8 = csq(z4), z128 = cexp(l2 * 128.f, tu * 128.f);
            cf a = z8;
            sts32(wr_, 0x00003f80u);
            put(1, a);
#pragma unroll
            for (int i = 2; i < 16; i++) { a = cmul(a, z8); put(i, a); }
            cf y = cmul({pick(cr), pick(ci)}, {dt * pick(br), dt * pick(bi)});
            y.i = -y.i;
#pragma unroll
            for (int k = 0; k < 16; k++) {
                const int n = k < 2 ? 8 : k < 4 ? 4 : k < 8 ? 2 : 1;
                const int row = 16 + (k < 2 ? 8 * k : k < 4 ? 8 + 4 * k : k < 8 ? 16 + 2 * k : 24 + k);
                cf x = y;
                put(row, x);
#pragma unroll
                for (int b = 1; b < n; b++) { x = cmulc(x, k < 2 ? z1 : k < 4 ? z2 : z4); put(row + b, x); }
                y = cmulc(y, z128);
            }
            klast += y.r;
            __syncwarp();
#pragma unroll
            for (int kp = 0; kp < 2; kp++) {
                uint32_t A0[4], A1[4];
                ldsm4(A0, ra + kp * 64);
                ldsm4(A1, ra + kp * 64 + 32);
#pragma unroll
                for (int i = 0; i < 5; i++) {
                    uint32_t B[4];
                    ldsm4(B, rb + i * 8 * 144 + kp * 64);
                    mma16816(T[i], A0[0], A0[1], A0[2], A0[3], B[0], B[1]);
                    mma16816(T[i], A1[0], A1[1], A1[2], A1[3], B[2], B[3]);
                }
            }
#pragma unroll
            for (int i = 0; i < 2; i++)
                stsm4t(sb + S4_U + tr_off * S4_US + 256 + (w * 128 + c * 32 + i * 16) * 2 + tr_l, v[2 * i].x, v[2 * i].y, v[2 * i + 1].x, v[2 * i + 1].y);
            __syncwarp();
        }
#pragma unroll
        for (int o2 = 16; o2; o2 >>= 1) klast += __shfl_xor_sync(~0u, klast, o2);
#pragma unroll
        for (int hh = 0; hh < 2; hh++) {
            const int i = g + 8 * hh;
            sts32(kd + (8 * i + 2 * t) * 2, pack2(T[0][2 * hh], T[0][2 * hh + 1]));
            sts32(kd + (128 + 8 * i + 2 * t) * 2, pack2(T[1][2 * hh], T[1][2 * hh + 1]));
            sts32(kd + (256 + 4 * i + 2 * (t & 1) + 64 * (t >> 1)) * 2, pack2(T[2][2 * hh], T[2][2 * hh + 1]));
            sts32(kd + (384 + 2 * i + 32 * t) * 2, pack2(T[3][2 * hh], T[3][2 * hh + 1]));
        }
        asm volatile("stmatrix.sync.aligned.m8n8.x2.trans.shared.b16 [%0], {%1,%2};"
                     ::"r"(kd + 1024 + (lane & 7) * 32 + ((lane >> 3) & 1) * 16), "r"(pack2(T[4][0], T[4][1])), "r"(pack2(T[4][2], T[4][3])) : "memory");
        if (lane == 0) sts32(kd + 1280, pack2(klast, 0.f));
    }
    __syncwarp();
    const uint32_t pk = rs + S4_PK + 64;
    {
#pragma unroll
        for (int i = 0; i < 2; i++) {
            const int x = i * 128 + lane * 4;
            const uint2 c = lds64(kd + x * 2);
            uint32_t p = lds16(kd + x * 2 - 2);
            if (x == 0) p = 0;
            sts128(pk + x * 4, __byte_perm(c.x, p, 0x5410), __byte_perm(c.x, 0, 0x1032), __byte_perm(c.y, c.x, 0x7610), __byte_perm(c.y, 0, 0x1032));
        }
#pragma unroll
        for (int i = 2; i < 4; i++) {
            const int x = i * 128 + lane * 4;
            const uint32_t ab = lds32(kd + 256 + x), c = lds16(kd + 256 + x + 4);
            const uint32_t p = x == 256 ? lds16(kd + 510) : ab;
            sts128(pk + x * 4, __byte_perm(ab, p, 0x5410), __byte_perm(ab, 0, 0x1010), __byte_perm(ab, 0, 0x1032), __byte_perm(c, ab, 0x7610));
        }
        const uint32_t v = lds16(kd + 768), v2 = lds16(kd + 1024);
        if (lane < 24) {
            uint32_t x0 = 0, x1 = 0, x2 = 0, x3 = 0;
            if (lane == 0) { x0 = x1 = x2 = v | (v << 16); x3 = v << 16; }
            if (lane == 12) x3 = v2;
            if (lane == 13) { x0 = v2 | (v2 << 16); x1 = v2 << 16; }
            sts128(lane < 20 ? pk + 2048 + lane * 16 : pk - 64 + (lane - 20) * 16, x0, x1, x2, x3);
        }
        if (lane < 4) sts128(rs + (lane >> 1) * S4_SIG + (lane & 1) * 16, 0, 0, 0, 0);
    }
    __syncthreads();
    float acc[16][4];
#pragma unroll
    for (int i = 0; i < 16; i++) acc[i][0] = acc[i][1] = acc[i][2] = acc[i][3] = 0.f;
    const uint32_t lf = (lane & 7) * 32 + ((lane >> 3) & 1) * 16 + (lane >> 4) * 256;
#pragma unroll
    for (int rg = 3; rg >= 2; rg--) {
#pragma unroll 1
        for (int it = 0; it < (rg == 3 ? 4 : 6); it++) {
            const int n = it * 32 + lane;
            uint32_t x[2][4];
            lds128(x[0], ur + 256 + n * 16 - 16);
            lds128(x[1], ur + 256 + n * 16);
            float e[16], p[15], s[11];
#pragma unroll
            for (int i = 0; i < 8; i++) { e[2 * i] = bf_lo(x[i >> 2][i & 3]); e[2 * i + 1] = bf_hi(x[i >> 2][i & 3]); }
#pragma unroll
            for (int i = 0; i < 15; i++) p[i] = e[i] + e[i + 1];
#pragma unroll
            for (int i = 0; i < 11; i++) s[i] = p[i + 3] + e[i + 5];
            const uint32_t o = rs + 16 + n * 16;
            if (rg == 2) sts128(o, pack2(s[0], s[1]), pack2(s[2], s[3]), pack2(s[4], s[5]), pack2(s[6], s[7]));
#pragma unroll
            for (int i = 0; i < 10; i++) s[i] = p[i + 2] + s[i + 1];
            if (rg == 2) {
                sts64(o + S4_SIG + 8, pack2(s[0], s[1]), pack2(s[2], s[3]));
                sts64(o + S4_SIG + 16, pack2(s[4], s[5]), pack2(s[6], s[7]));
            } else {
#pragma unroll
                for (int i = 0; i < 9; i++) s[i] = p[i + 1] + s[i + 1];
                sts64(o + 8, pack2(s[0], s[1]), pack2(s[2], s[3]));
                sts64(o + 16, pack2(s[4], s[5]), pack2(s[6], s[7]));
#pragma unroll
                for (int i = 0; i < 8; i++) s[i] = p[i] + s[i + 1];
                sts64(o + S4_SIG + 8, pack2(s[0], s[1]), pack2(s[2], s[3]));
                sts64(o + S4_SIG + 16, pack2(s[4], s[5]), pack2(s[6], s[7]));
            }
        }
        __syncwarp();
        if (rg == 3) {
#pragma unroll 1
            for (int q = 1; q <= 2; q++) s4_class<64, 2>(acc, rs + lf + (q == 1 ? 16 : S4_SIG), kd + (384 + q) * 2, g - 2 * t);
        } else {
#pragma unroll 1
            for (int q = 1; q <= 4; q++) s4_class<32, 4>(acc, rs + lf + ((q & 1) ? 0 : S4_SIG) + (q < 3 ? 16 : 0), kd + (256 + q) * 2, g - 2 * t);
        }
        __syncwarp();
    }
    {
        const uint32_t ub = ur + 256 + lf, kb = pk + (g - 2 * t) * 4;
#pragma unroll 1
        for (int j0 = 0; j0 < 8; j0++) {
            uint32_t B[8][4];
#pragma unroll
            for (int i = 0; i < 8; i++) ldsm4(B[i], ub + i * 512 - j0 * 32);
            auto block = [&](int J, uint32_t a) {
                const uint32_t r0 = lds32(a), rp = lds32(a + 32), rm = lds32(a - 32), r3 = lds32(a);
#pragma unroll
                for (int I = J; I < 16; I++)
                    mma16816(acc[I], r0, rp, rm, r3, B[(I - J) >> 1][((I - J) & 1) * 2], B[(I - J) >> 1][((I - J) & 1) * 2 + 1]);
            };
#pragma unroll
            for (int J = 0; J < 4; J++) block(J, kb + j0 * 64 + J * 512);
            if (j0 < 2) { block(4, kb + j0 * 64 + 2048); block(8, kb + j0 * 64 + (544 + 16) * 4); }
        }
        __syncwarp();
#pragma unroll
        for (int i = 0; i < 8; i++)
            stsm4t(rs + lf + i * 512, pack2(acc[2 * i][0], acc[2 * i][1]), pack2(acc[2 * i][2], acc[2 * i][3]),
                   pack2(acc[2 * i + 1][0], acc[2 * i + 1][1]), pack2(acc[2 * i + 1][2], acc[2 * i + 1][3]));
    }
    __syncthreads();
    {
        const uint2 dv = __ldg((const uint2*)(Dsk + d0 + 4 * t));
        bf16* dst = out + (size_t)(w * 128 + g) * 2048 + 1024 + d0 + 4 * t;
#pragma unroll
        for (int i = 0; i < 8; i++) {
            uint32_t y[4], x[4], o[4];
            ldsm4t(y, sb + S4_R + tr_off * S4_RS + (w * 128 + i * 16) * 2 + tr_l);
            ldsm4t(x, sb + S4_U + tr_off * S4_US + 256 + (w * 128 + i * 16) * 2 + tr_l);
#pragma unroll
            for (int j = 0; j < 4; j++)
                asm("{\n.reg .b32 s;\nmul.rn.bf16x2 s, %2, %3;\nadd.rn.bf16x2 %0, %1, s;\n}" : "=r"(o[j]) : "r"(y[j]), "r"(x[j]), "r"((j & 1) ? dv.y : dv.x));
            *reinterpret_cast<uint2*>(dst + (size_t)(i * 16) * 2048) = make_uint2(o[0], o[1]);
            *reinterpret_cast<uint2*>(dst + (size_t)(i * 16 + 8) * 2048) = make_uint2(o[2], o[3]);
        }
    }
    if (tid == 0) TL(2, 1);
}

constexpr int WO_BN = 128, WO_PER = DM / WO_BN;
constexpr int BG_ITEMS = 16 * (16 + WO_PER);

template <int BN, typename ACC>
__device__ __forceinline__ void gemm_mainloop(ACC& acc, const GemmSmem& g, int cw, int nk) {
#pragma unroll 1
    for (int k0 = 0; k0 < nk; k0 += 4) {
#pragma unroll
        for (int s = 0; s < 4; s++) {
            mbar_wait_u(g.full + 8 * s, (k0 >> 2) & 1);
            gemm_kblock<BN>(acc, g.st + s * STAGE_BYTES, cw, s == 0 && k0 == 0);
            wg_wait<1>();
            if (s > 0 || k0 > 0) mbar_arrive_one(g.empty + 8 * ((s + 3) & 3), threadIdx.x & 127);
        }
    }
    wg_wait<0>();
    mbar_arrive_one(g.empty + 8 * 3, threadIdx.x & 127);
}

__global__ void __launch_bounds__(384, 1)
k_bg(const __grid_constant__ CUtensorMap mx, const __grid_constant__ CUtensorMap mwq, const __grid_constant__ CUtensorMap mkv4,
     const __grid_constant__ CUtensorMap mkvm, const __grid_constant__ CUtensorMap mo, const __grid_constant__ CUtensorMap mwo,
     bf16* __restrict__ out) {
    extern __shared__ __align__(1024) uint8_t smem_gemm[];
    int blk, idx; bool is_qa;
    {
        const int it = blockIdx.x;
        if (it < 16) { blk = 0; idx = it; is_qa = true; }
        else {
            const int q = (it - 16) / (16 + WO_PER), rr = (it - 16) - q * (16 + WO_PER);
            if (q == 15) { blk = 15; idx = rr; is_qa = false; }
            else if (rr < 16) { blk = q + 1; idx = rr; is_qa = true; }
            else { blk = q; idx = rr - 16; is_qa = false; }
        }
    }
    if (threadIdx.x == 0) TL(3, 0);
    GemmSmem g = gemm_setup(smem_gemm);
    const int m0 = blk * 128, wg = __shfl_sync(~0u, threadIdx.x >> 7, 0);
    if (wg == 0) {
        asm volatile("setmaxnreg.dec.sync.aligned.u32 40;");
        if (threadIdx.x == 0) {
            if (is_qa) {
                for (int it = 0; it < 20; it++) {
                    const int s = it & 3;
                    const uint32_t st = g.st + s * STAGE_BYTES, fb = g.full + 8 * s;
                    mbar_wait(g.empty + 8 * s, ((it >> 2) & 1) ^ 1);
                    if (it < 16) {
                        mbar_expect_tx(fb, STAGE_BYTES);
                        tma2d(st, &mx, it * 64, m0, fb);
                        tma3d(st + 16384, &mwq, 0, it * 64, idx * 4, fb);
                    } else {
                        mbar_expect_tx(fb, 40960);
                        tma3d(st, &mkv4, 0, m0 + s * 32, idx * 4, fb);
                        tma3d(st + 16384, &mkv4, 0, m0 + s * 32, 64 + idx * 4, fb);
                    }
                }
                wait_flag(g_flag + 2 * idx, 4 * blk + 4);
                wait_flag(g_flag + 2 * idx + 1, 4 * blk + 4);
                asm volatile("fence.proxy.async.global;" ::: "memory");
                for (int s = 0; s < 4; s++) {
                    const uint32_t st = g.st + s * STAGE_BYTES, fb = g.full + 8 * s;
                    tma3d(st + 32768, &mkvm, 0, (blk * 4 + s) * 8, idx * 4, fb);
                    tma3d(st + 36864, &mkvm, 0, (blk * 4 + s) * 8, 64 + idx * 4, fb);
                }
            } else {
                wait_flag(g_flag + 64 + blk, 16);
                TL(3, 2);
                asm volatile("fence.proxy.async.global;" ::: "memory");
                for (int it = 0; it < 64; it++) {
                    const int s = it & 3;
                    const uint32_t st = g.st + s * STAGE_BYTES, fb = g.full + 8 * s;
                    mbar_wait(g.empty + 8 * s, ((it >> 2) & 1) ^ 1);
                    mbar_expect_tx(fb, 16384 + WO_BN * 128);
                    tma2d(st, &mo, it * 64, m0, fb);
                    tma3d(st + 16384, &mwo, 0, it * 64, idx * (WO_BN / 64), fb);
                }
            }
        }
    } else {
        asm volatile("setmaxnreg.inc.sync.aligned.u32 232;");
        const int cw = wg - 1, ww = __shfl_sync(~0u, (threadIdx.x >> 5) & 3, 0), lane = threadIdx.x & 31, gq = lane >> 2, t = lane & 3;
        const int row = m0 + cw * 64 + ww * 16 + gq;
        if (is_qa) {
            uint32_t q[64];
            {
                float acc[128];
                gemm_mainloop<256>(acc, g, cw, 16);
#pragma unroll
                for (int i = 0; i < 64; i++) q[i] = pack2(acc[2 * i], acc[2 * i + 1]);
            }
            const int sg = cw * 2 + (ww >> 1), hf = ww & 1;
            const uint32_t st = g.st + sg * STAGE_BYTES;
            if (threadIdx.x == 128) TL(3, 2);
            mbar_wait_u(g.full + 8 * sg, 0);
            if (threadIdx.x == 128) TL(3, 3);
            const float scale = 0.08838834764831845f, l2e = 1.4426950408889634f;
            const int r8 = lane & 7, m4 = lane >> 3;
#pragma unroll
            for (int hh = 0; hh < 2; hh++) {
                float sc[5][4];
#pragma unroll
                for (int nt = 0; nt < 5; nt++) {
                    sc[nt][0] = sc[nt][1] = sc[nt][2] = sc[nt][3] = 0.f;
                    if (nt < 3 || hf) {
#pragma unroll
                        for (int kp = 0; kp < 4; kp++) {
                            const int nb = hh * 2 + (kp >> 1);
                            const uint32_t base = nt == 0 ? st + 32768 + nb * 1024 : st + nb * 4096 + (nt - 1) * 1024;
                            uint32_t b[4];
                            ldsm4(b, base + r8 * 128 + ((((kp & 1) * 4 + m4) ^ r8) << 4));
                            const int j = (hh * 16 + kp * 4) * 2;
                            mma16816(sc[nt], q[j], q[j + 1], q[j + 2], q[j + 3], b[0], b[1]);
                            mma16816(sc[nt], q[j + 4], q[j + 5], q[j + 6], q[j + 7], b[2], b[3]);
                        }
                    }
                }
                float mx[2] = {-3.0e38f, -3.0e38f};
#pragma unroll
                for (int nt = 0; nt < 5; nt++)
#pragma unroll
                    for (int c = 0; c < 4; c++) {
                        float v = bf_round(bf_round(sc[nt][c]) * scale);
                        if (nt > 0 && (nt - 1) * 8 + 2 * t + (c & 1) > hf * 16 + gq + (c >> 1) * 8) v = -1.0e9f;
                        sc[nt][c] = v;
                        mx[c >> 1] = fmaxf(mx[c >> 1], v);
                    }
                float sum[2] = {0.f, 0.f};
#pragma unroll
                for (int i = 0; i < 2; i++) {
                    mx[i] = fmaxf(mx[i], __shfl_xor_sync(~0u, mx[i], 1));
                    mx[i] = fmaxf(mx[i], __shfl_xor_sync(~0u, mx[i], 2));
                }
#pragma unroll
                for (int nt = 0; nt < 5; nt++)
#pragma unroll
                    for (int c = 0; c < 4; c++) {
                        sc[nt][c] = ex2((sc[nt][c] - mx[c >> 1]) * l2e);
                        sum[c >> 1] += sc[nt][c];
                    }
#pragma unroll
                for (int i = 0; i < 2; i++) {
                    sum[i] += __shfl_xor_sync(~0u, sum[i], 1);
                    sum[i] += __shfl_xor_sync(~0u, sum[i], 2);
                    sum[i] = __frcp_rn(sum[i]);
                }
                uint32_t p[5][2];
#pragma unroll
                for (int nt = 0; nt < 5; nt++) {
                    p[nt][0] = pack2(sc[nt][0] * sum[0], sc[nt][1] * sum[0]);
                    p[nt][1] = pack2(sc[nt][2] * sum[1], sc[nt][3] * sum[1]);
                }
                bf16* dst = g_o + (size_t)row * HD + idx * 256 + hh * 128 + t * 8;
#pragma unroll
                for (int G = 0; G < 4; G++) {
                    const int nb = hh * 2 + (G >> 1), c0 = (G & 1) * 4;
                    float o[4][4];
#pragma unroll
                    for (int i = 0; i < 4; i++) o[i][0] = o[i][1] = o[i][2] = o[i][3] = 0.f;
                    uint32_t b[4];
                    ldsm4t(b, st + 36864 + nb * 1024 + r8 * 128 + (((c0 + m4) ^ r8) << 4));
#pragma unroll
                    for (int i = 0; i < 4; i++) mma1688(o[i], p[0][0], p[0][1], b[i]);
#pragma unroll
                    for (int kk = 0; kk < 2; kk++) {
                        if (kk == 0 || hf) {
#pragma unroll
                            for (int i = 0; i < 2; i++) {
                                ldsm4t(b, st + 16384 + nb * 4096 + (kk * 16 + (m4 & 1) * 8 + r8) * 128 + (((c0 + 2 * i + (m4 >> 1)) ^ r8) << 4));
                                mma16816(o[2 * i], p[1 + 2 * kk][0], p[1 + 2 * kk][1], p[2 + 2 * kk][0], p[2 + 2 * kk][1], b[0], b[1]);
                                mma16816(o[2 * i + 1], p[1 + 2 * kk][0], p[1 + 2 * kk][1], p[2 + 2 * kk][0], p[2 + 2 * kk][1], b[2], b[3]);
                            }
                        }
                    }
#pragma unroll
                    for (int rr = 0; rr < 2; rr++) {
                        uint32_t r0 = pack2(o[0][2 * rr], o[0][2 * rr + 1]), r1 = pack2(o[1][2 * rr], o[1][2 * rr + 1]);
                        uint32_t r2 = pack2(o[2][2 * rr], o[2][2 * rr + 1]), r3 = pack2(o[3][2 * rr], o[3][2 * rr + 1]);
                        quad_transpose(r0, r1, r2, r3, t);
                        *reinterpret_cast<uint4*>(dst + (size_t)rr * 8 * HD + G * 32) = make_uint4(r0, r1, r2, r3);
                    }
                }
            }
            bar_sync(1, 256);
            if (threadIdx.x == 128)
                asm volatile("fence.acq_rel.gpu;\nred.relaxed.gpu.global.add.u32 [%0], 1;" ::"l"(g_flag + 64 + blk) : "memory");
        } else {
            float acc[WO_BN / 2];
            gemm_mainloop<WO_BN>(acc, g, cw, 64);
            if (threadIdx.x == 128) TL(3, 3);
            bf16* dst = out + (size_t)row * 2048 + idx * WO_BN + t * 8;
#pragma unroll
            for (int G = 0; G < WO_BN / 32; G++)
#pragma unroll
                for (int rr = 0; rr < 2; rr++) {
                    uint32_t r0 = pack2(acc[16 * G + 2 * rr], acc[16 * G + 2 * rr + 1]), r1 = pack2(acc[16 * G + 4 + 2 * rr], acc[16 * G + 5 + 2 * rr]);
                    uint32_t r2 = pack2(acc[16 * G + 8 + 2 * rr], acc[16 * G + 9 + 2 * rr]), r3 = pack2(acc[16 * G + 12 + 2 * rr], acc[16 * G + 13 + 2 * rr]);
                    quad_transpose(r0, r1, r2, r3, t);
                    *reinterpret_cast<uint4*>(dst + (size_t)rr * 8 * 2048 + G * 32) = make_uint4(r0, r1, r2, r3);
                }
        }
        if (threadIdx.x == 128) TL(3, 1);
    }
}

typedef CUresult (*EncodeFn)(CUtensorMap*, CUtensorMapDataType, cuuint32_t, void*, const cuuint64_t*, const cuuint64_t*,
                             const cuuint32_t*, const cuuint32_t*, CUtensorMapInterleave, CUtensorMapSwizzle,
                             CUtensorMapL2promotion, CUtensorMapFloatOOBfill);

static void map2d(EncodeFn enc, CUtensorMap* m, const void* p, int rows, int cols, int box_rows) {
    cuuint64_t dim[2] = {(cuuint64_t)cols, (cuuint64_t)rows}, str[1] = {(cuuint64_t)cols * 2};
    cuuint32_t box[2] = {64, (cuuint32_t)box_rows}, es[2] = {1, 1};
    enc(m, CU_TENSOR_MAP_DATA_TYPE_BFLOAT16, 2, (void*)p, dim, str, box, es, CU_TENSOR_MAP_INTERLEAVE_NONE,
        CU_TENSOR_MAP_SWIZZLE_128B, CU_TENSOR_MAP_L2_PROMOTION_L2_256B, CU_TENSOR_MAP_FLOAT_OOB_FILL_NONE);
}
static void map3d(EncodeFn enc, CUtensorMap* m, const void* p, int rows, int cols, int box_rows, int nblk) {
    cuuint64_t dim[3] = {64, (cuuint64_t)rows, (cuuint64_t)cols / 64}, str[2] = {(cuuint64_t)cols * 2, 128};
    cuuint32_t box[3] = {64, (cuuint32_t)box_rows, (cuuint32_t)nblk}, es[3] = {1, 1, 1};
    enc(m, CU_TENSOR_MAP_DATA_TYPE_BFLOAT16, 3, (void*)p, dim, str, box, es, CU_TENSOR_MAP_INTERLEAVE_NONE,
        CU_TENSOR_MAP_SWIZZLE_128B, CU_TENSOR_MAP_L2_PROMOTION_L2_256B, CU_TENSOR_MAP_FLOAT_OOB_FILL_NONE);
}

#define USE_PDL 1

extern "C" void kernel_launch(void* const* d_in, const int* in_sizes, int n_in, void* d_out, int out_size) {
    const bf16 *x = (const bf16*)d_in[0], *mem0 = (const bf16*)d_in[1], *Wq = (const bf16*)d_in[2], *Wk = (const bf16*)d_in[3];
    const bf16 *Wv = (const bf16*)d_in[4], *Wo = (const bf16*)d_in[5];
    const bf16 *u = (const bf16*)d_in[7], *Are = (const bf16*)d_in[8], *Aim = (const bf16*)d_in[9], *Bre = (const bf16*)d_in[10];
    const bf16 *Bim = (const bf16*)d_in[11], *Cre = (const bf16*)d_in[12], *Cim = (const bf16*)d_in[13];
    const bf16 *logdt = (const bf16*)d_in[14], *Dsk = (const bf16*)d_in[15];
    bf16* out = (bf16*)d_out;

    void* fn = nullptr;
    cudaDriverEntryPointQueryResult qr;
    cudaGetDriverEntryPoint("cuTensorMapEncodeTiled", &fn, cudaEnableDefault, &qr);
    EncodeFn enc = (EncodeFn)fn;
    void *kv, *kvm, *o;
    cudaGetSymbolAddress(&kv, g_kv);
    cudaGetSymbolAddress(&kvm, g_kvm);
    cudaGetSymbolAddress(&o, g_o);
    CUtensorMap mx, mwq, mwk, mwv, mwo, mkv2, mkv4, mkvm, mo;
    map2d(enc, &mx, x, SEQ, DM, 128);
    map2d(enc, &mo, o, SEQ, HD, 128);
    map3d(enc, &mwq, Wq, DM, HD, 64, 4);
    map3d(enc, &mwk, Wk, DM, HD, 64, 4);
    map3d(enc, &mwv, Wv, DM, HD, 64, 4);
    map3d(enc, &mwo, Wo, HD, DM, 64, WO_BN / 64);
    map3d(enc, &mkv2, kv, SEQ, 8192, 32, 2);
    map3d(enc, &mkv4, kv, SEQ, 8192, 32, 4);
    map3d(enc, &mkvm, kvm, NSEG * 8, 8192, 8, 4);
    cudaFuncSetAttribute(k_kv, cudaFuncAttributeMaxDynamicSharedMemorySize, GEMM_SMEM);
    cudaFuncSetAttribute(k_bg, cudaFuncAttributeMaxDynamicSharedMemorySize, GEMM_SMEM);
    cudaFuncSetAttribute(k_chain, cudaFuncAttributeMaxDynamicSharedMemorySize, CHAIN_SMEM);
    cudaFuncSetAttribute(k_s4, cudaFuncAttributeMaxDynamicSharedMemorySize, S4_SMEM);

    cudaStream_t st = cudaStreamPerThread;
    k_kv<<<132, 384, GEMM_SMEM, st>>>(mx, mwk, mwv, Wq, Wo);
    k_chain<<<96, 256, CHAIN_SMEM, st>>>(mem0, Wq, Wk, Wv, Wo, mkv2);
    cudaLaunchAttribute pdl[1];
    pdl[0].id = cudaLaunchAttributeProgrammaticStreamSerialization;
    pdl[0].val.programmaticStreamSerializationAllowed = 1;
    cudaLaunchConfig_t cfg = {};
    cfg.stream = st; cfg.attrs = pdl; cfg.numAttrs = USE_PDL;
    cfg.gridDim = dim3(64); cfg.blockDim = dim3(512); cfg.dynamicSmemBytes = S4_SMEM;
    cudaLaunchKernelEx(&cfg, k_s4, u, Are, Aim, Bre, Bim, Cre, Cim, logdt, Dsk, out);
    cfg.gridDim = dim3(BG_ITEMS); cfg.blockDim = dim3(384); cfg.dynamicSmemBytes = GEMM_SMEM;
    cudaLaunchKernelEx(&cfg, k_bg, mx, mwq, mkv4, mkvm, mo, mwo, out);
}
```

```cpp
#include <cuda_runtime.h>
#include <cuda_bf16.h>
#include <cuda.h>
#include <stdint.h>

typedef __nv_bfloat16 bf16;

constexpr int SEQ = 2048, DM = 1024, HD = 4096, NSEG = 64;

__device__ __align__(1024) bf16 g_kv[(size_t)SEQ * 8192];
__device__ __align__(1024) bf16 g_kvm[(size_t)NSEG * 8 * 8192];
__device__ __align__(1024) bf16 g_o[(size_t)SEQ * HD];
__device__ __align__(1024) uint2 g_memx[NSEG * 64 * 32];
__device__ __align__(1024) uint2 g_part[64 * 32 * 32];
__device__ __align__(1024) uint32_t g_flag[256];

#define TL(kern, slot)

__device__ __forceinline__ uint32_t smem_u32(const void* p) { return (uint32_t)__cvta_generic_to_shared(p); }
__device__ __forceinline__ void mbar_init(uint32_t bar, uint32_t cnt) {
    asm volatile("mbarrier.init.shared::cta.b64 [%0], %1;" ::"r"(bar), "r"(cnt) : "memory");
}
__device__ __forceinline__ void mbar_expect_tx(uint32_t bar, uint32_t bytes) {
    asm volatile("mbarrier.arrive.expect_tx.shared::cta.b64 _, [%0], %1;" ::"r"(bar), "r"(bytes) : "memory");
}
__device__ __forceinline__ void mbar_arrive(uint32_t bar) {
    asm volatile("mbarrier.arrive.shared::cta.b64 _, [%0];" ::"r"(bar) : "memory");
}
__device__ __forceinline__ bool mbar_try(uint32_t bar, uint32_t parity) {
    uint32_t ok;
    asm volatile("{\n.reg .pred p;\nmbarrier.try_wait.parity.shared::cta.b64 p, [%1], %2;\nselp.u32 %0, 1, 0, p;\n}"
                 : "=r"(ok) : "r"(bar), "r"(parity) : "memory");
    return ok;
}
constexpr int SPIN_LIMIT = 1 << 20;
__device__ __forceinline__ void mbar_wait(uint32_t bar, uint32_t parity) {
    int n = 0;
    while (!mbar_try(bar, parity)) { if (++n > SPIN_LIMIT) __trap(); }
}
__device__ __forceinline__ void mbar_wait_u(uint32_t bar, uint32_t parity) {
    asm volatile("{\n.reg .pred p;\n.reg .u32 n;\n"
                 "mbarrier.try_wait.parity.shared::cta.b64 p, [%0], %1;\n@p bra.uni DONE;\nmov.u32 n, 0;\n"
                 "AGAIN:\nmbarrier.try_wait.parity.shared::cta.b64 p, [%0], %1;\n@p bra.uni DONE;\n"
                 "add.u32 n, n, 1;\nsetp.lt.u32 p, n, 0x100000;\n@p bra.uni AGAIN;\ntrap;\nDONE:\n}"
                 ::"r"(bar), "r"(parity) : "memory");
}
__device__ __forceinline__ void tma2d(uint32_t dst, const CUtensorMap* m, int c0, int c1, uint32_t bar) {
    asm volatile("cp.async.bulk.tensor.2d.shared::cluster.global.mbarrier::complete_tx::bytes [%0], [%1, {%3, %4}], [%2];"
                 ::"r"(dst), "l"(m), "r"(bar), "r"(c0), "r"(c1) : "memory");
}
__device__ __forceinline__ void tma3d(uint32_t dst, const CUtensorMap* m, int c0, int c1, int c2, uint32_t bar) {
    asm volatile("cp.async.bulk.tensor.3d.shared::cluster.global.mbarrier::complete_tx::bytes [%0], [%1, {%3, %4, %5}], [%2];"
                 ::"r"(dst), "l"(m), "r"(bar), "r"(c0), "r"(c1), "r"(c2) : "memory");
}
__device__ __forceinline__ uint32_t pack2(float lo, float hi) {
    uint32_t r;
    asm("cvt.rn.bf16x2.f32 %0, %1, %2;" : "=r"(r) : "f"(hi), "f"(lo));
    return r;
}
__device__ __forceinline__ float bf_lo(uint32_t v) { return __uint_as_float(v << 16); }
__device__ __forceinline__ float bf_hi(uint32_t v) { return __uint_as_float(v & 0xffff0000u); }
__device__ __forceinline__ float bf_round(float x) { return bf_lo(pack2(x, 0.f)); }
__device__ __forceinline__ float ex2(float x) { float y; asm("ex2.approx.ftz.f32 %0, %1;" : "=f"(y) : "f"(x)); return y; }
__device__ __forceinline__ void mma16816(float (&c)[4], uint32_t a0, uint32_t a1, uint32_t a2, uint32_t a3, uint32_t b0, uint32_t b1) {
    asm volatile("mma.sync.aligned.m16n8k16.row.col.f32.bf16.bf16.f32 {%0,%1,%2,%3}, {%4,%5,%6,%7}, {%8,%9}, {%0,%1,%2,%3};"
                 : "+f"(c[0]), "+f"(c[1]), "+f"(c[2]), "+f"(c[3]) : "r"(a0), "r"(a1), "r"(a2), "r"(a3), "r"(b0), "r"(b1));
}
__device__ __forceinline__ void mma1688(float (&c)[4], uint32_t a0, uint32_t a1, uint32_t b0) {
    asm volatile("mma.sync.aligned.m16n8k8.row.col.f32.bf16.bf16.f32 {%0,%1,%2,%3}, {%4,%5}, {%6}, {%0,%1,%2,%3};"
                 : "+f"(c[0]), "+f"(c[1]), "+f"(c[2]), "+f"(c[3]) : "r"(a0), "r"(a1), "r"(b0));
}
__device__ __forceinline__ void ldsm4(uint32_t (&r)[4], uint32_t a) {
    asm volatile("ldmatrix.sync.aligned.m8n8.x4.shared.b16 {%0,%1,%2,%3}, [%4];"
                 : "=r"(r[0]), "=r"(r[1]), "=r"(r[2]), "=r"(r[3]) : "r"(a) : "memory");
}
__device__ __forceinline__ void ldsm4t(uint32_t (&r)[4], uint32_t a) {
    asm volatile("ldmatrix.sync.aligned.m8n8.x4.trans.shared.b16 {%0,%1,%2,%3}, [%4];"
                 : "=r"(r[0]), "=r"(r[1]), "=r"(r[2]), "=r"(r[3]) : "r"(a) : "memory");
}
__device__ __forceinline__ void ldsm2t(uint32_t& r0, uint32_t& r1, uint32_t a) {
    asm volatile("ldmatrix.sync.aligned.m8n8.x2.trans.shared.b16 {%0,%1}, [%2];" : "=r"(r0), "=r"(r1) : "r"(a) : "memory");
}
__device__ __forceinline__ void stsm4t(uint32_t a, uint32_t r0, uint32_t r1, uint32_t r2, uint32_t r3) {
    asm volatile("stmatrix.sync.aligned.m8n8.x4.trans.shared.b16 [%0], {%1,%2,%3,%4};"
                 ::"r"(a), "r"(r0), "r"(r1), "r"(r2), "r"(r3) : "memory");
}
__device__ __forceinline__ void lds128(uint32_t (&r)[4], uint32_t a) {
    asm volatile("ld.shared.v4.u32 {%0,%1,%2,%3}, [%4];" : "=r"(r[0]), "=r"(r[1]), "=r"(r[2]), "=r"(r[3]) : "r"(a) : "memory");
}
__device__ __forceinline__ float4 lds128f(uint32_t a) {
    float4 v;
    asm volatile("ld.shared.v4.f32 {%0,%1,%2,%3}, [%4];" : "=f"(v.x), "=f"(v.y), "=f"(v.z), "=f"(v.w) : "r"(a) : "memory");
    return v;
}
__device__ __forceinline__ float2 lds64f(uint32_t a) {
    float2 v;
    asm volatile("ld.shared.v2.f32 {%0,%1}, [%2];" : "=f"(v.x), "=f"(v.y) : "r"(a) : "memory");
    return v;
}
__device__ __forceinline__ uint32_t lds32(uint32_t a) {
    uint32_t v;
    asm volatile("ld.shared.u32 %0, [%1];" : "=r"(v) : "r"(a) : "memory");
    return v;
}
__device__ __forceinline__ void sts128(uint32_t a, uint32_t r0, uint32_t r1, uint32_t r2, uint32_t r3) {
    asm volatile("st.shared.v4.u32 [%0], {%1,%2,%3,%4};" ::"r"(a), "r"(r0), "r"(r1), "r"(r2), "r"(r3) : "memory");
}
__device__ __forceinline__ void sts128f(uint32_t a, float r0, float r1, float r2, float r3) {
    asm volatile("st.shared.v4.f32 [%0], {%1,%2,%3,%4};" ::"r"(a), "f"(r0), "f"(r1), "f"(r2), "f"(r3) : "memory");
}
__device__ __forceinline__ void sts64(uint32_t a, uint32_t r0, uint32_t r1) {
    asm volatile("st.shared.v2.u32 [%0], {%1,%2};" ::"r"(a), "r"(r0), "r"(r1) : "memory");
}
__device__ __forceinline__ void sts64f(uint32_t a, float r0, float r1) {
    asm volatile("st.shared.v2.f32 [%0], {%1,%2};" ::"r"(a), "f"(r0), "f"(r1) : "memory");
}
__device__ __forceinline__ void sts32f(uint32_t a, float r0) {
    asm volatile("st.shared.f32 [%0], %1;" ::"r"(a), "f"(r0) : "memory");
}
__device__ __forceinline__ uint2 ld_rlx64(const uint2* p) {
    uint2 v;
    asm volatile("{\n.reg .b64 t;\nld.relaxed.gpu.global.b64 t, [%2];\nmov.b64 {%0,%1}, t;\n}" : "=r"(v.x), "=r"(v.y) : "l"(p) : "memory");
    return v;
}
__device__ __forceinline__ void st_rlx64(uint2* p, uint32_t x, uint32_t y) {
    asm volatile("{\n.reg .b64 t;\nmov.b64 t, {%1,%2};\nst.relaxed.gpu.global.b64 [%0], t;\n}" ::"l"(p), "r"(x), "r"(y) : "memory");
}
__device__ __forceinline__ uint32_t ld_acq32(const uint32_t* p) {
    uint32_t v;
    asm volatile("ld.acquire.gpu.global.u32 %0, [%1];" : "=r"(v) : "l"(p) : "memory");
    return v;
}
__device__ __forceinline__ void wait_flag(const uint32_t* p, uint32_t need) {
    int n = 0;
    while (ld_acq32(p) < need) { __nanosleep(200); if (++n > SPIN_LIMIT) __trap(); }
}
__device__ __forceinline__ void bar_sync(int id, int n) { asm volatile("bar.sync %0, %1;" ::"r"(id), "r"(n) : "memory"); }
__device__ __forceinline__ void wg_fence() { asm volatile("wgmma.fence.sync.aligned;" ::: "memory"); }
__device__ __forceinline__ void wg_commit() { asm volatile("wgmma.commit_group.sync.aligned;" ::: "memory"); }
template <int N> __device__ __forceinline__ void wg_wait() { asm volatile("wgmma.wait_group.sync.aligned %0;" ::"n"(N) : "memory"); }
__device__ __forceinline__ uint64_t desc_sw128(uint32_t addr, uint32_t lbo, uint32_t sbo) {
    return (uint64_t)((addr & 0x3FFFF) >> 4) | ((uint64_t)(lbo >> 4) << 16) | ((uint64_t)(sbo >> 4) << 32) | (1ull << 62);
}
__device__ __forceinline__ void quad_transpose(uint32_t& r0, uint32_t& r1, uint32_t& r2, uint32_t& r3, int t) {
    const bool o = t & 1, h = t & 2;
    uint32_t s0 = __shfl_xor_sync(~0u, o ? r0 : r1, 1), s1 = __shfl_xor_sync(~0u, o ? r2 : r3, 1);
    uint32_t a0 = o ? s0 : r0, a1 = o ? r1 : s0, a2 = o ? s1 : r2, a3 = o ? r3 : s1;
    s0 = __shfl_xor_sync(~0u, h ? a0 : a2, 2); s1 = __shfl_xor_sync(~0u, h ? a1 : a3, 2);
    r0 = h ? s0 : a0; r1 = h ? s1 : a1; r2 = h ? a2 : s0; r3 = h ? a3 : s1;
}

__device__ __forceinline__ void wgmma_n256(float (&d)[128], uint64_t da, uint64_t db, int sd) {
    asm volatile("{\n.reg .pred p;\nsetp.ne.b32 p, %130, 0;\n"
        "wgmma.mma_async.sync.aligned.m64n256k16.f32.bf16.bf16 "
        "{%0,%1,%2,%3,%4,%5,%6,%7,%8,%9,%10,%11,%12,%13,%14,%15,"
        "%16,%17,%18,%19,%20,%21,%22,%23,%24,%25,%26,%27,%28,%29,%30,%31,"
        "%32,%33,%34,%35,%36,%37,%38,%39,%40,%41,%42,%43,%44,%45,%46,%47,"
        "%48,%49,%50,%51,%52,%53,%54,%55,%56,%57,%58,%59,%60,%61,%62,%63,"
        "%64,%65,%66,%67,%68,%69,%70,%71,%72,%73,%74,%75,%76,%77,%78,%79,"
        "%80,%81,%82,%83,%84,%85,%86,%87,%88,%89,%90,%91,%92,%93,%94,%95,"
        "%96,%97,%98,%99,%100,%101,%102,%103,%104,%105,%106,%107,%108,%109,%110,%111,"
        "%112,%113,%114,%115,%116,%117,%118,%119,%120,%121,%122,%123,%124,%125,%126,%127}, %128, %129, p, 1, 1, 0, 1;\n}\n"
        : "+f"(d[0]), "+f"(d[1]), "+f"(d[2]), "+f"(d[3]), "+f"(d[4]), "+f"(d[5]), "+f"(d[6]), "+f"(d[7]),
          "+f"(d[8]), "+f"(d[9]), "+f"(d[10]), "+f"(d[11]), "+f"(d[12]), "+f"(d[13]), "+f"(d[14]), "+f"(d[15]),
          "+f"(d[16]), "+f"(d[17]), "+f"(d[18]), "+f"(d[19]), "+f"(d[20]), "+f"(d[21]), "+f"(d[22]), "+f"(d[23]),
          "+f"(d[24]), "+f"(d[25]), "+f"(d[26]), "+f"(d[27]), "+f"(d[28]), "+f"(d[29]), "+f"(d[30]), "+f"(d[31]),
          "+f"(d[32]), "+f"(d[33]), "+f"(d[34]), "+f"(d[35]), "+f"(d[36]), "+f"(d[37]), "+f"(d[38]), "+f"(d[39]),
          "+f"(d[40]), "+f"(d[41]), "+f"(d[42]), "+f"(d[43]), "+f"(d[44]), "+f"(d[45]), "+f"(d[46]), "+f"(d[47]),
          "+f"(d[48]), "+f"(d[49]), "+f"(d[50]), "+f"(d[51]), "+f"(d[52]), "+f"(d[53]), "+f"(d[54]), "+f"(d[55]),
          "+f"(d[56]), "+f"(d[57]), "+f"(d[58]), "+f"(d[59]), "+f"(d[60]), "+f"(d[61]), "+f"(d[62]), "+f"(d[63]),
          "+f"(d[64]), "+f"(d[65]), "+f"(d[66]), "+f"(d[67]), "+f"(d[68]), "+f"(d[69]), "+f"(d[70]), "+f"(d[71]),
          "+f"(d[72]), "+f"(d[73]), "+f"(d[74]), "+f"(d[75]), "+f"(d[76]), "+f"(d[77]), "+f"(d[78]), "+f"(d[79]),
          "+f"(d[80]), "+f"(d[81]), "+f"(d[82]), "+f"(d[83]), "+f"(d[84]), "+f"(d[85]), "+f"(d[86]), "+f"(d[87]),
          "+f"(d[88]), "+f"(d[89]), "+f"(d[90]), "+f"(d[91]), "+f"(d[92]), "+f"(d[93]), "+f"(d[94]), "+f"(d[95]),
          "+f"(d[96]), "+f"(d[97]), "+f"(d[98]), "+f"(d[99]), "+f"(d[100]), "+f"(d[101]), "+f"(d[102]), "+f"(d[103]),
          "+f"(d[104]), "+f"(d[105]), "+f"(d[106]), "+f"(d[107]), "+f"(d[108]), "+f"(d[109]), "+f"(d[110]), "+f"(d[111]),
          "+f"(d[112]), "+f"(d[113]), "+f"(d[114]), "+f"(d[115]), "+f"(d[116]), "+f"(d[117]), "+f"(d[118]), "+f"(d[119]),
          "+f"(d[120]), "+f"(d[121]), "+f"(d[122]), "+f"(d[123]), "+f"(d[124]), "+f"(d[125]), "+f"(d[126]), "+f"(d[127])
        : "l"(da), "l"(db), "r"(sd));
}

__device__ __forceinline__ void wgmma_n128(float (&d)[64], uint64_t da, uint64_t db, int sd) {
    asm volatile("{\n.reg .pred p;\nsetp.ne.b32 p, %66, 0;\n"
        "wgmma.mma_async.sync.aligned.m64n128k16.f32.bf16.bf16 "
        "{%0,%1,%2,%3,%4,%5,%6,%7,%8,%9,%10,%11,%12,%13,%14,%15,"
        "%16,%17,%18,%19,%20,%21,%22,%23,%24,%25,%26,%27,%28,%29,%30,%31,"
        "%32,%33,%34,%35,%36,%37,%38,%39,%40,%41,%42,%43,%44,%45,%46,%47,"
        "%48,%49,%50,%51,%52,%53,%54,%55,%56,%57,%58,%59,%60,%61,%62,%63}, %64, %65, p, 1, 1, 0, 1;\n}\n"
        : "+f"(d[0]), "+f"(d[1]), "+f"(d[2]), "+f"(d[3]), "+f"(d[4]), "+f"(d[5]), "+f"(d[6]), "+f"(d[7]),
          "+f"(d[8]), "+f"(d[9]), "+f"(d[10]), "+f"(d[11]), "+f"(d[12]), "+f"(d[13]), "+f"(d[14]), "+f"(d[15]),
          "+f"(d[16]), "+f"(d[17]), "+f"(d[18]), "+f"(d[19]), "+f"(d[20]), "+f"(d[21]), "+f"(d[22]), "+f"(d[23]),
          "+f"(d[24]), "+f"(d[25]), "+f"(d[26]), "+f"(d[27]), "+f"(d[28]), "+f"(d[29]), "+f"(d[30]), "+f"(d[31]),
          "+f"(d[32]), "+f"(d[33]), "+f"(d[34]), "+f"(d[35]), "+f"(d[36]), "+f"(d[37]), "+f"(d[38]), "+f"(d[39]),
          "+f"(d[40]), "+f"(d[41]), "+f"(d[42]), "+f"(d[43]), "+f"(d[44]), "+f"(d[45]), "+f"(d[46]), "+f"(d[47]),
          "+f"(d[48]), "+f"(d[49]), "+f"(d[50]), "+f"(d[51]), "+f"(d[52]), "+f"(d[53]), "+f"(d[54]), "+f"(d[55]),
          "+f"(d[56]), "+f"(d[57]), "+f"(d[58]), "+f"(d[59]), "+f"(d[60]), "+f"(d[61]), "+f"(d[62]), "+f"(d[63])
        : "l"(da), "l"(db), "r"(sd));
}

__device__ __forceinline__ void wgmma_n64(float (&d)[32], uint64_t da, uint64_t db, int sd) {
    asm volatile("{\n.reg .pred p;\nsetp.ne.b32 p, %34, 0;\n"
        "wgmma.mma_async.sync.aligned.m64n64k16.f32.bf16.bf16 "
        "{%0,%1,%2,%3,%4,%5,%6,%7,%8,%9,%10,%11,%12,%13,%14,%15,"
        "%16,%17,%18,%19,%20,%21,%22,%23,%24,%25,%26,%27,%28,%29,%30,%31}, %32, %33, p, 1, 1, 0, 1;\n}\n"
        : "+f"(d[0]), "+f"(d[1]), "+f"(d[2]), "+f"(d[3]), "+f"(d[4]), "+f"(d[5]), "+f"(d[6]), "+f"(d[7]),
          "+f"(d[8]), "+f"(d[9]), "+f"(d[10]), "+f"(d[11]), "+f"(d[12]), "+f"(d[13]), "+f"(d[14]), "+f"(d[15]),
          "+f"(d[16]), "+f"(d[17]), "+f"(d[18]), "+f"(d[19]), "+f"(d[20]), "+f"(d[21]), "+f"(d[22]), "+f"(d[23]),
          "+f"(d[24]), "+f"(d[25]), "+f"(d[26]), "+f"(d[27]), "+f"(d[28]), "+f"(d[29]), "+f"(d[30]), "+f"(d[31])
        : "l"(da), "l"(db), "r"(sd));
}

constexpr int STAGE_BYTES = 49152, NSTAGE = 4;
constexpr int GEMM_SMEM = NSTAGE * STAGE_BYTES + 128;

struct GemmSmem { uint32_t st, full, empty; };
__device__ __forceinline__ GemmSmem gemm_setup(uint8_t* raw) {
    GemmSmem g;
    g.st = smem_u32(raw);
    if (g.st & 1023) __trap();
    g.full = g.st + NSTAGE * STAGE_BYTES; g.empty = g.full + 64;
    if (threadIdx.x == 0) {
        for (int s = 0; s < NSTAGE; s++) { mbar_init(g.full + 8 * s, 1); mbar_init(g.empty + 8 * s, 2); }
        asm volatile("fence.mbarrier_init.release.cluster;" ::: "memory");
        asm volatile("fence.proxy.async.shared::cta;" ::: "memory");
    }
    __syncthreads();
    return g;
}
__device__ __forceinline__ void mbar_arrive_one(uint32_t bar, uint32_t who) {
    asm volatile("{\n.reg .pred p;\nsetp.eq.u32 p, %1, 0;\n@p mbarrier.arrive.shared::cta.b64 _, [%0];\n}" ::"r"(bar), "r"(who) : "memory");
}
template <int BM, int BN, int KPS, typename ACC>
__device__ __forceinline__ void gemm_stage(ACC& acc, uint32_t stage, int wg, bool first) {
    const uint64_t da = desc_sw128(stage + wg * 8192, 16, 1024);
    const uint64_t db = desc_sw128(stage + KPS * BM * 128, 8192, 1024);
    wg_fence();
#pragma unroll
    for (int k = 0; k < 4 * KPS; k++) {
        const uint64_t a = da + (k >> 2) * (BM * 8) + (k & 3) * 2, b = db + k * 128;
        if constexpr (BN == 256) wgmma_n256(acc, a, b, first && k == 0 ? 0 : 1);
        else if constexpr (BN == 128) wgmma_n128(acc, a, b, first && k == 0 ? 0 : 1);
        else wgmma_n64(acc, a, b, first && k == 0 ? 0 : 1);
    }
    wg_commit();
}

__device__ __forceinline__ void kv_store_unit(const uint32_t (&pk)[64], int u, bf16* dst, int t) {
    const int G = (u >> 2) * 2 + (u & 1), hh = (u >> 1) & 1;
    uint32_t r0 = pk[(4 * G + 0) * 2 + hh], r1 = pk[(4 * G + 1) * 2 + hh], r2 = pk[(4 * G + 2) * 2 + hh], r3 = pk[(4 * G + 3) * 2 + hh];
    quad_transpose(r0, r1, r2, r3, t);
#define KVST ".cs"
    asm volatile("st.global" KVST ".v4.u32 [%0], {%1,%2,%3,%4};" ::"l"(dst + (size_t)hh * 8 * 8192 + G * 32), "r"(r0), "r"(r1), "r"(r2), "r"(r3) : "memory");
}

__global__ void __launch_bounds__(384, 1)
k_kv(const __grid_constant__ CUtensorMap mx, const __grid_constant__ CUtensorMap mwk, const __grid_constant__ CUtensorMap mwv,
     const bf16* __restrict__ Wq, const bf16* __restrict__ Wo) {
    extern __shared__ __align__(1024) uint8_t smem_gemm[];
    const int c = blockIdx.x;
    if (threadIdx.x == 0) TL(0, 0);
    if (c >= 128) {
        const int i0 = (c - 128) * 384 + threadIdx.x;
        const uint4 ones = make_uint4(~0u, ~0u, ~0u, ~0u);
        for (int i = i0; i < NSEG * 64 * 32 / 2; i += 4 * 384) reinterpret_cast<uint4*>(g_memx)[i] = ones;
        for (int i = i0; i < 64 * 32 * 32 / 2; i += 4 * 384) reinterpret_cast<uint4*>(g_part)[i] = ones;
        if (i0 < 256) g_flag[i0] = 0;
        if (threadIdx.x == 0) {
            const char* p = (const char*)(c < 130 ? Wq : Wo) + (size_t)(c & 1) * (4 << 20);
            for (int i = 0; i < 256; i++) {
                asm volatile("cp.async.bulk.prefetch.L2.global [%0], 16384;" ::"l"(p + i * 16384) : "memory");
                __nanosleep(40);
            }
        }
        if (threadIdx.x == 0) TL(0, 1);
        return;
    }
    GemmSmem g = gemm_setup(smem_gemm);
    const int m0 = (c & 15) * 128, nb0 = c >> 4;
    const int wg = __shfl_sync(~0u, threadIdx.x >> 7, 0);
    if (wg == 0) {
        asm volatile("setmaxnreg.dec.sync.aligned.u32 40;");
        if (threadIdx.x == 0) {
            for (int it = 0; it < 64; it++) {
                const int s = it & 3, tile = it >> 4, kb = it & 15;
                mbar_wait(g.empty + 8 * s, ((it >> 2) & 1) ^ 1);
                mbar_expect_tx(g.full + 8 * s, STAGE_BYTES);
                const int nb = nb0 + 8 * tile;
                tma2d(g.st + s * STAGE_BYTES, &mx, kb * 64, m0, g.full + 8 * s);
                tma3d(g.st + s * STAGE_BYTES + 16384, nb < 16 ? &mwk : &mwv, 0, kb * 64, (nb & 15) * 4, g.full + 8 * s);
            }
        }
    } else {
        asm volatile("setmaxnreg.inc.sync.aligned.u32 232;");
        const int cw = wg - 1, lane = threadIdx.x & 31, t = lane & 3;
        const int row = m0 + cw * 64 + ((threadIdx.x >> 5) & 3) * 16 + (lane >> 2);
        bf16* dst = g_kv + (size_t)row * 8192 + nb0 * 256 + t * 8;
        float acc[128];
        uint32_t pk[64];
#pragma unroll 1
        for (int tile = 0; tile < 4; tile++) {
#pragma unroll
            for (int kb = 0; kb < 16; kb++) {
                mbar_wait_u(g.full + 8 * (kb & 3), (kb >> 2) & 1);
                gemm_stage<128, 256, 1>(acc, g.st + (kb & 3) * STAGE_BYTES, cw, kb == 0);
                if (tile > 0) kv_store_unit(pk, kb, dst + (tile - 1) * 2048, t);
                if (kb > 0) {
                    wg_wait<1>();
                    mbar_arrive_one(g.empty + 8 * ((kb - 1) & 3), threadIdx.x & 127);
                }
            }
            wg_wait<0>();
            mbar_arrive_one(g.empty + 8 * 3, threadIdx.x & 127);
#pragma unroll
            for (int i = 0; i < 64; i++) pk[i] = pack2(acc[2 * i], acc[2 * i + 1]);
        }
        if (threadIdx.x == 128) TL(0, 2);
#pragma unroll
        for (int u = 0; u < 16; u++) kv_store_unit(pk, u, dst + 3 * 2048, t);
        if (threadIdx.x == 128) TL(0, 1);
    }
}

constexpr int NS1 = 30;
#define RB1 4
#define PFC 4
constexpr int C_W1 = 0;
constexpr int C_W2 = C_W1 + 8 * NS1 * 512;
constexpr int C_KV = C_W2 + 14 * 8 * 512;
constexpr int C_RED = C_KV + 16384;
constexpr int C_R3 = C_RED + 64 * 272;
constexpr int C_QKV = C_R3 + 2560;
constexpr int C_SC = C_QKV + 3 * 8 * 272;
constexpr int C_OB = C_SC + 2 * 8 * 52 * 4;
constexpr int C_BAR = C_OB + 8 * 272;
__host__ __device__ constexpr int smem_idx(int ks, int j) {
    return ks == 0 ? j : ks == 1 ? (j < 4 ? 8 + j : -1) : (j < 3 ? 6 + 3 * ks + j : -1);
}
constexpr int CHAIN_SMEM = C_BAR + 64;
#define TS(i)

#define DLY3 3
#define DLY1 16
#define DLY0 8
#define DLYW 3
template <int N> __device__ __forceinline__ uint32_t delayed(uint32_t x, int lane) {
#pragma unroll
    for (int i = 0; i < N; i++) asm volatile("shfl.sync.idx.b32 %0, %0, %1, 31, -1;" : "+r"(x) : "r"(lane) : "memory");
    return x;
}
__device__ __forceinline__ void lds128v(uint32_t (&r)[4], uint32_t a) {
    asm volatile("ld.volatile.shared.v4.u32 {%0,%1,%2,%3}, [%4];" : "=r"(r[0]), "=r"(r[1]), "=r"(r[2]), "=r"(r[3]) : "r"(a) : "memory");
}
__device__ __forceinline__ uint2 lds64(uint32_t a) {
    uint2 v;
    asm volatile("ld.shared.v2.u32 {%0,%1}, [%2];" : "=r"(v.x), "=r"(v.y) : "r"(a) : "memory");
    return v;
}
#define LDQ ".L1::no_allocate"
__device__ __forceinline__ uint4 ldw128(const void* p) {
    uint4 v;
    asm volatile("ld.global.nc" LDQ ".v4.u32 {%0,%1,%2,%3}, [%4];" : "=r"(v.x), "=r"(v.y), "=r"(v.z), "=r"(v.w) : "l"(p));
    return v;
}
__device__ __forceinline__ void fetch8(uint64_t (&d)[8], const void* src) {
#define P8_LD(i) "ld.relaxed.gpu.global.b64 %" #i ", [%8 + " #i " * 256];\n"
    asm volatile(P8_LD(0) P8_LD(1) P8_LD(2) P8_LD(3) P8_LD(4) P8_LD(5) P8_LD(6) P8_LD(7)
                 : "=&l"(d[0]), "=&l"(d[1]), "=&l"(d[2]), "=&l"(d[3]), "=&l"(d[4]), "=&l"(d[5]), "=&l"(d[6]), "=&l"(d[7]) : "l"(src) : "memory");
}
template <bool TAG> __device__ __forceinline__ void settle8(uint2 (&v)[8], uint64_t (&d)[8], const void* src, uint32_t tag) {
#define P8_X(i) "mov.b64 {x" #i ", _}, %" #i ";\n"
#define P8_HEAD "{\n.reg .pred p, q;\n.reg .u32 n, x0, x1, x2, x3, x4, x5, x6, x7, m0, m1;\nmov.u32 n, 0;\nCHECK:\n" \
                P8_X(0) P8_X(1) P8_X(2) P8_X(3) P8_X(4) P8_X(5) P8_X(6) P8_X(7)
#define P8_VOTE "vote.sync.all.pred p, p, -1;\n@p bra.uni DONE;\n"
#define P8_TAIL "add.u32 n, n, 1;\nsetp.lt.u32 p, n, 0x100000;\n@p bra.uni CHECK;\ntrap;\nDONE:\n}"
#define P8_OPS : "+l"(d[0]), "+l"(d[1]), "+l"(d[2]), "+l"(d[3]), "+l"(d[4]), "+l"(d[5]), "+l"(d[6]), "+l"(d[7]) : "l"(src), "r"(tag) : "memory"
#define P8_RT(i) "lop3.b32 m0, x" #i ", %9, 1, 0x28;\nsetp.ne.u32 q, m0, 0;\n@q " P8_LD(i)
#define P8_RS(i) "setp.eq.u32 q, x" #i ", 0xffffffff;\n@q " P8_LD(i)
    if (TAG)
        asm volatile(P8_HEAD "lop3.b32 m0, x0, x1, %9, 0x7e;\nlop3.b32 m1, x2, x3, %9, 0x7e;\nlop3.b32 m0, m0, x4, %9, 0xf6;\n"
                     "lop3.b32 m1, m1, x5, %9, 0xf6;\nlop3.b32 m0, m0, x6, %9, 0xf6;\nlop3.b32 m1, m1, x7, %9, 0xf6;\n"
                     "lop3.b32 m0, m0, m1, 1, 0xa8;\nsetp.eq.u32 p, m0, 0;\n" P8_VOTE
                     P8_RT(0) P8_RT(1) P8_RT(2) P8_RT(3) P8_RT(4) P8_RT(5) P8_RT(6) P8_RT(7) P8_TAIL P8_OPS);
    else
        asm volatile(P8_HEAD "max.u32 m0, x0, x1;\nmax.u32 m0, m0, x2;\nmax.u32 m1, x3, x4;\nmax.u32 m1, m1, x5;\nmax.u32 m0, m0, x6;\n"
                     "max.u32 m0, m0, x7;\nmax.u32 m0, m0, m1;\nsetp.ne.u32 p, m0, 0xffffffff;\n" P8_VOTE
                     P8_RS(0) P8_RS(1) P8_RS(2) P8_RS(3) P8_RS(4) P8_RS(5) P8_RS(6) P8_RS(7) P8_TAIL P8_OPS);
#pragma unroll
    for (int i = 0; i < 8; i++) { v[i].x = (uint32_t)d[i]; v[i].y = (uint32_t)(d[i] >> 32); }
}
__device__ __forceinline__ void sum8(float (&c)[4], const uint2 (&v)[8], uint32_t idn) {
    float d[4] = {0.f, 0.f, 0.f, 0.f};
    c[0] = c[1] = c[2] = c[3] = 0.f;
    mma16816(c, v[0].x, v[0].y, v[1].x, v[1].y, idn, idn);
    mma16816(d, v[2].x, v[2].y, v[3].x, v[3].y, idn, idn);
    mma16816(c, v[4].x, v[4].y, v[5].x, v[5].y, idn, idn);
    mma16816(d, v[6].x, v[6].y, v[7].x, v[7].y, idn, idn);
    c[0] += d[0]; c[1] += d[1]; c[2] += d[2]; c[3] += d[3];
}

__global__ void __cluster_dims__(3, 1, 1) __launch_bounds__(256, 1)
k_chain(const bf16* __restrict__ mem0, const bf16* __restrict__ Wq, const bf16* __restrict__ Wk, const bf16* __restrict__ Wv,
        const bf16* __restrict__ Wo, const __grid_constant__ CUtensorMap mkv) {
    extern __shared__ __align__(1024) uint8_t smem_chain[];
    const uint32_t sb = smem_u32(smem_chain);
    if (sb & 1023) __trap();
    const int w = __shfl_sync(~0u, threadIdx.x >> 5, 0), lane = __shfl_sync(~0u, threadIdx.x & 31, threadIdx.x & 31);
    const int tid = w * 32 + lane, g = lane >> 2, t = lane & 3;
    auto pin = [&](uint32_t x) { return delayed<1>(x, lane); };
    const int h = blockIdx.x / 3, r = blockIdx.x - 3 * h;
    const uint32_t bar_x = sb + C_BAR, bar_kv = sb + C_BAR + 8, bar_go = sb + C_BAR + 16, bar_w = sb + C_BAR + 24;
    asm volatile("griddepcontrol.launch_dependents;");
    const int tbase = r == 0 ? 0 : 1 + 21 * r, ntile = r == 0 ? 22 : 21;
    if (tid == 0) {
        mbar_init(bar_x, 8); mbar_init(bar_kv, 1); mbar_init(bar_go, 1); mbar_init(bar_w, 1);
        asm volatile("fence.mbarrier_init.release.cluster;" ::: "memory");
        asm volatile("fence.proxy.async.shared::cta;" ::: "memory");
        mbar_expect_tx(bar_w, 128 * 32 * ntile);
    }
    __syncthreads();
    asm volatile("barrier.cluster.arrive.relaxed.aligned;" ::: "memory");
    if (tid < 128)
        asm volatile("cp.async.bulk.shared::cluster.global.mbarrier::complete_tx::bytes [%0], [%1], %2, [%3];"
                     ::"r"(sb + C_W1 + tid * 720), "l"(Wo + (size_t)(h * 128 + tid) * DM + tbase * 16), "r"(32 * ntile), "r"(bar_w) : "memory");
    const int tile0 = tbase + 7 - w;
    const bool three = w >= (r == 0 ? 2 : 3);
    const uint32_t wa = pin(sb + tid * 16);
#define W1A(i) (wa + C_W1 + (i) * 4096)
#define W2A(x) (wa + C_W2 + ((x) < 8 ? (x) * 4096 : 32768 - 1024 + ((x) - 8) * 3072))
    uint32_t wo0[8][4], wr[64][4];
    {
        const bf16* W = (r == 0 ? Wq : r == 1 ? Wk : Wv) + (size_t)(128 * w + (lane >> 4)) * HD + h * 128 + 8 * (lane & 15);
        uint4 raw[8][8];
        auto fetch = [&](int ks) {
#pragma unroll
            for (int i = 0; i < 8; i++) raw[ks][i] = ldw128(W + (size_t)(16 * ks + 2 * i) * HD);
        };
        fetch(0); fetch(1); fetch(2); fetch(3);
        mbar_wait_u(bar_w, 0);
        const uint32_t p = sb + C_W1 + ((lane & 7) + (lane >> 4) * 8) * 720 + (7 - w) * 32 + ((lane >> 3) & 1) * 16;
#pragma unroll
        for (int ks = 0; ks < 8; ks++) {
            uint32_t a[4];
            ldsm4t(wo0[ks], p + ks * 16 * 720);
            ldsm4t(a, p + ks * 16 * 720 + 256);
            sts128(W2A(ks), a[0], a[1], a[2], a[3]);
            if (three) { ldsm4t(a, p + ks * 16 * 720 + 512); sts128(W2A(8 + ks), a[0], a[1], a[2], a[3]); }
        }
        __syncthreads();
        const uint32_t stg = sb + C_KV + w * 4096;
        const uint32_t rd = stg + ((lane & 6) + 8 * (lane & 1) + (lane >> 4)) * 256 + ((((lane >> 3) & 1) ^ (lane & 7)) << 4);
#pragma unroll
        for (int ks = 0; ks < 8; ks++) {
#pragma unroll
            for (int i = 0; i < 8; i++)
                sts128(stg + (2 * i + (lane >> 4)) * 256 + (((lane & 15) ^ (((2 * i) & 6) | (i >> 2))) << 4),
                       raw[ks][i].x, raw[ks][i].y, raw[ks][i].z, raw[ks][i].w);
            if (ks < 2) fetch(ks + 4);
            if (ks == 3 || ks == 5) fetch(ks / 2 + 5);
            __syncwarp();
#pragma unroll
            for (int j = 0; j < 8; j++) {
                if (smem_idx(ks, j) >= 0) {
                    uint32_t a[4];
                    ldsm4t(a, rd ^ (j << 5));
                    sts128(W1A(smem_idx(ks, j)), a[0], a[1], a[2], a[3]);
                } else ldsm4t(wr[8 * ks + j], rd ^ (j << 5));
            }
            __syncwarp();
        }
    }
    asm volatile("fence.proxy.async.shared::cta;" ::: "memory");
    __syncthreads();
    if (tid == 0) {
        mbar_expect_tx(bar_kv, 16384);
        tma3d(sb + C_KV, &mkv, 0, 0, 2 * h, bar_kv);
        tma3d(sb + C_KV + 8192, &mkv, 0, 0, 64 + 2 * h, bar_kv);
    }
    asm volatile("barrier.cluster.wait.aligned;" ::: "memory");

    auto publish_kvm = [&](int s) {
        uint32_t v[4];
        lds128(v, sb + C_QKV + (8 + (tid >> 4)) * 272 + (tid & 15) * 16);
        asm volatile("st.global.v4.u32 [%0], {%1,%2,%3,%4};"
                     ::"l"(g_kvm + (size_t)(s * 8 + ((tid >> 4) & 7)) * 8192 + (tid >> 7) * HD + h * 128 + (tid & 15) * 8),
                       "r"(v[0]), "r"(v[1]), "r"(v[2]), "r"(v[3]) : "memory");
        if ((s & 3) == 3) {
            __syncthreads();
            if (w == 7) asm volatile("{\n.reg .pred p;\nsetp.eq.u32 p, %2, 0;\nfence.acq_rel.gpu;\n@p st.relaxed.gpu.global.u32 [%0], %1;\n}"
                                     ::"l"(g_flag + h), "r"(s + 1), "r"(lane) : "memory");
        }
    };
    const float sl2e = 0.08838834764831845f * 1.4426950408889634f;
    const uint32_t idn = pin(g == 2 * t ? 0x00003f80u : g == 2 * t + 1 ? 0x3f800000u : 0u);
    const uint32_t lm = pin(sb + (lane & 7) * 272 + (lane >> 3) * 16);
    const uint32_t sa = pin(sb + C_SC + (w & 1) * (8 * 52 * 4) + (2 * t * 52 + (w < 4 ? 32 : (w & 2) * 8) + g) * 4);
    const uint32_t sr = pin(sb + C_SC + (g * 52 + 8 * t) * 4), sr2 = pin(sb + C_SC + (g * 52 + 32 + 2 * t) * 4);
    uint32_t kva;
    {
        const int pos = (w & 2) * 8 + (lane & 15), row = (pos & 24) + ((pos + (pos >> 2 & 6)) & 7);
        const int key = 4 * (lane & 6) + (((lane & 7) + 2 * (lane >> 4)) & 7);
        kva = pin(w >= 4 ? sb + C_KV + (w & 1) * 4096 + row * 128 + (((lane >> 4) ^ (row & 7)) << 4)
                         : sb + C_KV + 8192 + (w >> 1) * 4096 + key * 128 + ((((w & 1) * 4 + ((lane >> 3) & 1)) ^ (key & 7)) << 4));
    }
    uint32_t buf0[8][4], ring[RB1][4];
    auto stage_w1 = [&]() {
#pragma unroll
        for (int i = 0; i < 8; i++) lds128v(buf0[i], W1A(i));
#pragma unroll
        for (int i = 0; i < RB1; i++) lds128v(ring[i], W1A(8 + i));
    };
    stage_w1();
    if (r > 0 && w < 2) asm volatile("prefetch.global.L2 [%0];" ::"l"(g_memx + ((w + 1) * 64 + 2 * h + r - 1) * 32 + lane) : "memory");
    if (r > 0) asm volatile("prefetch.global.L2 [%0];" ::"l"(g_part + (2 * h + r - 1) * 1024 + tid * 4) : "memory");
    uint2 bm[8];
#pragma unroll
    for (int ks = 0; ks < 8; ks++) {
        const uint32_t* p = (const uint32_t*)(mem0 + g * DM + (8 * w + ks) * 16) + t;
        const uint32_t x = __ldg(p), y = __ldg(p + 4);
        bm[ks] = make_uint2(__byte_perm(x, y, 0x5410), __byte_perm(x, y, 0x7632));
    }
#pragma unroll 1
    for (int s = 0;; s++) {
        TS(1);
        {
            float acc[8][4];
#pragma unroll
            for (int ks = 0; ks < 8; ks++) {
#pragma unroll
                for (int j = 0; j < 8; j++) {
                    const int i = smem_idx(ks, j) - 8;
                    if (ks == 0) {
                        acc[j][0] = acc[j][1] = acc[j][2] = acc[j][3] = 0.f;
                        mma16816(acc[j], buf0[j][0], buf0[j][1], buf0[j][2], buf0[j][3], bm[ks].x, bm[ks].y);
                    } else if (i >= 0) {
                        uint32_t(&a)[4] = ring[i % RB1];
                        mma16816(acc[j], a[0], a[1], a[2], a[3], bm[ks].x, bm[ks].y);
                        if (8 + i + RB1 < NS1) lds128v(a, W1A(8 + i + RB1));
                    } else {
                        const uint32_t(&a)[4] = wr[8 * ks + j];
                        mma16816(acc[j], a[0], a[1], a[2], a[3], bm[ks].x, bm[ks].y);
                    }
                }
            }
#pragma unroll
            for (int c = 0; c < 4; c++)
                stsm4t(lm + C_RED + w * 2176 + c * 64, pack2(acc[2 * c][0], acc[2 * c][1]), pack2(acc[2 * c][2], acc[2 * c][3]),
                       pack2(acc[2 * c + 1][0], acc[2 * c + 1][1]), pack2(acc[2 * c + 1][2], acc[2 * c + 1][3]));
        }
        {
            const uint32_t a = sb + C_RED + w * 272 + lane * 8;
            if (s < NSEG - 1) mbar_wait_u(bar_kv, s & 1);
            TS(2);
            __syncthreads();
            TS(3);
            uint2 v[8];
#pragma unroll
            for (int i = 0; i < 8; i++) v[i] = lds64(a + i * 2176);
            float c[4];
            sum8(c, v, idn);
            const uint32_t p0 = pack2(c[0], c[1]), p1 = pack2(c[2], c[3]);
            const uint32_t dst = sb + C_QKV + (r * 8 + w) * 272 + lane * 8;
#pragma unroll
            for (int i = 1; i < 3; i++) {
                const uint32_t peer = r + i >= 3 ? r + i - 3 : r + i;
                uint32_t rd, rb;
                asm("mapa.shared::cluster.u32 %0, %1, %2;" : "=r"(rd) : "r"(dst), "r"(peer));
                asm("mapa.shared::cluster.u32 %0, %1, %2;" : "=r"(rb) : "r"(bar_x), "r"(peer));
                asm volatile("st.async.weak.shared::cluster.mbarrier::complete_tx::bytes.v2.b32 [%0], {%1,%2}, [%3];"
                             ::"r"(rd), "r"(p0), "r"(p1), "r"(rb) : "memory");
            }
            sts64(dst, p0, p1);
            __syncwarp();
            asm volatile("{\n.reg .pred p;\nsetp.eq.u32 p, %1, 0;\n@p mbarrier.arrive.expect_tx.shared::cta.b64 _, [%0], 512;\n}"
                         ::"r"(bar_x), "r"(lane) : "memory");
        }
        TS(4);
        if (s == NSEG - 1) break;
        uint32_t wb[8][4], wc[8][4];
        const uint32_t po = ((tile0 * 32 + h) * 32 + lane) * 8;
        const uint32_t tag = s & 1;
        auto project = [&](const uint32_t(&wt)[8][4], const uint32_t(&ob)[4][4], int i) {
            float c0[4] = {0.f, 0.f, 0.f, 0.f}, c1[4] = {0.f, 0.f, 0.f, 0.f};
#pragma unroll
            for (int ks = 0; ks < 8; ks++)
                mma16816((ks & 1) ? c1 : c0, wt[ks][0], wt[ks][1], wt[ks][2], wt[ks][3], ob[ks >> 1][(ks & 1) * 2], ob[ks >> 1][(ks & 1) * 2 + 1]);
            st_rlx64((uint2*)((char*)g_part + po) + i * 8192, (pack2(c0[0] + c1[0], c0[2] + c1[2]) & ~1u) | tag, pack2(c0[1] + c1[1], c0[3] + c1[3]));
        };
        if (w >= 4) {
            uint32_t ka[4][4];
#pragma unroll
            for (int ks = 0; ks < 4; ks++) ldsm4(ka[ks], kva ^ (ks << 5));
            const uint32_t qa = lm + C_QKV + (w & 1) * 128;
            TS(5);
            mbar_wait_u(bar_x, s & 1);
            TS(6);
            {
                uint32_t qb[2][4];
                ldsm4(qb[0], qa);
                ldsm4(qb[1], qa + 64);
                float c0[4] = {0.f, 0.f, 0.f, 0.f}, c1[4] = {0.f, 0.f, 0.f, 0.f};
                mma16816(c0, ka[0][0], ka[0][1], ka[0][2], ka[0][3], qb[0][0], qb[0][1]);
                mma16816(c1, ka[1][0], ka[1][1], ka[1][2], ka[1][3], qb[0][2], qb[0][3]);
                mma16816(c0, ka[2][0], ka[2][1], ka[2][2], ka[2][3], qb[1][0], qb[1][1]);
                mma16816(c1, ka[3][0], ka[3][1], ka[3][2], ka[3][3], qb[1][2], qb[1][3]);
                sts32f(sa, c0[0] + c1[0]);
                sts32f(sa + 208, c0[1] + c1[1]);
                sts32f(sa + 32, c0[2] + c1[2]);
                sts32f(sa + 240, c0[3] + c1[3]);
            }
            __syncthreads();
            TS(7);
            if (w == 7 && s + 1 < NSEG - 1) {
                if (lane == 0) {
                    mbar_expect_tx(bar_kv, 16384);
                    tma3d(sb + C_KV, &mkv, 0, (s + 1) * 32, 2 * h, bar_kv);
                    tma3d(sb + C_KV + 8192, &mkv, 0, (s + 1) * 32, 64 + 2 * h, bar_kv);
                }
                __syncwarp();
            }
            const uint32_t wd = delayed<DLYW>(wa, lane);
#pragma unroll
            for (int i = 0; i < 8; i++) lds128(wb[i], wd + C_W2 + i * 4096);
#pragma unroll
            for (int i = 0; i < PFC; i++) lds128(wc[i], wd + C_W2 + 32768 - 1024 + i * 3072);
            TS(8);
            __syncthreads();
            TS(9);
            uint32_t ob[4][4];
#pragma unroll
            for (int i = 0; i < 4; i++) ldsm4(ob[i], lm + C_OB + i * 64);
#pragma unroll
            for (int i = PFC; i < 8; i++) lds128v(wc[i], W2A(8 + i));
            project(wb, ob, 1);
            project(wo0, ob, 0);
            project(wc, ob, 2);
        } else {
            uint32_t va[4][4];
#pragma unroll
            for (int i = 0; i < 4; i++) ldsm4t(va[i], kva ^ (((i >> 1) << 5) | ((i & 1) * 0x240)));
#pragma unroll
            for (int i = 0; i < 8; i++) lds128(wb[i], W2A(i));
            const uint32_t qa = lm + C_QKV + (w & 1) * 128, oa = lm + w * 64;
            TS(5);
            mbar_wait_u(bar_x, s & 1);
            TS(6);
            if (w < 2) {
                uint32_t qb[2][4], km[2][4];
                ldsm4(qb[0], qa);
                ldsm4(km[0], qa + 8 * 272);
                ldsm4(qb[1], qa + 64);
                ldsm4(km[1], qa + 8 * 272 + 64);
                float c0[4] = {0.f, 0.f, 0.f, 0.f}, c1[4] = {0.f, 0.f, 0.f, 0.f};
                mma16816(c0, km[0][0], km[0][1], km[0][2], km[0][3], qb[0][0], qb[0][2]);
                mma16816(c1, km[0][0], km[0][1], km[0][2], km[0][3], qb[0][1], qb[0][3]);
                mma16816(c0, km[1][0], km[1][1], km[1][2], km[1][3], qb[1][0], qb[1][2]);
                mma16816(c1, km[1][0], km[1][1], km[1][2], km[1][3], qb[1][1], qb[1][3]);
                sts32f(sa, c0[0] + c1[2]);
                sts32f(sa + 208, c0[1] + c1[3]);
            }
            __syncthreads();
            TS(7);
            {
                float4 x0 = lds128f(sr), y0 = lds128f(sr + 1664), x1 = lds128f(sr + 16), y1 = lds128f(sr + 1680);
                float2 x2 = lds64f(sr2), y2 = lds64f(sr2 + 1664);
                float p[10] = {x0.x + y0.x, x0.y + y0.y, x0.z + y0.z, x0.w + y0.w, x1.x + y1.x,
                               x1.y + y1.y, x1.z + y1.z, x1.w + y1.w, x2.x + y2.x, x2.y + y2.y};
                float m = fmaxf(fmaxf(fmaxf(p[0], p[1]), fmaxf(p[2], p[3])), fmaxf(fmaxf(fmaxf(p[4], p[5]), fmaxf(p[6], p[7])), fmaxf(p[8], p[9])));
                const float m1 = __shfl_xor_sync(~0u, m, 1), m2 = __shfl_xor_sync(~0u, m, 2), m3 = __shfl_xor_sync(~0u, m, 3);
                uint32_t vm[4];
                ldsm4t(vm, oa + C_QKV + 16 * 272);
                m = fmaxf(fmaxf(m, m1), fmaxf(m2, m3));
                const float ms = m * sl2e;
#pragma unroll
                for (int i = 0; i < 10; i++) p[i] = ex2(fmaf(p[i], sl2e, -ms));
                const uint32_t b0 = pack2(p[0], p[1]), b1 = pack2(p[2], p[3]), b2 = pack2(p[4], p[5]), b3 = pack2(p[6], p[7]), b4 = pack2(p[8], p[9]);
                const uint32_t one = 0x3f803f80u;
                float o0[4] = {0.f, 0.f, 0.f, 0.f}, o1[4] = {0.f, 0.f, 0.f, 0.f}, sm[4] = {0.f, 0.f, 0.f, 0.f};
                mma16816(sm, one, one, one, one, b0, b1);
                mma16816(o0, va[0][0], va[0][1], va[0][2], va[0][3], b0, b1);
                mma16816(o1, va[2][0], va[2][1], va[2][2], va[2][3], b0, b1);
                mma16816(sm, one, one, one, one, b2, b3);
                mma16816(o0, va[1][0], va[1][1], va[1][2], va[1][3], b2, b3);
                mma16816(o1, va[3][0], va[3][1], va[3][2], va[3][3], b2, b3);
                mma1688(sm, one, one, b4);
                mma1688(o0, vm[0], vm[1], b4);
                mma1688(o1, vm[2], vm[3], b4);
                float i0, i1;
                asm("rcp.approx.ftz.f32 %0, %1;" : "=f"(i0) : "f"(sm[0]));
                asm("rcp.approx.ftz.f32 %0, %1;" : "=f"(i1) : "f"(sm[1]));
                stsm4t(oa + C_OB, pack2(o0[0] * i0, o0[1] * i1), pack2(o0[2] * i0, o0[3] * i1),
                       pack2(o1[0] * i0, o1[1] * i1), pack2(o1[2] * i0, o1[3] * i1));
            }
            TS(8);
            __syncthreads();
            TS(9);
            uint32_t ob[4][4];
#pragma unroll
            for (int i = 0; i < 4; i++) ldsm4(ob[i], lm + C_OB + i * 64);
            if (three) {
#pragma unroll
                for (int i = 0; i < 8; i++) lds128v(wc[i], W2A(8 + i));
                project(wb, ob, 1);
                project(wo0, ob, 0);
                project(wc, ob, 2);
            } else {
                project(wb, ob, 1);
                project(wo0, ob, 0);
            }
        }
        TS(10);
        __syncthreads();
        uint32_t eo = (((s + 1) * 64 + 8 * w) * 32 + lane) * 8;
        uint64_t d[8];
        if (r == 0) {
            TS(11); TS(12);
            stage_w1();
            publish_kvm(s);
            mbar_wait_u(bar_go, s & 1);
            eo = delayed<DLY0>(eo, lane);
        } else {
            const int j = 2 * h + r - 1;
            if (w < 4) {
                const char* src = (const char*)g_part + delayed<DLY3>(((j * 32 + 8 * w) * 32 + lane) * 8, lane);
                fetch8(d, src);
                const uint32_t a = pin(sb + C_R3 + w * 640 + t * 160 + g * 8), a2 = pin(sb + C_R3 + g * 80 + t * 16);
                stage_w1();
                uint2 v[8];
                settle8<true>(v, d, src, tag);
                TS(11);
                float c[4];
                sum8(c, v, idn);
                sts64f(a, c[0], c[1]);
                sts64f(a + 80, c[2], c[3]);
                __syncthreads();
                TS(12);
                if (w == 0) {
                    const float4 u0 = lds128f(a2), u1 = lds128f(a2 + 640), u2 = lds128f(a2 + 1280), u3 = lds128f(a2 + 1920);
                    st_rlx64((uint2*)((char*)g_memx + eo) + j * 32, pack2((u0.x + u1.x) + (u2.x + u3.x), (u0.y + u1.y) + (u2.y + u3.y)),
                             pack2((u0.z + u1.z) + (u2.z + u3.z), (u0.w + u1.w) + (u2.w + u3.w)));
                }
            } else {
                if (w == 5 && s + 3 < NSEG)
                    asm volatile("prefetch.global.L2 [%0];" ::"l"(g_memx + ((s + 3) * 64 + j) * 32 + lane) : "memory");
                stage_w1();
                TS(11);
                __syncthreads();
                TS(12);
                if (w == 4 && r == 1)
                    asm volatile("{\n.reg .pred p;\n.reg .u32 a;\nelect.sync _|p, -1;\nmapa.shared::cluster.u32 a, %0, 0;\n"
                                 "@p mbarrier.arrive.relaxed.cluster.shared::cluster.b64 _, [a];\n}" ::"r"(bar_go) : "memory");
            }
            eo = delayed<DLY1>(eo, lane);
        }
        { const int s_ = s; { const int s = s_ + 1; TS(0); } }
        fetch8(d, (const char*)g_memx + eo);
        settle8<false>(bm, d, (const char*)g_memx + eo, 0);
    }
    mbar_wait_u(bar_x, (NSEG - 1) & 1);
    if (r == 0) publish_kvm(NSEG - 1);
    asm volatile("barrier.cluster.arrive.relaxed.aligned;\nbarrier.cluster.wait.aligned;" ::: "memory");
}

constexpr int S4_US = 4368;
constexpr int S4_RS = 8848;
constexpr int S4_KS = 1296;
constexpr int S4_U = 0, S4_R = 16 * S4_US, S4_K = S4_R + 16 * S4_RS;
constexpr int S4_SMEM = S4_K + 16 * S4_KS;
constexpr int S4_SIG = 3104, S4_PK = 2 * S4_SIG;

struct cf { float r, i; };
__device__ __forceinline__ cf cmul(cf a, cf b) { return {fmaf(a.r, b.r, -a.i * b.i), fmaf(a.r, b.i, a.i * b.r)}; }
__device__ __forceinline__ cf cmulc(cf a, cf b) { return {fmaf(a.r, b.r, a.i * b.i), fmaf(a.i, b.r, -a.r * b.i)}; }
__device__ __forceinline__ cf csq(cf a) { const float t = a.r * a.i; return {fmaf(a.r, a.r, -a.i * a.i), t + t}; }
__device__ __forceinline__ cf cexp(float l2, float turns) {
    const float mag = ex2(l2), fr = (turns - rintf(turns)) * 6.283185307179586f;
    return {mag * __cosf(fr), mag * __sinf(fr)};
}
__device__ __forceinline__ void sts32(uint32_t a, uint32_t v) { asm volatile("st.shared.u32 [%0], %1;" ::"r"(a), "r"(v) : "memory"); }
__device__ __forceinline__ uint32_t lds16(uint32_t a) {
    uint32_t v;
    asm volatile("ld.shared.u16 %0, [%1];" : "=r"(v) : "r"(a) : "memory");
    return v;
}

template <int M0, int NQ>
__device__ __forceinline__ void s4_class(float (&acc)[16][4], uint32_t sig, uint32_t taps, int x0) {
    constexpr int D0 = M0 / 8, D1 = M0 == 32 ? 9 : 15;
    uint32_t R[D1 - D0 + 2];
#pragma unroll
    for (int D = D0 - 1; D <= D1; D++) {
        if (D < D0 || 8 * D - 7 >= 2 * M0) { R[D - D0 + 1] = 0; continue; }
        const int m = 8 * D + x0;
        uint32_t lo = lds16(taps + m * (2 * NQ)), hi = lds16(taps + (m - 1) * (2 * NQ));
        if (D == D0) { lo = m >= M0 ? lo : 0; hi = m > M0 ? hi : 0; }
        if (D == 2 * D0) { lo = m < 2 * M0 ? lo : 0; hi = m <= 2 * M0 ? hi : 0; }
        R[D - D0 + 1] = lo | (hi << 16);
    }
#pragma unroll
    for (int J = 0; 2 * J + D0 < 16; J++) {
        uint32_t a[4];
        ldsm4t(a, sig + J * 512);
#pragma unroll
        for (int D = D0; D <= D1; D++)
            if (2 * J + D < 16) mma16816(acc[2 * J + D], a[0], a[1], a[2], a[3], R[D - D0 + 1], R[D - D0]);
    }
}

__global__ void __launch_bounds__(512, 1)
k_s4(const bf16* __restrict__ u, const bf16* __restrict__ Are, const bf16* __restrict__ Aim, const bf16* __restrict__ Bre,
     const bf16* __restrict__ Bim, const bf16* __restrict__ Cre, const bf16* __restrict__ Cim, const bf16* __restrict__ logdt,
     const bf16* __restrict__ Dsk, bf16* __restrict__ out) {
    extern __shared__ __align__(16) uint8_t smem_s4[];
    const uint32_t sb = smem_u32(smem_s4);
    asm volatile("griddepcontrol.launch_dependents;");
    const int tid = threadIdx.x, w = __shfl_sync(~0u, tid >> 5, 0), lane = tid & 31, g = lane >> 2, t = lane & 3;
    if (tid == 0) TL(2, 0);
    const int d0 = blockIdx.x * 16;
    const int d = d0 + (w & 1) + ((w >> 1) & 3) * 4 + (w >> 3) * 2;
    const uint32_t tr_off = (lane & 15), tr_l = (lane >> 4) * 16;
    const uint32_t ur = sb + S4_U + w * S4_US, rs = sb + S4_R + w * S4_RS, kd = sb + S4_K + w * S4_KS;
    if (lane < 16) sts128(ur + lane * 16, 0, 0, 0, 0);
    {
        const int o = d * 128 + lane * 4;
        const uint2 ar = __ldg((const uint2*)(Are + o)), ai = __ldg((const uint2*)(Aim + o)), br = __ldg((const uint2*)(Bre + o));
        const uint2 bi = __ldg((const uint2*)(Bim + o)), cr = __ldg((const uint2*)(Cre + o)), ci = __ldg((const uint2*)(Cim + o));
        const float dt = bf_round(expf(__bfloat162float(logdt[d])));
        const bf16* src = u + (size_t)(w * 128 + g) * DM + d0 + 4 * t;
        float T[5][4];
#pragma unroll
        for (int i = 0; i < 5; i++) T[i][0] = T[i][1] = T[i][2] = T[i][3] = 0.f;
        float klast = 0.f;
        const uint32_t wr_ = rs + lane * 4;
        const uint32_t ra = rs + (lane & 15) * 144 + (lane >> 4) * 16, rb = rs + (16 + (lane & 7)) * 144 + (lane >> 3) * 16;
#pragma unroll 1
        for (int c = 0; c < 4; c++) {
            uint2 v[4];
#pragma unroll
            for (int i = 0; i < 4; i++) v[i] = __ldg((const uint2*)(src + (size_t)(c * 32 + i * 8) * DM));
            auto pick = [&](const uint2& x) { const uint32_t y = c < 2 ? x.x : x.y; return (c & 1) ? bf_hi(y) : bf_lo(y); };
            auto put = [&](int row, cf x) { sts32(wr_ + row * 144, pack2(x.r, x.i)); };
            const float l2 = dt * pick(ar) * 1.4426950408889634f, tu = dt * pick(ai) * 0.15915494309189535f;
            const cf z1 = cexp(l2, tu), z2 = csq(z1), z4 = csq(z2), z8 = csq(z4), z128 = cexp(l2 * 128.f, tu * 128.f);
            cf a = z8;
            sts32(wr_, 0x00003f80u);
            put(1, a);
#pragma unroll
            for (int i = 2; i < 16; i++) { a = cmul(a, z8); put(i, a); }
            cf y = cmul({pick(cr), pick(ci)}, {dt * pick(br), dt * pick(bi)});
            y.i = -y.i;
#pragma unroll
            for (int k = 0; k < 16; k++) {
                const int n = k < 2 ? 8 : k < 4 ? 4 : k < 8 ? 2 : 1;
                const int row = 16 + (k < 2 ? 8 * k : k < 4 ? 8 + 4 * k : k < 8 ? 16 + 2 * k : 24 + k);
                cf x = y;
                put(row, x);
#pragma unroll
                for (int b = 1; b < n; b++) { x = cmulc(x, k < 2 ? z1 : k < 4 ? z2 : z4); put(row + b, x); }
                y = cmulc(y, z128);
            }
            klast += y.r;
            __syncwarp();
#pragma unroll
            for (int kp = 0; kp < 2; kp++) {
                uint32_t A0[4], A1[4];
                ldsm4(A0, ra + kp * 64);
                ldsm4(A1, ra + kp * 64 + 32);
#pragma unroll
                for (int i = 0; i < 5; i++) {
                    uint32_t B[4];
                    ldsm4(B, rb + i * 8 * 144 + kp * 64);
                    mma16816(T[i], A0[0], A0[1], A0[2], A0[3], B[0], B[1]);
                    mma16816(T[i], A1[0], A1[1], A1[2], A1[3], B[2], B[3]);
                }
            }
#pragma unroll
            for (int i = 0; i < 2; i++)
                stsm4t(sb + S4_U + tr_off * S4_US + 256 + (w * 128 + c * 32 + i * 16) * 2 + tr_l, v[2 * i].x, v[2 * i].y, v[2 * i + 1].x, v[2 * i + 1].y);
            __syncwarp();
        }
#pragma unroll
        for (int o2 = 16; o2; o2 >>= 1) klast += __shfl_xor_sync(~0u, klast, o2);
#pragma unroll
        for (int hh = 0; hh < 2; hh++) {
            const int i = g + 8 * hh;
            sts32(kd + (8 * i + 2 * t) * 2, pack2(T[0][2 * hh], T[0][2 * hh + 1]));
            sts32(kd + (128 + 8 * i + 2 * t) * 2, pack2(T[1][2 * hh], T[1][2 * hh + 1]));
            sts32(kd + (256 + 4 * i + 2 * (t & 1) + 64 * (t >> 1)) * 2, pack2(T[2][2 * hh], T[2][2 * hh + 1]));
            sts32(kd + (384 + 2 * i + 32 * t) * 2, pack2(T[3][2 * hh], T[3][2 * hh + 1]));
        }
        asm volatile("stmatrix.sync.aligned.m8n8.x2.trans.shared.b16 [%0], {%1,%2};"
                     ::"r"(kd + 1024 + (lane & 7) * 32 + ((lane >> 3) & 1) * 16), "r"(pack2(T[4][0], T[4][1])), "r"(pack2(T[4][2], T[4][3])) : "memory");
        if (lane == 0) sts32(kd + 1280, pack2(klast, 0.f));
    }
    __syncwarp();
    const uint32_t pk = rs + S4_PK + 64;
    {
#pragma unroll
        for (int i = 0; i < 2; i++) {
            const int x = i * 128 + lane * 4;
            const uint2 c = lds64(kd + x * 2);
            uint32_t p = lds16(kd + x * 2 - 2);
            if (x == 0) p = 0;
            sts128(pk + x * 4, __byte_perm(c.x, p, 0x5410), __byte_perm(c.x, 0, 0x1032), __byte_perm(c.y, c.x, 0x7610), __byte_perm(c.y, 0, 0x1032));
        }
#pragma unroll
        for (int i = 2; i < 4; i++) {
            const int x = i * 128 + lane * 4;
            const uint32_t ab = lds32(kd + 256 + x), c = lds16(kd + 256 + x + 4);
            const uint32_t p = x == 256 ? lds16(kd + 510) : ab;
            sts128(pk + x * 4, __byte_perm(ab, p, 0x5410), __byte_perm(ab, 0, 0x1010), __byte_perm(ab, 0, 0x1032), __byte_perm(c, ab, 0x7610));
        }
        const uint32_t v = lds16(kd + 768), v2 = lds16(kd + 1024);
        if (lane < 24) {
            uint32_t x0 = 0, x1 = 0, x2 = 0, x3 = 0;
            if (lane == 0) { x0 = x1 = x2 = v | (v << 16); x3 = v << 16; }
            if (lane == 12) x3 = v2;
            if (lane == 13) { x0 = v2 | (v2 << 16); x1 = v2 << 16; }
            sts128(lane < 20 ? pk + 2048 + lane * 16 : pk - 64 + (lane - 20) * 16, x0, x1, x2, x3);
        }
        if (lane < 4) sts128(rs + (lane >> 1) * S4_SIG + (lane & 1) * 16, 0, 0, 0, 0);
    }
    __syncthreads();
    float acc[16][4];
#pragma unroll
    for (int i = 0; i < 16; i++) acc[i][0] = acc[i][1] = acc[i][2] = acc[i][3] = 0.f;
    const uint32_t lf = (lane & 7) * 32 + ((lane >> 3) & 1) * 16 + (lane >> 4) * 256;
#pragma unroll
    for (int rg = 3; rg >= 2; rg--) {
#pragma unroll 1
        for (int it = 0; it < (rg == 3 ? 4 : 6); it++) {
            const int n = it * 32 + lane;
            uint32_t x[2][4];
            lds128(x[0], ur + 256 + n * 16 - 16);
            lds128(x[1], ur + 256 + n * 16);
            float e[16], p[15], s[11];
#pragma unroll
            for (int i = 0; i < 8; i++) { e[2 * i] = bf_lo(x[i >> 2][i & 3]); e[2 * i + 1] = bf_hi(x[i >> 2][i & 3]); }
#pragma unroll
            for (int i = 0; i < 15; i++) p[i] = e[i] + e[i + 1];
#pragma unroll
            for (int i = 0; i < 11; i++) s[i] = p[i + 3] + e[i + 5];
            const uint32_t o = rs + 16 + n * 16;
            if (rg == 2) sts128(o, pack2(s[0], s[1]), pack2(s[2], s[3]), pack2(s[4], s[5]), pack2(s[6], s[7]));
#pragma unroll
            for (int i = 0; i < 10; i++) s[i] = p[i + 2] + s[i + 1];
            if (rg == 2) {
                sts64(o + S4_SIG + 8, pack2(s[0], s[1]), pack2(s[2], s[3]));
                sts64(o + S4_SIG + 16, pack2(s[4], s[5]), pack2(s[6], s[7]));
            } else {
#pragma unroll
                for (int i = 0; i < 9; i++) s[i] = p[i + 1] + s[i + 1];
                sts64(o + 8, pack2(s[0], s[1]), pack2(s[2], s[3]));
                sts64(o + 16, pack2(s[4], s[5]), pack2(s[6], s[7]));
#pragma unroll
                for (int i = 0; i < 8; i++) s[i] = p[i] + s[i + 1];
                sts64(o + S4_SIG + 8, pack2(s[0], s[1]), pack2(s[2], s[3]));
                sts64(o + S4_SIG + 16, pack2(s[4], s[5]), pack2(s[6], s[7]));
            }
        }
        __syncwarp();
        if (rg == 3) {
#pragma unroll 1
            for (int q = 1; q <= 2; q++) s4_class<64, 2>(acc, rs + lf + (q == 1 ? 16 : S4_SIG), kd + (384 + q) * 2, g - 2 * t);
        } else {
#pragma unroll 1
            for (int q = 1; q <= 4; q++) s4_class<32, 4>(acc, rs + lf + ((q & 1) ? 0 : S4_SIG) + (q < 3 ? 16 : 0), kd + (256 + q) * 2, g - 2 * t);
        }
        __syncwarp();
    }
    {
        const uint32_t ub = ur + 256 + lf, kb = pk + (g - 2 * t) * 4;
#pragma unroll 1
        for (int j0 = 0; j0 < 8; j0++) {
            uint32_t B[8][4];
#pragma unroll
            for (int i = 0; i < 8; i++) ldsm4(B[i], ub + i * 512 - j0 * 32);
            auto block = [&](int J, uint32_t a) {
                const uint32_t r0 = lds32(a), rp = lds32(a + 32), rm = lds32(a - 32), r3 = lds32(a);
#pragma unroll
                for (int I = J; I < 16; I++)
                    mma16816(acc[I], r0, rp, rm, r3, B[(I - J) >> 1][((I - J) & 1) * 2], B[(I - J) >> 1][((I - J) & 1) * 2 + 1]);
            };
#pragma unroll
            for (int J = 0; J < 4; J++) block(J, kb + j0 * 64 + J * 512);
            if (j0 < 2) { block(4, kb + j0 * 64 + 2048); block(8, kb + j0 * 64 + (544 + 16) * 4); }
        }
        __syncwarp();
#pragma unroll
        for (int i = 0; i < 8; i++)
            stsm4t(rs + lf + i * 512, pack2(acc[2 * i][0], acc[2 * i][1]), pack2(acc[2 * i][2], acc[2 * i][3]),
                   pack2(acc[2 * i + 1][0], acc[2 * i + 1][1]), pack2(acc[2 * i + 1][2], acc[2 * i + 1][3]));
    }
    __syncthreads();
    {
        const uint2 dv = __ldg((const uint2*)(Dsk + d0 + 4 * t));
        bf16* dst = out + (size_t)(w * 128 + g) * 2048 + 1024 + d0 + 4 * t;
#pragma unroll
        for (int i = 0; i < 8; i++) {
            uint32_t y[4], x[4], o[4];
            ldsm4t(y, sb + S4_R + tr_off * S4_RS + (w * 128 + i * 16) * 2 + tr_l);
            ldsm4t(x, sb + S4_U + tr_off * S4_US + 256 + (w * 128 + i * 16) * 2 + tr_l);
#pragma unroll
            for (int j = 0; j < 4; j++)
                asm("{\n.reg .b32 s;\nmul.rn.bf16x2 s, %2, %3;\nadd.rn.bf16x2 %0, %1, s;\n}" : "=r"(o[j]) : "r"(y[j]), "r"(x[j]), "r"((j & 1) ? dv.y : dv.x));
            *reinterpret_cast<uint2*>(dst + (size_t)(i * 16) * 2048) = make_uint2(o[0], o[1]);
            *reinterpret_cast<uint2*>(dst + (size_t)(i * 16 + 8) * 2048) = make_uint2(o[2], o[3]);
        }
    }
    if (tid == 0) TL(2, 1);
}

enum { IT_QA = 0, IT_W256 = 1, IT_W128 = 2, IT_W64 = 3, IT_W64S = 4, IT_END = 7 };
constexpr int MAX_ITEMS = 640;
struct BgParams { CUtensorMap mx, mwq, mkv4, mkvm, mo, mo2, mo2s, mwo4, mwo2, mwo1, mos; int n; uint16_t item[MAX_ITEMS]; };
constexpr int B_OST = NSTAGE * STAGE_BYTES + 1024;
constexpr int BG_SMEM = B_OST + 32768;

template <int BM, int BN, int KPS, typename ACC>
__device__ __forceinline__ void gemm_mainloop(ACC& acc, const GemmSmem& g, int cw, int rounds, uint32_t& round) {
#pragma unroll
    for (int i = 0; i < BN / 2; i++) acc[i] = 0.f;
#pragma unroll 1
    for (int k0 = 0; k0 < rounds; k0++, round++) {
#pragma unroll
        for (int s = 0; s < 4; s++) {
            mbar_wait_u(g.full + 8 * s, round & 1);
            gemm_stage<BM, BN, KPS>(acc, g.st + s * STAGE_BYTES, cw, false);
            wg_wait<1>();
            if (s > 0 || k0 > 0) mbar_arrive_one(g.empty + 8 * ((s + 3) & 3), threadIdx.x & 127);
        }
    }
    wg_wait<0>();
    mbar_arrive_one(g.empty + 8 * 3, threadIdx.x & 127);
}

template <int BM, int BN, int KPS>
__device__ __forceinline__ void wo_item(const GemmSmem& g, int cw, uint32_t& round, bf16* dst, int t) {
    if (BM == 64 && cw == 1) {
#pragma unroll 1
        for (int k0 = 0; k0 < 16 / KPS; k0++, round++)
#pragma unroll
            for (int s = 0; s < 4; s++) { mbar_wait_u(g.full + 8 * s, round & 1); mbar_arrive_one(g.empty + 8 * s, threadIdx.x & 127); }
        return;
    }
    float acc[BN / 2];
    gemm_mainloop<BM, BN, KPS>(acc, g, cw, 16 / KPS, round);
#pragma unroll
    for (int G = 0; G < BN / 32; G++)
#pragma unroll
        for (int rr = 0; rr < 2; rr++) {
            uint32_t r0 = pack2(acc[16 * G + 2 * rr], acc[16 * G + 2 * rr + 1]), r1 = pack2(acc[16 * G + 4 + 2 * rr], acc[16 * G + 5 + 2 * rr]);
            uint32_t r2 = pack2(acc[16 * G + 8 + 2 * rr], acc[16 * G + 9 + 2 * rr]), r3 = pack2(acc[16 * G + 12 + 2 * rr], acc[16 * G + 13 + 2 * rr]);
            quad_transpose(r0, r1, r2, r3, t);
            *reinterpret_cast<uint4*>(dst + (size_t)rr * 8 * 2048 + G * 32) = make_uint4(r0, r1, r2, r3);
        }
}

template <int HF>
__device__ __forceinline__ void attend(const uint32_t* q, uint32_t st, int hh, uint32_t ost, int lane) {
    constexpr int NT = HF ? 5 : 3;
    const int r8 = lane & 7, m4 = lane >> 3, gq = lane >> 2, t = lane & 3;
    const float sl2e = 0.08838834764831845f * 1.4426950408889634f;
    const uint32_t la = r8 * 128 + ((m4 ^ r8) << 4);
    float sc[NT][4];
#pragma unroll
    for (int nt = 0; nt < NT; nt++) sc[nt][0] = sc[nt][1] = sc[nt][2] = sc[nt][3] = 0.f;
#pragma unroll
    for (int kp = 0; kp < 4; kp++)
#pragma unroll
        for (int nt = 0; nt < NT; nt++) {
            const int nb = hh * 2 + (kp >> 1);
            uint32_t b[4];
            ldsm4(b, (nt == 0 ? st + 32768 + nb * 1024 : st + nb * 4096 + (nt - 1) * 1024) + (la ^ ((kp & 1) << 6)));
            mma16816(sc[nt], q[kp * 8], q[kp * 8 + 1], q[kp * 8 + 2], q[kp * 8 + 3], b[0], b[1]);
            mma16816(sc[nt], q[kp * 8 + 4], q[kp * 8 + 5], q[kp * 8 + 6], q[kp * 8 + 7], b[2], b[3]);
        }
    const float ninf = -3.0e38f;
    if (2 * t > gq) sc[NT - 2][0] = sc[NT - 1][2] = ninf;
    if (2 * t + 1 > gq) sc[NT - 2][1] = sc[NT - 1][3] = ninf;
    sc[NT - 1][0] = sc[NT - 1][1] = ninf;
    uint32_t p[NT][2];
#pragma unroll
    for (int i = 0; i < 2; i++) {
        float m = fmaxf(sc[0][2 * i], sc[0][2 * i + 1]);
#pragma unroll
        for (int nt = 1; nt < NT - 1 + i; nt++) m = fmaxf(m, fmaxf(sc[nt][2 * i], sc[nt][2 * i + 1]));
        m = fmaxf(m, __shfl_xor_sync(~0u, m, 1));
        m = fmaxf(m, __shfl_xor_sync(~0u, m, 2));
        const float ms = m * sl2e;
        float sum = 0.f;
#pragma unroll
        for (int nt = 0; nt < NT - 1 + i; nt++) {
            sc[nt][2 * i] = ex2(fmaf(sc[nt][2 * i], sl2e, -ms));
            sc[nt][2 * i + 1] = ex2(fmaf(sc[nt][2 * i + 1], sl2e, -ms));
            sum += sc[nt][2 * i] + sc[nt][2 * i + 1];
        }
        sum += __shfl_xor_sync(~0u, sum, 1);
        sum += __shfl_xor_sync(~0u, sum, 2);
        float inv;
        asm("rcp.approx.ftz.f32 %0, %1;" : "=f"(inv) : "f"(sum));
#pragma unroll
        for (int nt = 0; nt < NT - 1 + i; nt++) p[nt][i] = pack2(sc[nt][2 * i] * inv, sc[nt][2 * i + 1] * inv);
    }
    p[NT - 1][0] = 0;
    const uint32_t lv = ((m4 & 1) * 8 + r8) * 128 + (((m4 >> 1) ^ r8) << 4);
#pragma unroll
    for (int G = 0; G < 4; G++) {
        const int nb = hh * 2 + (G >> 1);
        float o[4][4];
#pragma unroll
        for (int i = 0; i < 4; i++) o[i][0] = o[i][1] = o[i][2] = o[i][3] = 0.f;
        uint32_t b[4];
        ldsm4t(b, st + 36864 + nb * 1024 + (la ^ ((G & 1) << 6)));
#pragma unroll
        for (int i = 0; i < 4; i++) mma1688(o[i], p[0][0], p[0][1], b[i]);
#pragma unroll
        for (int kk = 0; kk <= HF; kk++)
#pragma unroll
            for (int i = 0; i < 2; i++) {
                ldsm4t(b, st + 16384 + nb * 4096 + kk * 2048 + (lv ^ (((G & 1) * 2 + i) << 5)));
                mma16816(o[2 * i], p[1 + 2 * kk][0], p[1 + 2 * kk][1], p[2 + 2 * kk][0], p[2 + 2 * kk][1], b[0], b[1]);
                mma16816(o[2 * i + 1], p[1 + 2 * kk][0], p[1 + 2 * kk][1], p[2 + 2 * kk][0], p[2 + 2 * kk][1], b[2], b[3]);
            }
#pragma unroll
        for (int i = 0; i < 2; i++)
            asm volatile("stmatrix.sync.aligned.m8n8.x4.shared.b16 [%0], {%1,%2,%3,%4};"
                         ::"r"(ost + (G >> 1) * 4096 + HF * 2048 + (lv ^ (((G & 1) * 2 + i) << 5))),
                           "r"(pack2(o[2 * i][0], o[2 * i][1])), "r"(pack2(o[2 * i][2], o[2 * i][3])),
                           "r"(pack2(o[2 * i + 1][0], o[2 * i + 1][1])), "r"(pack2(o[2 * i + 1][2], o[2 * i + 1][3])) : "memory");
    }
    asm volatile("fence.proxy.async.shared::cta;" ::: "memory");
    __syncwarp();
}

__device__ __forceinline__ void tma_prefetch3d(const CUtensorMap* m, int c0, int c1, int c2) {
    asm volatile("cp.async.bulk.prefetch.tensor.3d.L2.global [%0, {%1, %2, %3}];" ::"l"(m), "r"(c0), "r"(c1), "r"(c2) : "memory");
}

__global__ void __launch_bounds__(384, 1) k_bg(const __grid_constant__ BgParams P, bf16* __restrict__ out) {
    extern __shared__ __align__(1024) uint8_t smem_gemm[];
    const uint32_t xb = smem_u32(smem_gemm) + NSTAGE * STAGE_BYTES + 128;
    const uint32_t bar_item = xb, bar_o = xb + 16, slot = xb + 32, slot_o = xb + 40;
    if (threadIdx.x == 0) { mbar_init(bar_item, 1); mbar_init(bar_item + 8, 1); mbar_init(bar_o, 8); mbar_init(bar_o + 8, 8); }
    GemmSmem g = gemm_setup(smem_gemm);
    const int wg = __shfl_sync(~0u, threadIdx.x >> 7, 0);
    if (wg == 0) {
        asm volatile("setmaxnreg.dec.sync.aligned.u32 40;");
        if (threadIdx.x == 0) {
            uint32_t it = 0;
            auto acquire = [&](uint32_t bytes) {
                const int s = it & 3;
                mbar_wait(g.empty + 8 * s, ((it >> 2) & 1) ^ 1);
                mbar_expect_tx(g.full + 8 * s, bytes);
                it++;
                return s;
            };
            for (int n = 0;; n++) {
                const int qi = atomicAdd(g_flag + 96, 1);
                const int code = qi < P.n ? P.item[qi] : IT_END;
                sts32(slot + (n & 1) * 4, code | (qi << 16));
                mbar_arrive(bar_item + (n & 1) * 8);
                const int type = code & 7, blk = (code >> 3) & 15, idx = code >> 7, m0 = blk * 128;
                if (type == IT_END) {
                    mbar_wait(g.empty, ((it >> 2) & 1) ^ 1);
                    sts32(slot_o, IT_END);
                    for (int i = 0; i < 8; i++) mbar_arrive(bar_o);
                    break;
                }
                if (type == IT_QA) {
                    for (int k = 0; k < 16; k++) {
                        const int s = acquire(STAGE_BYTES);
                        const uint32_t st = g.st + s * STAGE_BYTES, fb = g.full + 8 * s;
                        tma2d(st, &P.mx, k * 64, m0, fb);
                        tma3d(st + 16384, &P.mwq, 0, k * 64, idx * 4, fb);
                        if (k >= 4 && k < 12) tma_prefetch3d(&P.mkv4, 0, m0 + (k & 3) * 32, (k & 8) * 8 + idx * 4);
                    }
                    bool ready = ld_acq32(g_flag + 2 * idx) >= 4 * blk + 4 && ld_acq32(g_flag + 2 * idx + 1) >= 4 * blk + 4;
                    if (ready) asm volatile("fence.proxy.async.global;" ::: "memory");
                    for (int pass = 0; pass < 2; pass++) {
                        for (int s = 0; s < 4; s++) {
                            const uint32_t st = g.st + s * STAGE_BYTES, fb = g.full + 8 * s;
                            if (pass == 0) {
                                acquire(40960);
                                tma3d(st, &P.mkv4, 0, m0 + s * 32, idx * 4, fb);
                                tma3d(st + 16384, &P.mkv4, 0, m0 + s * 32, 64 + idx * 4, fb);
                            }
                            if (ready) {
                                tma3d(st + 32768, &P.mkvm, 0, (blk * 4 + s) * 8, idx * 4, fb);
                                tma3d(st + 36864, &P.mkvm, 0, (blk * 4 + s) * 8, 64 + idx * 4, fb);
                            }
                        }
                        if (ready) break;
                        wait_flag(g_flag + 2 * idx, 4 * blk + 4);
                        wait_flag(g_flag + 2 * idx + 1, 4 * blk + 4);
                        asm volatile("fence.proxy.async.global;" ::: "memory");
                        ready = true;
                    }
                } else {
                    wait_flag(g_flag + 64 + blk, 16);
                    asm volatile("fence.proxy.async.global;" ::: "memory");
                    if (type <= IT_W128) {
                        const int nb = type == IT_W256 ? 4 : 2;
                        for (int k = 0; k < 64; k++) {
                            const int s = acquire(16384 + nb * 8192);
                            const uint32_t st = g.st + s * STAGE_BYTES, fb = g.full + 8 * s;
                            tma2d(st, &P.mo, k * 64, m0, fb);
                            tma3d(st + 16384, nb == 4 ? &P.mwo4 : &P.mwo2, 0, k * 64, idx * nb, fb);
                        }
                    } else {
                        const uint32_t ab = type == IT_W64 ? 32768 : 16384;
                        for (int k = 0; k < 32; k++) {
                            const int s = acquire(ab + 16384);
                            const uint32_t st = g.st + s * STAGE_BYTES, fb = g.full + 8 * s;
                            tma3d(st, type == IT_W64 ? &P.mo2 : &P.mo2s, 0, m0 + (idx >> 4) * 64, k * 2, fb);
                            tma3d(st + ab, &P.mwo1, 0, k * 128, idx & 15, fb);
                        }
                    }
                }
            }
        } else if (threadIdx.x == 32) {
            for (uint32_t n = 0;; n++) {
                mbar_wait(bar_o, n & 1);
                const int code = lds32(slot_o), blk = (code >> 3) & 15, idx = (code >> 7) & 31;
                if ((code & 7) == IT_END) break;
                for (int hh = 0; hh < 2; hh++) {
                    if (hh) mbar_wait(bar_o + 8, n & 1);
                    for (int s = 0; s < 4; s++)
                        asm volatile("cp.async.bulk.tensor.3d.global.shared::cta.bulk_group [%0, {%2, %3, %4}], [%1];"
                                     ::"l"(&P.mos), "r"(hh ? g.st + B_OST + s * 8192 : g.st + s * STAGE_BYTES + 40960),
                                       "r"(0), "r"(blk * 128 + s * 32), "r"(idx * 4 + hh * 2) : "memory");
                    asm volatile("cp.async.bulk.commit_group;" ::: "memory");
                }
                asm volatile("cp.async.bulk.wait_group.read 1;" ::: "memory");
                for (int s = 0; s < 8; s++) mbar_arrive(g.empty + 8 * (s >> 1));
                asm volatile("cp.async.bulk.wait_group 0;\nfence.acq_rel.gpu;\nred.relaxed.gpu.global.add.u32 [%0], 1;"
                             ::"l"(g_flag + 64 + blk) : "memory");
            }
        }
    } else {
        asm volatile("setmaxnreg.inc.sync.aligned.u32 232;");
        const int cw = wg - 1, ww = __shfl_sync(~0u, (threadIdx.x >> 5) & 3, 0), lane = threadIdx.x & 31;
        uint32_t round = 0;
#pragma unroll 1
        for (int n = 0;; n++) {
            mbar_wait_u(bar_item + (n & 1) * 8, (n >> 1) & 1);
            const int code = __shfl_sync(~0u, lds32(slot + (n & 1) * 4), 0);
            const int type = code & 7, blk = (code >> 3) & 15, idx = (code >> 7) & 31;
#define TLB(slot_)
            if (type == IT_END) break;
            TLB(0);
            if (type == IT_QA) {
                uint32_t q[64];
                {
                    float acc[128];
                    gemm_mainloop<128, 256, 1>(acc, g, cw, 4, round);
#pragma unroll
                    for (int i = 0; i < 64; i++) q[i] = pack2(acc[2 * i], acc[2 * i + 1]);
                }
                const int sg = cw * 2 + (ww >> 1);
                const uint32_t st = g.st + sg * STAGE_BYTES;
                if (threadIdx.x == 128) sts32(slot_o, code);
                TLB(2);
                mbar_wait_u(g.full + 8 * sg, round & 1);
                TLB(3);
                if (ww & 1) {
                    attend<1>(q, st, 0, st + 40960, lane);
                    mbar_arrive_one(bar_o, lane);
                    attend<1>(q + 32, st, 1, g.st + B_OST + sg * 8192, lane);
                } else {
                    attend<0>(q, st, 0, st + 40960, lane);
                    mbar_arrive_one(bar_o, lane);
                    attend<0>(q + 32, st, 1, g.st + B_OST + sg * 8192, lane);
                }
#pragma unroll
                for (int s = 0; s < 4; s++) mbar_wait_u(g.full + 8 * s, round & 1);
                round++;
                mbar_arrive_one(bar_o + 8, lane);
            } else {
                bf16* dst = out + (size_t)(blk * 128 + cw * 64 + ww * 16 + (lane >> 2)) * 2048 + (lane & 3) * 8;
                if (type == IT_W256) wo_item<128, 256, 1>(g, cw, round, dst + idx * 256, lane & 3);
                else if (type == IT_W128) wo_item<128, 128, 1>(g, cw, round, dst + idx * 128, lane & 3);
                else if (type == IT_W64) wo_item<128, 64, 2>(g, cw, round, dst + idx * 64, lane & 3);
                else wo_item<64, 64, 2>(g, cw, round, dst + (size_t)(idx >> 4) * 64 * 2048 + (idx & 15) * 64, lane & 3);
            }
            TLB(1);
        }
    }
}

typedef CUresult (*EncodeFn)(CUtensorMap*, CUtensorMapDataType, cuuint32_t, void*, const cuuint64_t*, const cuuint64_t*,
                             const cuuint32_t*, const cuuint32_t*, CUtensorMapInterleave, CUtensorMapSwizzle,
                             CUtensorMapL2promotion, CUtensorMapFloatOOBfill);

static void map2d(EncodeFn enc, CUtensorMap* m, const void* p, int rows, int cols, int box_rows) {
    cuuint64_t dim[2] = {(cuuint64_t)cols, (cuuint64_t)rows}, str[1] = {(cuuint64_t)cols * 2};
    cuuint32_t box[2] = {64, (cuuint32_t)box_rows}, es[2] = {1, 1};
    enc(m, CU_TENSOR_MAP_DATA_TYPE_BFLOAT16, 2, (void*)p, dim, str, box, es, CU_TENSOR_MAP_INTERLEAVE_NONE,
        CU_TENSOR_MAP_SWIZZLE_128B, CU_TENSOR_MAP_L2_PROMOTION_L2_256B, CU_TENSOR_MAP_FLOAT_OOB_FILL_NONE);
}
static void map3d(EncodeFn enc, CUtensorMap* m, const void* p, int rows, int cols, int box_rows, int nblk) {
    cuuint64_t dim[3] = {64, (cuuint64_t)rows, (cuuint64_t)cols / 64}, str[2] = {(cuuint64_t)cols * 2, 128};
    cuuint32_t box[3] = {64, (cuuint32_t)box_rows, (cuuint32_t)nblk}, es[3] = {1, 1, 1};
    enc(m, CU_TENSOR_MAP_DATA_TYPE_BFLOAT16, 3, (void*)p, dim, str, box, es, CU_TENSOR_MAP_INTERLEAVE_NONE,
        CU_TENSOR_MAP_SWIZZLE_128B, CU_TENSOR_MAP_L2_PROMOTION_L2_256B, CU_TENSOR_MAP_FLOAT_OOB_FILL_NONE);
}

#define WO_LAG 2
#define NB256 9
#define NB128 12
#define NB64 15
#define USE_PDL 1

extern "C" void kernel_launch(void* const* d_in, const int* in_sizes, int n_in, void* d_out, int out_size) {
    const bf16 *x = (const bf16*)d_in[0], *mem0 = (const bf16*)d_in[1], *Wq = (const bf16*)d_in[2], *Wk = (const bf16*)d_in[3];
    const bf16 *Wv = (const bf16*)d_in[4], *Wo = (const bf16*)d_in[5];
    const bf16 *u = (const bf16*)d_in[7], *Are = (const bf16*)d_in[8], *Aim = (const bf16*)d_in[9], *Bre = (const bf16*)d_in[10];
    const bf16 *Bim = (const bf16*)d_in[11], *Cre = (const bf16*)d_in[12], *Cim = (const bf16*)d_in[13];
    const bf16 *logdt = (const bf16*)d_in[14], *Dsk = (const bf16*)d_in[15];
    bf16* out = (bf16*)d_out;

    void* fn = nullptr;
    cudaDriverEntryPointQueryResult qr;
    cudaGetDriverEntryPoint("cuTensorMapEncodeTiled", &fn, cudaEnableDefault, &qr);
    EncodeFn enc = (EncodeFn)fn;
    void *kv, *kvm, *o;
    cudaGetSymbolAddress(&kv, g_kv);
    cudaGetSymbolAddress(&kvm, g_kvm);
    cudaGetSymbolAddress(&o, g_o);
    CUtensorMap mwk, mwv, mkv2;
    BgParams P;
    map2d(enc, &P.mx, x, SEQ, DM, 128);
    map2d(enc, &P.mo, o, SEQ, HD, 128);
    map3d(enc, &P.mo2, o, SEQ, HD, 128, 2);
    map3d(enc, &P.mo2s, o, SEQ, HD, 64, 2);
    map3d(enc, &P.mos, o, SEQ, HD, 32, 2);
    map3d(enc, &P.mwq, Wq, DM, HD, 64, 4);
    map3d(enc, &mwk, Wk, DM, HD, 64, 4);
    map3d(enc, &mwv, Wv, DM, HD, 64, 4);
    map3d(enc, &P.mwo4, Wo, HD, DM, 64, 4);
    map3d(enc, &P.mwo2, Wo, HD, DM, 64, 2);
    map3d(enc, &P.mwo1, Wo, HD, DM, 128, 1);
    map3d(enc, &mkv2, kv, SEQ, 8192, 32, 2);
    map3d(enc, &P.mkv4, kv, SEQ, 8192, 32, 4);
    map3d(enc, &P.mkvm, kvm, NSEG * 8, 8192, 8, 4);
    P.n = 0;
    auto push = [&](int type, int blk, int cnt) { for (int i = 0; i < cnt; i++) P.item[P.n++] = (uint16_t)(type | blk << 3 | i << 7); };
    auto push_wo = [&](int b) {
        if (b < NB256) push(IT_W256, b, 4);
        else if (b < NB128) push(IT_W128, b, 8);
        else if (b < NB64) push(IT_W64, b, 16);
        else push(IT_W64S, b, 32);
    };
    for (int b = 0; b < 16 + WO_LAG; b++) {
        if (b < 16) push(IT_QA, b, 16);
        if (b >= WO_LAG) push_wo(b - WO_LAG);
    }
    cudaFuncSetAttribute(k_kv, cudaFuncAttributeMaxDynamicSharedMemorySize, GEMM_SMEM);
    cudaFuncSetAttribute(k_bg, cudaFuncAttributeMaxDynamicSharedMemorySize, BG_SMEM);
    cudaFuncSetAttribute(k_chain, cudaFuncAttributeMaxDynamicSharedMemorySize, CHAIN_SMEM);
    cudaFuncSetAttribute(k_s4, cudaFuncAttributeMaxDynamicSharedMemorySize, S4_SMEM);

    cudaStream_t st = cudaStreamPerThread;
    k_kv<<<132, 384, GEMM_SMEM, st>>>(P.mx, mwk, mwv, Wq, Wo);
    k_chain<<<96, 256, CHAIN_SMEM, st>>>(mem0, Wq, Wk, Wv, Wo, mkv2);
    cudaLaunchAttribute pdl[1];
    pdl[0].id = cudaLaunchAttributeProgrammaticStreamSerialization;
    pdl[0].val.programmaticStreamSerializationAllowed = 1;
    cudaLaunchConfig_t cfg = {};
    cfg.stream = st; cfg.attrs = pdl; cfg.numAttrs = USE_PDL;
    cfg.gridDim = dim3(64); cfg.blockDim = dim3(512); cfg.dynamicSmemBytes = S4_SMEM;
    cudaLaunchKernelEx(&cfg, k_s4, u, Are, Aim, Bre, Bim, Cre, Cim, logdt, Dsk, out);
    cfg.gridDim = dim3(132); cfg.blockDim = dim3(384); cfg.dynamicSmemBytes = BG_SMEM;
    cudaLaunchKernelEx(&cfg, k_bg, P, out);
}
```

```cpp
#include <cuda_runtime.h>
#include <cuda_bf16.h>
#include <cuda.h>
#include <stdint.h>

typedef __nv_bfloat16 bf16;

constexpr int SEQ = 2048, DM = 1024, HD = 4096, NSEG = 64;

__device__ __align__(1024) bf16 g_kv[(size_t)SEQ * 8192];
__device__ __align__(1024) bf16 g_kvm[(size_t)NSEG * 8 * 8192];
__device__ __align__(1024) bf16 g_o[(size_t)SEQ * HD];
constexpr int XPAIRS = 128 + NSEG * 4;
__device__ __align__(8192) uint2 g_x[XPAIRS * 1024];
__device__ uint32_t g_home[XPAIRS];
__device__ uint32_t g_side[256];
__device__ __align__(1024) uint32_t g_flag[256];

#define TL(kern, slot)

__device__ __forceinline__ uint32_t smem_u32(const void* p) { return (uint32_t)__cvta_generic_to_shared(p); }
__device__ __forceinline__ void mbar_init(uint32_t bar, uint32_t cnt) {
    asm volatile("mbarrier.init.shared::cta.b64 [%0], %1;" ::"r"(bar), "r"(cnt) : "memory");
}
__device__ __forceinline__ void mbar_expect_tx(uint32_t bar, uint32_t bytes) {
    asm volatile("mbarrier.arrive.expect_tx.shared::cta.b64 _, [%0], %1;" ::"r"(bar), "r"(bytes) : "memory");
}
__device__ __forceinline__ void mbar_arrive(uint32_t bar) {
    asm volatile("mbarrier.arrive.shared::cta.b64 _, [%0];" ::"r"(bar) : "memory");
}
__device__ __forceinline__ bool mbar_try(uint32_t bar, uint32_t parity) {
    uint32_t ok;
    asm volatile("{\n.reg .pred p;\nmbarrier.try_wait.parity.shared::cta.b64 p, [%1], %2;\nselp.u32 %0, 1, 0, p;\n}"
                 : "=r"(ok) : "r"(bar), "r"(parity) : "memory");
    return ok;
}
constexpr int SPIN_LIMIT = 1 << 20;
__device__ __forceinline__ void mbar_wait(uint32_t bar, uint32_t parity) {
    int n = 0;
    while (!mbar_try(bar, parity)) { if (++n > SPIN_LIMIT) __trap(); }
}
__device__ __forceinline__ void mbar_wait_u(uint32_t bar, uint32_t parity) {
    asm volatile("{\n.reg .pred p;\n.reg .u32 n;\n"
                 "mbarrier.try_wait.parity.shared::cta.b64 p, [%0], %1;\n@p bra.uni DONE;\nmov.u32 n, 0;\n"
                 "AGAIN:\nmbarrier.try_wait.parity.shared::cta.b64 p, [%0], %1;\n@p bra.uni DONE;\n"
                 "add.u32 n, n, 1;\nsetp.lt.u32 p, n, 0x100000;\n@p bra.uni AGAIN;\ntrap;\nDONE:\n}"
                 ::"r"(bar), "r"(parity) : "memory");
}
__device__ __forceinline__ void tma2d(uint32_t dst, const CUtensorMap* m, int c0, int c1, uint32_t bar) {
    asm volatile("cp.async.bulk.tensor.2d.shared::cluster.global.mbarrier::complete_tx::bytes [%0], [%1, {%3, %4}], [%2];"
                 ::"r"(dst), "l"(m), "r"(bar), "r"(c0), "r"(c1) : "memory");
}
__device__ __forceinline__ void tma3d(uint32_t dst, const CUtensorMap* m, int c0, int c1, int c2, uint32_t bar) {
    asm volatile("cp.async.bulk.tensor.3d.shared::cluster.global.mbarrier::complete_tx::bytes [%0], [%1, {%3, %4, %5}], [%2];"
                 ::"r"(dst), "l"(m), "r"(bar), "r"(c0), "r"(c1), "r"(c2) : "memory");
}
__device__ __forceinline__ uint32_t pack2(float lo, float hi) {
    uint32_t r;
    asm("cvt.rn.bf16x2.f32 %0, %1, %2;" : "=r"(r) : "f"(hi), "f"(lo));
    return r;
}
__device__ __forceinline__ float bf_lo(uint32_t v) { return __uint_as_float(v << 16); }
__device__ __forceinline__ float bf_hi(uint32_t v) { return __uint_as_float(v & 0xffff0000u); }
__device__ __forceinline__ float bf_round(float x) { return bf_lo(pack2(x, 0.f)); }
__device__ __forceinline__ float ex2(float x) { float y; asm("ex2.approx.ftz.f32 %0, %1;" : "=f"(y) : "f"(x)); return y; }
__device__ __forceinline__ void mma16816(float (&c)[4], uint32_t a0, uint32_t a1, uint32_t a2, uint32_t a3, uint32_t b0, uint32_t b1) {
    asm volatile("mma.sync.aligned.m16n8k16.row.col.f32.bf16.bf16.f32 {%0,%1,%2,%3}, {%4,%5,%6,%7}, {%8,%9}, {%0,%1,%2,%3};"
                 : "+f"(c[0]), "+f"(c[1]), "+f"(c[2]), "+f"(c[3]) : "r"(a0), "r"(a1), "r"(a2), "r"(a3), "r"(b0), "r"(b1));
}
__device__ __forceinline__ void mma1688(float (&c)[4], uint32_t a0, uint32_t a1, uint32_t b0) {
    asm volatile("mma.sync.aligned.m16n8k8.row.col.f32.bf16.bf16.f32 {%0,%1,%2,%3}, {%4,%5}, {%6}, {%0,%1,%2,%3};"
                 : "+f"(c[0]), "+f"(c[1]), "+f"(c[2]), "+f"(c[3]) : "r"(a0), "r"(a1), "r"(b0));
}
__device__ __forceinline__ void ldsm4(uint32_t (&r)[4], uint32_t a) {
    asm volatile("ldmatrix.sync.aligned.m8n8.x4.shared.b16 {%0,%1,%2,%3}, [%4];"
                 : "=r"(r[0]), "=r"(r[1]), "=r"(r[2]), "=r"(r[3]) : "r"(a) : "memory");
}
__device__ __forceinline__ void ldsm4t(uint32_t (&r)[4], uint32_t a) {
    asm volatile("ldmatrix.sync.aligned.m8n8.x4.trans.shared.b16 {%0,%1,%2,%3}, [%4];"
                 : "=r"(r[0]), "=r"(r[1]), "=r"(r[2]), "=r"(r[3]) : "r"(a) : "memory");
}
__device__ __forceinline__ void ldsm2t(uint32_t& r0, uint32_t& r1, uint32_t a) {
    asm volatile("ldmatrix.sync.aligned.m8n8.x2.trans.shared.b16 {%0,%1}, [%2];" : "=r"(r0), "=r"(r1) : "r"(a) : "memory");
}
__device__ __forceinline__ void stsm4t(uint32_t a, uint32_t r0, uint32_t r1, uint32_t r2, uint32_t r3) {
    asm volatile("stmatrix.sync.aligned.m8n8.x4.trans.shared.b16 [%0], {%1,%2,%3,%4};"
                 ::"r"(a), "r"(r0), "r"(r1), "r"(r2), "r"(r3) : "memory");
}
__device__ __forceinline__ void lds128(uint32_t (&r)[4], uint32_t a) {
    asm volatile("ld.shared.v4.u32 {%0,%1,%2,%3}, [%4];" : "=r"(r[0]), "=r"(r[1]), "=r"(r[2]), "=r"(r[3]) : "r"(a) : "memory");
}
__device__ __forceinline__ float4 lds128f(uint32_t a) {
    float4 v;
    asm volatile("ld.shared.v4.f32 {%0,%1,%2,%3}, [%4];" : "=f"(v.x), "=f"(v.y), "=f"(v.z), "=f"(v.w) : "r"(a) : "memory");
    return v;
}
__device__ __forceinline__ float2 lds64f(uint32_t a) {
    float2 v;
    asm volatile("ld.shared.v2.f32 {%0,%1}, [%2];" : "=f"(v.x), "=f"(v.y) : "r"(a) : "memory");
    return v;
}
__device__ __forceinline__ uint32_t lds32(uint32_t a) {
    uint32_t v;
    asm volatile("ld.shared.u32 %0, [%1];" : "=r"(v) : "r"(a) : "memory");
    return v;
}
__device__ __forceinline__ void sts128(uint32_t a, uint32_t r0, uint32_t r1, uint32_t r2, uint32_t r3) {
    asm volatile("st.shared.v4.u32 [%0], {%1,%2,%3,%4};" ::"r"(a), "r"(r0), "r"(r1), "r"(r2), "r"(r3) : "memory");
}
__device__ __forceinline__ void sts128f(uint32_t a, float r0, float r1, float r2, float r3) {
    asm volatile("st.shared.v4.f32 [%0], {%1,%2,%3,%4};" ::"r"(a), "f"(r0), "f"(r1), "f"(r2), "f"(r3) : "memory");
}
__device__ __forceinline__ void sts64(uint32_t a, uint32_t r0, uint32_t r1) {
    asm volatile("st.shared.v2.u32 [%0], {%1,%2};" ::"r"(a), "r"(r0), "r"(r1) : "memory");
}
__device__ __forceinline__ void sts64f(uint32_t a, float r0, float r1) {
    asm volatile("st.shared.v2.f32 [%0], {%1,%2};" ::"r"(a), "f"(r0), "f"(r1) : "memory");
}
__device__ __forceinline__ void sts32f(uint32_t a, float r0) {
    asm volatile("st.shared.f32 [%0], %1;" ::"r"(a), "f"(r0) : "memory");
}
__device__ __forceinline__ uint2 ld_rlx64(const uint2* p) {
    uint2 v;
    asm volatile("{\n.reg .b64 t;\nld.relaxed.gpu.global.b64 t, [%2];\nmov.b64 {%0,%1}, t;\n}" : "=r"(v.x), "=r"(v.y) : "l"(p) : "memory");
    return v;
}
__device__ __forceinline__ void st_rlx64(uint2* p, uint32_t x, uint32_t y) {
    asm volatile("{\n.reg .b64 t;\nmov.b64 t, {%1,%2};\nst.relaxed.gpu.global.b64 [%0], t;\n}" ::"l"(p), "r"(x), "r"(y) : "memory");
}
__device__ __forceinline__ uint32_t ld_acq32(const uint32_t* p) {
    uint32_t v;
    asm volatile("ld.acquire.gpu.global.u32 %0, [%1];" : "=r"(v) : "l"(p) : "memory");
    return v;
}
__device__ __forceinline__ void wait_flag(const uint32_t* p, uint32_t need) {
    int n = 0;
    while (ld_acq32(p) < need) { __nanosleep(200); if (++n > SPIN_LIMIT) __trap(); }
}
__device__ __forceinline__ void bar_sync(int id, int n) { asm volatile("bar.sync %0, %1;" ::"r"(id), "r"(n) : "memory"); }
__device__ __forceinline__ void wg_fence() { asm volatile("wgmma.fence.sync.aligned;" ::: "memory"); }
__device__ __forceinline__ void wg_commit() { asm volatile("wgmma.commit_group.sync.aligned;" ::: "memory"); }
template <int N> __device__ __forceinline__ void wg_wait() { asm volatile("wgmma.wait_group.sync.aligned %0;" ::"n"(N) : "memory"); }
__device__ __forceinline__ uint64_t desc_sw128(uint32_t addr, uint32_t lbo, uint32_t sbo) {
    return (uint64_t)((addr & 0x3FFFF) >> 4) | ((uint64_t)(lbo >> 4) << 16) | ((uint64_t)(sbo >> 4) << 32) | (1ull << 62);
}
__device__ __forceinline__ void quad_transpose(uint32_t& r0, uint32_t& r1, uint32_t& r2, uint32_t& r3, int t) {
    const bool o = t & 1, h = t & 2;
    uint32_t s0 = __shfl_xor_sync(~0u, o ? r0 : r1, 1), s1 = __shfl_xor_sync(~0u, o ? r2 : r3, 1);
    uint32_t a0 = o ? s0 : r0, a1 = o ? r1 : s0, a2 = o ? s1 : r2, a3 = o ? r3 : s1;
    s0 = __shfl_xor_sync(~0u, h ? a0 : a2, 2); s1 = __shfl_xor_sync(~0u, h ? a1 : a3, 2);
    r0 = h ? s0 : a0; r1 = h ? s1 : a1; r2 = h ? a2 : s0; r3 = h ? a3 : s1;
}

__device__ __forceinline__ void wgmma_n256(float (&d)[128], uint64_t da, uint64_t db, int sd) {
    asm volatile("{\n.reg .pred p;\nsetp.ne.b32 p, %130, 0;\n"
        "wgmma.mma_async.sync.aligned.m64n256k16.f32.bf16.bf16 "
        "{%0,%1,%2,%3,%4,%5,%6,%7,%8,%9,%10,%11,%12,%13,%14,%15,"
        "%16,%17,%18,%19,%20,%21,%22,%23,%24,%25,%26,%27,%28,%29,%30,%31,"
        "%32,%33,%34,%35,%36,%37,%38,%39,%40,%41,%42,%43,%44,%45,%46,%47,"
        "%48,%49,%50,%51,%52,%53,%54,%55,%56,%57,%58,%59,%60,%61,%62,%63,"
        "%64,%65,%66,%67,%68,%69,%70,%71,%72,%73,%74,%75,%76,%77,%78,%79,"
        "%80,%81,%82,%83,%84,%85,%86,%87,%88,%89,%90,%91,%92,%93,%94,%95,"
        "%96,%97,%98,%99,%100,%101,%102,%103,%104,%105,%106,%107,%108,%109,%110,%111,"
        "%112,%113,%114,%115,%116,%117,%118,%119,%120,%121,%122,%123,%124,%125,%126,%127}, %128, %129, p, 1, 1, 0, 1;\n}\n"
        : "+f"(d[0]), "+f"(d[1]), "+f"(d[2]), "+f"(d[3]), "+f"(d[4]), "+f"(d[5]), "+f"(d[6]), "+f"(d[7]),
          "+f"(d[8]), "+f"(d[9]), "+f"(d[10]), "+f"(d[11]), "+f"(d[12]), "+f"(d[13]), "+f"(d[14]), "+f"(d[15]),
          "+f"(d[16]), "+f"(d[17]), "+f"(d[18]), "+f"(d[19]), "+f"(d[20]), "+f"(d[21]), "+f"(d[22]), "+f"(d[23]),
          "+f"(d[24]), "+f"(d[25]), "+f"(d[26]), "+f"(d[27]), "+f"(d[28]), "+f"(d[29]), "+f"(d[30]), "+f"(d[31]),
          "+f"(d[32]), "+f"(d[33]), "+f"(d[34]), "+f"(d[35]), "+f"(d[36]), "+f"(d[37]), "+f"(d[38]), "+f"(d[39]),
          "+f"(d[40]), "+f"(d[41]), "+f"(d[42]), "+f"(d[43]), "+f"(d[44]), "+f"(d[45]), "+f"(d[46]), "+f"(d[47]),
          "+f"(d[48]), "+f"(d[49]), "+f"(d[50]), "+f"(d[51]), "+f"(d[52]), "+f"(d[53]), "+f"(d[54]), "+f"(d[55]),
          "+f"(d[56]), "+f"(d[57]), "+f"(d[58]), "+f"(d[59]), "+f"(d[60]), "+f"(d[61]), "+f"(d[62]), "+f"(d[63]),
          "+f"(d[64]), "+f"(d[65]), "+f"(d[66]), "+f"(d[67]), "+f"(d[68]), "+f"(d[69]), "+f"(d[70]), "+f"(d[71]),
          "+f"(d[72]), "+f"(d[73]), "+f"(d[74]), "+f"(d[75]), "+f"(d[76]), "+f"(d[77]), "+f"(d[78]), "+f"(d[79]),
          "+f"(d[80]), "+f"(d[81]), "+f"(d[82]), "+f"(d[83]), "+f"(d[84]), "+f"(d[85]), "+f"(d[86]), "+f"(d[87]),
          "+f"(d[88]), "+f"(d[89]), "+f"(d[90]), "+f"(d[91]), "+f"(d[92]), "+f"(d[93]), "+f"(d[94]), "+f"(d[95]),
          "+f"(d[96]), "+f"(d[97]), "+f"(d[98]), "+f"(d[99]), "+f"(d[100]), "+f"(d[101]), "+f"(d[102]), "+f"(d[103]),
          "+f"(d[104]), "+f"(d[105]), "+f"(d[106]), "+f"(d[107]), "+f"(d[108]), "+f"(d[109]), "+f"(d[110]), "+f"(d[111]),
          "+f"(d[112]), "+f"(d[113]), "+f"(d[114]), "+f"(d[115]), "+f"(d[116]), "+f"(d[117]), "+f"(d[118]), "+f"(d[119]),
          "+f"(d[120]), "+f"(d[121]), "+f"(d[122]), "+f"(d[123]), "+f"(d[124]), "+f"(d[125]), "+f"(d[126]), "+f"(d[127])
        : "l"(da), "l"(db), "r"(sd));
}

__device__ __forceinline__ void wgmma_n128(float (&d)[64], uint64_t da, uint64_t db, int sd) {
    asm volatile("{\n.reg .pred p;\nsetp.ne.b32 p, %66, 0;\n"
        "wgmma.mma_async.sync.aligned.m64n128k16.f32.bf16.bf16 "
        "{%0,%1,%2,%3,%4,%5,%6,%7,%8,%9,%10,%11,%12,%13,%14,%15,"
        "%16,%17,%18,%19,%20,%21,%22,%23,%24,%25,%26,%27,%28,%29,%30,%31,"
        "%32,%33,%34,%35,%36,%37,%38,%39,%40,%41,%42,%43,%44,%45,%46,%47,"
        "%48,%49,%50,%51,%52,%53,%54,%55,%56,%57,%58,%59,%60,%61,%62,%63}, %64, %65, p, 1, 1, 0, 1;\n}\n"
        : "+f"(d[0]), "+f"(d[1]), "+f"(d[2]), "+f"(d[3]), "+f"(d[4]), "+f"(d[5]), "+f"(d[6]), "+f"(d[7]),
          "+f"(d[8]), "+f"(d[9]), "+f"(d[10]), "+f"(d[11]), "+f"(d[12]), "+f"(d[13]), "+f"(d[14]), "+f"(d[15]),
          "+f"(d[16]), "+f"(d[17]), "+f"(d[18]), "+f"(d[19]), "+f"(d[20]), "+f"(d[21]), "+f"(d[22]), "+f"(d[23]),
          "+f"(d[24]), "+f"(d[25]), "+f"(d[26]), "+f"(d[27]), "+f"(d[28]), "+f"(d[29]), "+f"(d[30]), "+f"(d[31]),
          "+f"(d[32]), "+f"(d[33]), "+f"(d[34]), "+f"(d[35]), "+f"(d[36]), "+f"(d[37]), "+f"(d[38]), "+f"(d[39]),
          "+f"(d[40]), "+f"(d[41]), "+f"(d[42]), "+f"(d[43]), "+f"(d[44]), "+f"(d[45]), "+f"(d[46]), "+f"(d[47]),
          "+f"(d[48]), "+f"(d[49]), "+f"(d[50]), "+f"(d[51]), "+f"(d[52]), "+f"(d[53]), "+f"(d[54]), "+f"(d[55]),
          "+f"(d[56]), "+f"(d[57]), "+f"(d[58]), "+f"(d[59]), "+f"(d[60]), "+f"(d[61]), "+f"(d[62]), "+f"(d[63])
        : "l"(da), "l"(db), "r"(sd));
}

__device__ __forceinline__ void wgmma_n64(float (&d)[32], uint64_t da, uint64_t db, int sd) {
    asm volatile("{\n.reg .pred p;\nsetp.ne.b32 p, %34, 0;\n"
        "wgmma.mma_async.sync.aligned.m64n64k16.f32.bf16.bf16 "
        "{%0,%1,%2,%3,%4,%5,%6,%7,%8,%9,%10,%11,%12,%13,%14,%15,"
        "%16,%17,%18,%19,%20,%21,%22,%23,%24,%25,%26,%27,%28,%29,%30,%31}, %32, %33, p, 1, 1, 0, 1;\n}\n"
        : "+f"(d[0]), "+f"(d[1]), "+f"(d[2]), "+f"(d[3]), "+f"(d[4]), "+f"(d[5]), "+f"(d[6]), "+f"(d[7]),
          "+f"(d[8]), "+f"(d[9]), "+f"(d[10]), "+f"(d[11]), "+f"(d[12]), "+f"(d[13]), "+f"(d[14]), "+f"(d[15]),
          "+f"(d[16]), "+f"(d[17]), "+f"(d[18]), "+f"(d[19]), "+f"(d[20]), "+f"(d[21]), "+f"(d[22]), "+f"(d[23]),
          "+f"(d[24]), "+f"(d[25]), "+f"(d[26]), "+f"(d[27]), "+f"(d[28]), "+f"(d[29]), "+f"(d[30]), "+f"(d[31])
        : "l"(da), "l"(db), "r"(sd));
}

constexpr int STAGE_BYTES = 49152, NSTAGE = 4;
constexpr int GEMM_SMEM = NSTAGE * STAGE_BYTES + 128;

struct GemmSmem { uint32_t st, full, empty; };
__device__ __forceinline__ GemmSmem gemm_setup(uint8_t* raw) {
    GemmSmem g;
    g.st = smem_u32(raw);
    if (g.st & 1023) __trap();
    g.full = g.st + NSTAGE * STAGE_BYTES; g.empty = g.full + 64;
    if (threadIdx.x == 0) {
        for (int s = 0; s < NSTAGE; s++) { mbar_init(g.full + 8 * s, 1); mbar_init(g.empty + 8 * s, 2); }
        asm volatile("fence.mbarrier_init.release.cluster;" ::: "memory");
        asm volatile("fence.proxy.async.shared::cta;" ::: "memory");
    }
    __syncthreads();
    return g;
}
__device__ __forceinline__ void mbar_arrive_one(uint32_t bar, uint32_t who) {
    asm volatile("{\n.reg .pred p;\nsetp.eq.u32 p, %1, 0;\n@p mbarrier.arrive.shared::cta.b64 _, [%0];\n}" ::"r"(bar), "r"(who) : "memory");
}
template <int BM, int BN, int KPS, typename ACC>
__device__ __forceinline__ void gemm_stage(ACC& acc, uint32_t stage, int wg, bool first) {
    const uint64_t da = desc_sw128(stage + wg * 8192, 16, 1024);
    const uint64_t db = desc_sw128(stage + KPS * BM * 128, 8192, 1024);
    wg_fence();
#pragma unroll
    for (int k = 0; k < 4 * KPS; k++) {
        const uint64_t a = da + (k >> 2) * (BM * 8) + (k & 3) * 2, b = db + k * 128;
        if constexpr (BN == 256) wgmma_n256(acc, a, b, first && k == 0 ? 0 : 1);
        else if constexpr (BN == 128) wgmma_n128(acc, a, b, first && k == 0 ? 0 : 1);
        else wgmma_n64(acc, a, b, first && k == 0 ? 0 : 1);
    }
    wg_commit();
}

__device__ __forceinline__ void kv_store_unit(const uint32_t (&pk)[64], int u, bf16* dst, int t) {
    const int G = (u >> 2) * 2 + (u & 1), hh = (u >> 1) & 1;
    uint32_t r0 = pk[(4 * G + 0) * 2 + hh], r1 = pk[(4 * G + 1) * 2 + hh], r2 = pk[(4 * G + 2) * 2 + hh], r3 = pk[(4 * G + 3) * 2 + hh];
    quad_transpose(r0, r1, r2, r3, t);
#define KVST ".cs"
    asm volatile("st.global" KVST ".v4.u32 [%0], {%1,%2,%3,%4};" ::"l"(dst + (size_t)hh * 8 * 8192 + G * 32), "r"(r0), "r"(r1), "r"(r2), "r"(r3) : "memory");
}

__device__ __forceinline__ uint32_t near_page(int pair, int line) {
    uint32_t best[2] = {~0u, ~0u};
#pragma unroll 1
    for (int i = 0; i < 16; i++) {
        uint32_t t0, t1, v;
        asm volatile("mov.u32 %0, %%clock;" : "=r"(t0)::"memory");
        asm volatile("atom.relaxed.gpu.global.or.b32 %0, [%1], -1;" : "=r"(v) : "l"(g_x + pair * 1024 + (i & 1) * 512 + line * 16) : "memory");
        asm volatile("{\n.reg .pred p;\nsetp.ne.u32 p, %1, 0x12345;\nmov.u32 %0, -1;\n@p mov.u32 %0, %%clock;\n}" : "=r"(t1) : "r"(v) : "memory");
        if (i & 1) best[1] = min(best[1], t1 - t0); else best[0] = min(best[0], t1 - t0);
    }
    return best[1] < best[0];
}
__device__ __forceinline__ void map_pages(int c) {
    uint32_t smid;
    asm("mov.u32 %0, %%smid;" : "=r"(smid));
    const uint32_t side = near_page(0, c & 31);
    g_side[smid & 255] = side;
    for (int p = c; p < XPAIRS; p += 132) g_home[p] = near_page(p, 0) ^ side;
}

__global__ void __launch_bounds__(384, 1)
k_kv(const __grid_constant__ CUtensorMap mx, const __grid_constant__ CUtensorMap mwk, const __grid_constant__ CUtensorMap mwv,
     const bf16* __restrict__ Wq, const bf16* __restrict__ Wo) {
    extern __shared__ __align__(1024) uint8_t smem_gemm[];
    const int c = blockIdx.x;
    if (threadIdx.x == 0) TL(0, 0);
    if (c >= 128) {
        const int i0 = (c - 128) * 384 + threadIdx.x;
        const uint4 ones = make_uint4(~0u, ~0u, ~0u, ~0u);
        if (threadIdx.x == 32) map_pages(c);
        for (int i = i0; i < XPAIRS * 512; i += 4 * 384) reinterpret_cast<uint4*>(g_x)[i] = ones;
        if (i0 < 256) g_flag[i0] = 0;
        if (threadIdx.x == 0) {
            const char* p = (const char*)(c < 130 ? Wq : Wo) + (size_t)(c & 1) * (4 << 20);
            for (int i = 0; i < 256; i++) {
                asm volatile("cp.async.bulk.prefetch.L2.global [%0], 16384;" ::"l"(p + i * 16384) : "memory");
                __nanosleep(40);
            }
        }
        if (threadIdx.x == 0) TL(0, 1);
        return;
    }
    GemmSmem g = gemm_setup(smem_gemm);
    const int m0 = (c & 15) * 128, nb0 = c >> 4;
    const int wg = __shfl_sync(~0u, threadIdx.x >> 7, 0);
    if (wg == 0) {
        asm volatile("setmaxnreg.dec.sync.aligned.u32 40;");
        if (threadIdx.x == 0) {
            for (int it = 0; it < 64; it++) {
                const int s = it & 3, tile = it >> 4, kb = it & 15;
                mbar_wait(g.empty + 8 * s, ((it >> 2) & 1) ^ 1);
                mbar_expect_tx(g.full + 8 * s, STAGE_BYTES);
                const int nb = nb0 + 8 * tile;
                tma2d(g.st + s * STAGE_BYTES, &mx, kb * 64, m0, g.full + 8 * s);
                tma3d(g.st + s * STAGE_BYTES + 16384, nb < 16 ? &mwk : &mwv, 0, kb * 64, (nb & 15) * 4, g.full + 8 * s);
            }
        } else if (threadIdx.x == 32) map_pages(c);
    } else {
        asm volatile("setmaxnreg.inc.sync.aligned.u32 232;");
        const int cw = wg - 1, lane = threadIdx.x & 31, t = lane & 3;
        const int row = m0 + cw * 64 + ((threadIdx.x >> 5) & 3) * 16 + (lane >> 2);
        bf16* dst = g_kv + (size_t)row * 8192 + nb0 * 256 + t * 8;
        float acc[128];
        uint32_t pk[64];
#pragma unroll 1
        for (int tile = 0; tile < 4; tile++) {
#pragma unroll
            for (int kb = 0; kb < 16; kb++) {
                mbar_wait_u(g.full + 8 * (kb & 3), (kb >> 2) & 1);
                gemm_stage<128, 256, 1>(acc, g.st + (kb & 3) * STAGE_BYTES, cw, kb == 0);
                if (tile > 0) kv_store_unit(pk, kb, dst + (tile - 1) * 2048, t);
                if (kb > 0) {
                    wg_wait<1>();
                    mbar_arrive_one(g.empty + 8 * ((kb - 1) & 3), threadIdx.x & 127);
                }
            }
            wg_wait<0>();
            mbar_arrive_one(g.empty + 8 * 3, threadIdx.x & 127);
#pragma unroll
            for (int i = 0; i < 64; i++) pk[i] = pack2(acc[2 * i], acc[2 * i + 1]);
        }
        if (threadIdx.x == 128) TL(0, 2);
#pragma unroll
        for (int u = 0; u < 16; u++) kv_store_unit(pk, u, dst + 3 * 2048, t);
        if (threadIdx.x == 128) TL(0, 1);
    }
}

constexpr int NS1 = 31;
#define RB1 4
#define PFC 4
constexpr int C_W1 = 0;
constexpr int C_W2 = C_W1 + 8 * NS1 * 512;
constexpr int C_KV = C_W2 + 14 * 8 * 512;
constexpr int C_RED = C_KV + 16384;
constexpr int C_R3 = C_RED + 64 * 272;
constexpr int C_QKV = C_R3 + 2560;
constexpr int C_SC = C_RED;
constexpr int C_OB = C_SC + 2 * 8 * 52 * 4;
constexpr int C_BAR = C_QKV + 3 * 8 * 272;
__host__ __device__ constexpr int smem_idx(int ks, int j) {
    return ks == 0 ? j : ks < 3 ? (j < 4 ? 4 + 4 * ks + j : -1) : (j < 3 ? 7 + 3 * ks + j : -1);
}
constexpr int CHAIN_SMEM = C_BAR + 64;
#define TS(i)

#define DLY3 3
#define DLY1 16
#define DLY0 8
#define DLY1A DLY1
#define DLY0A DLY0
#define DLYW 3
template <int N> __device__ __forceinline__ uint32_t delayed(uint32_t x, int lane) {
#pragma unroll
    for (int i = 0; i < N; i++) asm volatile("shfl.sync.idx.b32 %0, %0, %1, 31, -1;" : "+r"(x) : "r"(lane) : "memory");
    return x;
}
__device__ __forceinline__ void lds128v(uint32_t (&r)[4], uint32_t a) {
    asm volatile("ld.volatile.shared.v4.u32 {%0,%1,%2,%3}, [%4];" : "=r"(r[0]), "=r"(r[1]), "=r"(r[2]), "=r"(r[3]) : "r"(a) : "memory");
}
__device__ __forceinline__ uint2 lds64(uint32_t a) {
    uint2 v;
    asm volatile("ld.shared.v2.u32 {%0,%1}, [%2];" : "=r"(v.x), "=r"(v.y) : "r"(a) : "memory");
    return v;
}
#define LDQ ".L1::no_allocate"
__device__ __forceinline__ uint4 ldw128(const void* p) {
    uint4 v;
    asm volatile("ld.global.nc" LDQ ".v4.u32 {%0,%1,%2,%3}, [%4];" : "=r"(v.x), "=r"(v.y), "=r"(v.z), "=r"(v.w) : "l"(p));
    return v;
}
__device__ __forceinline__ void fetch8(uint64_t (&d)[8], const void* src) {
#define P8_LD(i) "ld.relaxed.gpu.global.b64 %" #i ", [%8 + " #i " * 256];\n"
    asm volatile(P8_LD(0) P8_LD(1) P8_LD(2) P8_LD(3) P8_LD(4) P8_LD(5) P8_LD(6) P8_LD(7)
                 : "=&l"(d[0]), "=&l"(d[1]), "=&l"(d[2]), "=&l"(d[3]), "=&l"(d[4]), "=&l"(d[5]), "=&l"(d[6]), "=&l"(d[7]) : "l"(src) : "memory");
}
template <bool TAG> __device__ __forceinline__ void settle8(uint2 (&v)[8], uint64_t (&d)[8], const void* src, uint32_t tag) {
#define P8_X(i) "mov.b64 {x" #i ", _}, %" #i ";\n"
#define P8_HEAD "{\n.reg .pred p, q;\n.reg .u32 n, x0, x1, x2, x3, x4, x5, x6, x7, m0, m1;\nmov.u32 n, 0;\nCHECK:\n" \
                P8_X(0) P8_X(1) P8_X(2) P8_X(3) P8_X(4) P8_X(5) P8_X(6) P8_X(7)
#define P8_VOTE "vote.sync.all.pred p, p, -1;\n@p bra.uni DONE;\n"
#define P8_TAIL "add.u32 n, n, 1;\nsetp.lt.u32 p, n, 0x100000;\n@p bra.uni CHECK;\ntrap;\nDONE:\n}"
#define P8_OPS : "+l"(d[0]), "+l"(d[1]), "+l"(d[2]), "+l"(d[3]), "+l"(d[4]), "+l"(d[5]), "+l"(d[6]), "+l"(d[7]) : "l"(src), "r"(tag) : "memory"
#define P8_RT(i) "lop3.b32 m0, x" #i ", %9, 1, 0x28;\nsetp.ne.u32 q, m0, 0;\n@q " P8_LD(i)
#define P8_RS(i) "setp.eq.u32 q, x" #i ", 0xffffffff;\n@q " P8_LD(i)
    if (TAG)
        asm volatile(P8_HEAD "lop3.b32 m0, x0, x1, %9, 0x7e;\nlop3.b32 m1, x2, x3, %9, 0x7e;\nlop3.b32 m0, m0, x4, %9, 0xf6;\n"
                     "lop3.b32 m1, m1, x5, %9, 0xf6;\nlop3.b32 m0, m0, x6, %9, 0xf6;\nlop3.b32 m1, m1, x7, %9, 0xf6;\n"
                     "lop3.b32 m0, m0, m1, 1, 0xa8;\nsetp.eq.u32 p, m0, 0;\n" P8_VOTE
                     P8_RT(0) P8_RT(1) P8_RT(2) P8_RT(3) P8_RT(4) P8_RT(5) P8_RT(6) P8_RT(7) P8_TAIL P8_OPS);
    else
        asm volatile(P8_HEAD "max.u32 m0, x0, x1;\nmax.u32 m0, m0, x2;\nmax.u32 m1, x3, x4;\nmax.u32 m1, m1, x5;\nmax.u32 m0, m0, x6;\n"
                     "max.u32 m0, m0, x7;\nmax.u32 m0, m0, m1;\nsetp.ne.u32 p, m0, 0xffffffff;\n" P8_VOTE
                     P8_RS(0) P8_RS(1) P8_RS(2) P8_RS(3) P8_RS(4) P8_RS(5) P8_RS(6) P8_RS(7) P8_TAIL P8_OPS);
#pragma unroll
    for (int i = 0; i < 8; i++) { v[i].x = (uint32_t)d[i]; v[i].y = (uint32_t)(d[i] >> 32); }
}
__device__ __forceinline__ void sum8(float (&c)[4], const uint2 (&v)[8], uint32_t idn) {
    float d[4] = {0.f, 0.f, 0.f, 0.f};
    c[0] = c[1] = c[2] = c[3] = 0.f;
    mma16816(c, v[0].x, v[0].y, v[1].x, v[1].y, idn, idn);
    mma16816(d, v[2].x, v[2].y, v[3].x, v[3].y, idn, idn);
    mma16816(c, v[4].x, v[4].y, v[5].x, v[5].y, idn, idn);
    mma16816(d, v[6].x, v[6].y, v[7].x, v[7].y, idn, idn);
    c[0] += d[0]; c[1] += d[1]; c[2] += d[2]; c[3] += d[3];
}

__global__ void __cluster_dims__(3, 1, 1) __launch_bounds__(256, 1)
k_chain(const bf16* __restrict__ mem0, const bf16* __restrict__ Wq, const bf16* __restrict__ Wk, const bf16* __restrict__ Wv,
        const bf16* __restrict__ Wo, const __grid_constant__ CUtensorMap mkv) {
    extern __shared__ __align__(1024) uint8_t smem_chain[];
    const uint32_t sb = smem_u32(smem_chain);
    if (sb & 1023) __trap();
    const int w = __shfl_sync(~0u, threadIdx.x >> 5, 0), lane = __shfl_sync(~0u, threadIdx.x & 31, threadIdx.x & 31);
    const int tid = w * 32 + lane, g = lane >> 2, t = lane & 3;
    auto pin = [&](uint32_t x) { return delayed<1>(x, lane); };
    const int h = blockIdx.x / 3, r = blockIdx.x - 3 * h;
    const uint32_t bar_x = sb + C_BAR, bar_kv = sb + C_BAR + 8, bar_go = sb + C_BAR + 16, bar_w = sb + C_BAR + 24;
    asm volatile("griddepcontrol.launch_dependents;");
    const int tbase = r == 0 ? 0 : 1 + 21 * r, ntile = r == 0 ? 22 : 21;
    uint32_t side;
    asm("mov.u32 %0, %%smid;" : "=r"(side));
    side = g_side[side & 255] & 1;
    if (tid == 0 && r > 0) asm volatile("st.relaxed.gpu.global.u32 [%0], %1;" ::"l"(g_flag + 128 + 2 * h + r - 1), "r"(2 | side) : "memory");
    if (tid == 0) {
        mbar_init(bar_x, 8); mbar_init(bar_kv, 1); mbar_init(bar_go, 1); mbar_init(bar_w, 1);
        asm volatile("fence.mbarrier_init.release.cluster;" ::: "memory");
        asm volatile("fence.proxy.async.shared::cta;" ::: "memory");
        mbar_expect_tx(bar_w, 128 * 32 * ntile);
    }
    __syncthreads();
    asm volatile("barrier.cluster.arrive.relaxed.aligned;" ::: "memory");
    if (tid < 128)
        asm volatile("cp.async.bulk.shared::cluster.global.mbarrier::complete_tx::bytes [%0], [%1], %2, [%3];"
                     ::"r"(sb + C_W1 + tid * 720), "l"(Wo + (size_t)(h * 128 + tid) * DM + tbase * 16), "r"(32 * ntile), "r"(bar_w) : "memory");
    const int tile0 = tbase + 7 - w;
    const bool three = w >= (r == 0 ? 2 : 3);
    const uint32_t wa = pin(sb + tid * 16);
#define W1A(i) (wa + C_W1 + (i) * 4096)
#define W2A(x) (wa + C_W2 + ((x) < 8 ? (x) * 4096 : 32768 - 1024 + ((x) - 8) * 3072))
    uint32_t wo0[8][4], wr[64][4];
    {
        const bf16* W = (r == 0 ? Wq : r == 1 ? Wk : Wv) + (size_t)(128 * w + (lane >> 4)) * HD + h * 128 + 8 * (lane & 15);
        uint4 raw[8][8];
        auto fetch = [&](int ks) {
#pragma unroll
            for (int i = 0; i < 8; i++) raw[ks][i] = ldw128(W + (size_t)(16 * ks + 2 * i) * HD);
        };
        fetch(0); fetch(1); fetch(2); fetch(3);
        mbar_wait_u(bar_w, 0);
        const uint32_t p = sb + C_W1 + ((lane & 7) + (lane >> 4) * 8) * 720 + (7 - w) * 32 + ((lane >> 3) & 1) * 16;
#pragma unroll
        for (int ks = 0; ks < 8; ks++) {
            uint32_t a[4];
            ldsm4t(wo0[ks], p + ks * 16 * 720);
            ldsm4t(a, p + ks * 16 * 720 + 256);
            sts128(W2A(ks), a[0], a[1], a[2], a[3]);
            if (three) { ldsm4t(a, p + ks * 16 * 720 + 512); sts128(W2A(8 + ks), a[0], a[1], a[2], a[3]); }
        }
        __syncthreads();
        const uint32_t stg = sb + C_KV + w * 4096;
        const uint32_t rd = stg + ((lane & 6) + 8 * (lane & 1) + (lane >> 4)) * 256 + ((((lane >> 3) & 1) ^ (lane & 7)) << 4);
#pragma unroll
        for (int ks = 0; ks < 8; ks++) {
#pragma unroll
            for (int i = 0; i < 8; i++)
                sts128(stg + (2 * i + (lane >> 4)) * 256 + (((lane & 15) ^ (((2 * i) & 6) | (i >> 2))) << 4),
                       raw[ks][i].x, raw[ks][i].y, raw[ks][i].z, raw[ks][i].w);
            if (ks < 2) fetch(ks + 4);
            if (ks == 3 || ks == 5) fetch(ks / 2 + 5);
            __syncwarp();
#pragma unroll
            for (int j = 0; j < 8; j++) {
                if (smem_idx(ks, j) >= 0) {
                    uint32_t a[4];
                    ldsm4t(a, rd ^ (j << 5));
                    sts128(W1A(smem_idx(ks, j)), a[0], a[1], a[2], a[3]);
                } else ldsm4t(wr[8 * ks + j], rd ^ (j << 5));
            }
            __syncwarp();
        }
    }
    asm volatile("fence.proxy.async.shared::cta;" ::: "memory");
    __syncthreads();
    if (tid == 0) {
        mbar_expect_tx(bar_kv, 16384);
        tma3d(sb + C_KV, &mkv, 0, 0, 2 * h, bar_kv);
        tma3d(sb + C_KV + 8192, &mkv, 0, 0, 64 + 2 * h, bar_kv);
    }
    asm volatile("barrier.cluster.wait.aligned;" ::: "memory");

    auto publish_kvm = [&](int s) {
        uint32_t v[4];
        lds128(v, sb + C_QKV + (8 + (tid >> 4)) * 272 + (tid & 15) * 16);
        asm volatile("st.global.v4.u32 [%0], {%1,%2,%3,%4};"
                     ::"l"(g_kvm + (size_t)(s * 8 + ((tid >> 4) & 7)) * 8192 + (tid >> 7) * HD + h * 128 + (tid & 15) * 8),
                       "r"(v[0]), "r"(v[1]), "r"(v[2]), "r"(v[3]) : "memory");
        if (h == 0 && w == 6) asm volatile("st.relaxed.gpu.global.u32 [%0], %1;" ::"l"(g_flag + 98), "r"(s + 1) : "memory");
        if ((s & 3) == 3) {
            __syncthreads();
            if (w == 7) asm volatile("{\n.reg .pred p;\nsetp.eq.u32 p, %2, 0;\nfence.acq_rel.gpu;\n@p st.relaxed.gpu.global.u32 [%0], %1;\n}"
                                     ::"l"(g_flag + h), "r"(s + 1), "r"(lane) : "memory");
        }
    };
    const float sl2e = 0.08838834764831845f * 1.4426950408889634f;
    const uint32_t idn = pin(g == 2 * t ? 0x00003f80u : g == 2 * t + 1 ? 0x3f800000u : 0u);
    const uint32_t lm = pin(sb + (lane & 7) * 272 + (lane >> 3) * 16);
    const uint32_t sa = pin(sb + C_SC + (w & 1) * (8 * 52 * 4) + (2 * t * 52 + (w < 4 ? 32 : (w & 2) * 8) + g) * 4);
    const uint32_t sr = pin(sb + C_SC + (g * 52 + 8 * t) * 4), sr2 = pin(sb + C_SC + (g * 52 + 32 + 2 * t) * 4);
    uint32_t kva;
    {
        const int pos = (w & 2) * 8 + (lane & 15), row = (pos & 24) + ((pos + (pos >> 2 & 6)) & 7);
        const int key = 4 * (lane & 6) + (((lane & 7) + 2 * (lane >> 4)) & 7);
        kva = pin(w >= 4 ? sb + C_KV + (w & 1) * 4096 + row * 128 + (((lane >> 4) ^ (row & 7)) << 4)
                         : sb + C_KV + 8192 + (w >> 1) * 4096 + key * 128 + ((((w & 1) * 4 + ((lane >> 3) & 1)) ^ (key & 7)) << 4));
    }
    uint32_t buf0[8][4], ring[RB1][4];
    auto stage_w1 = [&]() {
#pragma unroll
        for (int i = 0; i < 8; i++) lds128v(buf0[i], W1A(i));
#pragma unroll
        for (int i = 0; i < RB1; i++) lds128v(ring[i], W1A(8 + i));
    };
    stage_w1();
    uint32_t psel, msel0, msel1;
    {
        const int j = r > 0 ? 2 * h + r - 1 : 0, tl = min(tile0 + 8 * lane, 63);
        uint32_t b;
        asm volatile("{\n.reg .pred p;\n.reg .u32 n;\nmov.u32 n, 0;\nAGAIN:\nld.relaxed.gpu.global.u32 %0, [%1];\nsetp.ne.u32 p, %0, 0;\n"
                     "vote.sync.all.pred p, p, -1;\n@p bra.uni DONE;\nadd.u32 n, n, 1;\nsetp.lt.u32 p, n, 0x100000;\n@p bra.uni AGAIN;\ntrap;\nDONE:\n}"
                     : "=&r"(b) : "l"(g_flag + 128 + tl) : "memory");
        psel = __ballot_sync(~0u, (g_home[lane == 3 ? j * 2 + ((w >> 1) & 1) : tl * 2 + (h >> 4)] ^ (lane == 3 ? side : b)) & 1);
        msel0 = __ballot_sync(~0u, (g_home[128 + lane * 4 + (w >> 1)] ^ side) & 1);
        msel1 = __ballot_sync(~0u, (g_home[256 + lane * 4 + (w >> 1)] ^ side) & 1);
        if (r > 0) {
            if (w < 4) asm volatile("prefetch.global.L2 [%0];" ::"l"(g_x + (128 + (1 + (w >> 1)) * 4 + (j >> 4)) * 1024 + (w & 1) * 512 + (j & 15) * 32 + lane) : "memory");
            if (w < 4) asm volatile("prefetch.global.L2 [%0];" ::"l"(g_x + j * 2048 + tid * 16) : "memory");
        }
    }
    uint2 bm[8];
#pragma unroll
    for (int ks = 0; ks < 8; ks++) {
        const uint32_t* p = (const uint32_t*)(mem0 + g * DM + (8 * w + ks) * 16) + t;
        const uint32_t x = __ldg(p), y = __ldg(p + 4);
        bm[ks] = make_uint2(__byte_perm(x, y, 0x5410), __byte_perm(x, y, 0x7632));
    }
    if (tid == 0) TL(1, 2);
#pragma unroll 1
    for (int s = 0;; s++) {
        TS(1);
        {
            float acc[8][4];
#pragma unroll
            for (int ks = 0; ks < 8; ks++) {
#pragma unroll
                for (int j = 0; j < 8; j++) {
                    const int i = smem_idx(ks, j) - 8;
                    if (ks == 0) {
                        acc[j][0] = acc[j][1] = acc[j][2] = acc[j][3] = 0.f;
                        mma16816(acc[j], buf0[j][0], buf0[j][1], buf0[j][2], buf0[j][3], bm[ks].x, bm[ks].y);
                    } else if (i >= 0) {
                        uint32_t(&a)[4] = ring[i % RB1];
                        mma16816(acc[j], a[0], a[1], a[2], a[3], bm[ks].x, bm[ks].y);
                        if (8 + i + RB1 < NS1) lds128v(a, W1A(8 + i + RB1));
                    } else {
                        const uint32_t(&a)[4] = wr[8 * ks + j];
                        mma16816(acc[j], a[0], a[1], a[2], a[3], bm[ks].x, bm[ks].y);
                    }
                }
            }
#pragma unroll
            for (int c = 0; c < 4; c++)
                stsm4t(lm + C_RED + w * 2176 + c * 64, pack2(acc[2 * c][0], acc[2 * c][1]), pack2(acc[2 * c][2], acc[2 * c][3]),
                       pack2(acc[2 * c + 1][0], acc[2 * c + 1][1]), pack2(acc[2 * c + 1][2], acc[2 * c + 1][3]));
        }
        {
            const uint32_t a = sb + C_RED + w * 272 + lane * 8;
            if (s < NSEG - 1) mbar_wait_u(bar_kv, s & 1);
            TS(2);
            __syncthreads();
            TS(3);
            uint2 v[8];
#pragma unroll
            for (int i = 0; i < 8; i++) v[i] = lds64(a + i * 2176);
            float c[4];
            sum8(c, v, idn);
            const uint32_t p0 = pack2(c[0], c[1]), p1 = pack2(c[2], c[3]);
            const uint32_t dst = sb + C_QKV + (r * 8 + w) * 272 + lane * 8;
#pragma unroll
            for (int i = 1; i < 3; i++) {
                const uint32_t peer = r + i >= 3 ? r + i - 3 : r + i;
                uint32_t rd, rb;
                asm("mapa.shared::cluster.u32 %0, %1, %2;" : "=r"(rd) : "r"(dst), "r"(peer));
                asm("mapa.shared::cluster.u32 %0, %1, %2;" : "=r"(rb) : "r"(bar_x), "r"(peer));
                asm volatile("st.async.weak.shared::cluster.mbarrier::complete_tx::bytes.v2.b32 [%0], {%1,%2}, [%3];"
                             ::"r"(rd), "r"(p0), "r"(p1), "r"(rb) : "memory");
            }
            sts64(dst, p0, p1);
            __syncwarp();
            asm volatile("{\n.reg .pred p;\nsetp.eq.u32 p, %1, 0;\n@p mbarrier.arrive.expect_tx.shared::cta.b64 _, [%0], 512;\n}"
                         ::"r"(bar_x), "r"(lane) : "memory");
        }
        TS(4);
        if (s == NSEG - 1) break;
        uint32_t wb[8][4], wc[8][4];
        const uint32_t po = (tile0 * 2 + (h >> 4)) * 8192 + (h & 15) * 256 + lane * 8;
        const uint32_t tag = s & 1;
        auto project = [&](const uint32_t(&wt)[8][4], const uint32_t(&ob)[4][4], int i) {
            float c0[4] = {0.f, 0.f, 0.f, 0.f}, c1[4] = {0.f, 0.f, 0.f, 0.f};
#pragma unroll
            for (int ks = 0; ks < 8; ks++)
                mma16816((ks & 1) ? c1 : c0, wt[ks][0], wt[ks][1], wt[ks][2], wt[ks][3], ob[ks >> 1][(ks & 1) * 2], ob[ks >> 1][(ks & 1) * 2 + 1]);
            st_rlx64((uint2*)((char*)g_x + po + i * 131072 + ((psel >> i) & 1) * 4096), (pack2(c0[0] + c1[0], c0[2] + c1[2]) & ~1u) | tag, pack2(c0[1] + c1[1], c0[3] + c1[3]));
        };
        if (w >= 4) {
            uint32_t ka[4][4];
#pragma unroll
            for (int ks = 0; ks < 4; ks++) ldsm4(ka[ks], kva ^ (ks << 5));
            const uint32_t qa = lm + C_QKV + (w & 1) * 128;
            TS(5);
            mbar_wait_u(bar_x, s & 1);
            TS(6);
            {
                uint32_t qb[2][4];
                ldsm4(qb[0], qa);
                ldsm4(qb[1], qa + 64);
                float c0[4] = {0.f, 0.f, 0.f, 0.f}, c1[4] = {0.f, 0.f, 0.f, 0.f};
                mma16816(c0, ka[0][0], ka[0][1], ka[0][2], ka[0][3], qb[0][0], qb[0][1]);
                mma16816(c1, ka[1][0], ka[1][1], ka[1][2], ka[1][3], qb[0][2], qb[0][3]);
                mma16816(c0, ka[2][0], ka[2][1], ka[2][2], ka[2][3], qb[1][0], qb[1][1]);
                mma16816(c1, ka[3][0], ka[3][1], ka[3][2], ka[3][3], qb[1][2], qb[1][3]);
                sts32f(sa, c0[0] + c1[0]);
                sts32f(sa + 208, c0[1] + c1[1]);
                sts32f(sa + 32, c0[2] + c1[2]);
                sts32f(sa + 240, c0[3] + c1[3]);
            }
            __syncthreads();
            TS(7);
            if (w == 7 && s + 1 < NSEG - 1) {
                if (lane == 0) {
                    mbar_expect_tx(bar_kv, 16384);
                    tma3d(sb + C_KV, &mkv, 0, (s + 1) * 32, 2 * h, bar_kv);
                    tma3d(sb + C_KV + 8192, &mkv, 0, (s + 1) * 32, 64 + 2 * h, bar_kv);
                }
                __syncwarp();
            }
            const uint32_t wd = delayed<DLYW>(wa, lane);
#pragma unroll
            for (int i = 0; i < 8; i++) lds128(wb[i], wd + C_W2 + i * 4096);
#pragma unroll
            for (int i = 0; i < PFC; i++) lds128(wc[i], wd + C_W2 + 32768 - 1024 + i * 3072);
            TS(8);
            __syncthreads();
            TS(9);
            uint32_t ob[4][4];
#pragma unroll
            for (int i = 0; i < 4; i++) ldsm4(ob[i], lm + C_OB + i * 64);
#pragma unroll
            for (int i = PFC; i < 8; i++) lds128(wc[i], W2A(8 + i));
            project(wb, ob, 1);
            project(wo0, ob, 0);
            project(wc, ob, 2);
        } else {
            uint32_t va[4][4];
#pragma unroll
            for (int i = 0; i < 4; i++) ldsm4t(va[i], kva ^ (((i >> 1) << 5) | ((i & 1) * 0x240)));
#pragma unroll
            for (int i = 0; i < 8; i++) lds128(wb[i], W2A(i));
            const uint32_t qa = lm + C_QKV + (w & 1) * 128, oa = lm + w * 64;
            TS(5);
            mbar_wait_u(bar_x, s & 1);
            TS(6);
            if (w < 2) {
                uint32_t qb[2][4], km[2][4];
                ldsm4(qb[0], qa);
                ldsm4(km[0], qa + 8 * 272);
                ldsm4(qb[1], qa + 64);
                ldsm4(km[1], qa + 8 * 272 + 64);
                float c0[4] = {0.f, 0.f, 0.f, 0.f}, c1[4] = {0.f, 0.f, 0.f, 0.f};
                mma16816(c0, km[0][0], km[0][1], km[0][2], km[0][3], qb[0][0], qb[0][2]);
                mma16816(c1, km[0][0], km[0][1], km[0][2], km[0][3], qb[0][1], qb[0][3]);
                mma16816(c0, km[1][0], km[1][1], km[1][2], km[1][3], qb[1][0], qb[1][2]);
                mma16816(c1, km[1][0], km[1][1], km[1][2], km[1][3], qb[1][1], qb[1][3]);
                sts32f(sa, c0[0] + c1[2]);
                sts32f(sa + 208, c0[1] + c1[3]);
            }
            __syncthreads();
            TS(7);
            {
                float4 x0 = lds128f(sr), y0 = lds128f(sr + 1664), x1 = lds128f(sr + 16), y1 = lds128f(sr + 1680);
                float2 x2 = lds64f(sr2), y2 = lds64f(sr2 + 1664);
                float p[10] = {x0.x + y0.x, x0.y + y0.y, x0.z + y0.z, x0.w + y0.w, x1.x + y1.x,
                               x1.y + y1.y, x1.z + y1.z, x1.w + y1.w, x2.x + y2.x, x2.y + y2.y};
                float m = fmaxf(fmaxf(fmaxf(p[0], p[1]), fmaxf(p[2], p[3])), fmaxf(fmaxf(fmaxf(p[4], p[5]), fmaxf(p[6], p[7])), fmaxf(p[8], p[9])));
                const float m1 = __shfl_xor_sync(~0u, m, 1), m2 = __shfl_xor_sync(~0u, m, 2), m3 = __shfl_xor_sync(~0u, m, 3);
                uint32_t vm[4];
                ldsm4t(vm, oa + C_QKV + 16 * 272);
                m = fmaxf(fmaxf(m, m1), fmaxf(m2, m3));
                const float ms = m * sl2e;
#pragma unroll
                for (int i = 0; i < 10; i++) p[i] = ex2(fmaf(p[i], sl2e, -ms));
                const uint32_t b0 = pack2(p[0], p[1]), b1 = pack2(p[2], p[3]), b2 = pack2(p[4], p[5]), b3 = pack2(p[6], p[7]), b4 = pack2(p[8], p[9]);
                const uint32_t one = 0x3f803f80u;
                float o0[4] = {0.f, 0.f, 0.f, 0.f}, o1[4] = {0.f, 0.f, 0.f, 0.f}, sm[4] = {0.f, 0.f, 0.f, 0.f};
                mma16816(sm, one, one, one, one, b0, b1);
                mma16816(o0, va[0][0], va[0][1], va[0][2], va[0][3], b0, b1);
                mma16816(o1, va[2][0], va[2][1], va[2][2], va[2][3], b0, b1);
                mma16816(sm, one, one, one, one, b2, b3);
                mma16816(o0, va[1][0], va[1][1], va[1][2], va[1][3], b2, b3);
                mma16816(o1, va[3][0], va[3][1], va[3][2], va[3][3], b2, b3);
                mma1688(sm, one, one, b4);
                mma1688(o0, vm[0], vm[1], b4);
                mma1688(o1, vm[2], vm[3], b4);
                float i0, i1;
                asm("rcp.approx.ftz.f32 %0, %1;" : "=f"(i0) : "f"(sm[0]));
                asm("rcp.approx.ftz.f32 %0, %1;" : "=f"(i1) : "f"(sm[1]));
                stsm4t(oa + C_OB, pack2(o0[0] * i0, o0[1] * i1), pack2(o0[2] * i0, o0[3] * i1),
                       pack2(o1[0] * i0, o1[1] * i1), pack2(o1[2] * i0, o1[3] * i1));
            }
            TS(8);
            __syncthreads();
            TS(9);
            uint32_t ob[4][4];
#pragma unroll
            for (int i = 0; i < 4; i++) ldsm4(ob[i], lm + C_OB + i * 64);
            if (three) {
#pragma unroll
                for (int i = 0; i < 8; i++) lds128(wc[i], W2A(8 + i));
                project(wb, ob, 1);
                project(wo0, ob, 0);
                project(wc, ob, 2);
            } else {
                project(wb, ob, 1);
                project(wo0, ob, 0);
            }
        }
        TS(10);
        __syncthreads();
        uint32_t eo = (128 + (s + 1) * 4 + (w >> 1)) * 8192 + (((s < 31 ? msel0 : msel1) >> ((s + 1) & 31)) & 1) * 4096 + (w & 1) * 2048 + lane * 8;
        uint64_t d[8];
        if (r == 0) {
            TS(11); TS(12);
            stage_w1();
            publish_kvm(s);
            mbar_wait_u(bar_go, s & 1);
            if (w < 4) eo = delayed<DLY0>(eo, lane); else eo = delayed<DLY0A>(eo, lane);
        } else {
            const int j = 2 * h + r - 1;
            if (w < 4) {
                const char* src = (const char*)g_x + delayed<DLY3>((j * 2 + (w >> 1)) * 8192 + (psel & 8) * 512 + (w & 1) * 2048 + lane * 8, lane);
                fetch8(d, src);
                const uint32_t a = pin(sb + C_R3 + w * 640 + t * 160 + g * 8), a2 = pin(sb + C_R3 + g * 80 + t * 16);
                stage_w1();
                uint2 v[8];
                settle8<true>(v, d, src, tag);
                TS(11);
                float c[4];
                sum8(c, v, idn);
                sts64f(a, c[0], c[1]);
                sts64f(a + 80, c[2], c[3]);
                __syncthreads();
                TS(12);
                if (w < 2) {
                    const float4 u0 = lds128f(a2), u1 = lds128f(a2 + 640), u2 = lds128f(a2 + 1280), u3 = lds128f(a2 + 1920);
                    st_rlx64(g_x + (128 + (s + 1) * 4 + (j >> 4)) * 1024 + w * 512 + (j & 15) * 32 + lane, pack2((u0.x + u1.x) + (u2.x + u3.x), (u0.y + u1.y) + (u2.y + u3.y)),
                             pack2((u0.z + u1.z) + (u2.z + u3.z), (u0.w + u1.w) + (u2.w + u3.w)));
                }
                eo = delayed<DLY1>(eo, lane);
            } else {
                if (w >= 6 && s + 3 < NSEG)
                    asm volatile("prefetch.global.L2 [%0];" ::"l"(g_x + (128 + (s + 3) * 4 + (j >> 4)) * 1024 + (w & 1) * 512 + (j & 15) * 32 + lane) : "memory");
                stage_w1();
                TS(11);
                __syncthreads();
                TS(12);
                if (w == 4 && r == 1)
                    asm volatile("{\n.reg .pred p;\n.reg .u32 a;\nelect.sync _|p, -1;\nmapa.shared::cluster.u32 a, %0, 0;\n"
                                 "@p mbarrier.arrive.relaxed.cluster.shared::cluster.b64 _, [a];\n}" ::"r"(bar_go) : "memory");
                eo = delayed<DLY1A>(eo, lane);
            }
        }
        { const int s_ = s; { const int s = s_ + 1; TS(0); } }
        fetch8(d, (const char*)g_x + eo);
        settle8<false>(bm, d, (const char*)g_x + eo, 0);
    }
    mbar_wait_u(bar_x, (NSEG - 1) & 1);
    if (r == 0) publish_kvm(NSEG - 1);
    asm volatile("barrier.cluster.arrive.relaxed.aligned;\nbarrier.cluster.wait.aligned;" ::: "memory");
}

constexpr int S4_US = 4368;
constexpr int S4_RS = 8848;
constexpr int S4_KS = 1296;
constexpr int S4_U = 0, S4_R = 16 * S4_US, S4_K = S4_R + 16 * S4_RS;
constexpr int S4_SMEM = S4_K + 16 * S4_KS;
constexpr int S4_SIG = 3104, S4_PK = 2 * S4_SIG;

struct cf { float r, i; };
__device__ __forceinline__ cf cmul(cf a, cf b) { return {fmaf(a.r, b.r, -a.i * b.i), fmaf(a.r, b.i, a.i * b.r)}; }
__device__ __forceinline__ cf cmulc(cf a, cf b) { return {fmaf(a.r, b.r, a.i * b.i), fmaf(a.i, b.r, -a.r * b.i)}; }
__device__ __forceinline__ cf csq(cf a) { const float t = a.r * a.i; return {fmaf(a.r, a.r, -a.i * a.i), t + t}; }
__device__ __forceinline__ cf cexp(float l2, float turns) {
    const float mag = ex2(l2), fr = (turns - rintf(turns)) * 6.283185307179586f;
    return {mag * __cosf(fr), mag * __sinf(fr)};
}
__device__ __forceinline__ void sts32(uint32_t a, uint32_t v) { asm volatile("st.shared.u32 [%0], %1;" ::"r"(a), "r"(v) : "memory"); }
__device__ __forceinline__ uint32_t lds16(uint32_t a) {
    uint32_t v;
    asm volatile("ld.shared.u16 %0, [%1];" : "=r"(v) : "r"(a) : "memory");
    return v;
}

template <int M0, int NQ>
__device__ __forceinline__ void s4_class(float (&acc)[16][4], uint32_t sig, uint32_t taps, int x0) {
    constexpr int D0 = M0 / 8, D1 = M0 == 32 ? 9 : 15;
    uint32_t R[D1 - D0 + 2];
#pragma unroll
    for (int D = D0 - 1; D <= D1; D++) {
        if (D < D0 || 8 * D - 7 >= 2 * M0) { R[D - D0 + 1] = 0; continue; }
        const int m = 8 * D + x0;
        uint32_t lo = lds16(taps + m * (2 * NQ)), hi = lds16(taps + (m - 1) * (2 * NQ));
        if (D == D0) { lo = m >= M0 ? lo : 0; hi = m > M0 ? hi : 0; }
        if (D == 2 * D0) { lo = m < 2 * M0 ? lo : 0; hi = m <= 2 * M0 ? hi : 0; }
        R[D - D0 + 1] = lo | (hi << 16);
    }
#pragma unroll
    for (int J = 0; 2 * J + D0 < 16; J++) {
        uint32_t a[4];
        ldsm4t(a, sig + J * 512);
#pragma unroll
        for (int D = D0; D <= D1; D++)
            if (2 * J + D < 16) mma16816(acc[2 * J + D], a[0], a[1], a[2], a[3], R[D - D0 + 1], R[D - D0]);
    }
}

__global__ void __launch_bounds__(512, 1)
k_s4(const bf16* __restrict__ u, const bf16* __restrict__ Are, const bf16* __restrict__ Aim, const bf16* __restrict__ Bre,
     const bf16* __restrict__ Bim, const bf16* __restrict__ Cre, const bf16* __restrict__ Cim, const bf16* __restrict__ logdt,
     const bf16* __restrict__ Dsk, bf16* __restrict__ out) {
    extern __shared__ __align__(16) uint8_t smem_s4[];
    const uint32_t sb = smem_u32(smem_s4);
    asm volatile("griddepcontrol.launch_dependents;");
    const int tid = threadIdx.x, w = __shfl_sync(~0u, tid >> 5, 0), lane = tid & 31, g = lane >> 2, t = lane & 3;
    if (tid == 0) TL(2, 0);
    const int d0 = blockIdx.x * 16;
    const int d = d0 + (w & 1) + ((w >> 1) & 3) * 4 + (w >> 3) * 2;
    const uint32_t tr_off = (lane & 15), tr_l = (lane >> 4) * 16;
    const uint32_t ur = sb + S4_U + w * S4_US, rs = sb + S4_R + w * S4_RS, kd = sb + S4_K + w * S4_KS;
    if (lane < 16) sts128(ur + lane * 16, 0, 0, 0, 0);
    {
        const int o = d * 128 + lane * 4;
        const uint2 ar = __ldg((const uint2*)(Are + o)), ai = __ldg((const uint2*)(Aim + o)), br = __ldg((const uint2*)(Bre + o));
        const uint2 bi = __ldg((const uint2*)(Bim + o)), cr = __ldg((const uint2*)(Cre + o)), ci = __ldg((const uint2*)(Cim + o));
        const float dt = bf_round(expf(__bfloat162float(logdt[d])));
        const bf16* src = u + (size_t)(w * 128 + g) * DM + d0 + 4 * t;
        float T[5][4];
#pragma unroll
        for (int i = 0; i < 5; i++) T[i][0] = T[i][1] = T[i][2] = T[i][3] = 0.f;
        float klast = 0.f;
        const uint32_t wr_ = rs + lane * 4;
        const uint32_t ra = rs + (lane & 15) * 144 + (lane >> 4) * 16, rb = rs + (16 + (lane & 7)) * 144 + (lane >> 3) * 16;
#pragma unroll 1
        for (int c = 0; c < 4; c++) {
            uint2 v[4];
#pragma unroll
            for (int i = 0; i < 4; i++) v[i] = __ldg((const uint2*)(src + (size_t)(c * 32 + i * 8) * DM));
            auto pick = [&](const uint2& x) { const uint32_t y = c < 2 ? x.x : x.y; return (c & 1) ? bf_hi(y) : bf_lo(y); };
            auto put = [&](int row, cf x) { sts32(wr_ + row * 144, pack2(x.r, x.i)); };
            const float l2 = dt * pick(ar) * 1.4426950408889634f, tu = dt * pick(ai) * 0.15915494309189535f;
            const cf z1 = cexp(l2, tu), z2 = csq(z1), z4 = csq(z2), z8 = csq(z4), z128 = cexp(l2 * 128.f, tu * 128.f);
            cf a = z8;
            sts32(wr_, 0x00003f80u);
            put(1, a);
#pragma unroll
            for (int i = 2; i < 16; i++) { a = cmul(a, z8); put(i, a); }
            cf y = cmul({pick(cr), pick(ci)}, {dt * pick(br), dt * pick(bi)});
            y.i = -y.i;
#pragma unroll
            for (int k = 0; k < 16; k++) {
                const int n = k < 2 ? 8 : k < 4 ? 4 : k < 8 ? 2 : 1;
                const int row = 16 + (k < 2 ? 8 * k : k < 4 ? 8 + 4 * k : k < 8 ? 16 + 2 * k : 24 + k);
                cf x = y;
                put(row, x);
#pragma unroll
                for (int b = 1; b < n; b++) { x = cmulc(x, k < 2 ? z1 : k < 4 ? z2 : z4); put(row + b, x); }
                y = cmulc(y, z128);
            }
            klast += y.r;
            __syncwarp();
#pragma unroll
            for (int kp = 0; kp < 2; kp++) {
                uint32_t A0[4], A1[4];
                ldsm4(A0, ra + kp * 64);
                ldsm4(A1, ra + kp * 64 + 32);
#pragma unroll
                for (int i = 0; i < 5; i++) {
                    uint32_t B[4];
                    ldsm4(B, rb + i * 8 * 144 + kp * 64);
                    mma16816(T[i], A0[0], A0[1], A0[2], A0[3], B[0], B[1]);
                    mma16816(T[i], A1[0], A1[1], A1[2], A1[3], B[2], B[3]);
                }
            }
#pragma unroll
            for (int i = 0; i < 2; i++)
                stsm4t(sb + S4_U + tr_off * S4_US + 256 + (w * 128 + c * 32 + i * 16) * 2 + tr_l, v[2 * i].x, v[2 * i].y, v[2 * i + 1].x, v[2 * i + 1].y);
            __syncwarp();
        }
#pragma unroll
        for (int o2 = 16; o2; o2 >>= 1) klast += __shfl_xor_sync(~0u, klast, o2);
#pragma unroll
        for (int hh = 0; hh < 2; hh++) {
            const int i = g + 8 * hh;
            sts32(kd + (8 * i + 2 * t) * 2, pack2(T[0][2 * hh], T[0][2 * hh + 1]));
            sts32(kd + (128 + 8 * i + 2 * t) * 2, pack2(T[1][2 * hh], T[1][2 * hh + 1]));
            sts32(kd + (256 + 4 * i + 2 * (t & 1) + 64 * (t >> 1)) * 2, pack2(T[2][2 * hh], T[2][2 * hh + 1]));
            sts32(kd + (384 + 2 * i + 32 * t) * 2, pack2(T[3][2 * hh], T[3][2 * hh + 1]));
        }
        asm volatile("stmatrix.sync.aligned.m8n8.x2.trans.shared.b16 [%0], {%1,%2};"
                     ::"r"(kd + 1024 + (lane & 7) * 32 + ((lane >> 3) & 1) * 16), "r"(pack2(T[4][0], T[4][1])), "r"(pack2(T[4][2], T[4][3])) : "memory");
        if (lane == 0) sts32(kd + 1280, pack2(klast, 0.f));
    }
    __syncwarp();
    const uint32_t pk = rs + S4_PK + 64;
    {
#pragma unroll
        for (int i = 0; i < 2; i++) {
            const int x = i * 128 + lane * 4;
            const uint2 c = lds64(kd + x * 2);
            uint32_t p = lds16(kd + x * 2 - 2);
            if (x == 0) p = 0;
            sts128(pk + x * 4, __byte_perm(c.x, p, 0x5410), __byte_perm(c.x, 0, 0x1032), __byte_perm(c.y, c.x, 0x7610), __byte_perm(c.y, 0, 0x1032));
        }
#pragma unroll
        for (int i = 2; i < 4; i++) {
            const int x = i * 128 + lane * 4;
            const uint32_t ab = lds32(kd + 256 + x), c = lds16(kd + 256 + x + 4);
            const uint32_t p = x == 256 ? lds16(kd + 510) : ab;
            sts128(pk + x * 4, __byte_perm(ab, p, 0x5410), __byte_perm(ab, 0, 0x1010), __byte_perm(ab, 0, 0x1032), __byte_perm(c, ab, 0x7610));
        }
        const uint32_t v = lds16(kd + 768), v2 = lds16(kd + 1024);
        if (lane < 24) {
            uint32_t x0 = 0, x1 = 0, x2 = 0, x3 = 0;
            if (lane == 0) { x0 = x1 = x2 = v | (v << 16); x3 = v << 16; }
            if (lane == 12) x3 = v2;
            if (lane == 13) { x0 = v2 | (v2 << 16); x1 = v2 << 16; }
            sts128(lane < 20 ? pk + 2048 + lane * 16 : pk - 64 + (lane - 20) * 16, x0, x1, x2, x3);
        }
        if (lane < 4) sts128(rs + (lane >> 1) * S4_SIG + (lane & 1) * 16, 0, 0, 0, 0);
    }
    __syncthreads();
    float acc[16][4];
#pragma unroll
    for (int i = 0; i < 16; i++) acc[i][0] = acc[i][1] = acc[i][2] = acc[i][3] = 0.f;
    const uint32_t lf = (lane & 7) * 32 + ((lane >> 3) & 1) * 16 + (lane >> 4) * 256;
#pragma unroll
    for (int rg = 3; rg >= 2; rg--) {
#pragma unroll 1
        for (int it = 0; it < (rg == 3 ? 4 : 6); it++) {
            const int n = it * 32 + lane;
            uint32_t x[2][4];
            lds128(x[0], ur + 256 + n * 16 - 16);
            lds128(x[1], ur + 256 + n * 16);
            float e[16], p[15], s[11];
#pragma unroll
            for (int i = 0; i < 8; i++) { e[2 * i] = bf_lo(x[i >> 2][i & 3]); e[2 * i + 1] = bf_hi(x[i >> 2][i & 3]); }
#pragma unroll
            for (int i = 0; i < 15; i++) p[i] = e[i] + e[i + 1];
#pragma unroll
            for (int i = 0; i < 11; i++) s[i] = p[i + 3] + e[i + 5];
            const uint32_t o = rs + 16 + n * 16;
            if (rg == 2) sts128(o, pack2(s[0], s[1]), pack2(s[2], s[3]), pack2(s[4], s[5]), pack2(s[6], s[7]));
#pragma unroll
            for (int i = 0; i < 10; i++) s[i] = p[i + 2] + s[i + 1];
            if (rg == 2) {
                sts64(o + S4_SIG + 8, pack2(s[0], s[1]), pack2(s[2], s[3]));
                sts64(o + S4_SIG + 16, pack2(s[4], s[5]), pack2(s[6], s[7]));
            } else {
#pragma unroll
                for (int i = 0; i < 9; i++) s[i] = p[i + 1] + s[i + 1];
                sts64(o + 8, pack2(s[0], s[1]), pack2(s[2], s[3]));
                sts64(o + 16, pack2(s[4], s[5]), pack2(s[6], s[7]));
#pragma unroll
                for (int i = 0; i < 8; i++) s[i] = p[i] + s[i + 1];
                sts64(o + S4_SIG + 8, pack2(s[0], s[1]), pack2(s[2], s[3]));
                sts64(o + S4_SIG + 16, pack2(s[4], s[5]), pack2(s[6], s[7]));
            }
        }
        __syncwarp();
        if (rg == 3) {
#pragma unroll 1
            for (int q = 1; q <= 2; q++) s4_class<64, 2>(acc, rs + lf + (q == 1 ? 16 : S4_SIG), kd + (384 + q) * 2, g - 2 * t);
        } else {
#pragma unroll 1
            for (int q = 1; q <= 4; q++) s4_class<32, 4>(acc, rs + lf + ((q & 1) ? 0 : S4_SIG) + (q < 3 ? 16 : 0), kd + (256 + q) * 2, g - 2 * t);
        }
        __syncwarp();
    }
    {
        const uint32_t ub = ur + 256 + lf, kb = pk + (g - 2 * t) * 4;
#pragma unroll 1
        for (int j0 = 0; j0 < 8; j0++) {
            uint32_t B[8][4];
#pragma unroll
            for (int i = 0; i < 8; i++) ldsm4(B[i], ub + i * 512 - j0 * 32);
            auto block = [&](int J, uint32_t a) {
                const uint32_t r0 = lds32(a), rp = lds32(a + 32), rm = lds32(a - 32), r3 = lds32(a);
#pragma unroll
                for (int I = J; I < 16; I++)
                    mma16816(acc[I], r0, rp, rm, r3, B[(I - J) >> 1][((I - J) & 1) * 2], B[(I - J) >> 1][((I - J) & 1) * 2 + 1]);
            };
#pragma unroll
            for (int J = 0; J < 4; J++) block(J, kb + j0 * 64 + J * 512);
            if (j0 < 2) { block(4, kb + j0 * 64 + 2048); block(8, kb + j0 * 64 + (544 + 16) * 4); }
        }
        __syncwarp();
#pragma unroll
        for (int i = 0; i < 8; i++)
            stsm4t(rs + lf + i * 512, pack2(acc[2 * i][0], acc[2 * i][1]), pack2(acc[2 * i][2], acc[2 * i][3]),
                   pack2(acc[2 * i + 1][0], acc[2 * i + 1][1]), pack2(acc[2 * i + 1][2], acc[2 * i + 1][3]));
    }
    __syncthreads();
    {
        const uint2 dv = __ldg((const uint2*)(Dsk + d0 + 4 * t));
        bf16* dst = out + (size_t)(w * 128 + g) * 2048 + 1024 + d0 + 4 * t;
#pragma unroll
        for (int i = 0; i < 8; i++) {
            uint32_t y[4], x[4], o[4];
            ldsm4t(y, sb + S4_R + tr_off * S4_RS + (w * 128 + i * 16) * 2 + tr_l);
            ldsm4t(x, sb + S4_U + tr_off * S4_US + 256 + (w * 128 + i * 16) * 2 + tr_l);
#pragma unroll
            for (int j = 0; j < 4; j++)
                asm("{\n.reg .b32 s;\nmul.rn.bf16x2 s, %2, %3;\nadd.rn.bf16x2 %0, %1, s;\n}" : "=r"(o[j]) : "r"(y[j]), "r"(x[j]), "r"((j & 1) ? dv.y : dv.x));
            *reinterpret_cast<uint2*>(dst + (size_t)(i * 16) * 2048) = make_uint2(o[0], o[1]);
            *reinterpret_cast<uint2*>(dst + (size_t)(i * 16 + 8) * 2048) = make_uint2(o[2], o[3]);
        }
    }
    if (tid == 0) TL(2, 1);
}

enum { IT_QA = 0, IT_W256 = 1, IT_W128 = 2, IT_W64 = 3, IT_W64S = 4, IT_END = 7 };
struct BgParams { CUtensorMap mx, mwq, mkv4, mkvm, mo, mo2, mo2s, mwo4, mwo2, mwo1, mos; };
#define LOOK 2
#define LOOKL 5
#define P256 46
#define P128 53
__device__ __forceinline__ uint32_t ld_rlx32(const uint32_t* p) {
    uint32_t v;
    asm volatile("ld.relaxed.gpu.global.u32 %0, [%1];" : "=r"(v) : "l"(p) : "memory");
    return v;
}
struct Sched { uint32_t qb = 0, w0 = 0, w1 = 0; };
__device__ __forceinline__ int next_item(Sched& z) {
    for (int n = 0; n < SPIN_LIMIT; n++) {
        if (z.w0 < z.w1 && (z.qb >= 16 || ld_rlx32(g_flag + 64 + min(z.w0 >> 4, 15u)) >= 16)) {
            const uint32_t i = z.w0, k = i >= 240 ? 1 : z.w1 - i >= 4 && !(i & 3) ? 4 : z.w1 - i >= 2 && !(i & 1) ? 2 : 1;
            z.w0 += k;
            if (i >= 240) return IT_W64S | 15 << 3 | (i - 240) << 7;
            return (k == 4 ? IT_W256 : k == 2 ? IT_W128 : IT_W64) | (i >> 4) << 3 | ((i & 15) / k) << 7;
        }
        const uint32_t prog = ld_rlx32(g_flag + 98), wo = ld_rlx32(g_flag + 97);
        z.qb = max(z.qb, ld_rlx32(g_flag + 96));
        if (z.qb < 16 && prog + (z.qb == 15 ? LOOKL : LOOK) >= 4 * z.qb + 4) {
            const uint32_t i = atomicAdd(g_flag + 80 + z.qb, 1);
            if (i == 15) atomicMax(g_flag + 96, z.qb + 1);
            if (i < 16) return IT_QA | z.qb << 3 | i << 7;
            z.qb++;
            continue;
        }
        if (z.w0 < z.w1) {
            if (z.qb >= 16) continue;
        } else if (wo >= 272) {
            if (z.qb >= 16) return IT_END;
        } else if (z.qb >= 16 || ld_rlx32(g_flag + 64 + min(wo >> 4, 15u)) >= 16) {
            const uint32_t k = prog <= P256 ? 4 : prog <= P128 ? 2 : 1;
            z.w0 = atomicAdd(g_flag + 97, k);
            z.w1 = min(z.w0 + k, 272u);
            continue;
        }
        __nanosleep(300);
    }
    __trap();
    return IT_END;
}
constexpr int B_OST = NSTAGE * STAGE_BYTES + 1024;
constexpr int BG_SMEM = B_OST + 32768;

template <int BM, int BN, int KPS, typename ACC>
__device__ __forceinline__ void gemm_mainloop(ACC& acc, const GemmSmem& g, int cw, int rounds, uint32_t& round) {
#pragma unroll
    for (int i = 0; i < BN / 2; i++) acc[i] = 0.f;
#pragma unroll 1
    for (int k0 = 0; k0 < rounds; k0++, round++) {
#pragma unroll
        for (int s = 0; s < 4; s++) {
            mbar_wait_u(g.full + 8 * s, round & 1);
            gemm_stage<BM, BN, KPS>(acc, g.st + s * STAGE_BYTES, cw, false);
            wg_wait<1>();
            if (s > 0 || k0 > 0) mbar_arrive_one(g.empty + 8 * ((s + 3) & 3), threadIdx.x & 127);
        }
    }
    wg_wait<0>();
    mbar_arrive_one(g.empty + 8 * 3, threadIdx.x & 127);
}

template <int BM, int BN, int KPS>
__device__ __forceinline__ void wo_item(const GemmSmem& g, int cw, uint32_t& round, bf16* dst, int t) {
    if (BM == 64 && cw == 1) {
#pragma unroll 1
        for (int k0 = 0; k0 < 16 / KPS; k0++, round++)
#pragma unroll
            for (int s = 0; s < 4; s++) { mbar_wait_u(g.full + 8 * s, round & 1); mbar_arrive_one(g.empty + 8 * s, threadIdx.x & 127); }
        return;
    }
    float acc[BN / 2];
    gemm_mainloop<BM, BN, KPS>(acc, g, cw, 16 / KPS, round);
#pragma unroll
    for (int G = 0; G < BN / 32; G++)
#pragma unroll
        for (int rr = 0; rr < 2; rr++) {
            uint32_t r0 = pack2(acc[16 * G + 2 * rr], acc[16 * G + 2 * rr + 1]), r1 = pack2(acc[16 * G + 4 + 2 * rr], acc[16 * G + 5 + 2 * rr]);
            uint32_t r2 = pack2(acc[16 * G + 8 + 2 * rr], acc[16 * G + 9 + 2 * rr]), r3 = pack2(acc[16 * G + 12 + 2 * rr], acc[16 * G + 13 + 2 * rr]);
            quad_transpose(r0, r1, r2, r3, t);
            *reinterpret_cast<uint4*>(dst + (size_t)rr * 8 * 2048 + G * 32) = make_uint4(r0, r1, r2, r3);
        }
}

template <int HF>
__device__ __forceinline__ void attend(const uint32_t* q, uint32_t st, int hh, uint32_t ost, int lane) {
    constexpr int NT = HF ? 5 : 3;
    const int r8 = lane & 7, m4 = lane >> 3, gq = lane >> 2, t = lane & 3;
    const float sl2e = 0.08838834764831845f * 1.4426950408889634f;
    const uint32_t la = r8 * 128 + ((m4 ^ r8) << 4);
    float sc[NT][4];
#pragma unroll
    for (int nt = 0; nt < NT; nt++) sc[nt][0] = sc[nt][1] = sc[nt][2] = sc[nt][3] = 0.f;
#pragma unroll
    for (int kp = 0; kp < 4; kp++)
#pragma unroll
        for (int nt = 0; nt < NT; nt++) {
            const int nb = hh * 2 + (kp >> 1);
            uint32_t b[4];
            ldsm4(b, (nt == 0 ? st + 32768 + nb * 1024 : st + nb * 4096 + (nt - 1) * 1024) + (la ^ ((kp & 1) << 6)));
            mma16816(sc[nt], q[kp * 8], q[kp * 8 + 1], q[kp * 8 + 2], q[kp * 8 + 3], b[0], b[1]);
            mma16816(sc[nt], q[kp * 8 + 4], q[kp * 8 + 5], q[kp * 8 + 6], q[kp * 8 + 7], b[2], b[3]);
        }
    const float ninf = -3.0e38f;
    if (2 * t > gq) sc[NT - 2][0] = sc[NT - 1][2] = ninf;
    if (2 * t + 1 > gq) sc[NT - 2][1] = sc[NT - 1][3] = ninf;
    sc[NT - 1][0] = sc[NT - 1][1] = ninf;
    uint32_t p[NT][2];
#pragma unroll
    for (int i = 0; i < 2; i++) {
        float m = fmaxf(sc[0][2 * i], sc[0][2 * i + 1]);
#pragma unroll
        for (int nt = 1; nt < NT - 1 + i; nt++) m = fmaxf(m, fmaxf(sc[nt][2 * i], sc[nt][2 * i + 1]));
        m = fmaxf(m, __shfl_xor_sync(~0u, m, 1));
        m = fmaxf(m, __shfl_xor_sync(~0u, m, 2));
        const float ms = m * sl2e;
        float sum = 0.f;
#pragma unroll
        for (int nt = 0; nt < NT - 1 + i; nt++) {
            sc[nt][2 * i] = ex2(fmaf(sc[nt][2 * i], sl2e, -ms));
            sc[nt][2 * i + 1] = ex2(fmaf(sc[nt][2 * i + 1], sl2e, -ms));
            sum += sc[nt][2 * i] + sc[nt][2 * i + 1];
        }
        sum += __shfl_xor_sync(~0u, sum, 1);
        sum += __shfl_xor_sync(~0u, sum, 2);
        float inv;
        asm("rcp.approx.ftz.f32 %0, %1;" : "=f"(inv) : "f"(sum));
#pragma unroll
        for (int nt = 0; nt < NT - 1 + i; nt++) p[nt][i] = pack2(sc[nt][2 * i] * inv, sc[nt][2 * i + 1] * inv);
    }
    p[NT - 1][0] = 0;
    const uint32_t lv = ((m4 & 1) * 8 + r8) * 128 + (((m4 >> 1) ^ r8) << 4);
#pragma unroll
    for (int G = 0; G < 4; G++) {
        const int nb = hh * 2 + (G >> 1);
        float o[4][4];
#pragma unroll
        for (int i = 0; i < 4; i++) o[i][0] = o[i][1] = o[i][2] = o[i][3] = 0.f;
        uint32_t b[4];
        ldsm4t(b, st + 36864 + nb * 1024 + (la ^ ((G & 1) << 6)));
#pragma unroll
        for (int i = 0; i < 4; i++) mma1688(o[i], p[0][0], p[0][1], b[i]);
#pragma unroll
        for (int kk = 0; kk <= HF; kk++)
#pragma unroll
            for (int i = 0; i < 2; i++) {
                ldsm4t(b, st + 16384 + nb * 4096 + kk * 2048 + (lv ^ (((G & 1) * 2 + i) << 5)));
                mma16816(o[2 * i], p[1 + 2 * kk][0], p[1 + 2 * kk][1], p[2 + 2 * kk][0], p[2 + 2 * kk][1], b[0], b[1]);
                mma16816(o[2 * i + 1], p[1 + 2 * kk][0], p[1 + 2 * kk][1], p[2 + 2 * kk][0], p[2 + 2 * kk][1], b[2], b[3]);
            }
#pragma unroll
        for (int i = 0; i < 2; i++)
            asm volatile("stmatrix.sync.aligned.m8n8.x4.shared.b16 [%0], {%1,%2,%3,%4};"
                         ::"r"(ost + (G >> 1) * 4096 + HF * 2048 + (lv ^ (((G & 1) * 2 + i) << 5))),
                           "r"(pack2(o[2 * i][0], o[2 * i][1])), "r"(pack2(o[2 * i][2], o[2 * i][3])),
                           "r"(pack2(o[2 * i + 1][0], o[2 * i + 1][1])), "r"(pack2(o[2 * i + 1][2], o[2 * i + 1][3])) : "memory");
    }
    asm volatile("fence.proxy.async.shared::cta;" ::: "memory");
    __syncwarp();
}

__device__ __forceinline__ void tma_prefetch3d(const CUtensorMap* m, int c0, int c1, int c2) {
    asm volatile("cp.async.bulk.prefetch.tensor.3d.L2.global [%0, {%1, %2, %3}];" ::"l"(m), "r"(c0), "r"(c1), "r"(c2) : "memory");
}

__global__ void __launch_bounds__(384, 1) k_bg(const __grid_constant__ BgParams P, bf16* __restrict__ out) {
    extern __shared__ __align__(1024) uint8_t smem_gemm[];
    const uint32_t xb = smem_u32(smem_gemm) + NSTAGE * STAGE_BYTES + 128;
    const uint32_t bar_item = xb, bar_o = xb + 16, slot = xb + 32, slot_o = xb + 40;
    if (threadIdx.x == 0) { mbar_init(bar_item, 1); mbar_init(bar_item + 8, 1); mbar_init(bar_o, 8); mbar_init(bar_o + 8, 8); }
    GemmSmem g = gemm_setup(smem_gemm);
    const int wg = __shfl_sync(~0u, threadIdx.x >> 7, 0);
    if (wg == 0) {
        asm volatile("setmaxnreg.dec.sync.aligned.u32 40;");
        if (threadIdx.x == 0) {
            uint32_t it = 0;
            Sched z;
            auto acquire = [&](uint32_t bytes) {
                const int s = it & 3;
                mbar_wait(g.empty + 8 * s, ((it >> 2) & 1) ^ 1);
                mbar_expect_tx(g.full + 8 * s, bytes);
                it++;
                return s;
            };
            for (int n = 0;; n++) {
                const int code = next_item(z);
                sts32(slot + (n & 1) * 4, code);
                mbar_arrive(bar_item + (n & 1) * 8);
                const int type = code & 7, blk = (code >> 3) & 15, idx = code >> 7, m0 = blk * 128;
                if (type == IT_END) {
                    mbar_wait(g.empty, ((it >> 2) & 1) ^ 1);
                    sts32(slot_o, IT_END);
                    for (int i = 0; i < 8; i++) mbar_arrive(bar_o);
                    break;
                }
                if (type == IT_QA) {
                    for (int k = 0; k < 16; k++) {
                        const int s = acquire(STAGE_BYTES);
                        const uint32_t st = g.st + s * STAGE_BYTES, fb = g.full + 8 * s;
                        tma2d(st, &P.mx, k * 64, m0, fb);
                        tma3d(st + 16384, &P.mwq, 0, k * 64, idx * 4, fb);
                        if (k >= 4 && k < 12) tma_prefetch3d(&P.mkv4, 0, m0 + (k & 3) * 32, (k & 8) * 8 + idx * 4);
                    }
                    bool ready = ld_acq32(g_flag + 2 * idx) >= 4 * blk + 4 && ld_acq32(g_flag + 2 * idx + 1) >= 4 * blk + 4;
                    if (ready) asm volatile("fence.proxy.async.global;" ::: "memory");
                    for (int pass = 0; pass < 2; pass++) {
                        for (int s = 0; s < 4; s++) {
                            const uint32_t st = g.st + s * STAGE_BYTES, fb = g.full + 8 * s;
                            if (pass == 0) {
                                acquire(40960);
                                tma3d(st, &P.mkv4, 0, m0 + s * 32, idx * 4, fb);
                                tma3d(st + 16384, &P.mkv4, 0, m0 + s * 32, 64 + idx * 4, fb);
                            }
                            if (ready) {
                                tma3d(st + 32768, &P.mkvm, 0, (blk * 4 + s) * 8, idx * 4, fb);
                                tma3d(st + 36864, &P.mkvm, 0, (blk * 4 + s) * 8, 64 + idx * 4, fb);
                            }
                        }
                        if (ready) break;
                        wait_flag(g_flag + 2 * idx, 4 * blk + 4);
                        wait_flag(g_flag + 2 * idx + 1, 4 * blk + 4);
                        asm volatile("fence.proxy.async.global;" ::: "memory");
                        ready = true;
                    }
                } else {
                    wait_flag(g_flag + 64 + blk, 16);
                    asm volatile("fence.proxy.async.global;" ::: "memory");
                    if (type <= IT_W128) {
                        const int nb = type == IT_W256 ? 4 : 2;
                        for (int k = 0; k < 64; k++) {
                            const int s = acquire(16384 + nb * 8192);
                            const uint32_t st = g.st + s * STAGE_BYTES, fb = g.full + 8 * s;
                            tma2d(st, &P.mo, k * 64, m0, fb);
                            tma3d(st + 16384, nb == 4 ? &P.mwo4 : &P.mwo2, 0, k * 64, idx * nb, fb);
                        }
                    } else {
                        const uint32_t ab = type == IT_W64 ? 32768 : 16384;
                        for (int k = 0; k < 32; k++) {
                            const int s = acquire(ab + 16384);
                            const uint32_t st = g.st + s * STAGE_BYTES, fb = g.full + 8 * s;
                            tma3d(st, type == IT_W64 ? &P.mo2 : &P.mo2s, 0, m0 + (idx >> 4) * 64, k * 2, fb);
                            tma3d(st + ab, &P.mwo1, 0, k * 128, idx & 15, fb);
                        }
                    }
                }
            }
        } else if (threadIdx.x == 32) {
            for (uint32_t n = 0;; n++) {
                mbar_wait(bar_o, n & 1);
                const int code = lds32(slot_o), blk = (code >> 3) & 15, idx = (code >> 7) & 31;
                if ((code & 7) == IT_END) break;
                for (int hh = 0; hh < 2; hh++) {
                    if (hh) mbar_wait(bar_o + 8, n & 1);
                    for (int s = 0; s < 4; s++)
                        asm volatile("cp.async.bulk.tensor.3d.global.shared::cta.bulk_group [%0, {%2, %3, %4}], [%1];"
                                     ::"l"(&P.mos), "r"(hh ? g.st + B_OST + s * 8192 : g.st + s * STAGE_BYTES + 40960),
                                       "r"(0), "r"(blk * 128 + s * 32), "r"(idx * 4 + hh * 2) : "memory");
                    asm volatile("cp.async.bulk.commit_group;" ::: "memory");
                }
                asm volatile("cp.async.bulk.wait_group.read 1;" ::: "memory");
                for (int s = 0; s < 8; s++) mbar_arrive(g.empty + 8 * (s >> 1));
                asm volatile("cp.async.bulk.wait_group 0;\nfence.acq_rel.gpu;\nred.relaxed.gpu.global.add.u32 [%0], 1;"
                             ::"l"(g_flag + 64 + blk) : "memory");
            }
        }
    } else {
        asm volatile("setmaxnreg.inc.sync.aligned.u32 232;");
        const int cw = wg - 1, ww = __shfl_sync(~0u, (threadIdx.x >> 5) & 3, 0), lane = threadIdx.x & 31;
        uint32_t round = 0;
#pragma unroll 1
        for (int n = 0;; n++) {
            mbar_wait_u(bar_item + (n & 1) * 8, (n >> 1) & 1);
            const int code = __shfl_sync(~0u, lds32(slot + (n & 1) * 4), 0);
            const int type = code & 7, blk = (code >> 3) & 15, idx = (code >> 7) & 31;
#define TLB(slot_)
            if (type == IT_END) break;
            TLB(0);
            if (type == IT_QA) {
                uint32_t q[64];
                {
                    float acc[128];
                    gemm_mainloop<128, 256, 1>(acc, g, cw, 4, round);
#pragma unroll
                    for (int i = 0; i < 64; i++) q[i] = pack2(acc[2 * i], acc[2 * i + 1]);
                }
                const int sg = cw * 2 + (ww >> 1);
                const uint32_t st = g.st + sg * STAGE_BYTES;
                if (threadIdx.x == 128) sts32(slot_o, code);
                TLB(2);
                mbar_wait_u(g.full + 8 * sg, round & 1);
                TLB(3);
                if (ww & 1) {
                    attend<1>(q, st, 0, st + 40960, lane);
                    mbar_arrive_one(bar_o, lane);
                    attend<1>(q + 32, st, 1, g.st + B_OST + sg * 8192, lane);
                } else {
                    attend<0>(q, st, 0, st + 40960, lane);
                    mbar_arrive_one(bar_o, lane);
                    attend<0>(q + 32, st, 1, g.st + B_OST + sg * 8192, lane);
                }
#pragma unroll
                for (int s = 0; s < 4; s++) mbar_wait_u(g.full + 8 * s, round & 1);
                round++;
                mbar_arrive_one(bar_o + 8, lane);
            } else {
                bf16* dst = out + (size_t)(blk * 128 + cw * 64 + ww * 16 + (lane >> 2)) * 2048 + (lane & 3) * 8;
                if (type == IT_W256) wo_item<128, 256, 1>(g, cw, round, dst + idx * 256, lane & 3);
                else if (type == IT_W128) wo_item<128, 128, 1>(g, cw, round, dst + idx * 128, lane & 3);
                else if (type == IT_W64) wo_item<128, 64, 2>(g, cw, round, dst + idx * 64, lane & 3);
                else wo_item<64, 64, 2>(g, cw, round, dst + (size_t)(idx >> 4) * 64 * 2048 + (idx & 15) * 64, lane & 3);
            }
            TLB(1);
        }
    }
}

typedef CUresult (*EncodeFn)(CUtensorMap*, CUtensorMapDataType, cuuint32_t, void*, const cuuint64_t*, const cuuint64_t*,
                             const cuuint32_t*, const cuuint32_t*, CUtensorMapInterleave, CUtensorMapSwizzle,
                             CUtensorMapL2promotion, CUtensorMapFloatOOBfill);

static void map2d(EncodeFn enc, CUtensorMap* m, const void* p, int rows, int cols, int box_rows) {
    cuuint64_t dim[2] = {(cuuint64_t)cols, (cuuint64_t)rows}, str[1] = {(cuuint64_t)cols * 2};
    cuuint32_t box[2] = {64, (cuuint32_t)box_rows}, es[2] = {1, 1};
    enc(m, CU_TENSOR_MAP_DATA_TYPE_BFLOAT16, 2, (void*)p, dim, str, box, es, CU_TENSOR_MAP_INTERLEAVE_NONE,
        CU_TENSOR_MAP_SWIZZLE_128B, CU_TENSOR_MAP_L2_PROMOTION_L2_256B, CU_TENSOR_MAP_FLOAT_OOB_FILL_NONE);
}
static void map3d(EncodeFn enc, CUtensorMap* m, const void* p, int rows, int cols, int box_rows, int nblk) {
    cuuint64_t dim[3] = {64, (cuuint64_t)rows, (cuuint64_t)cols / 64}, str[2] = {(cuuint64_t)cols * 2, 128};
    cuuint32_t box[3] = {64, (cuuint32_t)box_rows, (cuuint32_t)nblk}, es[3] = {1, 1, 1};
    enc(m, CU_TENSOR_MAP_DATA_TYPE_BFLOAT16, 3, (void*)p, dim, str, box, es, CU_TENSOR_MAP_INTERLEAVE_NONE,
        CU_TENSOR_MAP_SWIZZLE_128B, CU_TENSOR_MAP_L2_PROMOTION_L2_256B, CU_TENSOR_MAP_FLOAT_OOB_FILL_NONE);
}

#define USE_PDL 1

extern "C" void kernel_launch(void* const* d_in, const int* in_sizes, int n_in, void* d_out, int out_size) {
    const bf16 *x = (const bf16*)d_in[0], *mem0 = (const bf16*)d_in[1], *Wq = (const bf16*)d_in[2], *Wk = (const bf16*)d_in[3];
    const bf16 *Wv = (const bf16*)d_in[4], *Wo = (const bf16*)d_in[5];
    const bf16 *u = (const bf16*)d_in[7], *Are = (const bf16*)d_in[8], *Aim = (const bf16*)d_in[9], *Bre = (const bf16*)d_in[10];
    const bf16 *Bim = (const bf16*)d_in[11], *Cre = (const bf16*)d_in[12], *Cim = (const bf16*)d_in[13];
    const bf16 *logdt = (const bf16*)d_in[14], *Dsk = (const bf16*)d_in[15];
    bf16* out = (bf16*)d_out;

    void* fn = nullptr;
    cudaDriverEntryPointQueryResult qr;
    cudaGetDriverEntryPoint("cuTensorMapEncodeTiled", &fn, cudaEnableDefault, &qr);
    EncodeFn enc = (EncodeFn)fn;
    void *kv, *kvm, *o;
    cudaGetSymbolAddress(&kv, g_kv);
    cudaGetSymbolAddress(&kvm, g_kvm);
    cudaGetSymbolAddress(&o, g_o);
    CUtensorMap mwk, mwv, mkv2;
    BgParams P;
    map2d(enc, &P.mx, x, SEQ, DM, 128);
    map2d(enc, &P.mo, o, SEQ, HD, 128);
    map3d(enc, &P.mo2, o, SEQ, HD, 128, 2);
    map3d(enc, &P.mo2s, o, SEQ, HD, 64, 2);
    map3d(enc, &P.mos, o, SEQ, HD, 32, 2);
    map3d(enc, &P.mwq, Wq, DM, HD, 64, 4);
    map3d(enc, &mwk, Wk, DM, HD, 64, 4);
    map3d(enc, &mwv, Wv, DM, HD, 64, 4);
    map3d(enc, &P.mwo4, Wo, HD, DM, 64, 4);
    map3d(enc, &P.mwo2, Wo, HD, DM, 64, 2);
    map3d(enc, &P.mwo1, Wo, HD, DM, 128, 1);
    map3d(enc, &mkv2, kv, SEQ, 8192, 32, 2);
    map3d(enc, &P.mkv4, kv, SEQ, 8192, 32, 4);
    map3d(enc, &P.mkvm, kvm, NSEG * 8, 8192, 8, 4);
    cudaFuncSetAttribute(k_kv, cudaFuncAttributeMaxDynamicSharedMemorySize, GEMM_SMEM);
    cudaFuncSetAttribute(k_bg, cudaFuncAttributeMaxDynamicSharedMemorySize, BG_SMEM);
    cudaFuncSetAttribute(k_chain, cudaFuncAttributeMaxDynamicSharedMemorySize, CHAIN_SMEM);
    cudaFuncSetAttribute(k_s4, cudaFuncAttributeMaxDynamicSharedMemorySize, S4_SMEM);

    cudaStream_t st = cudaStreamPerThread;
    k_kv<<<132, 384, GEMM_SMEM, st>>>(P.mx, mwk, mwv, Wq, Wo);
    k_chain<<<96, 256, CHAIN_SMEM, st>>>(mem0, Wq, Wk, Wv, Wo, mkv2);
    cudaLaunchAttribute pdl[1];
    pdl[0].id = cudaLaunchAttributeProgrammaticStreamSerialization;
    pdl[0].val.programmaticStreamSerializationAllowed = 1;
    cudaLaunchConfig_t cfg = {};
    cfg.stream = st; cfg.attrs = pdl; cfg.numAttrs = USE_PDL;
    cfg.gridDim = dim3(64); cfg.blockDim = dim3(512); cfg.dynamicSmemBytes = S4_SMEM;
    cudaLaunchKernelEx(&cfg, k_s4, u, Are, Aim, Bre, Bim, Cre, Cim, logdt, Dsk, out);
    cfg.gridDim = dim3(132); cfg.blockDim = dim3(384); cfg.dynamicSmemBytes = BG_SMEM;
    cudaLaunchKernelEx(&cfg, k_bg, P, out);
}
```

```cpp
#include <cuda_runtime.h>
#include <cuda_bf16.h>
#include <cuda.h>
#include <stdint.h>

typedef __nv_bfloat16 bf16;

constexpr int SEQ = 2048, DM = 1024, HD = 4096, NSEG = 64;

__device__ __align__(1024) bf16 g_kv[(size_t)SEQ * 8192];
__device__ __align__(1024) bf16 g_kvm[(size_t)NSEG * 8 * 8192];
__device__ __align__(1024) bf16 g_o[(size_t)SEQ * HD];
constexpr int XPAIRS = 128 + NSEG * 4;
__device__ __align__(8192) uint2 g_x[XPAIRS * 1024];
__device__ uint32_t g_home[XPAIRS];
__device__ uint32_t g_side[256];
__device__ __align__(1024) uint32_t g_flag[256];

#define TL(kern, slot)

__device__ __forceinline__ uint32_t smem_u32(const void* p) { return (uint32_t)__cvta_generic_to_shared(p); }
__device__ __forceinline__ void mbar_init(uint32_t bar, uint32_t cnt) {
    asm volatile("mbarrier.init.shared::cta.b64 [%0], %1;" ::"r"(bar), "r"(cnt) : "memory");
}
__device__ __forceinline__ void mbar_expect_tx(uint32_t bar, uint32_t bytes) {
    asm volatile("mbarrier.arrive.expect_tx.shared::cta.b64 _, [%0], %1;" ::"r"(bar), "r"(bytes) : "memory");
}
__device__ __forceinline__ void mbar_arrive(uint32_t bar) {
    asm volatile("mbarrier.arrive.shared::cta.b64 _, [%0];" ::"r"(bar) : "memory");
}
__device__ __forceinline__ bool mbar_try(uint32_t bar, uint32_t parity) {
    uint32_t ok;
    asm volatile("{\n.reg .pred p;\nmbarrier.try_wait.parity.shared::cta.b64 p, [%1], %2;\nselp.u32 %0, 1, 0, p;\n}"
                 : "=r"(ok) : "r"(bar), "r"(parity) : "memory");
    return ok;
}
constexpr int SPIN_LIMIT = 1 << 20;
__device__ __forceinline__ void mbar_wait(uint32_t bar, uint32_t parity) {
    int n = 0;
    while (!mbar_try(bar, parity)) { if (++n > SPIN_LIMIT) __trap(); }
}
__device__ __forceinline__ void mbar_wait_u(uint32_t bar, uint32_t parity) {
    asm volatile("{\n.reg .pred p;\n.reg .u32 n;\n"
                 "mbarrier.try_wait.parity.shared::cta.b64 p, [%0], %1;\n@p bra.uni DONE;\nmov.u32 n, 0;\n"
                 "AGAIN:\nmbarrier.try_wait.parity.shared::cta.b64 p, [%0], %1;\n@p bra.uni DONE;\n"
                 "add.u32 n, n, 1;\nsetp.lt.u32 p, n, 0x100000;\n@p bra.uni AGAIN;\ntrap;\nDONE:\n}"
                 ::"r"(bar), "r"(parity) : "memory");
}
__device__ __forceinline__ void tma2d(uint32_t dst, const CUtensorMap* m, int c0, int c1, uint32_t bar) {
    asm volatile("cp.async.bulk.tensor.2d.shared::cluster.global.mbarrier::complete_tx::bytes [%0], [%1, {%3, %4}], [%2];"
                 ::"r"(dst), "l"(m), "r"(bar), "r"(c0), "r"(c1) : "memory");
}
__device__ __forceinline__ void tma3d(uint32_t dst, const CUtensorMap* m, int c0, int c1, int c2, uint32_t bar) {
    asm volatile("cp.async.bulk.tensor.3d.shared::cluster.global.mbarrier::complete_tx::bytes [%0], [%1, {%3, %4, %5}], [%2];"
                 ::"r"(dst), "l"(m), "r"(bar), "r"(c0), "r"(c1), "r"(c2) : "memory");
}
__device__ __forceinline__ uint32_t pack2(float lo, float hi) {
    uint32_t r;
    asm("cvt.rn.bf16x2.f32 %0, %1, %2;" : "=r"(r) : "f"(hi), "f"(lo));
    return r;
}
__device__ __forceinline__ float bf_lo(uint32_t v) { return __uint_as_float(v << 16); }
__device__ __forceinline__ float bf_hi(uint32_t v) { return __uint_as_float(v & 0xffff0000u); }
__device__ __forceinline__ float bf_round(float x) { return bf_lo(pack2(x, 0.f)); }
__device__ __forceinline__ float ex2(float x) { float y; asm("ex2.approx.ftz.f32 %0, %1;" : "=f"(y) : "f"(x)); return y; }
__device__ __forceinline__ void mma16816(float (&c)[4], uint32_t a0, uint32_t a1, uint32_t a2, uint32_t a3, uint32_t b0, uint32_t b1) {
    asm volatile("mma.sync.aligned.m16n8k16.row.col.f32.bf16.bf16.f32 {%0,%1,%2,%3}, {%4,%5,%6,%7}, {%8,%9}, {%0,%1,%2,%3};"
                 : "+f"(c[0]), "+f"(c[1]), "+f"(c[2]), "+f"(c[3]) : "r"(a0), "r"(a1), "r"(a2), "r"(a3), "r"(b0), "r"(b1));
}
__device__ __forceinline__ void mma1688(float (&c)[4], uint32_t a0, uint32_t a1, uint32_t b0) {
    asm volatile("mma.sync.aligned.m16n8k8.row.col.f32.bf16.bf16.f32 {%0,%1,%2,%3}, {%4,%5}, {%6}, {%0,%1,%2,%3};"
                 : "+f"(c[0]), "+f"(c[1]), "+f"(c[2]), "+f"(c[3]) : "r"(a0), "r"(a1), "r"(b0));
}
__device__ __forceinline__ void ldsm4(uint32_t (&r)[4], uint32_t a) {
    asm volatile("ldmatrix.sync.aligned.m8n8.x4.shared.b16 {%0,%1,%2,%3}, [%4];"
                 : "=r"(r[0]), "=r"(r[1]), "=r"(r[2]), "=r"(r[3]) : "r"(a) : "memory");
}
__device__ __forceinline__ void ldsm4t(uint32_t (&r)[4], uint32_t a) {
    asm volatile("ldmatrix.sync.aligned.m8n8.x4.trans.shared.b16 {%0,%1,%2,%3}, [%4];"
                 : "=r"(r[0]), "=r"(r[1]), "=r"(r[2]), "=r"(r[3]) : "r"(a) : "memory");
}
__device__ __forceinline__ void ldsm2t(uint32_t& r0, uint32_t& r1, uint32_t a) {
    asm volatile("ldmatrix.sync.aligned.m8n8.x2.trans.shared.b16 {%0,%1}, [%2];" : "=r"(r0), "=r"(r1) : "r"(a) : "memory");
}
__device__ __forceinline__ void stsm4t(uint32_t a, uint32_t r0, uint32_t r1, uint32_t r2, uint32_t r3) {
    asm volatile("stmatrix.sync.aligned.m8n8.x4.trans.shared.b16 [%0], {%1,%2,%3,%4};"
                 ::"r"(a), "r"(r0), "r"(r1), "r"(r2), "r"(r3) : "memory");
}
__device__ __forceinline__ void lds128(uint32_t (&r)[4], uint32_t a) {
    asm volatile("ld.shared.v4.u32 {%0,%1,%2,%3}, [%4];" : "=r"(r[0]), "=r"(r[1]), "=r"(r[2]), "=r"(r[3]) : "r"(a) : "memory");
}
__device__ __forceinline__ float4 lds128f(uint32_t a) {
    float4 v;
    asm volatile("ld.shared.v4.f32 {%0,%1,%2,%3}, [%4];" : "=f"(v.x), "=f"(v.y), "=f"(v.z), "=f"(v.w) : "r"(a) : "memory");
    return v;
}
__device__ __forceinline__ float2 lds64f(uint32_t a) {
    float2 v;
    asm volatile("ld.shared.v2.f32 {%0,%1}, [%2];" : "=f"(v.x), "=f"(v.y) : "r"(a) : "memory");
    return v;
}
__device__ __forceinline__ uint32_t lds32(uint32_t a) {
    uint32_t v;
    asm volatile("ld.shared.u32 %0, [%1];" : "=r"(v) : "r"(a) : "memory");
    return v;
}
__device__ __forceinline__ void sts128(uint32_t a, uint32_t r0, uint32_t r1, uint32_t r2, uint32_t r3) {
    asm volatile("st.shared.v4.u32 [%0], {%1,%2,%3,%4};" ::"r"(a), "r"(r0), "r"(r1), "r"(r2), "r"(r3) : "memory");
}
__device__ __forceinline__ void sts128f(uint32_t a, float r0, float r1, float r2, float r3) {
    asm volatile("st.shared.v4.f32 [%0], {%1,%2,%3,%4};" ::"r"(a), "f"(r0), "f"(r1), "f"(r2), "f"(r3) : "memory");
}
__device__ __forceinline__ void sts64(uint32_t a, uint32_t r0, uint32_t r1) {
    asm volatile("st.shared.v2.u32 [%0], {%1,%2};" ::"r"(a), "r"(r0), "r"(r1) : "memory");
}
__device__ __forceinline__ void sts64f(uint32_t a, float r0, float r1) {
    asm volatile("st.shared.v2.f32 [%0], {%1,%2};" ::"r"(a), "f"(r0), "f"(r1) : "memory");
}
__device__ __forceinline__ void sts32f(uint32_t a, float r0) {
    asm volatile("st.shared.f32 [%0], %1;" ::"r"(a), "f"(r0) : "memory");
}
__device__ __forceinline__ uint2 ld_rlx64(const uint2* p) {
    uint2 v;
    asm volatile("{\n.reg .b64 t;\nld.relaxed.gpu.global.b64 t, [%2];\nmov.b64 {%0,%1}, t;\n}" : "=r"(v.x), "=r"(v.y) : "l"(p) : "memory");
    return v;
}
__device__ __forceinline__ void st_rlx64(uint2* p, uint32_t x, uint32_t y) {
    asm volatile("{\n.reg .b64 t;\nmov.b64 t, {%1,%2};\nst.relaxed.gpu.global.b64 [%0], t;\n}" ::"l"(p), "r"(x), "r"(y) : "memory");
}
__device__ __forceinline__ uint32_t ld_acq32(const uint32_t* p) {
    uint32_t v;
    asm volatile("ld.acquire.gpu.global.u32 %0, [%1];" : "=r"(v) : "l"(p) : "memory");
    return v;
}
__device__ __forceinline__ void wait_flag(const uint32_t* p, uint32_t need) {
    int n = 0;
    while (ld_acq32(p) < need) { __nanosleep(200); if (++n > SPIN_LIMIT) __trap(); }
}
__device__ __forceinline__ void bar_sync(int id, int n) { asm volatile("bar.sync %0, %1;" ::"r"(id), "r"(n) : "memory"); }
__device__ __forceinline__ void wg_fence() { asm volatile("wgmma.fence.sync.aligned;" ::: "memory"); }
__device__ __forceinline__ void wg_commit() { asm volatile("wgmma.commit_group.sync.aligned;" ::: "memory"); }
template <int N> __device__ __forceinline__ void wg_wait() { asm volatile("wgmma.wait_group.sync.aligned %0;" ::"n"(N) : "memory"); }
__device__ __forceinline__ uint64_t desc_sw128(uint32_t addr, uint32_t lbo, uint32_t sbo) {
    return (uint64_t)((addr & 0x3FFFF) >> 4) | ((uint64_t)(lbo >> 4) << 16) | ((uint64_t)(sbo >> 4) << 32) | (1ull << 62);
}
__device__ __forceinline__ void quad_transpose(uint32_t& r0, uint32_t& r1, uint32_t& r2, uint32_t& r3, int t) {
    const bool o = t & 1, h = t & 2;
    uint32_t s0 = __shfl_xor_sync(~0u, o ? r0 : r1, 1), s1 = __shfl_xor_sync(~0u, o ? r2 : r3, 1);
    uint32_t a0 = o ? s0 : r0, a1 = o ? r1 : s0, a2 = o ? s1 : r2, a3 = o ? r3 : s1;
    s0 = __shfl_xor_sync(~0u, h ? a0 : a2, 2); s1 = __shfl_xor_sync(~0u, h ? a1 : a3, 2);
    r0 = h ? s0 : a0; r1 = h ? s1 : a1; r2 = h ? a2 : s0; r3 = h ? a3 : s1;
}

__device__ __forceinline__ void wgmma_n256(float (&d)[128], uint64_t da, uint64_t db, int sd) {
    asm volatile("{\n.reg .pred p;\nsetp.ne.b32 p, %130, 0;\n"
        "wgmma.mma_async.sync.aligned.m64n256k16.f32.bf16.bf16 "
        "{%0,%1,%2,%3,%4,%5,%6,%7,%8,%9,%10,%11,%12,%13,%14,%15,"
        "%16,%17,%18,%19,%20,%21,%22,%23,%24,%25,%26,%27,%28,%29,%30,%31,"
        "%32,%33,%34,%35,%36,%37,%38,%39,%40,%41,%42,%43,%44,%45,%46,%47,"
        "%48,%49,%50,%51,%52,%53,%54,%55,%56,%57,%58,%59,%60,%61,%62,%63,"
        "%64,%65,%66,%67,%68,%69,%70,%71,%72,%73,%74,%75,%76,%77,%78,%79,"
        "%80,%81,%82,%83,%84,%85,%86,%87,%88,%89,%90,%91,%92,%93,%94,%95,"
        "%96,%97,%98,%99,%100,%101,%102,%103,%104,%105,%106,%107,%108,%109,%110,%111,"
        "%112,%113,%114,%115,%116,%117,%118,%119,%120,%121,%122,%123,%124,%125,%126,%127}, %128, %129, p, 1, 1, 0, 1;\n}\n"
        : "+f"(d[0]), "+f"(d[1]), "+f"(d[2]), "+f"(d[3]), "+f"(d[4]), "+f"(d[5]), "+f"(d[6]), "+f"(d[7]),
          "+f"(d[8]), "+f"(d[9]), "+f"(d[10]), "+f"(d[11]), "+f"(d[12]), "+f"(d[13]), "+f"(d[14]), "+f"(d[15]),
          "+f"(d[16]), "+f"(d[17]), "+f"(d[18]), "+f"(d[19]), "+f"(d[20]), "+f"(d[21]), "+f"(d[22]), "+f"(d[23]),
          "+f"(d[24]), "+f"(d[25]), "+f"(d[26]), "+f"(d[27]), "+f"(d[28]), "+f"(d[29]), "+f"(d[30]), "+f"(d[31]),
          "+f"(d[32]), "+f"(d[33]), "+f"(d[34]), "+f"(d[35]), "+f"(d[36]), "+f"(d[37]), "+f"(d[38]), "+f"(d[39]),
          "+f"(d[40]), "+f"(d[41]), "+f"(d[42]), "+f"(d[43]), "+f"(d[44]), "+f"(d[45]), "+f"(d[46]), "+f"(d[47]),
          "+f"(d[48]), "+f"(d[49]), "+f"(d[50]), "+f"(d[51]), "+f"(d[52]), "+f"(d[53]), "+f"(d[54]), "+f"(d[55]),
          "+f"(d[56]), "+f"(d[57]), "+f"(d[58]), "+f"(d[59]), "+f"(d[60]), "+f"(d[61]), "+f"(d[62]), "+f"(d[63]),
          "+f"(d[64]), "+f"(d[65]), "+f"(d[66]), "+f"(d[67]), "+f"(d[68]), "+f"(d[69]), "+f"(d[70]), "+f"(d[71]),
          "+f"(d[72]), "+f"(d[73]), "+f"(d[74]), "+f"(d[75]), "+f"(d[76]), "+f"(d[77]), "+f"(d[78]), "+f"(d[79]),
          "+f"(d[80]), "+f"(d[81]), "+f"(d[82]), "+f"(d[83]), "+f"(d[84]), "+f"(d[85]), "+f"(d[86]), "+f"(d[87]),
          "+f"(d[88]), "+f"(d[89]), "+f"(d[90]), "+f"(d[91]), "+f"(d[92]), "+f"(d[93]), "+f"(d[94]), "+f"(d[95]),
          "+f"(d[96]), "+f"(d[97]), "+f"(d[98]), "+f"(d[99]), "+f"(d[100]), "+f"(d[101]), "+f"(d[102]), "+f"(d[103]),
          "+f"(d[104]), "+f"(d[105]), "+f"(d[106]), "+f"(d[107]), "+f"(d[108]), "+f"(d[109]), "+f"(d[110]), "+f"(d[111]),
          "+f"(d[112]), "+f"(d[113]), "+f"(d[114]), "+f"(d[115]), "+f"(d[116]), "+f"(d[117]), "+f"(d[118]), "+f"(d[119]),
          "+f"(d[120]), "+f"(d[121]), "+f"(d[122]), "+f"(d[123]), "+f"(d[124]), "+f"(d[125]), "+f"(d[126]), "+f"(d[127])
        : "l"(da), "l"(db), "r"(sd));
}

__device__ __forceinline__ void wgmma_n128(float (&d)[64], uint64_t da, uint64_t db, int sd) {
    asm volatile("{\n.reg .pred p;\nsetp.ne.b32 p, %66, 0;\n"
        "wgmma.mma_async.sync.aligned.m64n128k16.f32.bf16.bf16 "
        "{%0,%1,%2,%3,%4,%5,%6,%7,%8,%9,%10,%11,%12,%13,%14,%15,"
        "%16,%17,%18,%19,%20,%21,%22,%23,%24,%25,%26,%27,%28,%29,%30,%31,"
        "%32,%33,%34,%35,%36,%37,%38,%39,%40,%41,%42,%43,%44,%45,%46,%47,"
        "%48,%49,%50,%51,%52,%53,%54,%55,%56,%57,%58,%59,%60,%61,%62,%63}, %64, %65, p, 1, 1, 0, 1;\n}\n"
        : "+f"(d[0]), "+f"(d[1]), "+f"(d[2]), "+f"(d[3]), "+f"(d[4]), "+f"(d[5]), "+f"(d[6]), "+f"(d[7]),
          "+f"(d[8]), "+f"(d[9]), "+f"(d[10]), "+f"(d[11]), "+f"(d[12]), "+f"(d[13]), "+f"(d[14]), "+f"(d[15]),
          "+f"(d[16]), "+f"(d[17]), "+f"(d[18]), "+f"(d[19]), "+f"(d[20]), "+f"(d[21]), "+f"(d[22]), "+f"(d[23]),
          "+f"(d[24]), "+f"(d[25]), "+f"(d[26]), "+f"(d[27]), "+f"(d[28]), "+f"(d[29]), "+f"(d[30]), "+f"(d[31]),
          "+f"(d[32]), "+f"(d[33]), "+f"(d[34]), "+f"(d[35]), "+f"(d[36]), "+f"(d[37]), "+f"(d[38]), "+f"(d[39]),
          "+f"(d[40]), "+f"(d[41]), "+f"(d[42]), "+f"(d[43]), "+f"(d[44]), "+f"(d[45]), "+f"(d[46]), "+f"(d[47]),
          "+f"(d[48]), "+f"(d[49]), "+f"(d[50]), "+f"(d[51]), "+f"(d[52]), "+f"(d[53]), "+f"(d[54]), "+f"(d[55]),
          "+f"(d[56]), "+f"(d[57]), "+f"(d[58]), "+f"(d[59]), "+f"(d[60]), "+f"(d[61]), "+f"(d[62]), "+f"(d[63])
        : "l"(da), "l"(db), "r"(sd));
}

__device__ __forceinline__ void wgmma_n64(float (&d)[32], uint64_t da, uint64_t db, int sd) {
    asm volatile("{\n.reg .pred p;\nsetp.ne.b32 p, %34, 0;\n"
        "wgmma.mma_async.sync.aligned.m64n64k16.f32.bf16.bf16 "
        "{%0,%1,%2,%3,%4,%5,%6,%7,%8,%9,%10,%11,%12,%13,%14,%15,"
        "%16,%17,%18,%19,%20,%21,%22,%23,%24,%25,%26,%27,%28,%29,%30,%31}, %32, %33, p, 1, 1, 0, 1;\n}\n"
        : "+f"(d[0]), "+f"(d[1]), "+f"(d[2]), "+f"(d[3]), "+f"(d[4]), "+f"(d[5]), "+f"(d[6]), "+f"(d[7]),
          "+f"(d[8]), "+f"(d[9]), "+f"(d[10]), "+f"(d[11]), "+f"(d[12]), "+f"(d[13]), "+f"(d[14]), "+f"(d[15]),
          "+f"(d[16]), "+f"(d[17]), "+f"(d[18]), "+f"(d[19]), "+f"(d[20]), "+f"(d[21]), "+f"(d[22]), "+f"(d[23]),
          "+f"(d[24]), "+f"(d[25]), "+f"(d[26]), "+f"(d[27]), "+f"(d[28]), "+f"(d[29]), "+f"(d[30]), "+f"(d[31])
        : "l"(da), "l"(db), "r"(sd));
}

constexpr int STAGE_BYTES = 49152, NSTAGE = 4;
constexpr int GEMM_SMEM = NSTAGE * STAGE_BYTES + 128;

struct GemmSmem { uint32_t st, full, empty; };
__device__ __forceinline__ GemmSmem gemm_setup(uint8_t* raw, int releases) {
    GemmSmem g;
    g.st = smem_u32(raw);
    if (g.st & 1023) __trap();
    g.full = g.st + NSTAGE * STAGE_BYTES; g.empty = g.full + 64;
    if (threadIdx.x == 0) {
        for (int s = 0; s < NSTAGE; s++) { mbar_init(g.full + 8 * s, 1); mbar_init(g.empty + 8 * s, releases); }
        asm volatile("fence.mbarrier_init.release.cluster;" ::: "memory");
        asm volatile("fence.proxy.async.shared::cta;" ::: "memory");
    }
    __syncthreads();
    return g;
}
__device__ __forceinline__ void mbar_arrive_one(uint32_t bar, uint32_t who) {
    asm volatile("{\n.reg .pred p;\nsetp.eq.u32 p, %1, 0;\n@p mbarrier.arrive.shared::cta.b64 _, [%0];\n}" ::"r"(bar), "r"(who) : "memory");
}
template <int BM, int BN, int KPS, typename ACC>
__device__ __forceinline__ void gemm_stage(ACC& acc, uint32_t stage, int wg, bool first) {
    const uint64_t da = desc_sw128(stage + wg * 8192, 16, 1024);
    const uint64_t db = desc_sw128(stage + KPS * BM * 128, 8192, 1024);
    wg_fence();
#pragma unroll
    for (int k = 0; k < 4 * KPS; k++) {
        const uint64_t a = da + (k >> 2) * (BM * 8) + (k & 3) * 2, b = db + k * 128;
        if constexpr (BN == 256) wgmma_n256(acc, a, b, first && k == 0 ? 0 : 1);
        else if constexpr (BN == 128) wgmma_n128(acc, a, b, first && k == 0 ? 0 : 1);
        else wgmma_n64(acc, a, b, first && k == 0 ? 0 : 1);
    }
    wg_commit();
}

__device__ __forceinline__ void kv_store_unit(const uint32_t (&pk)[64], int u, bf16* dst, int t) {
    const int G = (u >> 2) * 2 + (u & 1), hh = (u >> 1) & 1;
    uint32_t r0 = pk[(4 * G + 0) * 2 + hh], r1 = pk[(4 * G + 1) * 2 + hh], r2 = pk[(4 * G + 2) * 2 + hh], r3 = pk[(4 * G + 3) * 2 + hh];
    quad_transpose(r0, r1, r2, r3, t);
#define KVST ".cs"
    asm volatile("st.global" KVST ".v4.u32 [%0], {%1,%2,%3,%4};" ::"l"(dst + (size_t)hh * 8 * 8192 + G * 32), "r"(r0), "r"(r1), "r"(r2), "r"(r3) : "memory");
}

__device__ __forceinline__ uint32_t near_page(int pair, int line) {
    uint32_t best[2] = {~0u, ~0u};
#pragma unroll 1
    for (int i = 0; i < 16; i++) {
        uint32_t t0, t1, v;
        asm volatile("mov.u32 %0, %%clock;" : "=r"(t0)::"memory");
        asm volatile("atom.relaxed.gpu.global.or.b32 %0, [%1], -1;" : "=r"(v) : "l"(g_x + pair * 1024 + (i & 1) * 512 + line * 16) : "memory");
        asm volatile("{\n.reg .pred p;\nsetp.ne.u32 p, %1, 0x12345;\nmov.u32 %0, -1;\n@p mov.u32 %0, %%clock;\n}" : "=r"(t1) : "r"(v) : "memory");
        if (i & 1) best[1] = min(best[1], t1 - t0); else best[0] = min(best[0], t1 - t0);
    }
    return best[1] < best[0];
}
__device__ __forceinline__ void map_pages(int c) {
    uint32_t smid;
    asm("mov.u32 %0, %%smid;" : "=r"(smid));
    const uint32_t side = near_page(0, c & 31);
    g_side[smid & 255] = side;
    for (int p = c; p < XPAIRS; p += 132) g_home[p] = near_page(p, 0) ^ side;
}

__global__ void __launch_bounds__(384, 1)
k_kv(const __grid_constant__ CUtensorMap mx, const __grid_constant__ CUtensorMap mwk, const __grid_constant__ CUtensorMap mwv,
     const bf16* __restrict__ Wq, const bf16* __restrict__ Wo, const bf16* __restrict__ u) {
    extern __shared__ __align__(1024) uint8_t smem_gemm[];
    const int c = blockIdx.x;
    if (threadIdx.x == 0) TL(0, 0);
    if (c >= 128) {
        const int i0 = (c - 128) * 384 + threadIdx.x;
        const uint4 ones = make_uint4(~0u, ~0u, ~0u, ~0u);
        if (threadIdx.x == 32) map_pages(c);
        for (int i = i0; i < XPAIRS * 512; i += 4 * 384) reinterpret_cast<uint4*>(g_x)[i] = ones;
        if (i0 < 256) g_flag[i0] = 0;
        if (threadIdx.x == 0) {
            const char* p = (const char*)(c < 130 ? Wq : Wo) + (size_t)(c & 1) * (4 << 20);
            for (int i = 0; i < 256; i++) {
                asm volatile("cp.async.bulk.prefetch.L2.global [%0], 16384;" ::"l"(p + i * 16384) : "memory");
                if (i >= 192) asm volatile("cp.async.bulk.prefetch.L2.global [%0], 16384;" ::"l"((const char*)u + ((c - 128) * 64 + i - 192) * 16384) : "memory");
                __nanosleep(40);
            }
        }
        if (threadIdx.x == 0) TL(0, 1);
        return;
    }
    GemmSmem g = gemm_setup(smem_gemm, 2);
    const int m0 = (c & 15) * 128, nb0 = c >> 4;
    const int wg = __shfl_sync(~0u, threadIdx.x >> 7, 0);
    if (wg == 0) {
        asm volatile("setmaxnreg.dec.sync.aligned.u32 40;");
        if (threadIdx.x == 0) {
            for (int it = 0; it < 64; it++) {
                const int s = it & 3, tile = it >> 4, kb = it & 15;
                mbar_wait(g.empty + 8 * s, ((it >> 2) & 1) ^ 1);
                mbar_expect_tx(g.full + 8 * s, STAGE_BYTES);
                const int nb = nb0 + 8 * tile;
                tma2d(g.st + s * STAGE_BYTES, &mx, kb * 64, m0, g.full + 8 * s);
                tma3d(g.st + s * STAGE_BYTES + 16384, nb < 16 ? &mwk : &mwv, 0, kb * 64, (nb & 15) * 4, g.full + 8 * s);
            }
        } else if (threadIdx.x == 32) map_pages(c);
    } else {
        asm volatile("setmaxnreg.inc.sync.aligned.u32 232;");
        const int cw = wg - 1, lane = threadIdx.x & 31, t = lane & 3;
        const int row = m0 + cw * 64 + ((threadIdx.x >> 5) & 3) * 16 + (lane >> 2);
        bf16* dst = g_kv + (size_t)row * 8192 + nb0 * 256 + t * 8;
        float acc[128];
        uint32_t pk[64];
#pragma unroll 1
        for (int tile = 0; tile < 4; tile++) {
#pragma unroll
            for (int kb = 0; kb < 16; kb++) {
                mbar_wait_u(g.full + 8 * (kb & 3), (kb >> 2) & 1);
                gemm_stage<128, 256, 1>(acc, g.st + (kb & 3) * STAGE_BYTES, cw, kb == 0);
                if (tile > 0) kv_store_unit(pk, kb, dst + (tile - 1) * 2048, t);
                if (kb > 0) {
                    wg_wait<1>();
                    mbar_arrive_one(g.empty + 8 * ((kb - 1) & 3), threadIdx.x & 127);
                }
            }
            wg_wait<0>();
            mbar_arrive_one(g.empty + 8 * 3, threadIdx.x & 127);
#pragma unroll
            for (int i = 0; i < 64; i++) pk[i] = pack2(acc[2 * i], acc[2 * i + 1]);
        }
        if (threadIdx.x == 128) TL(0, 2);
#pragma unroll
        for (int u = 0; u < 16; u++) kv_store_unit(pk, u, dst + 3 * 2048, t);
        if (threadIdx.x == 128) TL(0, 1);
    }
}

constexpr int NS1 = 31;
#define RB1 4
#define PFC 4
constexpr int C_W1 = 0;
constexpr int C_W2 = C_W1 + 8 * NS1 * 512;
constexpr int C_KV = C_W2 + 14 * 8 * 512;
constexpr int C_RED = C_KV + 16384;
constexpr int C_R3 = C_RED + 64 * 272;
constexpr int C_QKV = C_R3 + 2560;
constexpr int C_SC = C_RED;
constexpr int C_OB = C_SC + 2 * 8 * 52 * 4;
constexpr int C_BAR = C_QKV + 3 * 8 * 272;
__host__ __device__ constexpr int smem_idx(int ks, int j) {
    return ks == 0 ? j : ks < 3 ? (j < 4 ? 4 + 4 * ks + j : -1) : (j < 3 ? 7 + 3 * ks + j : -1);
}
constexpr int CHAIN_SMEM = C_BAR + 64;
#define TS(i)

#define DLY3 3
#define DLY1 16
#define DLY0 8
#define DLY1A DLY1
#define DLY0A DLY0
#define DLYW 3
template <int N> __device__ __forceinline__ uint32_t delayed(uint32_t x, int lane) {
#pragma unroll
    for (int i = 0; i < N; i++) asm volatile("shfl.sync.idx.b32 %0, %0, %1, 31, -1;" : "+r"(x) : "r"(lane) : "memory");
    return x;
}
__device__ __forceinline__ void lds128v(uint32_t (&r)[4], uint32_t a) {
    asm volatile("ld.volatile.shared.v4.u32 {%0,%1,%2,%3}, [%4];" : "=r"(r[0]), "=r"(r[1]), "=r"(r[2]), "=r"(r[3]) : "r"(a) : "memory");
}
__device__ __forceinline__ uint2 lds64(uint32_t a) {
    uint2 v;
    asm volatile("ld.shared.v2.u32 {%0,%1}, [%2];" : "=r"(v.x), "=r"(v.y) : "r"(a) : "memory");
    return v;
}
#define LDQ ".L1::no_allocate"
__device__ __forceinline__ uint4 ldw128(const void* p) {
    uint4 v;
    asm volatile("ld.global.nc" LDQ ".v4.u32 {%0,%1,%2,%3}, [%4];" : "=r"(v.x), "=r"(v.y), "=r"(v.z), "=r"(v.w) : "l"(p));
    return v;
}
__device__ __forceinline__ void fetch8(uint64_t (&d)[8], const void* src) {
#define P8_LD(i) "ld.relaxed.gpu.global.b64 %" #i ", [%8 + " #i " * 256];\n"
    asm volatile(P8_LD(0) P8_LD(1) P8_LD(2) P8_LD(3) P8_LD(4) P8_LD(5) P8_LD(6) P8_LD(7)
                 : "=&l"(d[0]), "=&l"(d[1]), "=&l"(d[2]), "=&l"(d[3]), "=&l"(d[4]), "=&l"(d[5]), "=&l"(d[6]), "=&l"(d[7]) : "l"(src) : "memory");
}
template <bool TAG> __device__ __forceinline__ void settle8(uint2 (&v)[8], uint64_t (&d)[8], const void* src, uint32_t tag) {
#define P8_X(i) "mov.b64 {x" #i ", _}, %" #i ";\n"
#define P8_HEAD "{\n.reg .pred p, q;\n.reg .u32 n, x0, x1, x2, x3, x4, x5, x6, x7, m0, m1;\nmov.u32 n, 0;\nCHECK:\n" \
                P8_X(0) P8_X(1) P8_X(2) P8_X(3) P8_X(4) P8_X(5) P8_X(6) P8_X(7)
#define P8_VOTE "vote.sync.all.pred p, p, -1;\n@p bra.uni DONE;\n"
#define P8_TAIL "add.u32 n, n, 1;\nsetp.lt.u32 p, n, 0x100000;\n@p bra.uni CHECK;\ntrap;\nDONE:\n}"
#define P8_OPS : "+l"(d[0]), "+l"(d[1]), "+l"(d[2]), "+l"(d[3]), "+l"(d[4]), "+l"(d[5]), "+l"(d[6]), "+l"(d[7]) : "l"(src), "r"(tag) : "memory"
#define P8_RT(i) "lop3.b32 m0, x" #i ", %9, 1, 0x28;\nsetp.ne.u32 q, m0, 0;\n@q " P8_LD(i)
#define P8_RS(i) "setp.eq.u32 q, x" #i ", 0xffffffff;\n@q " P8_LD(i)
    if (TAG)
        asm volatile(P8_HEAD "lop3.b32 m0, x0, x1, %9, 0x7e;\nlop3.b32 m1, x2, x3, %9, 0x7e;\nlop3.b32 m0, m0, x4, %9, 0xf6;\n"
                     "lop3.b32 m1, m1, x5, %9, 0xf6;\nlop3.b32 m0, m0, x6, %9, 0xf6;\nlop3.b32 m1, m1, x7, %9, 0xf6;\n"
                     "lop3.b32 m0, m0, m1, 1, 0xa8;\nsetp.eq.u32 p, m0, 0;\n" P8_VOTE
                     P8_RT(0) P8_RT(1) P8_RT(2) P8_RT(3) P8_RT(4) P8_RT(5) P8_RT(6) P8_RT(7) P8_TAIL P8_OPS);
    else
        asm volatile(P8_HEAD "max.u32 m0, x0, x1;\nmax.u32 m0, m0, x2;\nmax.u32 m1, x3, x4;\nmax.u32 m1, m1, x5;\nmax.u32 m0, m0, x6;\n"
                     "max.u32 m0, m0, x7;\nmax.u32 m0, m0, m1;\nsetp.ne.u32 p, m0, 0xffffffff;\n" P8_VOTE
                     P8_RS(0) P8_RS(1) P8_RS(2) P8_RS(3) P8_RS(4) P8_RS(5) P8_RS(6) P8_RS(7) P8_TAIL P8_OPS);
#pragma unroll
    for (int i = 0; i < 8; i++) { v[i].x = (uint32_t)d[i]; v[i].y = (uint32_t)(d[i] >> 32); }
}
__device__ __forceinline__ void sum8(float (&c)[4], const uint2 (&v)[8], uint32_t idn) {
    float d[4] = {0.f, 0.f, 0.f, 0.f};
    c[0] = c[1] = c[2] = c[3] = 0.f;
    mma16816(c, v[0].x, v[0].y, v[1].x, v[1].y, idn, idn);
    mma16816(d, v[2].x, v[2].y, v[3].x, v[3].y, idn, idn);
    mma16816(c, v[4].x, v[4].y, v[5].x, v[5].y, idn, idn);
    mma16816(d, v[6].x, v[6].y, v[7].x, v[7].y, idn, idn);
    c[0] += d[0]; c[1] += d[1]; c[2] += d[2]; c[3] += d[3];
}

__global__ void __cluster_dims__(3, 1, 1) __launch_bounds__(256, 1)
k_chain(const bf16* __restrict__ mem0, const bf16* __restrict__ Wq, const bf16* __restrict__ Wk, const bf16* __restrict__ Wv,
        const bf16* __restrict__ Wo, const __grid_constant__ CUtensorMap mkv) {
    extern __shared__ __align__(1024) uint8_t smem_chain[];
    const uint32_t sb = smem_u32(smem_chain);
    if (sb & 1023) __trap();
    const int w = __shfl_sync(~0u, threadIdx.x >> 5, 0), lane = __shfl_sync(~0u, threadIdx.x & 31, threadIdx.x & 31);
    const int tid = w * 32 + lane, g = lane >> 2, t = lane & 3;
    auto pin = [&](uint32_t x) { return delayed<1>(x, lane); };
    const int h = blockIdx.x / 3, r = blockIdx.x - 3 * h;
    const uint32_t bar_x = sb + C_BAR, bar_kv = sb + C_BAR + 8, bar_go = sb + C_BAR + 16, bar_w = sb + C_BAR + 24;
    asm volatile("griddepcontrol.launch_dependents;");
    const int tbase = r == 0 ? 0 : 1 + 21 * r, ntile = r == 0 ? 22 : 21;
    uint32_t side;
    asm("mov.u32 %0, %%smid;" : "=r"(side));
    side = g_side[side & 255] & 1;
    if (tid == 0 && r > 0) asm volatile("st.relaxed.gpu.global.u32 [%0], %1;" ::"l"(g_flag + 128 + 2 * h + r - 1), "r"(2 | side) : "memory");
    if (tid == 0) {
        mbar_init(bar_x, 8); mbar_init(bar_kv, 1); mbar_init(bar_go, 1); mbar_init(bar_w, 1);
        asm volatile("fence.mbarrier_init.release.cluster;" ::: "memory");
        asm volatile("fence.proxy.async.shared::cta;" ::: "memory");
        mbar_expect_tx(bar_w, 128 * 32 * ntile);
    }
    __syncthreads();
    asm volatile("barrier.cluster.arrive.relaxed.aligned;" ::: "memory");
    if (tid < 128)
        asm volatile("cp.async.bulk.shared::cluster.global.mbarrier::complete_tx::bytes [%0], [%1], %2, [%3];"
                     ::"r"(sb + C_W1 + tid * 720), "l"(Wo + (size_t)(h * 128 + tid) * DM + tbase * 16), "r"(32 * ntile), "r"(bar_w) : "memory");
    const int tile0 = tbase + 7 - w;
    const bool three = w >= (r == 0 ? 2 : 3);
    const uint32_t wa = pin(sb + tid * 16);
#define W1A(i) (wa + C_W1 + (i) * 4096)
#define W2A(x) (wa + C_W2 + ((x) < 8 ? (x) * 4096 : 32768 - 1024 + ((x) - 8) * 3072))
    uint32_t wo0[8][4], wr[64][4];
    {
        const bf16* W = (r == 0 ? Wq : r == 1 ? Wk : Wv) + (size_t)(128 * w + (lane >> 4)) * HD + h * 128 + 8 * (lane & 15);
        uint4 raw[8][8];
        auto fetch = [&](int ks) {
#pragma unroll
            for (int i = 0; i < 8; i++) raw[ks][i] = ldw128(W + (size_t)(16 * ks + 2 * i) * HD);
        };
        fetch(0); fetch(1); fetch(2); fetch(3);
        mbar_wait_u(bar_w, 0);
        const uint32_t p = sb + C_W1 + ((lane & 7) + (lane >> 4) * 8) * 720 + (7 - w) * 32 + ((lane >> 3) & 1) * 16;
#pragma unroll
        for (int ks = 0; ks < 8; ks++) {
            uint32_t a[4];
            ldsm4t(wo0[ks], p + ks * 16 * 720);
            ldsm4t(a, p + ks * 16 * 720 + 256);
            sts128(W2A(ks), a[0], a[1], a[2], a[3]);
            if (three) { ldsm4t(a, p + ks * 16 * 720 + 512); sts128(W2A(8 + ks), a[0], a[1], a[2], a[3]); }
        }
        __syncthreads();
        const uint32_t stg = sb + C_KV + w * 4096;
        const uint32_t rd = stg + ((lane & 6) + 8 * (lane & 1) + (lane >> 4)) * 256 + ((((lane >> 3) & 1) ^ (lane & 7)) << 4);
#pragma unroll
        for (int ks = 0; ks < 8; ks++) {
#pragma unroll
            for (int i = 0; i < 8; i++)
                sts128(stg + (2 * i + (lane >> 4)) * 256 + (((lane & 15) ^ (((2 * i) & 6) | (i >> 2))) << 4),
                       raw[ks][i].x, raw[ks][i].y, raw[ks][i].z, raw[ks][i].w);
            if (ks < 2) fetch(ks + 4);
            if (ks == 3 || ks == 5) fetch(ks / 2 + 5);
            __syncwarp();
#pragma unroll
            for (int j = 0; j < 8; j++) {
                if (smem_idx(ks, j) >= 0) {
                    uint32_t a[4];
                    ldsm4t(a, rd ^ (j << 5));
                    sts128(W1A(smem_idx(ks, j)), a[0], a[1], a[2], a[3]);
                } else ldsm4t(wr[8 * ks + j], rd ^ (j << 5));
            }
            __syncwarp();
        }
    }
    asm volatile("fence.proxy.async.shared::cta;" ::: "memory");
    __syncthreads();
    if (tid == 0) {
        mbar_expect_tx(bar_kv, 16384);
        tma3d(sb + C_KV, &mkv, 0, 0, 2 * h, bar_kv);
        tma3d(sb + C_KV + 8192, &mkv, 0, 0, 64 + 2 * h, bar_kv);
    }
    asm volatile("barrier.cluster.wait.aligned;" ::: "memory");

    auto publish_kvm = [&](int s) {
        uint32_t v[4];
        lds128(v, sb + C_QKV + (8 + (tid >> 4)) * 272 + (tid & 15) * 16);
        asm volatile("st.global.v4.u32 [%0], {%1,%2,%3,%4};"
                     ::"l"(g_kvm + (size_t)(s * 8 + ((tid >> 4) & 7)) * 8192 + (tid >> 7) * HD + h * 128 + (tid & 15) * 8),
                       "r"(v[0]), "r"(v[1]), "r"(v[2]), "r"(v[3]) : "memory");
        if (h == 0 && w == 6) asm volatile("st.relaxed.gpu.global.u32 [%0], %1;" ::"l"(g_flag + 98), "r"(s + 1) : "memory");
        if ((s & 3) == 3) {
            __syncthreads();
            if (w == 7) asm volatile("{\n.reg .pred p;\nsetp.eq.u32 p, %2, 0;\nfence.acq_rel.gpu;\n@p st.relaxed.gpu.global.u32 [%0], %1;\n}"
                                     ::"l"(g_flag + h), "r"(s + 1), "r"(lane) : "memory");
        }
    };
    const float sl2e = 0.08838834764831845f * 1.4426950408889634f;
    const uint32_t idn = pin(g == 2 * t ? 0x00003f80u : g == 2 * t + 1 ? 0x3f800000u : 0u);
    const uint32_t lm = pin(sb + (lane & 7) * 272 + (lane >> 3) * 16);
    const uint32_t sa = pin(sb + C_SC + (w & 1) * (8 * 52 * 4) + (2 * t * 52 + (w < 4 ? 32 : (w & 2) * 8) + g) * 4);
    const uint32_t sr = pin(sb + C_SC + (g * 52 + 8 * t) * 4), sr2 = pin(sb + C_SC + (g * 52 + 32 + 2 * t) * 4);
    uint32_t kva;
    {
        const int pos = (w & 2) * 8 + (lane & 15), row = (pos & 24) + ((pos + (pos >> 2 & 6)) & 7);
        const int key = 4 * (lane & 6) + (((lane & 7) + 2 * (lane >> 4)) & 7);
        kva = pin(w >= 4 ? sb + C_KV + (w & 1) * 4096 + row * 128 + (((lane >> 4) ^ (row & 7)) << 4)
                         : sb + C_KV + 8192 + (w >> 1) * 4096 + key * 128 + ((((w & 1) * 4 + ((lane >> 3) & 1)) ^ (key & 7)) << 4));
    }
    uint32_t buf0[8][4], ring[RB1][4];
    auto stage_w1 = [&]() {
#pragma unroll
        for (int i = 0; i < 8; i++) lds128v(buf0[i], W1A(i));
#pragma unroll
        for (int i = 0; i < RB1; i++) lds128v(ring[i], W1A(8 + i));
    };
    stage_w1();
    uint32_t psel, msel0, msel1;
    {
        const int j = r > 0 ? 2 * h + r - 1 : 0, tl = min(tile0 + 8 * lane, 63);
        uint32_t b;
        asm volatile("{\n.reg .pred p;\n.reg .u32 n;\nmov.u32 n, 0;\nAGAIN:\nld.relaxed.gpu.global.u32 %0, [%1];\nsetp.ne.u32 p, %0, 0;\n"
                     "vote.sync.all.pred p, p, -1;\n@p bra.uni DONE;\nadd.u32 n, n, 1;\nsetp.lt.u32 p, n, 0x100000;\n@p bra.uni AGAIN;\ntrap;\nDONE:\n}"
                     : "=&r"(b) : "l"(g_flag + 128 + tl) : "memory");
        psel = __ballot_sync(~0u, (g_home[lane == 3 ? j * 2 + ((w >> 1) & 1) : tl * 2 + (h >> 4)] ^ (lane == 3 ? side : b)) & 1);
        msel0 = __ballot_sync(~0u, (g_home[128 + lane * 4 + (w >> 1)] ^ side) & 1);
        msel1 = __ballot_sync(~0u, (g_home[256 + lane * 4 + (w >> 1)] ^ side) & 1);
        if (r > 0) {
            if (w < 4) asm volatile("prefetch.global.L2 [%0];" ::"l"(g_x + (128 + (1 + (w >> 1)) * 4 + (j >> 4)) * 1024 + (w & 1) * 512 + (j & 15) * 32 + lane) : "memory");
            if (w < 4) asm volatile("prefetch.global.L2 [%0];" ::"l"(g_x + j * 2048 + tid * 16) : "memory");
        }
    }
    uint2 bm[8];
#pragma unroll
    for (int ks = 0; ks < 8; ks++) {
        const uint32_t* p = (const uint32_t*)(mem0 + g * DM + (8 * w + ks) * 16) + t;
        const uint32_t x = __ldg(p), y = __ldg(p + 4);
        bm[ks] = make_uint2(__byte_perm(x, y, 0x5410), __byte_perm(x, y, 0x7632));
    }
    if (tid == 0) TL(1, 2);
#pragma unroll 1
    for (int s = 0;; s++) {
        TS(1);
        {
            float acc[8][4];
#pragma unroll
            for (int ks = 0; ks < 8; ks++) {
#pragma unroll
                for (int j = 0; j < 8; j++) {
                    const int i = smem_idx(ks, j) - 8;
                    if (ks == 0) {
                        acc[j][0] = acc[j][1] = acc[j][2] = acc[j][3] = 0.f;
                        mma16816(acc[j], buf0[j][0], buf0[j][1], buf0[j][2], buf0[j][3], bm[ks].x, bm[ks].y);
                    } else if (i >= 0) {
                        uint32_t(&a)[4] = ring[i % RB1];
                        mma16816(acc[j], a[0], a[1], a[2], a[3], bm[ks].x, bm[ks].y);
                        if (8 + i + RB1 < NS1) lds128v(a, W1A(8 + i + RB1));
                    } else {
                        const uint32_t(&a)[4] = wr[8 * ks + j];
                        mma16816(acc[j], a[0], a[1], a[2], a[3], bm[ks].x, bm[ks].y);
                    }
                }
            }
#pragma unroll
            for (int c = 0; c < 4; c++)
                stsm4t(lm + C_RED + w * 2176 + c * 64, pack2(acc[2 * c][0], acc[2 * c][1]), pack2(acc[2 * c][2], acc[2 * c][3]),
                       pack2(acc[2 * c + 1][0], acc[2 * c + 1][1]), pack2(acc[2 * c + 1][2], acc[2 * c + 1][3]));
        }
        {
            const uint32_t a = sb + C_RED + w * 272 + lane * 8;
            if (s < NSEG - 1) mbar_wait_u(bar_kv, s & 1);
            TS(2);
            __syncthreads();
            TS(3);
            uint2 v[8];
#pragma unroll
            for (int i = 0; i < 8; i++) v[i] = lds64(a + i * 2176);
            float c[4];
            sum8(c, v, idn);
            const uint32_t p0 = pack2(c[0], c[1]), p1 = pack2(c[2], c[3]);
            const uint32_t dst = sb + C_QKV + (r * 8 + w) * 272 + lane * 8;
#pragma unroll
            for (int i = 1; i < 3; i++) {
                const uint32_t peer = r + i >= 3 ? r + i - 3 : r + i;
                uint32_t rd, rb;
                asm("mapa.shared::cluster.u32 %0, %1, %2;" : "=r"(rd) : "r"(dst), "r"(peer));
                asm("mapa.shared::cluster.u32 %0, %1, %2;" : "=r"(rb) : "r"(bar_x), "r"(peer));
                asm volatile("st.async.weak.shared::cluster.mbarrier::complete_tx::bytes.v2.b32 [%0], {%1,%2}, [%3];"
                             ::"r"(rd), "r"(p0), "r"(p1), "r"(rb) : "memory");
            }
            sts64(dst, p0, p1);
            __syncwarp();
            asm volatile("{\n.reg .pred p;\nsetp.eq.u32 p, %1, 0;\n@p mbarrier.arrive.expect_tx.shared::cta.b64 _, [%0], 512;\n}"
                         ::"r"(bar_x), "r"(lane) : "memory");
        }
        TS(4);
        if (s == NSEG - 1) break;
        uint32_t wb[8][4], wc[8][4];
        const uint32_t po = (tile0 * 2 + (h >> 4)) * 8192 + (h & 15) * 256 + lane * 8;
        const uint32_t tag = s & 1;
        auto project = [&](const uint32_t(&wt)[8][4], const uint32_t(&ob)[4][4], int i) {
            float c0[4] = {0.f, 0.f, 0.f, 0.f}, c1[4] = {0.f, 0.f, 0.f, 0.f};
#pragma unroll
            for (int ks = 0; ks < 8; ks++)
                mma16816((ks & 1) ? c1 : c0, wt[ks][0], wt[ks][1], wt[ks][2], wt[ks][3], ob[ks >> 1][(ks & 1) * 2], ob[ks >> 1][(ks & 1) * 2 + 1]);
            st_rlx64((uint2*)((char*)g_x + po + i * 131072 + ((psel >> i) & 1) * 4096), (pack2(c0[0] + c1[0], c0[2] + c1[2]) & ~1u) | tag, pack2(c0[1] + c1[1], c0[3] + c1[3]));
        };
        if (w >= 4) {
            uint32_t ka[4][4];
#pragma unroll
            for (int ks = 0; ks < 4; ks++) ldsm4(ka[ks], kva ^ (ks << 5));
            const uint32_t qa = lm + C_QKV + (w & 1) * 128;
            TS(5);
            mbar_wait_u(bar_x, s & 1);
            TS(6);
            {
                uint32_t qb[2][4];
                ldsm4(qb[0], qa);
                ldsm4(qb[1], qa + 64);
                float c0[4] = {0.f, 0.f, 0.f, 0.f}, c1[4] = {0.f, 0.f, 0.f, 0.f};
                mma16816(c0, ka[0][0], ka[0][1], ka[0][2], ka[0][3], qb[0][0], qb[0][1]);
                mma16816(c1, ka[1][0], ka[1][1], ka[1][2], ka[1][3], qb[0][2], qb[0][3]);
                mma16816(c0, ka[2][0], ka[2][1], ka[2][2], ka[2][3], qb[1][0], qb[1][1]);
                mma16816(c1, ka[3][0], ka[3][1], ka[3][2], ka[3][3], qb[1][2], qb[1][3]);
                sts32f(sa, c0[0] + c1[0]);
                sts32f(sa + 208, c0[1] + c1[1]);
                sts32f(sa + 32, c0[2] + c1[2]);
                sts32f(sa + 240, c0[3] + c1[3]);
            }
            __syncthreads();
            TS(7);
            if (w == 7 && s + 1 < NSEG - 1) {
                if (lane == 0) {
                    mbar_expect_tx(bar_kv, 16384);
                    tma3d(sb + C_KV, &mkv, 0, (s + 1) * 32, 2 * h, bar_kv);
                    tma3d(sb + C_KV + 8192, &mkv, 0, (s + 1) * 32, 64 + 2 * h, bar_kv);
                }
                __syncwarp();
            }
            const uint32_t wd = delayed<DLYW>(wa, lane);
#pragma unroll
            for (int i = 0; i < 8; i++) lds128(wb[i], wd + C_W2 + i * 4096);
#pragma unroll
            for (int i = 0; i < PFC; i++) lds128(wc[i], wd + C_W2 + 32768 - 1024 + i * 3072);
            TS(8);
            __syncthreads();
            TS(9);
            uint32_t ob[4][4];
#pragma unroll
            for (int i = 0; i < 4; i++) ldsm4(ob[i], lm + C_OB + i * 64);
#pragma unroll
            for (int i = PFC; i < 8; i++) lds128(wc[i], W2A(8 + i));
            project(wb, ob, 1);
            project(wo0, ob, 0);
            project(wc, ob, 2);
        } else {
            uint32_t va[4][4];
#pragma unroll
            for (int i = 0; i < 4; i++) ldsm4t(va[i], kva ^ (((i >> 1) << 5) | ((i & 1) * 0x240)));
#pragma unroll
            for (int i = 0; i < 8; i++) lds128(wb[i], W2A(i));
            const uint32_t qa = lm + C_QKV + (w & 1) * 128, oa = lm + w * 64;
            TS(5);
            mbar_wait_u(bar_x, s & 1);
            TS(6);
            if (w < 2) {
                uint32_t qb[2][4], km[2][4];
                ldsm4(qb[0], qa);
                ldsm4(km[0], qa + 8 * 272);
                ldsm4(qb[1], qa + 64);
                ldsm4(km[1], qa + 8 * 272 + 64);
                float c0[4] = {0.f, 0.f, 0.f, 0.f}, c1[4] = {0.f, 0.f, 0.f, 0.f};
                mma16816(c0, km[0][0], km[0][1], km[0][2], km[0][3], qb[0][0], qb[0][2]);
                mma16816(c1, km[0][0], km[0][1], km[0][2], km[0][3], qb[0][1], qb[0][3]);
                mma16816(c0, km[1][0], km[1][1], km[1][2], km[1][3], qb[1][0], qb[1][2]);
                mma16816(c1, km[1][0], km[1][1], km[1][2], km[1][3], qb[1][1], qb[1][3]);
                sts32f(sa, c0[0] + c1[2]);
                sts32f(sa + 208, c0[1] + c1[3]);
            }
            __syncthreads();
            TS(7);
            {
                float4 x0 = lds128f(sr), y0 = lds128f(sr + 1664), x1 = lds128f(sr + 16), y1 = lds128f(sr + 1680);
                float2 x2 = lds64f(sr2), y2 = lds64f(sr2 + 1664);
                float p[10] = {x0.x + y0.x, x0.y + y0.y, x0.z + y0.z, x0.w + y0.w, x1.x + y1.x,
                               x1.y + y1.y, x1.z + y1.z, x1.w + y1.w, x2.x + y2.x, x2.y + y2.y};
                float m = fmaxf(fmaxf(fmaxf(p[0], p[1]), fmaxf(p[2], p[3])), fmaxf(fmaxf(fmaxf(p[4], p[5]), fmaxf(p[6], p[7])), fmaxf(p[8], p[9])));
                const float m1 = __shfl_xor_sync(~0u, m, 1), m2 = __shfl_xor_sync(~0u, m, 2), m3 = __shfl_xor_sync(~0u, m, 3);
                uint32_t vm[4];
                ldsm4t(vm, oa + C_QKV + 16 * 272);
                m = fmaxf(fmaxf(m, m1), fmaxf(m2, m3));
                const float ms = m * sl2e;
#pragma unroll
                for (int i = 0; i < 10; i++) p[i] = ex2(fmaf(p[i], sl2e, -ms));
                const uint32_t b0 = pack2(p[0], p[1]), b1 = pack2(p[2], p[3]), b2 = pack2(p[4], p[5]), b3 = pack2(p[6], p[7]), b4 = pack2(p[8], p[9]);
                const uint32_t one = 0x3f803f80u;
                float o0[4] = {0.f, 0.f, 0.f, 0.f}, o1[4] = {0.f, 0.f, 0.f, 0.f}, sm[4] = {0.f, 0.f, 0.f, 0.f};
                mma16816(sm, one, one, one, one, b0, b1);
                mma16816(o0, va[0][0], va[0][1], va[0][2], va[0][3], b0, b1);
                mma16816(o1, va[2][0], va[2][1], va[2][2], va[2][3], b0, b1);
                mma16816(sm, one, one, one, one, b2, b3);
                mma16816(o0, va[1][0], va[1][1], va[1][2], va[1][3], b2, b3);
                mma16816(o1, va[3][0], va[3][1], va[3][2], va[3][3], b2, b3);
                mma1688(sm, one, one, b4);
                mma1688(o0, vm[0], vm[1], b4);
                mma1688(o1, vm[2], vm[3], b4);
                float i0, i1;
                asm("rcp.approx.ftz.f32 %0, %1;" : "=f"(i0) : "f"(sm[0]));
                asm("rcp.approx.ftz.f32 %0, %1;" : "=f"(i1) : "f"(sm[1]));
                stsm4t(oa + C_OB, pack2(o0[0] * i0, o0[1] * i1), pack2(o0[2] * i0, o0[3] * i1),
                       pack2(o1[0] * i0, o1[1] * i1), pack2(o1[2] * i0, o1[3] * i1));
            }
            TS(8);
            __syncthreads();
            TS(9);
            uint32_t ob[4][4];
#pragma unroll
            for (int i = 0; i < 4; i++) ldsm4(ob[i], lm + C_OB + i * 64);
            if (three) {
#pragma unroll
                for (int i = 0; i < 8; i++) lds128(wc[i], W2A(8 + i));
                project(wb, ob, 1);
                project(wo0, ob, 0);
                project(wc, ob, 2);
            } else {
                project(wb, ob, 1);
                project(wo0, ob, 0);
            }
        }
        TS(10);
        __syncthreads();
        uint32_t eo = (128 + (s + 1) * 4 + (w >> 1)) * 8192 + (((s < 31 ? msel0 : msel1) >> ((s + 1) & 31)) & 1) * 4096 + (w & 1) * 2048 + lane * 8;
        uint64_t d[8];
        if (r == 0) {
            TS(11); TS(12);
            stage_w1();
            publish_kvm(s);
            mbar_wait_u(bar_go, s & 1);
            if (w < 4) eo = delayed<DLY0>(eo, lane); else eo = delayed<DLY0A>(eo, lane);
        } else {
            const int j = 2 * h + r - 1;
            if (w < 4) {
                const char* src = (const char*)g_x + delayed<DLY3>((j * 2 + (w >> 1)) * 8192 + (psel & 8) * 512 + (w & 1) * 2048 + lane * 8, lane);
                fetch8(d, src);
                const uint32_t a = pin(sb + C_R3 + w * 640 + t * 160 + g * 8), a2 = pin(sb + C_R3 + g * 80 + t * 16);
                stage_w1();
                uint2 v[8];
                settle8<true>(v, d, src, tag);
                TS(11);
                float c[4];
                sum8(c, v, idn);
                sts64f(a, c[0], c[1]);
                sts64f(a + 80, c[2], c[3]);
                __syncthreads();
                TS(12);
                if (w < 2) {
                    const float4 u0 = lds128f(a2), u1 = lds128f(a2 + 640), u2 = lds128f(a2 + 1280), u3 = lds128f(a2 + 1920);
                    st_rlx64(g_x + (128 + (s + 1) * 4 + (j >> 4)) * 1024 + w * 512 + (j & 15) * 32 + lane, pack2((u0.x + u1.x) + (u2.x + u3.x), (u0.y + u1.y) + (u2.y + u3.y)),
                             pack2((u0.z + u1.z) + (u2.z + u3.z), (u0.w + u1.w) + (u2.w + u3.w)));
                }
                eo = delayed<DLY1>(eo, lane);
            } else {
                if (w >= 6 && s + 3 < NSEG)
                    asm volatile("prefetch.global.L2 [%0];" ::"l"(g_x + (128 + (s + 3) * 4 + (j >> 4)) * 1024 + (w & 1) * 512 + (j & 15) * 32 + lane) : "memory");
                stage_w1();
                TS(11);
                __syncthreads();
                TS(12);
                if (w == 4 && r == 1)
                    asm volatile("{\n.reg .pred p;\n.reg .u32 a;\nelect.sync _|p, -1;\nmapa.shared::cluster.u32 a, %0, 0;\n"
                                 "@p mbarrier.arrive.relaxed.cluster.shared::cluster.b64 _, [a];\n}" ::"r"(bar_go) : "memory");
                eo = delayed<DLY1A>(eo, lane);
            }
        }
        { const int s_ = s; { const int s = s_ + 1; TS(0); } }
        fetch8(d, (const char*)g_x + eo);
        settle8<false>(bm, d, (const char*)g_x + eo, 0);
    }
    mbar_wait_u(bar_x, (NSEG - 1) & 1);
    if (r == 0) publish_kvm(NSEG - 1);
    asm volatile("barrier.cluster.arrive.relaxed.aligned;\nbarrier.cluster.wait.aligned;" ::: "memory");
}

constexpr int S4_US = 4368;
constexpr int S4_RS = 8848;
constexpr int S4_KS = 1296;
constexpr int S4_U = 0, S4_R = 16 * S4_US, S4_K = S4_R + 16 * S4_RS;
constexpr int S4_SMEM = S4_K + 16 * S4_KS;
constexpr int S4_SIG = 3104, S4_PK = 2 * S4_SIG;

struct cf { float r, i; };
__device__ __forceinline__ cf cmul(cf a, cf b) { return {fmaf(a.r, b.r, -a.i * b.i), fmaf(a.r, b.i, a.i * b.r)}; }
__device__ __forceinline__ cf cmulc(cf a, cf b) { return {fmaf(a.r, b.r, a.i * b.i), fmaf(a.i, b.r, -a.r * b.i)}; }
__device__ __forceinline__ cf csq(cf a) { const float t = a.r * a.i; return {fmaf(a.r, a.r, -a.i * a.i), t + t}; }
__device__ __forceinline__ cf cexp(float l2, float turns) {
    const float mag = ex2(l2), fr = (turns - rintf(turns)) * 6.283185307179586f;
    return {mag * __cosf(fr), mag * __sinf(fr)};
}
__device__ __forceinline__ void sts32(uint32_t a, uint32_t v) { asm volatile("st.shared.u32 [%0], %1;" ::"r"(a), "r"(v) : "memory"); }
__device__ __forceinline__ uint32_t lds16(uint32_t a) {
    uint32_t v;
    asm volatile("ld.shared.u16 %0, [%1];" : "=r"(v) : "r"(a) : "memory");
    return v;
}

template <int M0, int NQ>
__device__ __forceinline__ void s4_class(float (&acc)[16][4], uint32_t sig, uint32_t taps, int x0) {
    constexpr int D0 = M0 / 8, D1 = M0 == 32 ? 9 : 15;
    uint32_t R[D1 - D0 + 2];
#pragma unroll
    for (int D = D0 - 1; D <= D1; D++) {
        if (D < D0 || 8 * D - 7 >= 2 * M0) { R[D - D0 + 1] = 0; continue; }
        const int m = 8 * D + x0;
        uint32_t lo = lds16(taps + m * (2 * NQ)), hi = lds16(taps + (m - 1) * (2 * NQ));
        if (D == D0) { lo = m >= M0 ? lo : 0; hi = m > M0 ? hi : 0; }
        if (D == 2 * D0) { lo = m < 2 * M0 ? lo : 0; hi = m <= 2 * M0 ? hi : 0; }
        R[D - D0 + 1] = lo | (hi << 16);
    }
#pragma unroll
    for (int J = 0; 2 * J + D0 < 16; J++) {
        uint32_t a[4];
        ldsm4t(a, sig + J * 512);
#pragma unroll
        for (int D = D0; D <= D1; D++)
            if (2 * J + D < 16) mma16816(acc[2 * J + D], a[0], a[1], a[2], a[3], R[D - D0 + 1], R[D - D0]);
    }
}

__global__ void __launch_bounds__(512, 1)
k_s4(const bf16* __restrict__ u, const bf16* __restrict__ Are, const bf16* __restrict__ Aim, const bf16* __restrict__ Bre,
     const bf16* __restrict__ Bim, const bf16* __restrict__ Cre, const bf16* __restrict__ Cim, const bf16* __restrict__ logdt,
     const bf16* __restrict__ Dsk, bf16* __restrict__ out) {
    extern __shared__ __align__(16) uint8_t smem_s4[];
    const uint32_t sb = smem_u32(smem_s4);
    asm volatile("griddepcontrol.launch_dependents;");
    const int tid = threadIdx.x, w = __shfl_sync(~0u, tid >> 5, 0), lane = tid & 31, g = lane >> 2, t = lane & 3;
    if (tid == 0) TL(2, 0);
    const int d0 = blockIdx.x * 16;
    const int d = d0 + (w & 1) + ((w >> 1) & 3) * 4 + (w >> 3) * 2;
    const uint32_t tr_off = (lane & 15), tr_l = (lane >> 4) * 16;
    const uint32_t ur = sb + S4_U + w * S4_US, rs = sb + S4_R + w * S4_RS, kd = sb + S4_K + w * S4_KS;
    if (lane < 16) sts128(ur + lane * 16, 0, 0, 0, 0);
    {
        const int o = d * 128 + lane * 4;
        const uint2 ar = __ldg((const uint2*)(Are + o)), ai = __ldg((const uint2*)(Aim + o)), br = __ldg((const uint2*)(Bre + o));
        const uint2 bi = __ldg((const uint2*)(Bim + o)), cr = __ldg((const uint2*)(Cre + o)), ci = __ldg((const uint2*)(Cim + o));
        const float dt = bf_round(expf(__bfloat162float(logdt[d])));
        const bf16* src = u + (size_t)(w * 128 + g) * DM + d0 + 4 * t;
        float T[5][4];
#pragma unroll
        for (int i = 0; i < 5; i++) T[i][0] = T[i][1] = T[i][2] = T[i][3] = 0.f;
        float klast = 0.f;
        const uint32_t wr_ = rs + lane * 4;
        const uint32_t ra = rs + (lane & 15) * 144 + (lane >> 4) * 16, rb = rs + (16 + (lane & 7)) * 144 + (lane >> 3) * 16;
#pragma unroll 1
        for (int c = 0; c < 4; c++) {
            uint2 v[4];
#pragma unroll
            for (int i = 0; i < 4; i++) v[i] = __ldg((const uint2*)(src + (size_t)(c * 32 + i * 8) * DM));
            auto pick = [&](const uint2& x) { const uint32_t y = c < 2 ? x.x : x.y; return (c & 1) ? bf_hi(y) : bf_lo(y); };
            auto put = [&](int row, cf x) { sts32(wr_ + row * 144, pack2(x.r, x.i)); };
            const float l2 = dt * pick(ar) * 1.4426950408889634f, tu = dt * pick(ai) * 0.15915494309189535f;
            const cf z1 = cexp(l2, tu), z2 = csq(z1), z4 = csq(z2), z8 = csq(z4), z128 = cexp(l2 * 128.f, tu * 128.f);
            cf a = z8;
            sts32(wr_, 0x00003f80u);
            put(1, a);
#pragma unroll
            for (int i = 2; i < 16; i++) { a = cmul(a, z8); put(i, a); }
            cf y = cmul({pick(cr), pick(ci)}, {dt * pick(br), dt * pick(bi)});
            y.i = -y.i;
#pragma unroll
            for (int k = 0; k < 16; k++) {
                const int n = k < 2 ? 8 : k < 4 ? 4 : k < 8 ? 2 : 1;
                const int row = 16 + (k < 2 ? 8 * k : k < 4 ? 8 + 4 * k : k < 8 ? 16 + 2 * k : 24 + k);
                cf x = y;
                put(row, x);
#pragma unroll
                for (int b = 1; b < n; b++) { x = cmulc(x, k < 2 ? z1 : k < 4 ? z2 : z4); put(row + b, x); }
                y = cmulc(y, z128);
            }
            klast += y.r;
            __syncwarp();
#pragma unroll
            for (int kp = 0; kp < 2; kp++) {
                uint32_t A0[4], A1[4];
                ldsm4(A0, ra + kp * 64);
                ldsm4(A1, ra + kp * 64 + 32);
#pragma unroll
                for (int i = 0; i < 5; i++) {
                    uint32_t B[4];
                    ldsm4(B, rb + i * 8 * 144 + kp * 64);
                    mma16816(T[i], A0[0], A0[1], A0[2], A0[3], B[0], B[1]);
                    mma16816(T[i], A1[0], A1[1], A1[2], A1[3], B[2], B[3]);
                }
            }
#pragma unroll
            for (int i = 0; i < 2; i++)
                stsm4t(sb + S4_U + tr_off * S4_US + 256 + (w * 128 + c * 32 + i * 16) * 2 + tr_l, v[2 * i].x, v[2 * i].y, v[2 * i + 1].x, v[2 * i + 1].y);
            __syncwarp();
        }
#pragma unroll
        for (int o2 = 16; o2; o2 >>= 1) klast += __shfl_xor_sync(~0u, klast, o2);
#pragma unroll
        for (int hh = 0; hh < 2; hh++) {
            const int i = g + 8 * hh;
            sts32(kd + (8 * i + 2 * t) * 2, pack2(T[0][2 * hh], T[0][2 * hh + 1]));
            sts32(kd + (128 + 8 * i + 2 * t) * 2, pack2(T[1][2 * hh], T[1][2 * hh + 1]));
            sts32(kd + (256 + 4 * i + 2 * (t & 1) + 64 * (t >> 1)) * 2, pack2(T[2][2 * hh], T[2][2 * hh + 1]));
            sts32(kd + (384 + 2 * i + 32 * t) * 2, pack2(T[3][2 * hh], T[3][2 * hh + 1]));
        }
        asm volatile("stmatrix.sync.aligned.m8n8.x2.trans.shared.b16 [%0], {%1,%2};"
                     ::"r"(kd + 1024 + (lane & 7) * 32 + ((lane >> 3) & 1) * 16), "r"(pack2(T[4][0], T[4][1])), "r"(pack2(T[4][2], T[4][3])) : "memory");
        if (lane == 0) sts32(kd + 1280, pack2(klast, 0.f));
    }
    __syncwarp();
    const uint32_t pk = rs + S4_PK + 64;
    {
#pragma unroll
        for (int i = 0; i < 2; i++) {
            const int x = i * 128 + lane * 4;
            const uint2 c = lds64(kd + x * 2);
            uint32_t p = lds16(kd + x * 2 - 2);
            if (x == 0) p = 0;
            sts128(pk + x * 4, __byte_perm(c.x, p, 0x5410), __byte_perm(c.x, 0, 0x1032), __byte_perm(c.y, c.x, 0x7610), __byte_perm(c.y, 0, 0x1032));
        }
#pragma unroll
        for (int i = 2; i < 4; i++) {
            const int x = i * 128 + lane * 4;
            const uint32_t ab = lds32(kd + 256 + x), c = lds16(kd + 256 + x + 4);
            const uint32_t p = x == 256 ? lds16(kd + 510) : ab;
            sts128(pk + x * 4, __byte_perm(ab, p, 0x5410), __byte_perm(ab, 0, 0x1010), __byte_perm(ab, 0, 0x1032), __byte_perm(c, ab, 0x7610));
        }
        const uint32_t v = lds16(kd + 768), v2 = lds16(kd + 1024);
        if (lane < 24) {
            uint32_t x0 = 0, x1 = 0, x2 = 0, x3 = 0;
            if (lane == 0) { x0 = x1 = x2 = v | (v << 16); x3 = v << 16; }
            if (lane == 12) x3 = v2;
            if (lane == 13) { x0 = v2 | (v2 << 16); x1 = v2 << 16; }
            sts128(lane < 20 ? pk + 2048 + lane * 16 : pk - 64 + (lane - 20) * 16, x0, x1, x2, x3);
        }
        if (lane < 4) sts128(rs + (lane >> 1) * S4_SIG + (lane & 1) * 16, 0, 0, 0, 0);
    }
    __syncthreads();
    float acc[16][4];
#pragma unroll
    for (int i = 0; i < 16; i++) acc[i][0] = acc[i][1] = acc[i][2] = acc[i][3] = 0.f;
    const uint32_t lf = (lane & 7) * 32 + ((lane >> 3) & 1) * 16 + (lane >> 4) * 256;
#pragma unroll
    for (int rg = 3; rg >= 2; rg--) {
#pragma unroll 1
        for (int it = 0; it < (rg == 3 ? 4 : 6); it++) {
            const int n = it * 32 + lane;
            uint32_t x[2][4];
            lds128(x[0], ur + 256 + n * 16 - 16);
            lds128(x[1], ur + 256 + n * 16);
            float e[16], p[15], s[11];
#pragma unroll
            for (int i = 0; i < 8; i++) { e[2 * i] = bf_lo(x[i >> 2][i & 3]); e[2 * i + 1] = bf_hi(x[i >> 2][i & 3]); }
#pragma unroll
            for (int i = 0; i < 15; i++) p[i] = e[i] + e[i + 1];
#pragma unroll
            for (int i = 0; i < 11; i++) s[i] = p[i + 3] + e[i + 5];
            const uint32_t o = rs + 16 + n * 16;
            if (rg == 2) sts128(o, pack2(s[0], s[1]), pack2(s[2], s[3]), pack2(s[4], s[5]), pack2(s[6], s[7]));
#pragma unroll
            for (int i = 0; i < 10; i++) s[i] = p[i + 2] + s[i + 1];
            if (rg == 2) {
                sts64(o + S4_SIG + 8, pack2(s[0], s[1]), pack2(s[2], s[3]));
                sts64(o + S4_SIG + 16, pack2(s[4], s[5]), pack2(s[6], s[7]));
            } else {
#pragma unroll
                for (int i = 0; i < 9; i++) s[i] = p[i + 1] + s[i + 1];
                sts64(o + 8, pack2(s[0], s[1]), pack2(s[2], s[3]));
                sts64(o + 16, pack2(s[4], s[5]), pack2(s[6], s[7]));
#pragma unroll
                for (int i = 0; i < 8; i++) s[i] = p[i] + s[i + 1];
                sts64(o + S4_SIG + 8, pack2(s[0], s[1]), pack2(s[2], s[3]));
                sts64(o + S4_SIG + 16, pack2(s[4], s[5]), pack2(s[6], s[7]));
            }
        }
        __syncwarp();
        if (rg == 3) {
#pragma unroll 1
            for (int q = 1; q <= 2; q++) s4_class<64, 2>(acc, rs + lf + (q == 1 ? 16 : S4_SIG), kd + (384 + q) * 2, g - 2 * t);
        } else {
#pragma unroll 1
            for (int q = 1; q <= 4; q++) s4_class<32, 4>(acc, rs + lf + ((q & 1) ? 0 : S4_SIG) + (q < 3 ? 16 : 0), kd + (256 + q) * 2, g - 2 * t);
        }
        __syncwarp();
    }
    {
        const uint32_t ub = ur + 256 + lf, kb = pk + (g - 2 * t) * 4;
#pragma unroll 1
        for (int j0 = 0; j0 < 8; j0++) {
            uint32_t B[8][4];
#pragma unroll
            for (int i = 0; i < 8; i++) ldsm4(B[i], ub + i * 512 - j0 * 32);
            auto block = [&](int J, uint32_t a) {
                const uint32_t r0 = lds32(a), rp = lds32(a + 32), rm = lds32(a - 32), r3 = lds32(a);
#pragma unroll
                for (int I = J; I < 16; I++)
                    mma16816(acc[I], r0, rp, rm, r3, B[(I - J) >> 1][((I - J) & 1) * 2], B[(I - J) >> 1][((I - J) & 1) * 2 + 1]);
            };
#pragma unroll
            for (int J = 0; J < 4; J++) block(J, kb + j0 * 64 + J * 512);
            if (j0 < 2) { block(4, kb + j0 * 64 + 2048); block(8, kb + j0 * 64 + (544 + 16) * 4); }
        }
        __syncwarp();
#pragma unroll
        for (int i = 0; i < 8; i++)
            stsm4t(rs + lf + i * 512, pack2(acc[2 * i][0], acc[2 * i][1]), pack2(acc[2 * i][2], acc[2 * i][3]),
                   pack2(acc[2 * i + 1][0], acc[2 * i + 1][1]), pack2(acc[2 * i + 1][2], acc[2 * i + 1][3]));
    }
    __syncthreads();
    {
        const uint2 dv = __ldg((const uint2*)(Dsk + d0 + 4 * t));
        bf16* dst = out + (size_t)(w * 128 + g) * 2048 + 1024 + d0 + 4 * t;
#pragma unroll
        for (int i = 0; i < 8; i++) {
            uint32_t y[4], x[4], o[4];
            ldsm4t(y, sb + S4_R + tr_off * S4_RS + (w * 128 + i * 16) * 2 + tr_l);
            ldsm4t(x, sb + S4_U + tr_off * S4_US + 256 + (w * 128 + i * 16) * 2 + tr_l);
#pragma unroll
            for (int j = 0; j < 4; j++)
                asm("{\n.reg .b32 s;\nmul.rn.bf16x2 s, %2, %3;\nadd.rn.bf16x2 %0, %1, s;\n}" : "=r"(o[j]) : "r"(y[j]), "r"(x[j]), "r"((j & 1) ? dv.y : dv.x));
            *reinterpret_cast<uint2*>(dst + (size_t)(i * 16) * 2048) = make_uint2(o[0], o[1]);
            *reinterpret_cast<uint2*>(dst + (size_t)(i * 16 + 8) * 2048) = make_uint2(o[2], o[3]);
        }
    }
    if (tid == 0) TL(2, 1);
}

enum { IT_QA = 0, IT_W256 = 1, IT_W128 = 2, IT_W64 = 3, IT_W64S = 4, IT_END = 7 };
struct BgParams { CUtensorMap mx, mwq, mkv, mkvm, mo, mo2, mo2s, mwo4, mwo2, mwo1; };
#define LOOK 3
#define LOOKL 8
#define LOOKM 5
#define LOOKN 4
#define PWO 40
#define P256 44
#define P128 50
__device__ __forceinline__ uint32_t ld_rlx32(const uint32_t* p) {
    uint32_t v;
    asm volatile("ld.relaxed.gpu.global.u32 %0, [%1];" : "=r"(v) : "l"(p) : "memory");
    return v;
}
struct Sched { uint32_t qb = 0, w0 = 0, w1 = 0; };
__device__ __forceinline__ int next_item(Sched& z) {
    for (int n = 0; n < SPIN_LIMIT; n++) {
        if (z.w0 < z.w1 && (z.qb >= 16 || ld_rlx32(g_flag + 64 + min(z.w0 >> 4, 15u)) >= 16)) {
            const uint32_t i = z.w0, k = i >= 240 ? 1 : z.w1 - i >= 4 && !(i & 3) ? 4 : z.w1 - i >= 2 && !(i & 1) ? 2 : 1;
            z.w0 += k;
            if (i >= 240) return IT_W64S | 15 << 3 | (i - 240) << 7;
            return (k == 4 ? IT_W256 : k == 2 ? IT_W128 : IT_W64) | (i >> 4) << 3 | ((i & 15) / k) << 7;
        }
        const uint32_t prog = ld_rlx32(g_flag + 98), wo = ld_rlx32(g_flag + 97);
        z.qb = max(z.qb, ld_rlx32(g_flag + 96));
        const bool wo_ready = z.w0 >= z.w1 && wo < 272 && (z.qb >= 16 || ld_rlx32(g_flag + 64 + min(wo >> 4, 15u)) >= 16);
        if (z.qb < 16 && prog + (z.qb == 15 ? LOOKL : z.qb == 14 ? LOOKM : z.qb == 13 ? LOOKN : LOOK) >= 4 * z.qb + 4 && !(wo_ready && prog <= PWO)) {
            const uint32_t i = atomicAdd(g_flag + 80 + z.qb, 1);
            if (i == 15) atomicMax(g_flag + 96, z.qb + 1);
            if (i < 16) return IT_QA | z.qb << 3 | i << 7;
            z.qb++;
            continue;
        }
        if (z.w0 < z.w1) {
            if (z.qb >= 16) continue;
        } else if (wo >= 272) {
            if (z.qb >= 16) return IT_END;
        } else if (wo_ready) {
            const uint32_t k = prog <= P256 ? 4 : prog <= P128 ? 2 : 1;
            z.w0 = atomicAdd(g_flag + 97, k);
            z.w1 = min(z.w0 + k, 272u);
            continue;
        }
        __nanosleep(300);
    }
    __trap();
    return IT_END;
}
constexpr int B_OST = NSTAGE * STAGE_BYTES + 1024;
constexpr int BG_SMEM = B_OST + 32768;

template <int BM, int BN, int KPS, typename ACC>
__device__ __forceinline__ void gemm_mainloop(ACC& acc, const GemmSmem& g, int cw, int rounds, uint32_t& round) {
#pragma unroll
    for (int i = 0; i < BN / 2; i++) acc[i] = 0.f;
#pragma unroll 1
    for (int k0 = 0; k0 < rounds; k0++, round++) {
#pragma unroll
        for (int s = 0; s < 4; s++) {
            mbar_wait_u(g.full + 8 * s, round & 1);
            gemm_stage<BM, BN, KPS>(acc, g.st + s * STAGE_BYTES, cw, false);
            wg_wait<1>();
            if (s > 0 || k0 > 0) mbar_arrive_one(g.empty + 8 * ((s + 3) & 3), threadIdx.x & 31);
        }
    }
    wg_wait<0>();
    mbar_arrive_one(g.empty + 8 * 3, threadIdx.x & 31);
}

template <int BM, int BN, int KPS>
__device__ __forceinline__ void wo_item(const GemmSmem& g, int cw, uint32_t& round, bf16* dst, int t) {
    if (BM == 64 && cw == 1) {
#pragma unroll 1
        for (int k0 = 0; k0 < 16 / KPS; k0++, round++)
#pragma unroll
            for (int s = 0; s < 4; s++) { mbar_wait_u(g.full + 8 * s, round & 1); mbar_arrive_one(g.empty + 8 * s, threadIdx.x & 31); }
        return;
    }
    float acc[BN / 2];
    gemm_mainloop<BM, BN, KPS>(acc, g, cw, 16 / KPS, round);
#pragma unroll
    for (int G = 0; G < BN / 32; G++)
#pragma unroll
        for (int rr = 0; rr < 2; rr++) {
            uint32_t r0 = pack2(acc[16 * G + 2 * rr], acc[16 * G + 2 * rr + 1]), r1 = pack2(acc[16 * G + 4 + 2 * rr], acc[16 * G + 5 + 2 * rr]);
            uint32_t r2 = pack2(acc[16 * G + 8 + 2 * rr], acc[16 * G + 9 + 2 * rr]), r3 = pack2(acc[16 * G + 12 + 2 * rr], acc[16 * G + 13 + 2 * rr]);
            quad_transpose(r0, r1, r2, r3, t);
            *reinterpret_cast<uint4*>(dst + (size_t)rr * 8 * 2048 + G * 32) = make_uint4(r0, r1, r2, r3);
        }
}

template <int HF>
__device__ __forceinline__ void attend(const uint32_t* q, uint32_t st, uint32_t sm, uint32_t ost, uint32_t bar_free, uint32_t parity, int lane) {
    constexpr int NT = HF ? 5 : 3;
    const int r8 = lane & 7, m4 = lane >> 3, gq = lane >> 2, t = lane & 3;
    const float sl2e = 0.08838834764831845f * 1.4426950408889634f;
    const uint32_t la = r8 * 128 + ((m4 ^ r8) << 4);
    float sc[NT][4];
#pragma unroll
    for (int nt = 0; nt < NT; nt++) sc[nt][0] = sc[nt][1] = sc[nt][2] = sc[nt][3] = 0.f;
#pragma unroll
    for (int kp = 0; kp < 4; kp++)
#pragma unroll
        for (int nt = 0; nt < NT; nt++) {
            uint32_t b[4];
            ldsm4(b, (nt == 0 ? sm + (kp >> 1) * 2048 : st + (kp >> 1) * 8192 + (nt - 1) * 1024) + (la ^ ((kp & 1) << 6)));
            mma16816(sc[nt], q[kp * 8], q[kp * 8 + 1], q[kp * 8 + 2], q[kp * 8 + 3], b[0], b[1]);
            mma16816(sc[nt], q[kp * 8 + 4], q[kp * 8 + 5], q[kp * 8 + 6], q[kp * 8 + 7], b[2], b[3]);
        }
    const float ninf = -3.0e38f;
    if (2 * t > gq) sc[NT - 2][0] = sc[NT - 1][2] = ninf;
    if (2 * t + 1 > gq) sc[NT - 2][1] = sc[NT - 1][3] = ninf;
    sc[NT - 1][0] = sc[NT - 1][1] = ninf;
    uint32_t p[NT][2];
#pragma unroll
    for (int i = 0; i < 2; i++) {
        float m = fmaxf(sc[0][2 * i], sc[0][2 * i + 1]);
#pragma unroll
        for (int nt = 1; nt < NT - 1 + i; nt++) m = fmaxf(m, fmaxf(sc[nt][2 * i], sc[nt][2 * i + 1]));
        m = fmaxf(m, __shfl_xor_sync(~0u, m, 1));
        m = fmaxf(m, __shfl_xor_sync(~0u, m, 2));
        const float ms = m * sl2e;
        float sum = 0.f;
#pragma unroll
        for (int nt = 0; nt < NT - 1 + i; nt++) {
            sc[nt][2 * i] = ex2(fmaf(sc[nt][2 * i], sl2e, -ms));
            sc[nt][2 * i + 1] = ex2(fmaf(sc[nt][2 * i + 1], sl2e, -ms));
            sum += sc[nt][2 * i] + sc[nt][2 * i + 1];
        }
        sum += __shfl_xor_sync(~0u, sum, 1);
        sum += __shfl_xor_sync(~0u, sum, 2);
        float inv;
        asm("rcp.approx.ftz.f32 %0, %1;" : "=f"(inv) : "f"(sum));
#pragma unroll
        for (int nt = 0; nt < NT - 1 + i; nt++) p[nt][i] = pack2(sc[nt][2 * i] * inv, sc[nt][2 * i + 1] * inv);
    }
    p[NT - 1][0] = 0;
    const uint32_t lv = ((m4 & 1) * 8 + r8) * 128 + (((m4 >> 1) ^ r8) << 4);
    mbar_wait_u(bar_free, parity);
#pragma unroll
    for (int G = 0; G < 4; G++) {
        float o[4][4];
#pragma unroll
        for (int i = 0; i < 4; i++) o[i][0] = o[i][1] = o[i][2] = o[i][3] = 0.f;
        uint32_t b[4];
        ldsm4t(b, sm + 4096 + (G >> 1) * 2048 + (la ^ ((G & 1) << 6)));
#pragma unroll
        for (int i = 0; i < 4; i++) mma1688(o[i], p[0][0], p[0][1], b[i]);
#pragma unroll
        for (int kk = 0; kk <= HF; kk++)
#pragma unroll
            for (int i = 0; i < 2; i++) {
                ldsm4t(b, st + 16384 + (G >> 1) * 8192 + kk * 2048 + (lv ^ (((G & 1) * 2 + i) << 5)));
                mma16816(o[2 * i], p[1 + 2 * kk][0], p[1 + 2 * kk][1], p[2 + 2 * kk][0], p[2 + 2 * kk][1], b[0], b[1]);
                mma16816(o[2 * i + 1], p[1 + 2 * kk][0], p[1 + 2 * kk][1], p[2 + 2 * kk][0], p[2 + 2 * kk][1], b[2], b[3]);
            }
#pragma unroll
        for (int i = 0; i < 2; i++)
            asm volatile("stmatrix.sync.aligned.m8n8.x4.shared.b16 [%0], {%1,%2,%3,%4};"
                         ::"r"(ost + (G >> 1) * 16384 + (lv ^ (((G & 1) * 2 + i) << 5))),
                           "r"(pack2(o[2 * i][0], o[2 * i][1])), "r"(pack2(o[2 * i][2], o[2 * i][3])),
                           "r"(pack2(o[2 * i + 1][0], o[2 * i + 1][1])), "r"(pack2(o[2 * i + 1][2], o[2 * i + 1][3])) : "memory");
    }
    asm volatile("fence.proxy.async.shared::cta;" ::: "memory");
    __syncwarp();
}

__device__ __forceinline__ void tma_prefetch3d(const CUtensorMap* m, int c0, int c1, int c2) {
    asm volatile("cp.async.bulk.prefetch.tensor.3d.L2.global [%0, {%1, %2, %3}];" ::"l"(m), "r"(c0), "r"(c1), "r"(c2) : "memory");
}

__global__ void __launch_bounds__(384, 1) k_bg(const __grid_constant__ BgParams P, bf16* __restrict__ out) {
    extern __shared__ __align__(1024) uint8_t smem_gemm[];
    const uint32_t xb = smem_u32(smem_gemm) + NSTAGE * STAGE_BYTES + 128;
    const uint32_t bar_item = xb, bar_o = xb + 16, bar_f = xb + 24, slot = xb + 32, slot_o = xb + 40;
    if (threadIdx.x == 0) { mbar_init(bar_item, 1); mbar_init(bar_item + 8, 1); mbar_init(bar_o, 8); mbar_init(bar_f, 1); }
    GemmSmem g = gemm_setup(smem_gemm, 8);
    const int wg = __shfl_sync(~0u, threadIdx.x >> 7, 0);
    if (wg == 0) {
        asm volatile("setmaxnreg.dec.sync.aligned.u32 40;");
        if (threadIdx.x == 0) {
            uint32_t it = 0;
            Sched z;
            auto acquire = [&](uint32_t bytes) {
                const int s = it & 3;
                mbar_wait(g.empty + 8 * s, ((it >> 2) & 1) ^ 1);
                mbar_expect_tx(g.full + 8 * s, bytes);
                it++;
                return s;
            };
            for (int n = 0;; n++) {
                const int code = next_item(z);
                sts32(slot + (n & 1) * 4, code);
                mbar_arrive(bar_item + (n & 1) * 8);
                const int type = code & 7, blk = (code >> 3) & 15, idx = code >> 7, m0 = blk * 128;
                if (type == IT_END) break;
                if (type == IT_QA) {
                    for (int k = 0; k < 16; k++) {
                        const int s = acquire(STAGE_BYTES);
                        const uint32_t st = g.st + s * STAGE_BYTES, fb = g.full + 8 * s;
                        tma2d(st, &P.mx, k * 64, m0, fb);
                        tma3d(st + 16384, &P.mwq, 0, k * 64, idx * 4, fb);
                        if (k >= 4 && k < 12) tma_prefetch3d(&P.mkv, 0, m0 + (k & 1) * 64, (k & 8) * 8 + idx * 4 + (k & 2));
                    }
                    bool ready = ld_acq32(g_flag + 2 * idx) >= 4 * blk + 4 && ld_acq32(g_flag + 2 * idx + 1) >= 4 * blk + 4;
                    if (ready) asm volatile("fence.proxy.async.global;" ::: "memory");
                    for (int pass = 0; pass < 2; pass++) {
                        for (int s = 0; s < 4; s++) {
                            const uint32_t st = g.st + s * STAGE_BYTES, fb = g.full + 8 * s;
                            if (pass == 0) {
                                acquire(40960);
                                tma3d(st, &P.mkv, 0, m0 + (s & 1) * 64, idx * 4 + (s & 2), fb);
                                tma3d(st + 16384, &P.mkv, 0, m0 + (s & 1) * 64, 64 + idx * 4 + (s & 2), fb);
                            }
                            if (ready) {
                                tma3d(st + 32768, &P.mkvm, 0, blk * 32 + (s & 1) * 16, idx * 4 + (s & 2), fb);
                                tma3d(st + 36864, &P.mkvm, 0, blk * 32 + (s & 1) * 16, 64 + idx * 4 + (s & 2), fb);
                            }
                        }
                        if (ready) break;
                        wait_flag(g_flag + 2 * idx, 4 * blk + 4);
                        wait_flag(g_flag + 2 * idx + 1, 4 * blk + 4);
                        asm volatile("fence.proxy.async.global;" ::: "memory");
                        ready = true;
                    }
                } else {
                    wait_flag(g_flag + 64 + blk, 16);
                    asm volatile("fence.proxy.async.global;" ::: "memory");
                    if (type <= IT_W128) {
                        const int nb = type == IT_W256 ? 4 : 2;
                        for (int k = 0; k < 64; k++) {
                            const int s = acquire(16384 + nb * 8192);
                            const uint32_t st = g.st + s * STAGE_BYTES, fb = g.full + 8 * s;
                            tma2d(st, &P.mo, k * 64, m0, fb);
                            tma3d(st + 16384, nb == 4 ? &P.mwo4 : &P.mwo2, 0, k * 64, idx * nb, fb);
                        }
                    } else {
                        const uint32_t ab = type == IT_W64 ? 32768 : 16384;
                        for (int k = 0; k < 32; k++) {
                            const int s = acquire(ab + 16384);
                            const uint32_t st = g.st + s * STAGE_BYTES, fb = g.full + 8 * s;
                            tma3d(st, type == IT_W64 ? &P.mo2 : &P.mo2s, 0, m0 + (idx >> 4) * 64, k * 2, fb);
                            tma3d(st + ab, &P.mwo1, 0, k * 128, idx & 15, fb);
                        }
                    }
                }
            }
        } else if (threadIdx.x == 32) {
            for (;;) {
                mbar_wait(bar_o, 0);
                const int code = lds32(slot_o), blk = (code >> 3) & 15, idx = (code >> 7) & 31;
                if ((code & 7) == IT_END) break;
                for (int hh = 0; hh < 2; hh++) {
                    if (hh) mbar_wait(bar_o, 1);
                    asm volatile("cp.async.bulk.tensor.3d.global.shared::cta.bulk_group [%0, {%2, %3, %4}], [%1];\n"
                                 "cp.async.bulk.commit_group;\ncp.async.bulk.wait_group.read 0;"
                                 ::"l"(&P.mo2), "r"(g.st + B_OST), "r"(0), "r"(blk * 128), "r"(idx * 4 + hh * 2) : "memory");
                    mbar_arrive(bar_f);
                }
                asm volatile("cp.async.bulk.wait_group 0;\nfence.acq_rel.gpu;\nred.relaxed.gpu.global.add.u32 [%0], 1;"
                             ::"l"(g_flag + 64 + blk) : "memory");
            }
        }
    } else {
        asm volatile("setmaxnreg.inc.sync.aligned.u32 232;");
        const int cw = wg - 1, ww = __shfl_sync(~0u, (threadIdx.x >> 5) & 3, 0), lane = threadIdx.x & 31;
        uint32_t round = 0;
#pragma unroll 1
        for (int n = 0;; n++) {
            mbar_wait_u(bar_item + (n & 1) * 8, (n >> 1) & 1);
            const int code = __shfl_sync(~0u, lds32(slot + (n & 1) * 4), 0);
            const int type = code & 7, blk = (code >> 3) & 15, idx = (code >> 7) & 31;
#define TLB(slot_)
            if (type == IT_END) {
                mbar_wait_u(bar_f, 1);
                if (threadIdx.x == 128) sts32(slot_o, IT_END);
                __syncwarp();
                mbar_arrive_one(bar_o, lane);
                break;
            }
            TLB(0);
            if (type == IT_QA) {
                uint32_t q[64];
                {
                    float acc[128];
                    gemm_mainloop<128, 256, 1>(acc, g, cw, 4, round);
#pragma unroll
                    for (int i = 0; i < 64; i++) q[i] = pack2(acc[2 * i], acc[2 * i + 1]);
                }
                if (threadIdx.x == 128) sts32(slot_o, code);
                TLB(2);
#pragma unroll
                for (int hh = 0; hh < 2; hh++) {
                    const uint32_t st = g.st + (2 * hh + cw) * STAGE_BYTES, ost = g.st + B_OST + (cw * 4 + ww) * 2048;
                    mbar_wait_u(g.full + 16 * hh, round & 1);
                    mbar_wait_u(g.full + 16 * hh + 8, round & 1);
                    if (hh == 0) { TLB(3); }
                    if (ww & 1) attend<1>(q + 32 * hh, st + (ww >> 1) * 4096, st + 32768 + (ww >> 1) * 1024, ost, bar_f, hh ^ 1, lane);
                    else attend<0>(q + 32 * hh, st + (ww >> 1) * 4096, st + 32768 + (ww >> 1) * 1024, ost, bar_f, hh ^ 1, lane);
                    mbar_arrive_one(bar_o, lane);
                    mbar_arrive_one(g.empty + 16 * hh, lane);
                    mbar_arrive_one(g.empty + 16 * hh + 8, lane);
                }
                round++;
            } else {
                bf16* dst = out + (size_t)(blk * 128 + cw * 64 + ww * 16 + (lane >> 2)) * 2048 + (lane & 3) * 8;
                if (type == IT_W256) wo_item<128, 256, 1>(g, cw, round, dst + idx * 256, lane & 3);
                else if (type == IT_W128) wo_item<128, 128, 1>(g, cw, round, dst + idx * 128, lane & 3);
                else if (type == IT_W64) wo_item<128, 64, 2>(g, cw, round, dst + idx * 64, lane & 3);
                else wo_item<64, 64, 2>(g, cw, round, dst + (size_t)(idx >> 4) * 64 * 2048 + (idx & 15) * 64, lane & 3);
            }
            TLB(1);
        }
    }
}

typedef CUresult (*EncodeFn)(CUtensorMap*, CUtensorMapDataType, cuuint32_t, void*, const cuuint64_t*, const cuuint64_t*,
                             const cuuint32_t*, const cuuint32_t*, CUtensorMapInterleave, CUtensorMapSwizzle,
                             CUtensorMapL2promotion, CUtensorMapFloatOOBfill);

static void map2d(EncodeFn enc, CUtensorMap* m, const void* p, int rows, int cols, int box_rows) {
    cuuint64_t dim[2] = {(cuuint64_t)cols, (cuuint64_t)rows}, str[1] = {(cuuint64_t)cols * 2};
    cuuint32_t box[2] = {64, (cuuint32_t)box_rows}, es[2] = {1, 1};
    enc(m, CU_TENSOR_MAP_DATA_TYPE_BFLOAT16, 2, (void*)p, dim, str, box, es, CU_TENSOR_MAP_INTERLEAVE_NONE,
        CU_TENSOR_MAP_SWIZZLE_128B, CU_TENSOR_MAP_L2_PROMOTION_L2_256B, CU_TENSOR_MAP_FLOAT_OOB_FILL_NONE);
}
static void map3d(EncodeFn enc, CUtensorMap* m, const void* p, int rows, int cols, int box_rows, int nblk) {
    cuuint64_t dim[3] = {64, (cuuint64_t)rows, (cuuint64_t)cols / 64}, str[2] = {(cuuint64_t)cols * 2, 128};
    cuuint32_t box[3] = {64, (cuuint32_t)box_rows, (cuuint32_t)nblk}, es[3] = {1, 1, 1};
    enc(m, CU_TENSOR_MAP_DATA_TYPE_BFLOAT16, 3, (void*)p, dim, str, box, es, CU_TENSOR_MAP_INTERLEAVE_NONE,
        CU_TENSOR_MAP_SWIZZLE_128B, CU_TENSOR_MAP_L2_PROMOTION_L2_256B, CU_TENSOR_MAP_FLOAT_OOB_FILL_NONE);
}

#define USE_PDL 1

extern "C" void kernel_launch(void* const* d_in, const int* in_sizes, int n_in, void* d_out, int out_size) {
    const bf16 *x = (const bf16*)d_in[0], *mem0 = (const bf16*)d_in[1], *Wq = (const bf16*)d_in[2], *Wk = (const bf16*)d_in[3];
    const bf16 *Wv = (const bf16*)d_in[4], *Wo = (const bf16*)d_in[5];
    const bf16 *u = (const bf16*)d_in[7], *Are = (const bf16*)d_in[8], *Aim = (const bf16*)d_in[9], *Bre = (const bf16*)d_in[10];
    const bf16 *Bim = (const bf16*)d_in[11], *Cre = (const bf16*)d_in[12], *Cim = (const bf16*)d_in[13];
    const bf16 *logdt = (const bf16*)d_in[14], *Dsk = (const bf16*)d_in[15];
    bf16* out = (bf16*)d_out;

    void* fn = nullptr;
    cudaDriverEntryPointQueryResult qr;
    cudaGetDriverEntryPoint("cuTensorMapEncodeTiled", &fn, cudaEnableDefault, &qr);
    EncodeFn enc = (EncodeFn)fn;
    void *kv, *kvm, *o;
    cudaGetSymbolAddress(&kv, g_kv);
    cudaGetSymbolAddress(&kvm, g_kvm);
    cudaGetSymbolAddress(&o, g_o);
    CUtensorMap mwk, mwv, mkv2;
    BgParams P;
    map2d(enc, &P.mx, x, SEQ, DM, 128);
    map2d(enc, &P.mo, o, SEQ, HD, 128);
    map3d(enc, &P.mo2, o, SEQ, HD, 128, 2);
    map3d(enc, &P.mo2s, o, SEQ, HD, 64, 2);
    map3d(enc, &P.mwq, Wq, DM, HD, 64, 4);
    map3d(enc, &mwk, Wk, DM, HD, 64, 4);
    map3d(enc, &mwv, Wv, DM, HD, 64, 4);
    map3d(enc, &P.mwo4, Wo, HD, DM, 64, 4);
    map3d(enc, &P.mwo2, Wo, HD, DM, 64, 2);
    map3d(enc, &P.mwo1, Wo, HD, DM, 128, 1);
    map3d(enc, &mkv2, kv, SEQ, 8192, 32, 2);
    map3d(enc, &P.mkv, kv, SEQ, 8192, 64, 2);
    map3d(enc, &P.mkvm, kvm, NSEG * 8, 8192, 16, 2);
    cudaFuncSetAttribute(k_kv, cudaFuncAttributeMaxDynamicSharedMemorySize, GEMM_SMEM);
    cudaFuncSetAttribute(k_bg, cudaFuncAttributeMaxDynamicSharedMemorySize, BG_SMEM);
    cudaFuncSetAttribute(k_chain, cudaFuncAttributeMaxDynamicSharedMemorySize, CHAIN_SMEM);
    cudaFuncSetAttribute(k_s4, cudaFuncAttributeMaxDynamicSharedMemorySize, S4_SMEM);

    cudaStream_t st = cudaStreamPerThread;
    k_kv<<<132, 384, GEMM_SMEM, st>>>(P.mx, mwk, mwv, Wq, Wo, u);
    k_chain<<<96, 256, CHAIN_SMEM, st>>>(mem0, Wq, Wk, Wv, Wo, mkv2);
    cudaLaunchAttribute pdl[1];
    pdl[0].id = cudaLaunchAttributeProgrammaticStreamSerialization;
    pdl[0].val.programmaticStreamSerializationAllowed = 1;
    cudaLaunchConfig_t cfg = {};
    cfg.stream = st; cfg.attrs = pdl; cfg.numAttrs = USE_PDL;
    cfg.gridDim = dim3(64); cfg.blockDim = dim3(512); cfg.dynamicSmemBytes = S4_SMEM;
    cudaLaunchKernelEx(&cfg, k_s4, u, Are, Aim, Bre, Bim, Cre, Cim, logdt, Dsk, out);
    cfg.gridDim = dim3(132); cfg.blockDim = dim3(384); cfg.dynamicSmemBytes = BG_SMEM;
    cudaLaunchKernelEx(&cfg, k_bg, P, out);
}
```

```cpp
#include <cuda_runtime.h>
#include <cuda_bf16.h>
#include <cuda.h>
#include <stdint.h>

typedef __nv_bfloat16 bf16;

constexpr int SEQ = 2048, DM = 1024, HD = 4096, NSEG = 64;

__device__ __align__(1024) bf16 g_kv[(size_t)SEQ * 8192];
__device__ __align__(1024) bf16 g_kvm[(size_t)NSEG * 8 * 8192];
__device__ __align__(1024) bf16 g_o[(size_t)SEQ * HD];
constexpr int XPAIRS = 128 + NSEG * 4;
__device__ __align__(8192) uint2 g_x[XPAIRS * 1024];
__device__ uint32_t g_home[XPAIRS];
__device__ uint32_t g_side[256];
__device__ __align__(1024) uint32_t g_flag[256];

#define TL(kern, slot)

__device__ __forceinline__ uint32_t smem_u32(const void* p) { return (uint32_t)__cvta_generic_to_shared(p); }
__device__ __forceinline__ void mbar_init(uint32_t bar, uint32_t cnt) {
    asm volatile("mbarrier.init.shared::cta.b64 [%0], %1;" ::"r"(bar), "r"(cnt) : "memory");
}
__device__ __forceinline__ void mbar_expect_tx(uint32_t bar, uint32_t bytes) {
    asm volatile("mbarrier.arrive.expect_tx.shared::cta.b64 _, [%0], %1;" ::"r"(bar), "r"(bytes) : "memory");
}
__device__ __forceinline__ void mbar_arrive(uint32_t bar) {
    asm volatile("mbarrier.arrive.shared::cta.b64 _, [%0];" ::"r"(bar) : "memory");
}
__device__ __forceinline__ bool mbar_try(uint32_t bar, uint32_t parity) {
    uint32_t ok;
    asm volatile("{\n.reg .pred p;\nmbarrier.try_wait.parity.shared::cta.b64 p, [%1], %2;\nselp.u32 %0, 1, 0, p;\n}"
                 : "=r"(ok) : "r"(bar), "r"(parity) : "memory");
    return ok;
}
constexpr int SPIN_LIMIT = 1 << 20;
__device__ __forceinline__ void mbar_wait(uint32_t bar, uint32_t parity) {
    int n = 0;
    while (!mbar_try(bar, parity)) { if (++n > SPIN_LIMIT) __trap(); }
}
__device__ __forceinline__ void mbar_wait_u(uint32_t bar, uint32_t parity) {
    asm volatile("{\n.reg .pred p;\n.reg .u32 n;\n"
                 "mbarrier.try_wait.parity.shared::cta.b64 p, [%0], %1;\n@p bra.uni DONE;\nmov.u32 n, 0;\n"
                 "AGAIN:\nmbarrier.try_wait.parity.shared::cta.b64 p, [%0], %1;\n@p bra.uni DONE;\n"
                 "add.u32 n, n, 1;\nsetp.lt.u32 p, n, 0x100000;\n@p bra.uni AGAIN;\ntrap;\nDONE:\n}"
                 ::"r"(bar), "r"(parity) : "memory");
}
__device__ __forceinline__ void tma2d(uint32_t dst, const CUtensorMap* m, int c0, int c1, uint32_t bar) {
    asm volatile("cp.async.bulk.tensor.2d.shared::cluster.global.mbarrier::complete_tx::bytes [%0], [%1, {%3, %4}], [%2];"
                 ::"r"(dst), "l"(m), "r"(bar), "r"(c0), "r"(c1) : "memory");
}
__device__ __forceinline__ void tma3d(uint32_t dst, const CUtensorMap* m, int c0, int c1, int c2, uint32_t bar) {
    asm volatile("cp.async.bulk.tensor.3d.shared::cluster.global.mbarrier::complete_tx::bytes [%0], [%1, {%3, %4, %5}], [%2];"
                 ::"r"(dst), "l"(m), "r"(bar), "r"(c0), "r"(c1), "r"(c2) : "memory");
}
__device__ __forceinline__ uint32_t pack2(float lo, float hi) {
    uint32_t r;
    asm("cvt.rn.bf16x2.f32 %0, %1, %2;" : "=r"(r) : "f"(hi), "f"(lo));
    return r;
}
__device__ __forceinline__ float bf_lo(uint32_t v) { return __uint_as_float(v << 16); }
__device__ __forceinline__ float bf_hi(uint32_t v) { return __uint_as_float(v & 0xffff0000u); }
__device__ __forceinline__ float bf_round(float x) { return bf_lo(pack2(x, 0.f)); }
__device__ __forceinline__ float ex2(float x) { float y; asm("ex2.approx.ftz.f32 %0, %1;" : "=f"(y) : "f"(x)); return y; }
__device__ __forceinline__ void mma16816(float (&c)[4], uint32_t a0, uint32_t a1, uint32_t a2, uint32_t a3, uint32_t b0, uint32_t b1) {
    asm volatile("mma.sync.aligned.m16n8k16.row.col.f32.bf16.bf16.f32 {%0,%1,%2,%3}, {%4,%5,%6,%7}, {%8,%9}, {%0,%1,%2,%3};"
                 : "+f"(c[0]), "+f"(c[1]), "+f"(c[2]), "+f"(c[3]) : "r"(a0), "r"(a1), "r"(a2), "r"(a3), "r"(b0), "r"(b1));
}
__device__ __forceinline__ void mma1688(float (&c)[4], uint32_t a0, uint32_t a1, uint32_t b0) {
    asm volatile("mma.sync.aligned.m16n8k8.row.col.f32.bf16.bf16.f32 {%0,%1,%2,%3}, {%4,%5}, {%6}, {%0,%1,%2,%3};"
                 : "+f"(c[0]), "+f"(c[1]), "+f"(c[2]), "+f"(c[3]) : "r"(a0), "r"(a1), "r"(b0));
}
__device__ __forceinline__ void ldsm4(uint32_t (&r)[4], uint32_t a) {
    asm volatile("ldmatrix.sync.aligned.m8n8.x4.shared.b16 {%0,%1,%2,%3}, [%4];"
                 : "=r"(r[0]), "=r"(r[1]), "=r"(r[2]), "=r"(r[3]) : "r"(a) : "memory");
}
__device__ __forceinline__ void ldsm4t(uint32_t (&r)[4], uint32_t a) {
    asm volatile("ldmatrix.sync.aligned.m8n8.x4.trans.shared.b16 {%0,%1,%2,%3}, [%4];"
                 : "=r"(r[0]), "=r"(r[1]), "=r"(r[2]), "=r"(r[3]) : "r"(a) : "memory");
}
__device__ __forceinline__ void ldsm2t(uint32_t& r0, uint32_t& r1, uint32_t a) {
    asm volatile("ldmatrix.sync.aligned.m8n8.x2.trans.shared.b16 {%0,%1}, [%2];" : "=r"(r0), "=r"(r1) : "r"(a) : "memory");
}
__device__ __forceinline__ void stsm4t(uint32_t a, uint32_t r0, uint32_t r1, uint32_t r2, uint32_t r3) {
    asm volatile("stmatrix.sync.aligned.m8n8.x4.trans.shared.b16 [%0], {%1,%2,%3,%4};"
                 ::"r"(a), "r"(r0), "r"(r1), "r"(r2), "r"(r3) : "memory");
}
__device__ __forceinline__ void lds128(uint32_t (&r)[4], uint32_t a) {
    asm volatile("ld.shared.v4.u32 {%0,%1,%2,%3}, [%4];" : "=r"(r[0]), "=r"(r[1]), "=r"(r[2]), "=r"(r[3]) : "r"(a) : "memory");
}
__device__ __forceinline__ float4 lds128f(uint32_t a) {
    float4 v;
    asm volatile("ld.shared.v4.f32 {%0,%1,%2,%3}, [%4];" : "=f"(v.x), "=f"(v.y), "=f"(v.z), "=f"(v.w) : "r"(a) : "memory");
    return v;
}
__device__ __forceinline__ float2 lds64f(uint32_t a) {
    float2 v;
    asm volatile("ld.shared.v2.f32 {%0,%1}, [%2];" : "=f"(v.x), "=f"(v.y) : "r"(a) : "memory");
    return v;
}
__device__ __forceinline__ uint32_t lds32(uint32_t a) {
    uint32_t v;
    asm volatile("ld.shared.u32 %0, [%1];" : "=r"(v) : "r"(a) : "memory");
    return v;
}
__device__ __forceinline__ void sts128(uint32_t a, uint32_t r0, uint32_t r1, uint32_t r2, uint32_t r3) {
    asm volatile("st.shared.v4.u32 [%0], {%1,%2,%3,%4};" ::"r"(a), "r"(r0), "r"(r1), "r"(r2), "r"(r3) : "memory");
}
__device__ __forceinline__ void sts128f(uint32_t a, float r0, float r1, float r2, float r3) {
    asm volatile("st.shared.v4.f32 [%0], {%1,%2,%3,%4};" ::"r"(a), "f"(r0), "f"(r1), "f"(r2), "f"(r3) : "memory");
}
__device__ __forceinline__ void sts64(uint32_t a, uint32_t r0, uint32_t r1) {
    asm volatile("st.shared.v2.u32 [%0], {%1,%2};" ::"r"(a), "r"(r0), "r"(r1) : "memory");
}
__device__ __forceinline__ void sts64f(uint32_t a, float r0, float r1) {
    asm volatile("st.shared.v2.f32 [%0], {%1,%2};" ::"r"(a), "f"(r0), "f"(r1) : "memory");
}
__device__ __forceinline__ void sts32f(uint32_t a, float r0) {
    asm volatile("st.shared.f32 [%0], %1;" ::"r"(a), "f"(r0) : "memory");
}
__device__ __forceinline__ uint2 ld_rlx64(const uint2* p) {
    uint2 v;
    asm volatile("{\n.reg .b64 t;\nld.relaxed.gpu.global.b64 t, [%2];\nmov.b64 {%0,%1}, t;\n}" : "=r"(v.x), "=r"(v.y) : "l"(p) : "memory");
    return v;
}
__device__ __forceinline__ void st_rlx64(uint2* p, uint32_t x, uint32_t y) {
    asm volatile("{\n.reg .b64 t;\nmov.b64 t, {%1,%2};\nst.relaxed.gpu.global.b64 [%0], t;\n}" ::"l"(p), "r"(x), "r"(y) : "memory");
}
__device__ __forceinline__ uint32_t ld_acq32(const uint32_t* p) {
    uint32_t v;
    asm volatile("ld.acquire.gpu.global.u32 %0, [%1];" : "=r"(v) : "l"(p) : "memory");
    return v;
}
__device__ __forceinline__ void wait_flag(const uint32_t* p, uint32_t need) {
    int n = 0;
    while (ld_acq32(p) < need) { __nanosleep(200); if (++n > SPIN_LIMIT) __trap(); }
}
__device__ __forceinline__ void bar_sync(int id, int n) { asm volatile("bar.sync %0, %1;" ::"r"(id), "r"(n) : "memory"); }
__device__ __forceinline__ void wg_fence() { asm volatile("wgmma.fence.sync.aligned;" ::: "memory"); }
__device__ __forceinline__ void wg_commit() { asm volatile("wgmma.commit_group.sync.aligned;" ::: "memory"); }
template <int N> __device__ __forceinline__ void wg_wait() { asm volatile("wgmma.wait_group.sync.aligned %0;" ::"n"(N) : "memory"); }
__device__ __forceinline__ uint64_t desc_sw128(uint32_t addr, uint32_t lbo, uint32_t sbo) {
    return (uint64_t)((addr & 0x3FFFF) >> 4) | ((uint64_t)(lbo >> 4) << 16) | ((uint64_t)(sbo >> 4) << 32) | (1ull << 62);
}
__device__ __forceinline__ void quad_transpose(uint32_t& r0, uint32_t& r1, uint32_t& r2, uint32_t& r3, int t) {
    const bool o = t & 1, h = t & 2;
    uint32_t s0 = __shfl_xor_sync(~0u, o ? r0 : r1, 1), s1 = __shfl_xor_sync(~0u, o ? r2 : r3, 1);
    uint32_t a0 = o ? s0 : r0, a1 = o ? r1 : s0, a2 = o ? s1 : r2, a3 = o ? r3 : s1;
    s0 = __shfl_xor_sync(~0u, h ? a0 : a2, 2); s1 = __shfl_xor_sync(~0u, h ? a1 : a3, 2);
    r0 = h ? s0 : a0; r1 = h ? s1 : a1; r2 = h ? a2 : s0; r3 = h ? a3 : s1;
}

__device__ __forceinline__ void wgmma_n256(float (&d)[128], uint64_t da, uint64_t db, int sd) {
    asm volatile("{\n.reg .pred p;\nsetp.ne.b32 p, %130, 0;\n"
        "wgmma.mma_async.sync.aligned.m64n256k16.f32.bf16.bf16 "
        "{%0,%1,%2,%3,%4,%5,%6,%7,%8,%9,%10,%11,%12,%13,%14,%15,"
        "%16,%17,%18,%19,%20,%21,%22,%23,%24,%25,%26,%27,%28,%29,%30,%31,"
        "%32,%33,%34,%35,%36,%37,%38,%39,%40,%41,%42,%43,%44,%45,%46,%47,"
        "%48,%49,%50,%51,%52,%53,%54,%55,%56,%57,%58,%59,%60,%61,%62,%63,"
        "%64,%65,%66,%67,%68,%69,%70,%71,%72,%73,%74,%75,%76,%77,%78,%79,"
        "%80,%81,%82,%83,%84,%85,%86,%87,%88,%89,%90,%91,%92,%93,%94,%95,"
        "%96,%97,%98,%99,%100,%101,%102,%103,%104,%105,%106,%107,%108,%109,%110,%111,"
        "%112,%113,%114,%115,%116,%117,%118,%119,%120,%121,%122,%123,%124,%125,%126,%127}, %128, %129, p, 1, 1, 0, 1;\n}\n"
        : "+f"(d[0]), "+f"(d[1]), "+f"(d[2]), "+f"(d[3]), "+f"(d[4]), "+f"(d[5]), "+f"(d[6]), "+f"(d[7]),
          "+f"(d[8]), "+f"(d[9]), "+f"(d[10]), "+f"(d[11]), "+f"(d[12]), "+f"(d[13]), "+f"(d[14]), "+f"(d[15]),
          "+f"(d[16]), "+f"(d[17]), "+f"(d[18]), "+f"(d[19]), "+f"(d[20]), "+f"(d[21]), "+f"(d[22]), "+f"(d[23]),
          "+f"(d[24]), "+f"(d[25]), "+f"(d[26]), "+f"(d[27]), "+f"(d[28]), "+f"(d[29]), "+f"(d[30]), "+f"(d[31]),
          "+f"(d[32]), "+f"(d[33]), "+f"(d[34]), "+f"(d[35]), "+f"(d[36]), "+f"(d[37]), "+f"(d[38]), "+f"(d[39]),
          "+f"(d[40]), "+f"(d[41]), "+f"(d[42]), "+f"(d[43]), "+f"(d[44]), "+f"(d[45]), "+f"(d[46]), "+f"(d[47]),
          "+f"(d[48]), "+f"(d[49]), "+f"(d[50]), "+f"(d[51]), "+f"(d[52]), "+f"(d[53]), "+f"(d[54]), "+f"(d[55]),
          "+f"(d[56]), "+f"(d[57]), "+f"(d[58]), "+f"(d[59]), "+f"(d[60]), "+f"(d[61]), "+f"(d[62]), "+f"(d[63]),
          "+f"(d[64]), "+f"(d[65]), "+f"(d[66]), "+f"(d[67]), "+f"(d[68]), "+f"(d[69]), "+f"(d[70]), "+f"(d[71]),
          "+f"(d[72]), "+f"(d[73]), "+f"(d[74]), "+f"(d[75]), "+f"(d[76]), "+f"(d[77]), "+f"(d[78]), "+f"(d[79]),
          "+f"(d[80]), "+f"(d[81]), "+f"(d[82]), "+f"(d[83]), "+f"(d[84]), "+f"(d[85]), "+f"(d[86]), "+f"(d[87]),
          "+f"(d[88]), "+f"(d[89]), "+f"(d[90]), "+f"(d[91]), "+f"(d[92]), "+f"(d[93]), "+f"(d[94]), "+f"(d[95]),
          "+f"(d[96]), "+f"(d[97]), "+f"(d[98]), "+f"(d[99]), "+f"(d[100]), "+f"(d[101]), "+f"(d[102]), "+f"(d[103]),
          "+f"(d[104]), "+f"(d[105]), "+f"(d[106]), "+f"(d[107]), "+f"(d[108]), "+f"(d[109]), "+f"(d[110]), "+f"(d[111]),
          "+f"(d[112]), "+f"(d[113]), "+f"(d[114]), "+f"(d[115]), "+f"(d[116]), "+f"(d[117]), "+f"(d[118]), "+f"(d[119]),
          "+f"(d[120]), "+f"(d[121]), "+f"(d[122]), "+f"(d[123]), "+f"(d[124]), "+f"(d[125]), "+f"(d[126]), "+f"(d[127])
        : "l"(da), "l"(db), "r"(sd));
}

__device__ __forceinline__ void wgmma_n128(float (&d)[64], uint64_t da, uint64_t db, int sd) {
    asm volatile("{\n.reg .pred p;\nsetp.ne.b32 p, %66, 0;\n"
        "wgmma.mma_async.sync.aligned.m64n128k16.f32.bf16.bf16 "
        "{%0,%1,%2,%3,%4,%5,%6,%7,%8,%9,%10,%11,%12,%13,%14,%15,"
        "%16,%17,%18,%19,%20,%21,%22,%23,%24,%25,%26,%27,%28,%29,%30,%31,"
        "%32,%33,%34,%35,%36,%37,%38,%39,%40,%41,%42,%43,%44,%45,%46,%47,"
        "%48,%49,%50,%51,%52,%53,%54,%55,%56,%57,%58,%59,%60,%61,%62,%63}, %64, %65, p, 1, 1, 0, 1;\n}\n"
        : "+f"(d[0]), "+f"(d[1]), "+f"(d[2]), "+f"(d[3]), "+f"(d[4]), "+f"(d[5]), "+f"(d[6]), "+f"(d[7]),
          "+f"(d[8]), "+f"(d[9]), "+f"(d[10]), "+f"(d[11]), "+f"(d[12]), "+f"(d[13]), "+f"(d[14]), "+f"(d[15]),
          "+f"(d[16]), "+f"(d[17]), "+f"(d[18]), "+f"(d[19]), "+f"(d[20]), "+f"(d[21]), "+f"(d[22]), "+f"(d[23]),
          "+f"(d[24]), "+f"(d[25]), "+f"(d[26]), "+f"(d[27]), "+f"(d[28]), "+f"(d[29]), "+f"(d[30]), "+f"(d[31]),
          "+f"(d[32]), "+f"(d[33]), "+f"(d[34]), "+f"(d[35]), "+f"(d[36]), "+f"(d[37]), "+f"(d[38]), "+f"(d[39]),
          "+f"(d[40]), "+f"(d[41]), "+f"(d[42]), "+f"(d[43]), "+f"(d[44]), "+f"(d[45]), "+f"(d[46]), "+f"(d[47]),
          "+f"(d[48]), "+f"(d[49]), "+f"(d[50]), "+f"(d[51]), "+f"(d[52]), "+f"(d[53]), "+f"(d[54]), "+f"(d[55]),
          "+f"(d[56]), "+f"(d[57]), "+f"(d[58]), "+f"(d[59]), "+f"(d[60]), "+f"(d[61]), "+f"(d[62]), "+f"(d[63])
        : "l"(da), "l"(db), "r"(sd));
}

__device__ __forceinline__ void wgmma_n64(float (&d)[32], uint64_t da, uint64_t db, int sd) {
    asm volatile("{\n.reg .pred p;\nsetp.ne.b32 p, %34, 0;\n"
        "wgmma.mma_async.sync.aligned.m64n64k16.f32.bf16.bf16 "
        "{%0,%1,%2,%3,%4,%5,%6,%7,%8,%9,%10,%11,%12,%13,%14,%15,"
        "%16,%17,%18,%19,%20,%21,%22,%23,%24,%25,%26,%27,%28,%29,%30,%31}, %32, %33, p, 1, 1, 0, 1;\n}\n"
        : "+f"(d[0]), "+f"(d[1]), "+f"(d[2]), "+f"(d[3]), "+f"(d[4]), "+f"(d[5]), "+f"(d[6]), "+f"(d[7]),
          "+f"(d[8]), "+f"(d[9]), "+f"(d[10]), "+f"(d[11]), "+f"(d[12]), "+f"(d[13]), "+f"(d[14]), "+f"(d[15]),
          "+f"(d[16]), "+f"(d[17]), "+f"(d[18]), "+f"(d[19]), "+f"(d[20]), "+f"(d[21]), "+f"(d[22]), "+f"(d[23]),
          "+f"(d[24]), "+f"(d[25]), "+f"(d[26]), "+f"(d[27]), "+f"(d[28]), "+f"(d[29]), "+f"(d[30]), "+f"(d[31])
        : "l"(da), "l"(db), "r"(sd));
}

constexpr int STAGE_BYTES = 49152, NSTAGE = 4;
constexpr int GEMM_SMEM = NSTAGE * STAGE_BYTES + 128;

struct GemmSmem { uint32_t st, full, empty; };
__device__ __forceinline__ GemmSmem gemm_setup(uint8_t* raw, int releases) {
    GemmSmem g;
    g.st = smem_u32(raw);
    if (g.st & 1023) __trap();
    g.full = g.st + NSTAGE * STAGE_BYTES; g.empty = g.full + 64;
    if (threadIdx.x == 0) {
        for (int s = 0; s < NSTAGE; s++) { mbar_init(g.full + 8 * s, 1); mbar_init(g.empty + 8 * s, releases); }
        asm volatile("fence.mbarrier_init.release.cluster;" ::: "memory");
        asm volatile("fence.proxy.async.shared::cta;" ::: "memory");
    }
    __syncthreads();
    return g;
}
__device__ __forceinline__ void mbar_arrive_one(uint32_t bar, uint32_t who) {
    asm volatile("{\n.reg .pred p;\nsetp.eq.u32 p, %1, 0;\n@p mbarrier.arrive.shared::cta.b64 _, [%0];\n}" ::"r"(bar), "r"(who) : "memory");
}
template <int BM, int BN, int KPS, typename ACC>
__device__ __forceinline__ void gemm_stage(ACC& acc, uint32_t stage, int wg, bool first) {
    const uint64_t da = desc_sw128(stage + wg * 8192, 16, 1024);
    const uint64_t db = desc_sw128(stage + KPS * BM * 128, 8192, 1024);
    wg_fence();
#pragma unroll
    for (int k = 0; k < 4 * KPS; k++) {
        const uint64_t a = da + (k >> 2) * (BM * 8) + (k & 3) * 2, b = db + k * 128;
        if constexpr (BN == 256) wgmma_n256(acc, a, b, first && k == 0 ? 0 : 1);
        else if constexpr (BN == 128) wgmma_n128(acc, a, b, first && k == 0 ? 0 : 1);
        else wgmma_n64(acc, a, b, first && k == 0 ? 0 : 1);
    }
    wg_commit();
}

__device__ __forceinline__ void kv_store_unit(const uint32_t (&pk)[64], int u, bf16* dst, int t) {
    const int G = (u >> 2) * 2 + (u & 1), hh = (u >> 1) & 1;
    uint32_t r0 = pk[(4 * G + 0) * 2 + hh], r1 = pk[(4 * G + 1) * 2 + hh], r2 = pk[(4 * G + 2) * 2 + hh], r3 = pk[(4 * G + 3) * 2 + hh];
    quad_transpose(r0, r1, r2, r3, t);
#define KVST ".cs"
    asm volatile("st.global" KVST ".v4.u32 [%0], {%1,%2,%3,%4};" ::"l"(dst + (size_t)hh * 8 * 8192 + G * 32), "r"(r0), "r"(r1), "r"(r2), "r"(r3) : "memory");
}

__device__ __forceinline__ uint32_t near_page(int pair, int line) {
    uint32_t best[2] = {~0u, ~0u};
#pragma unroll 1
    for (int i = 0; i < 16; i++) {
        uint32_t t0, t1, v;
        asm volatile("mov.u32 %0, %%clock;" : "=r"(t0)::"memory");
        asm volatile("atom.relaxed.gpu.global.or.b32 %0, [%1], -1;" : "=r"(v) : "l"(g_x + pair * 1024 + (i & 1) * 512 + line * 16) : "memory");
        asm volatile("{\n.reg .pred p;\nsetp.ne.u32 p, %1, 0x12345;\nmov.u32 %0, -1;\n@p mov.u32 %0, %%clock;\n}" : "=r"(t1) : "r"(v) : "memory");
        if (i & 1) best[1] = min(best[1], t1 - t0); else best[0] = min(best[0], t1 - t0);
    }
    return best[1] < best[0];
}
__device__ __forceinline__ void map_pages(int c) {
    uint32_t smid;
    asm("mov.u32 %0, %%smid;" : "=r"(smid));
    const uint32_t side = near_page(0, c & 31);
    g_side[smid & 255] = side;
    for (int p = c; p < XPAIRS; p += 132) g_home[p] = near_page(p, 0) ^ side;
}

__global__ void __launch_bounds__(384, 1)
k_kv(const __grid_constant__ CUtensorMap mx, const __grid_constant__ CUtensorMap mwk, const __grid_constant__ CUtensorMap mwv,
     const bf16* __restrict__ Wq, const bf16* __restrict__ Wo, const bf16* __restrict__ u) {
    extern __shared__ __align__(1024) uint8_t smem_gemm[];
    const int c = blockIdx.x;
    if (threadIdx.x == 0) TL(0, 0);
    if (c >= 128) {
        const int i0 = (c - 128) * 384 + threadIdx.x;
        const uint4 ones = make_uint4(~0u, ~0u, ~0u, ~0u);
        if (threadIdx.x == 32) map_pages(c);
        for (int i = i0; i < XPAIRS * 512; i += 4 * 384) reinterpret_cast<uint4*>(g_x)[i] = ones;
        if (i0 < 256) g_flag[i0] = 0;
        if (threadIdx.x == 0) {
            const char* p = (const char*)(c < 130 ? Wq : Wo) + (size_t)(c & 1) * (4 << 20);
            for (int i = 0; i < 256; i++) {
                asm volatile("cp.async.bulk.prefetch.L2.global [%0], 16384;" ::"l"(p + i * 16384) : "memory");
                if (i >= 192) asm volatile("cp.async.bulk.prefetch.L2.global [%0], 16384;" ::"l"((const char*)u + ((c - 128) * 64 + i - 192) * 16384) : "memory");
                __nanosleep(40);
            }
        }
        if (threadIdx.x == 0) TL(0, 1);
        return;
    }
    GemmSmem g = gemm_setup(smem_gemm, 2);
    const int m0 = (c & 15) * 128, nb0 = c >> 4;
    const int wg = __shfl_sync(~0u, threadIdx.x >> 7, 0);
    if (wg == 0) {
        asm volatile("setmaxnreg.dec.sync.aligned.u32 40;");
        if (threadIdx.x == 0) {
            for (int it = 0; it < 64; it++) {
                const int s = it & 3, tile = it >> 4, kb = it & 15;
                mbar_wait(g.empty + 8 * s, ((it >> 2) & 1) ^ 1);
                mbar_expect_tx(g.full + 8 * s, STAGE_BYTES);
                const int nb = nb0 + 8 * tile;
                tma2d(g.st + s * STAGE_BYTES, &mx, kb * 64, m0, g.full + 8 * s);
                tma3d(g.st + s * STAGE_BYTES + 16384, nb < 16 ? &mwk : &mwv, 0, kb * 64, (nb & 15) * 4, g.full + 8 * s);
            }
        } else if (threadIdx.x == 32) map_pages(c);
    } else {
        asm volatile("setmaxnreg.inc.sync.aligned.u32 232;");
        const int cw = wg - 1, lane = threadIdx.x & 31, t = lane & 3;
        const int row = m0 + cw * 64 + ((threadIdx.x >> 5) & 3) * 16 + (lane >> 2);
        bf16* dst = g_kv + (size_t)row * 8192 + nb0 * 256 + t * 8;
        float acc[128];
        uint32_t pk[64];
#pragma unroll 1
        for (int tile = 0; tile < 4; tile++) {
#pragma unroll
            for (int kb = 0; kb < 16; kb++) {
                mbar_wait_u(g.full + 8 * (kb & 3), (kb >> 2) & 1);
                gemm_stage<128, 256, 1>(acc, g.st + (kb & 3) * STAGE_BYTES, cw, kb == 0);
                if (tile > 0) kv_store_unit(pk, kb, dst + (tile - 1) * 2048, t);
                if (kb > 0) {
                    wg_wait<1>();
                    mbar_arrive_one(g.empty + 8 * ((kb - 1) & 3), threadIdx.x & 127);
                }
            }
            wg_wait<0>();
            mbar_arrive_one(g.empty + 8 * 3, threadIdx.x & 127);
#pragma unroll
            for (int i = 0; i < 64; i++) pk[i] = pack2(acc[2 * i], acc[2 * i + 1]);
        }
        if (threadIdx.x == 128) TL(0, 2);
#pragma unroll
        for (int u = 0; u < 16; u++) kv_store_unit(pk, u, dst + 3 * 2048, t);
        if (threadIdx.x == 128) TL(0, 1);
    }
}

constexpr int NS1 = 31;
#define RB1 4
#define PFC 4
constexpr int C_W1 = 0;
constexpr int C_W2 = C_W1 + 8 * NS1 * 512;
constexpr int C_KV = C_W2 + 14 * 8 * 512;
constexpr int C_RED = C_KV + 16384;
constexpr int C_QKV = C_RED + 64 * 272;
constexpr int C_SC = C_RED;
constexpr int C_OB = C_SC + 2 * 8 * 52 * 4;
constexpr int C_BAR = C_QKV + 3 * 8 * 272;
__host__ __device__ constexpr int smem_idx(int ks, int j) {
    return ks == 0 ? j : ks < 3 ? (j < 4 ? 4 + 4 * ks + j : -1) : (j < 3 ? 7 + 3 * ks + j : -1);
}
constexpr int CHAIN_SMEM = C_BAR + 64;
#define TS(i)

#define DLY3 8
#define DLY1 2
#define DLY0 2
#define DLY1A 10
#define DLY0A DLY0
#define DLYW 3
template <int N> __device__ __forceinline__ uint32_t delayed(uint32_t x, int lane) {
#pragma unroll
    for (int i = 0; i < N; i++) asm volatile("shfl.sync.idx.b32 %0, %0, %1, 31, -1;" : "+r"(x) : "r"(lane) : "memory");
    return x;
}
__device__ __forceinline__ void lds128v(uint32_t (&r)[4], uint32_t a) {
    asm volatile("ld.volatile.shared.v4.u32 {%0,%1,%2,%3}, [%4];" : "=r"(r[0]), "=r"(r[1]), "=r"(r[2]), "=r"(r[3]) : "r"(a) : "memory");
}
__device__ __forceinline__ uint2 lds64(uint32_t a) {
    uint2 v;
    asm volatile("ld.shared.v2.u32 {%0,%1}, [%2];" : "=r"(v.x), "=r"(v.y) : "r"(a) : "memory");
    return v;
}
#define LDQ ".L1::no_allocate"
__device__ __forceinline__ uint4 ldw128(const void* p) {
    uint4 v;
    asm volatile("ld.global.nc" LDQ ".v4.u32 {%0,%1,%2,%3}, [%4];" : "=r"(v.x), "=r"(v.y), "=r"(v.z), "=r"(v.w) : "l"(p));
    return v;
}
#define P8_LD(i) "ld.relaxed.gpu.global.b64 d" #i ", [src + " #i " * 256];\n"
#define P8_X(i) "mov.b64 {x" #i ", y" #i "}, d" #i ";\n"
#define P8_HEAD(SRC) "{\n.reg .pred p, q;\n.reg .b64 src, d<8>;\n.reg .b32 n, x<8>, y<8>, m0, m1;\nmov.b64 src, " SRC ";\n"         \
                P8_LD(0) P8_LD(1) P8_LD(2) P8_LD(3) P8_LD(4) P8_LD(5) P8_LD(6) P8_LD(7) "mov.u32 n, 0;\nCHECK:\n" \
                P8_X(0) P8_X(1) P8_X(2) P8_X(3) P8_X(4) P8_X(5) P8_X(6) P8_X(7)
#define P8_VOTE "vote.sync.all.pred p, p, -1;\n@p bra.uni DONE;\n"
#define P8_TAIL "add.u32 n, n, 1;\nsetp.lt.u32 p, n, 0x100000;\n@p bra.uni CHECK;\ntrap;\nDONE:\n"
__device__ __forceinline__ void poll_state(uint2 (&v)[8], const void* src) {
#define P8_RS(i) "setp.eq.u32 q, x" #i ", 0xffffffff;\n@q " P8_LD(i)
#define P8_O(i) "mov.b64 %" #i ", d" #i ";\n"
    uint64_t d[8];
    asm volatile(P8_HEAD("%8") "max.u32 m0, x0, x1;\nmax.u32 m0, m0, x2;\nmax.u32 m1, x3, x4;\nmax.u32 m1, m1, x5;\nmax.u32 m0, m0, x6;\n"
                 "max.u32 m0, m0, x7;\nmax.u32 m0, m0, m1;\nsetp.ne.u32 p, m0, 0xffffffff;\n" P8_VOTE
                 P8_RS(0) P8_RS(1) P8_RS(2) P8_RS(3) P8_RS(4) P8_RS(5) P8_RS(6) P8_RS(7) P8_TAIL
                 P8_O(0) P8_O(1) P8_O(2) P8_O(3) P8_O(4) P8_O(5) P8_O(6) P8_O(7) "}"
                 : "=l"(d[0]), "=l"(d[1]), "=l"(d[2]), "=l"(d[3]), "=l"(d[4]), "=l"(d[5]), "=l"(d[6]), "=l"(d[7]) : "l"(src) : "memory");
#pragma unroll
    for (int i = 0; i < 8; i++) { v[i].x = (uint32_t)d[i]; v[i].y = (uint32_t)(d[i] >> 32); }
}
__device__ __forceinline__ uint64_t poll_sum(const void* src, uint32_t tag, uint32_t sel) {
#define P8_RT(i) "lop3.b32 m0, x" #i ", %2, 1, 0x28;\nsetp.ne.u32 q, m0, 0;\n@q " P8_LD(i)
#define P8_MMA(c, i, z) "mma.sync.aligned.m16n8k8.row.col.f32.bf16.bf16.f32 {" #c "0," #c "1," #c "2," #c "3}, {x" #i ", y" #i "}, {%3}, {" #z "0," #z "1," #z "2," #z "3};\n"
    uint64_t r;
    asm volatile(P8_HEAD("%1") "{\n.reg .f32 a<4>, b<4>, z<4>;\nmov.f32 z0, 0f00000000;\nmov.f32 z1, z0;\nmov.f32 z2, z0;\nmov.f32 z3, z0;\n"
                 P8_MMA(a, 0, z) P8_MMA(b, 1, z) P8_MMA(a, 2, a) P8_MMA(b, 3, b) P8_MMA(a, 4, a) P8_MMA(b, 5, b) P8_MMA(a, 6, a) P8_MMA(b, 7, b)
                 "add.f32 a0, a0, b0;\nadd.f32 a1, a1, b1;\nadd.f32 a2, a2, b2;\nadd.f32 a3, a3, b3;\n"
                 "cvt.rn.bf16x2.f32 m0, a1, a0;\ncvt.rn.bf16x2.f32 m1, a3, a2;\nmov.b64 %0, {m0, m1};\n}\n"
                 "lop3.b32 m0, x0, x1, %2, 0x7e;\nlop3.b32 m1, x2, x3, %2, 0x7e;\nlop3.b32 m0, m0, x4, %2, 0xf6;\n"
                 "lop3.b32 m1, m1, x5, %2, 0xf6;\nlop3.b32 m0, m0, x6, %2, 0xf6;\nlop3.b32 m1, m1, x7, %2, 0xf6;\n"
                 "lop3.b32 m0, m0, m1, 1, 0xa8;\nsetp.eq.u32 p, m0, 0;\n" P8_VOTE
                 P8_RT(0) P8_RT(1) P8_RT(2) P8_RT(3) P8_RT(4) P8_RT(5) P8_RT(6) P8_RT(7) P8_TAIL "}"
                 : "=&l"(r) : "l"(src), "r"(tag), "r"(sel) : "memory");
    return r;
}
__device__ __forceinline__ void sum8(float (&c)[4], const uint2 (&v)[8], uint32_t idn) {
    float d[4] = {0.f, 0.f, 0.f, 0.f};
    c[0] = c[1] = c[2] = c[3] = 0.f;
    mma16816(c, v[0].x, v[0].y, v[1].x, v[1].y, idn, idn);
    mma16816(d, v[2].x, v[2].y, v[3].x, v[3].y, idn, idn);
    mma16816(c, v[4].x, v[4].y, v[5].x, v[5].y, idn, idn);
    mma16816(d, v[6].x, v[6].y, v[7].x, v[7].y, idn, idn);
    c[0] += d[0]; c[1] += d[1]; c[2] += d[2]; c[3] += d[3];
}

__global__ void __cluster_dims__(3, 1, 1) __launch_bounds__(256, 1)
k_chain(const bf16* __restrict__ mem0, const bf16* __restrict__ Wq, const bf16* __restrict__ Wk, const bf16* __restrict__ Wv,
        const bf16* __restrict__ Wo, const __grid_constant__ CUtensorMap mkv) {
    extern __shared__ __align__(1024) uint8_t smem_chain[];
    const uint32_t sb = smem_u32(smem_chain);
    if (sb & 1023) __trap();
    const int w = __shfl_sync(~0u, threadIdx.x >> 5, 0), lane = __shfl_sync(~0u, threadIdx.x & 31, threadIdx.x & 31);
    const int tid = w * 32 + lane, g = lane >> 2, t = lane & 3;
    auto pin = [&](uint32_t x) { return delayed<1>(x, lane); };
    const int h = blockIdx.x / 3, r = blockIdx.x - 3 * h;
    const uint32_t bar_x = sb + C_BAR, bar_kv = sb + C_BAR + 8, bar_go = sb + C_BAR + 16, bar_w = sb + C_BAR + 24;
    asm volatile("griddepcontrol.launch_dependents;");
    const int tbase = r == 0 ? 0 : 1 + 21 * r, ntile = r == 0 ? 22 : 21;
    uint32_t side;
    asm("mov.u32 %0, %%smid;" : "=r"(side));
    side = g_side[side & 255] & 1;
    if (tid == 0 && r > 0) asm volatile("st.relaxed.gpu.global.u32 [%0], %1;" ::"l"(g_flag + 128 + 2 * h + r - 1), "r"(2 | side) : "memory");
    if (tid == 0) {
        mbar_init(bar_x, 8); mbar_init(bar_kv, 1); mbar_init(bar_go, 1); mbar_init(bar_w, 1);
        asm volatile("fence.mbarrier_init.release.cluster;" ::: "memory");
        asm volatile("fence.proxy.async.shared::cta;" ::: "memory");
        mbar_expect_tx(bar_w, 128 * 32 * ntile);
    }
    __syncthreads();
    asm volatile("barrier.cluster.arrive.relaxed.aligned;" ::: "memory");
    if (tid < 128)
        asm volatile("cp.async.bulk.shared::cluster.global.mbarrier::complete_tx::bytes [%0], [%1], %2, [%3];"
                     ::"r"(sb + C_W1 + tid * 720), "l"(Wo + (size_t)(h * 128 + tid) * DM + tbase * 16), "r"(32 * ntile), "r"(bar_w) : "memory");
    const int tile0 = tbase + 7 - w;
    const bool three = w >= (r == 0 ? 2 : 3);
    const uint32_t wa = pin(sb + tid * 16);
#define W1A(i) (wa + C_W1 + (i) * 4096)
#define W2A(x) (wa + C_W2 + ((x) < 8 ? (x) * 4096 : 32768 - 1024 + ((x) - 8) * 3072))
    uint32_t wo0[8][4], wr[64][4];
    {
        const bf16* W = (r == 0 ? Wq : r == 1 ? Wk : Wv) + (size_t)(128 * w + (lane >> 4)) * HD + h * 128 + 8 * (lane & 15);
        uint4 raw[8][8];
        auto fetch = [&](int ks) {
#pragma unroll
            for (int i = 0; i < 8; i++) raw[ks][i] = ldw128(W + (size_t)(16 * ks + 2 * i) * HD);
        };
        fetch(0); fetch(1); fetch(2); fetch(3);
        mbar_wait_u(bar_w, 0);
        const uint32_t p = sb + C_W1 + ((lane & 7) + (lane >> 4) * 8) * 720 + (7 - w) * 32 + ((lane >> 3) & 1) * 16;
#pragma unroll
        for (int ks = 0; ks < 8; ks++) {
            uint32_t a[4];
            ldsm4t(wo0[ks], p + ks * 16 * 720);
            ldsm4t(a, p + ks * 16 * 720 + 256);
            sts128(W2A(ks), a[0], a[1], a[2], a[3]);
            if (three) { ldsm4t(a, p + ks * 16 * 720 + 512); sts128(W2A(8 + ks), a[0], a[1], a[2], a[3]); }
        }
        __syncthreads();
        const uint32_t stg = sb + C_KV + w * 4096;
        const uint32_t rd = stg + ((lane & 7) + 8 * (lane >> 4)) * 256 + ((((lane >> 3) & 1) ^ (lane & 7)) << 4);
#pragma unroll
        for (int ks = 0; ks < 8; ks++) {
#pragma unroll
            for (int i = 0; i < 8; i++)
                sts128(stg + (2 * i + (lane >> 4)) * 256 + (((lane & 15) ^ (((2 * i) & 6) | (lane >> 4))) << 4),
                       raw[ks][i].x, raw[ks][i].y, raw[ks][i].z, raw[ks][i].w);
            if (ks < 2) fetch(ks + 4);
            if (ks == 3 || ks == 5) fetch(ks / 2 + 5);
            __syncwarp();
#pragma unroll
            for (int j = 0; j < 8; j++) {
                if (smem_idx(ks, j) >= 0) {
                    uint32_t a[4];
                    ldsm4t(a, rd ^ (j << 5));
                    sts128(W1A(smem_idx(ks, j)), a[0], a[1], a[2], a[3]);
                } else ldsm4t(wr[8 * ks + j], rd ^ (j << 5));
            }
            __syncwarp();
        }
    }
    asm volatile("fence.proxy.async.shared::cta;" ::: "memory");
    __syncthreads();
    if (tid == 0) {
        mbar_expect_tx(bar_kv, 16384);
        tma3d(sb + C_KV, &mkv, 0, 0, 2 * h, bar_kv);
        tma3d(sb + C_KV + 8192, &mkv, 0, 0, 64 + 2 * h, bar_kv);
    }
    asm volatile("barrier.cluster.wait.aligned;" ::: "memory");

    auto publish_kvm = [&](int s) {
        uint32_t v[4];
        lds128(v, sb + C_QKV + (8 + (tid >> 4)) * 272 + (tid & 15) * 16);
        asm volatile("st.global.v4.u32 [%0], {%1,%2,%3,%4};"
                     ::"l"(g_kvm + (size_t)(s * 8 + ((tid >> 4) & 7)) * 8192 + (tid >> 7) * HD + h * 128 + (tid & 15) * 8),
                       "r"(v[0]), "r"(v[1]), "r"(v[2]), "r"(v[3]) : "memory");
        if (h == 0 && w == 6) asm volatile("st.relaxed.gpu.global.u32 [%0], %1;" ::"l"(g_flag + 98), "r"(s + 1) : "memory");
        if ((s & 3) == 3) {
            __syncthreads();
            if (w == 7) asm volatile("{\n.reg .pred p;\nsetp.eq.u32 p, %2, 0;\nfence.acq_rel.gpu;\n@p st.relaxed.gpu.global.u32 [%0], %1;\n}"
                                     ::"l"(g_flag + h), "r"(s + 1), "r"(lane) : "memory");
        }
    };
    const float sl2e = 0.08838834764831845f * 1.4426950408889634f;
    const uint32_t idn = pin(g == 2 * t ? 0x00003f80u : g == 2 * t + 1 ? 0x3f800000u : 0u);
    const uint32_t lm = pin(sb + (lane & 7) * 272 + (lane >> 3) * 16);
    const uint32_t sa = pin(sb + C_SC + (w & 1) * (8 * 52 * 4) + (2 * t * 52 + (w < 4 ? 32 : (w & 2) * 8) + g) * 4);
    const uint32_t sr = pin(sb + C_SC + (g * 52 + 8 * t) * 4), sr2 = pin(sb + C_SC + (g * 52 + 32 + 2 * t) * 4);
    uint32_t kva;
    {
        const int pos = (w & 2) * 8 + (lane & 15), row = (pos & 24) + ((pos + (pos >> 2 & 6)) & 7);
        const int key = 4 * (lane & 6) + (((lane & 7) + 2 * (lane >> 4)) & 7);
        kva = pin(w >= 4 ? sb + C_KV + (w & 1) * 4096 + row * 128 + (((lane >> 4) ^ (row & 7)) << 4)
                         : sb + C_KV + 8192 + (w >> 1) * 4096 + key * 128 + ((((w & 1) * 4 + ((lane >> 3) & 1)) ^ (key & 7)) << 4));
    }
    uint32_t buf0[8][4], ring[RB1][4];
    auto stage_w1 = [&]() {
#pragma unroll
        for (int i = 0; i < 8; i++) lds128v(buf0[i], W1A(i));
#pragma unroll
        for (int i = 0; i < RB1; i++) lds128v(ring[i], W1A(8 + i));
    };
    stage_w1();
    uint32_t psel, msel0, msel1;
    {
        const int j = r > 0 ? 2 * h + r - 1 : 0, tl = min(tile0 + 8 * (lane >> 1), 63);
        uint32_t b;
        asm volatile("{\n.reg .pred p;\n.reg .u32 n;\nmov.u32 n, 0;\nAGAIN:\nld.relaxed.gpu.global.u32 %0, [%1];\nsetp.ne.u32 p, %0, 0;\n"
                     "vote.sync.all.pred p, p, -1;\n@p bra.uni DONE;\nadd.u32 n, n, 1;\nsetp.lt.u32 p, n, 0x100000;\n@p bra.uni AGAIN;\ntrap;\nDONE:\n}"
                     : "=&r"(b) : "l"(g_flag + 128 + tl) : "memory");
        psel = __ballot_sync(~0u, (g_home[lane == 6 ? j * 2 + ((w >> 1) & 1) : tl * 2 + (lane & 1)] ^ (lane == 6 ? side : b)) & 1);
        msel0 = __ballot_sync(~0u, (g_home[128 + lane * 4 + (w >> 1)] ^ side) & 1);
        msel1 = __ballot_sync(~0u, (g_home[256 + lane * 4 + (w >> 1)] ^ side) & 1);
        if (r > 0) {
            if (w < 4) asm volatile("prefetch.global.L2 [%0];" ::"l"(g_x + (128 + (1 + (w >> 1)) * 4 + (j >> 4)) * 1024 + (w & 1) * 512 + (j & 15) * 32 + lane) : "memory");
            if (w < 4) asm volatile("prefetch.global.L2 [%0];" ::"l"(g_x + j * 2048 + tid * 16) : "memory");
        }
    }
    uint2 bm[8];
#pragma unroll
    for (int ks = 0; ks < 8; ks++) {
        const uint32_t* p = (const uint32_t*)(mem0 + g * DM + (8 * w + ks) * 16) + t;
        bm[ks] = make_uint2(__ldg(p), __ldg(p + 4));
    }
    mbar_wait_u(bar_kv, 0);
    if (tid == 0) TL(1, 2);
#pragma unroll 1
    for (int s = 0;; s++) {
        TS(1);
        {
            float acc[8][4];
#pragma unroll
            for (int ks = 0; ks < 8; ks++) {
#pragma unroll
                for (int j = 0; j < 8; j++) {
                    const int i = smem_idx(ks, j) - 8;
                    if (ks == 0) {
                        acc[j][0] = acc[j][1] = acc[j][2] = acc[j][3] = 0.f;
                        mma16816(acc[j], buf0[j][0], buf0[j][1], buf0[j][2], buf0[j][3], bm[ks].x, bm[ks].y);
                    } else if (i >= 0) {
                        uint32_t(&a)[4] = ring[i % RB1];
                        mma16816(acc[j], a[0], a[1], a[2], a[3], bm[ks].x, bm[ks].y);
                        if (8 + i + RB1 < NS1) lds128v(a, W1A(8 + i + RB1));
                    } else {
                        const uint32_t(&a)[4] = wr[8 * ks + j];
                        mma16816(acc[j], a[0], a[1], a[2], a[3], bm[ks].x, bm[ks].y);
                    }
                }
            }
#pragma unroll
            for (int c = 0; c < 4; c++)
                stsm4t(lm + C_RED + w * 2176 + c * 64, pack2(acc[2 * c][0], acc[2 * c][1]), pack2(acc[2 * c][2], acc[2 * c][3]),
                       pack2(acc[2 * c + 1][0], acc[2 * c + 1][1]), pack2(acc[2 * c + 1][2], acc[2 * c + 1][3]));
        }
        {
            const uint32_t a = sb + C_RED + w * 272 + lane * 8;
            TS(2);
            __syncthreads();
            TS(3);
            uint2 v[8];
#pragma unroll
            for (int i = 0; i < 8; i++) v[i] = lds64(a + i * 2176);
            float c[4];
            sum8(c, v, idn);
            const uint32_t p0 = pack2(c[0], c[1]), p1 = pack2(c[2], c[3]);
            const uint32_t dst = sb + C_QKV + (r * 8 + w) * 272 + lane * 8;
#pragma unroll
            for (int i = 1; i < 3; i++) {
                const uint32_t peer = r + i >= 3 ? r + i - 3 : r + i;
                uint32_t rd, rb;
                asm("mapa.shared::cluster.u32 %0, %1, %2;" : "=r"(rd) : "r"(dst), "r"(peer));
                asm("mapa.shared::cluster.u32 %0, %1, %2;" : "=r"(rb) : "r"(bar_x), "r"(peer));
                asm volatile("st.async.weak.shared::cluster.mbarrier::complete_tx::bytes.v2.b32 [%0], {%1,%2}, [%3];"
                             ::"r"(rd), "r"(p0), "r"(p1), "r"(rb) : "memory");
            }
            sts64(dst, p0, p1);
            __syncwarp();
            asm volatile("{\n.reg .pred p;\nsetp.eq.u32 p, %1, 0;\n@p mbarrier.arrive.expect_tx.shared::cta.b64 _, [%0], 512;\n}"
                         ::"r"(bar_x), "r"(lane) : "memory");
        }
        TS(4);
        if (s == NSEG - 1) break;
        uint32_t wb[8][4], wc[8][4];
        const uint32_t po = (tile0 * 2 + (lane >> 4)) * 8192 + ((lane >> 3) & 1) * 2048 + h * 64 + (lane & 7) * 8;
        const uint32_t tag = s & 1;
        auto project = [&](const uint32_t(&wt)[8][4], const uint32_t(&ob)[4][4], int i) {
            float c0[4] = {0.f, 0.f, 0.f, 0.f}, c1[4] = {0.f, 0.f, 0.f, 0.f};
#pragma unroll
            for (int ks = 0; ks < 8; ks++)
                mma16816((ks & 1) ? c1 : c0, wt[ks][0], wt[ks][1], wt[ks][2], wt[ks][3], ob[ks >> 1][(ks & 1) * 2], ob[ks >> 1][(ks & 1) * 2 + 1]);
            uint32_t p0 = pack2(c0[0] + c1[0], c0[1] + c1[1]), p1 = pack2(c0[2] + c1[2], c0[3] + c1[3]);
            asm volatile("movmatrix.sync.aligned.m8n8.trans.b16 %0, %0;\nmovmatrix.sync.aligned.m8n8.trans.b16 %1, %1;" : "+r"(p0), "+r"(p1));
            st_rlx64((uint2*)((char*)g_x + po + i * 131072 + ((psel >> (2 * i + (lane >> 4))) & 1) * 4096), (p0 & ~1u) | tag, p1);
        };
        if (w >= 4) {
            uint32_t ka[4][4];
#pragma unroll
            for (int ks = 0; ks < 4; ks++) ldsm4(ka[ks], kva ^ (ks << 5));
            const uint32_t qa = lm + C_QKV + (w & 1) * 128;
            TS(5);
            mbar_wait_u(bar_x, s & 1);
            TS(6);
            {
                uint32_t qb[2][4];
                ldsm4(qb[0], qa);
                ldsm4(qb[1], qa + 64);
                float c0[4] = {0.f, 0.f, 0.f, 0.f}, c1[4] = {0.f, 0.f, 0.f, 0.f};
                mma16816(c0, ka[0][0], ka[0][1], ka[0][2], ka[0][3], qb[0][0], qb[0][1]);
                mma16816(c1, ka[1][0], ka[1][1], ka[1][2], ka[1][3], qb[0][2], qb[0][3]);
                mma16816(c0, ka[2][0], ka[2][1], ka[2][2], ka[2][3], qb[1][0], qb[1][1]);
                mma16816(c1, ka[3][0], ka[3][1], ka[3][2], ka[3][3], qb[1][2], qb[1][3]);
                sts32f(sa, c0[0] + c1[0]);
                sts32f(sa + 208, c0[1] + c1[1]);
                sts32f(sa + 32, c0[2] + c1[2]);
                sts32f(sa + 240, c0[3] + c1[3]);
            }
            __syncthreads();
            TS(7);
            if (w == 7 && s + 1 < NSEG - 1) {
                if (lane == 0) {
                    mbar_expect_tx(bar_kv, 16384);
                    tma3d(sb + C_KV, &mkv, 0, (s + 1) * 32, 2 * h, bar_kv);
                    tma3d(sb + C_KV + 8192, &mkv, 0, (s + 1) * 32, 64 + 2 * h, bar_kv);
                }
                __syncwarp();
            }
            const uint32_t wd = delayed<DLYW>(wa, lane);
#pragma unroll
            for (int i = 0; i < 8; i++) lds128(wb[i], wd + C_W2 + i * 4096);
#pragma unroll
            for (int i = 0; i < PFC; i++) lds128(wc[i], wd + C_W2 + 32768 - 1024 + i * 3072);
            TS(8);
            __syncthreads();
            TS(9);
            uint32_t ob[4][4];
#pragma unroll
            for (int i = 0; i < 4; i++) ldsm4(ob[i], lm + C_OB + i * 64);
#pragma unroll
            for (int i = PFC; i < 8; i++) lds128(wc[i], W2A(8 + i));
            project(wb, ob, 1);
            project(wo0, ob, 0);
            project(wc, ob, 2);
        } else {
            uint32_t va[4][4];
#pragma unroll
            for (int i = 0; i < 4; i++) ldsm4t(va[i], kva ^ (((i >> 1) << 5) | ((i & 1) * 0x240)));
#pragma unroll
            for (int i = 0; i < 8; i++) lds128(wb[i], W2A(i));
            const uint32_t qa = lm + C_QKV + (w & 1) * 128, oa = lm + w * 64;
            TS(5);
            mbar_wait_u(bar_x, s & 1);
            TS(6);
            if (w < 2) {
                uint32_t qb[2][4], km[2][4];
                ldsm4(qb[0], qa);
                ldsm4(km[0], qa + 8 * 272);
                ldsm4(qb[1], qa + 64);
                ldsm4(km[1], qa + 8 * 272 + 64);
                float c0[4] = {0.f, 0.f, 0.f, 0.f}, c1[4] = {0.f, 0.f, 0.f, 0.f};
                mma16816(c0, km[0][0], km[0][1], km[0][2], km[0][3], qb[0][0], qb[0][2]);
                mma16816(c1, km[0][0], km[0][1], km[0][2], km[0][3], qb[0][1], qb[0][3]);
                mma16816(c0, km[1][0], km[1][1], km[1][2], km[1][3], qb[1][0], qb[1][2]);
                mma16816(c1, km[1][0], km[1][1], km[1][2], km[1][3], qb[1][1], qb[1][3]);
                sts32f(sa, c0[0] + c1[2]);
                sts32f(sa + 208, c0[1] + c1[3]);
            }
            __syncthreads();
            TS(7);
            {
                float4 x0 = lds128f(sr), y0 = lds128f(sr + 1664), x1 = lds128f(sr + 16), y1 = lds128f(sr + 1680);
                float2 x2 = lds64f(sr2), y2 = lds64f(sr2 + 1664);
                float p[10] = {x0.x + y0.x, x0.y + y0.y, x0.z + y0.z, x0.w + y0.w, x1.x + y1.x,
                               x1.y + y1.y, x1.z + y1.z, x1.w + y1.w, x2.x + y2.x, x2.y + y2.y};
                float m = fmaxf(fmaxf(fmaxf(p[0], p[1]), fmaxf(p[2], p[3])), fmaxf(fmaxf(fmaxf(p[4], p[5]), fmaxf(p[6], p[7])), fmaxf(p[8], p[9])));
                const float m1 = __shfl_xor_sync(~0u, m, 1), m2 = __shfl_xor_sync(~0u, m, 2), m3 = __shfl_xor_sync(~0u, m, 3);
                uint32_t vm[4];
                ldsm4t(vm, oa + C_QKV + 16 * 272);
                m = fmaxf(fmaxf(m, m1), fmaxf(m2, m3));
                const float ms = m * sl2e;
#pragma unroll
                for (int i = 0; i < 10; i++) p[i] = ex2(fmaf(p[i], sl2e, -ms));
                const uint32_t b0 = pack2(p[0], p[1]), b1 = pack2(p[2], p[3]), b2 = pack2(p[4], p[5]), b3 = pack2(p[6], p[7]), b4 = pack2(p[8], p[9]);
                const uint32_t one = 0x3f803f80u;
                float o0[4] = {0.f, 0.f, 0.f, 0.f}, o1[4] = {0.f, 0.f, 0.f, 0.f}, sm[4] = {0.f, 0.f, 0.f, 0.f};
                mma16816(sm, one, one, one, one, b0, b1);
                mma16816(o0, va[0][0], va[0][1], va[0][2], va[0][3], b0, b1);
                mma16816(o1, va[2][0], va[2][1], va[2][2], va[2][3], b0, b1);
                mma16816(sm, one, one, one, one, b2, b3);
                mma16816(o0, va[1][0], va[1][1], va[1][2], va[1][3], b2, b3);
                mma16816(o1, va[3][0], va[3][1], va[3][2], va[3][3], b2, b3);
                mma1688(sm, one, one, b4);
                mma1688(o0, vm[0], vm[1], b4);
                mma1688(o1, vm[2], vm[3], b4);
                float i0, i1;
                asm("rcp.approx.ftz.f32 %0, %1;" : "=f"(i0) : "f"(sm[0]));
                asm("rcp.approx.ftz.f32 %0, %1;" : "=f"(i1) : "f"(sm[1]));
                stsm4t(oa + C_OB, pack2(o0[0] * i0, o0[1] * i1), pack2(o0[2] * i0, o0[3] * i1),
                       pack2(o1[0] * i0, o1[1] * i1), pack2(o1[2] * i0, o1[3] * i1));
            }
            TS(8);
            __syncthreads();
            TS(9);
            uint32_t ob[4][4];
#pragma unroll
            for (int i = 0; i < 4; i++) ldsm4(ob[i], lm + C_OB + i * 64);
            if (three) {
#pragma unroll
                for (int i = 0; i < 8; i++) lds128(wc[i], W2A(8 + i));
                project(wb, ob, 1);
                project(wo0, ob, 0);
                project(wc, ob, 2);
            } else {
                project(wb, ob, 1);
                project(wo0, ob, 0);
            }
        }
        TS(10);
        __syncthreads();
        uint32_t eo = (128 + (s + 1) * 4 + (w >> 1)) * 8192 + (((s < 31 ? msel0 : msel1) >> ((s + 1) & 31)) & 1) * 4096 + (w & 1) * 2048 + lane * 8;
        if (r == 0) {
            TS(11); TS(12);
            stage_w1();
            publish_kvm(s);
            if (s < NSEG - 2) mbar_wait_u(bar_kv, (s + 1) & 1);
            mbar_wait_u(bar_go, s & 1);
            if (w < 4) eo = delayed<DLY0>(eo, lane); else eo = delayed<DLY0A>(eo, lane);
        } else {
            const int j = 2 * h + r - 1;
            if (w < 4) {
                const char* src = (const char*)g_x + delayed<DLY3>((j * 2 + (w >> 1)) * 8192 + (psel & 64) * 64 + (w & 1) * 2048 + t * 64 + g * 8, lane);
                const char* dst = (const char*)g_x + pin((128 + (s + 1) * 4 + (j >> 4)) * 8192 + (j & 15) * 256 + w * 64 + (t & 1) * 4096 + g * 8);
                const uint64_t v = poll_sum(src, tag, (lane & 4) ? 0x3f800000u : 0x00003f80u);
                TS(11);
                asm volatile("st.relaxed.gpu.global.b64 [%0], %1;" ::"l"(dst), "l"(v) : "memory");
                asm volatile("bar.arrive 1, 256;" ::: "memory");
                TS(12);
                stage_w1();
                if (s < NSEG - 2) mbar_wait_u(bar_kv, (s + 1) & 1);
                eo = delayed<DLY1>(eo, lane);
            } else {
                if (w >= 6 && s + 3 < NSEG)
                    asm volatile("prefetch.global.L2 [%0];" ::"l"(g_x + (128 + (s + 3) * 4 + (j >> 4)) * 1024 + (w & 1) * 512 + (j & 15) * 32 + lane) : "memory");
                stage_w1();
                if (s < NSEG - 2) mbar_wait_u(bar_kv, (s + 1) & 1);
                TS(11);
                bar_sync(1, 256);
                TS(12);
                if (w == 4 && r == 1)
                    asm volatile("{\n.reg .pred p;\n.reg .u32 a;\nelect.sync _|p, -1;\nmapa.shared::cluster.u32 a, %0, 0;\n"
                                 "@p mbarrier.arrive.relaxed.cluster.shared::cluster.b64 _, [a];\n}" ::"r"(bar_go) : "memory");
                eo = delayed<DLY1A>(eo, lane);
            }
        }
        { const int s_ = s; { const int s = s_ + 1; TS(0); } }
        poll_state(bm, (const char*)g_x + eo);
    }
    mbar_wait_u(bar_x, (NSEG - 1) & 1);
    if (r == 0) publish_kvm(NSEG - 1);
    asm volatile("barrier.cluster.arrive.relaxed.aligned;\nbarrier.cluster.wait.aligned;" ::: "memory");
}

constexpr int S4_US = 4368;
constexpr int S4_RS = 8848;
constexpr int S4_KS = 1296;
constexpr int S4_U = 0, S4_R = 16 * S4_US, S4_K = S4_R + 16 * S4_RS;
constexpr int S4_SMEM = S4_K + 16 * S4_KS;
constexpr int S4_SIG = 3104, S4_PK = 2 * S4_SIG;

struct cf { float r, i; };
__device__ __forceinline__ cf cmul(cf a, cf b) { return {fmaf(a.r, b.r, -a.i * b.i), fmaf(a.r, b.i, a.i * b.r)}; }
__device__ __forceinline__ cf cmulc(cf a, cf b) { return {fmaf(a.r, b.r, a.i * b.i), fmaf(a.i, b.r, -a.r * b.i)}; }
__device__ __forceinline__ cf csq(cf a) { const float t = a.r * a.i; return {fmaf(a.r, a.r, -a.i * a.i), t + t}; }
__device__ __forceinline__ cf cexp(float l2, float turns) {
    const float mag = ex2(l2), fr = (turns - rintf(turns)) * 6.283185307179586f;
    return {mag * __cosf(fr), mag * __sinf(fr)};
}
__device__ __forceinline__ void sts32(uint32_t a, uint32_t v) { asm volatile("st.shared.u32 [%0], %1;" ::"r"(a), "r"(v) : "memory"); }
__device__ __forceinline__ uint32_t lds16(uint32_t a) {
    uint32_t v;
    asm volatile("ld.shared.u16 %0, [%1];" : "=r"(v) : "r"(a) : "memory");
    return v;
}

template <int M0, int NQ>
__device__ __forceinline__ void s4_class(float (&acc)[16][4], uint32_t sig, uint32_t taps, int x0) {
    constexpr int D0 = M0 / 8, D1 = M0 == 32 ? 9 : 15;
    uint32_t R[D1 - D0 + 2];
#pragma unroll
    for (int D = D0 - 1; D <= D1; D++) {
        if (D < D0 || 8 * D - 7 >= 2 * M0) { R[D - D0 + 1] = 0; continue; }
        const int m = 8 * D + x0;
        uint32_t lo = lds16(taps + m * (2 * NQ)), hi = lds16(taps + (m - 1) * (2 * NQ));
        if (D == D0) { lo = m >= M0 ? lo : 0; hi = m > M0 ? hi : 0; }
        if (D == 2 * D0) { lo = m < 2 * M0 ? lo : 0; hi = m <= 2 * M0 ? hi : 0; }
        R[D - D0 + 1] = lo | (hi << 16);
    }
#pragma unroll
    for (int J = 0; 2 * J + D0 < 16; J++) {
        uint32_t a[4];
        ldsm4t(a, sig + J * 512);
#pragma unroll
        for (int D = D0; D <= D1; D++)
            if (2 * J + D < 16) mma16816(acc[2 * J + D], a[0], a[1], a[2], a[3], R[D - D0 + 1], R[D - D0]);
    }
}

__global__ void __launch_bounds__(512, 1)
k_s4(const bf16* __restrict__ u, const bf16* __restrict__ Are, const bf16* __restrict__ Aim, const bf16* __restrict__ Bre,
     const bf16* __restrict__ Bim, const bf16* __restrict__ Cre, const bf16* __restrict__ Cim, const bf16* __restrict__ logdt,
     const bf16* __restrict__ Dsk, bf16* __restrict__ out) {
    extern __shared__ __align__(16) uint8_t smem_s4[];
    const uint32_t sb = smem_u32(smem_s4);
    asm volatile("griddepcontrol.launch_dependents;");
    const int tid = threadIdx.x, w = __shfl_sync(~0u, tid >> 5, 0), lane = tid & 31, g = lane >> 2, t = lane & 3;
    if (tid == 0) TL(2, 0);
    const int d0 = blockIdx.x * 16;
    const int d = d0 + (w & 1) + ((w >> 1) & 3) * 4 + (w >> 3) * 2;
    const uint32_t tr_off = (lane & 15), tr_l = (lane >> 4) * 16;
    const uint32_t ur = sb + S4_U + w * S4_US, rs = sb + S4_R + w * S4_RS, kd = sb + S4_K + w * S4_KS;
    if (lane < 16) sts128(ur + lane * 16, 0, 0, 0, 0);
    {
        const int o = d * 128 + lane * 4;
        const uint2 ar = __ldg((const uint2*)(Are + o)), ai = __ldg((const uint2*)(Aim + o)), br = __ldg((const uint2*)(Bre + o));
        const uint2 bi = __ldg((const uint2*)(Bim + o)), cr = __ldg((const uint2*)(Cre + o)), ci = __ldg((const uint2*)(Cim + o));
        const float dt = bf_round(expf(__bfloat162float(logdt[d])));
        const bf16* src = u + (size_t)(w * 128 + g) * DM + d0 + 4 * t;
        float T[5][4];
#pragma unroll
        for (int i = 0; i < 5; i++) T[i][0] = T[i][1] = T[i][2] = T[i][3] = 0.f;
        float klast = 0.f;
        const uint32_t wr_ = rs + lane * 4;
        const uint32_t ra = rs + (lane & 15) * 144 + (lane >> 4) * 16, rb = rs + (16 + (lane & 7)) * 144 + (lane >> 3) * 16;
#pragma unroll 1
        for (int c = 0; c < 4; c++) {
            uint2 v[4];
#pragma unroll
            for (int i = 0; i < 4; i++) v[i] = __ldg((const uint2*)(src + (size_t)(c * 32 + i * 8) * DM));
            auto pick = [&](const uint2& x) { const uint32_t y = c < 2 ? x.x : x.y; return (c & 1) ? bf_hi(y) : bf_lo(y); };
            auto put = [&](int row, cf x) { sts32(wr_ + row * 144, pack2(x.r, x.i)); };
            const float l2 = dt * pick(ar) * 1.4426950408889634f, tu = dt * pick(ai) * 0.15915494309189535f;
            const cf z1 = cexp(l2, tu), z2 = csq(z1), z4 = csq(z2), z8 = csq(z4), z128 = cexp(l2 * 128.f, tu * 128.f);
            cf a = z8;
            sts32(wr_, 0x00003f80u);
            put(1, a);
#pragma unroll
            for (int i = 2; i < 16; i++) { a = cmul(a, z8); put(i, a); }
            cf y = cmul({pick(cr), pick(ci)}, {dt * pick(br), dt * pick(bi)});
            y.i = -y.i;
#pragma unroll
            for (int k = 0; k < 16; k++) {
                const int n = k < 2 ? 8 : k < 4 ? 4 : k < 8 ? 2 : 1;
                const int row = 16 + (k < 2 ? 8 * k : k < 4 ? 8 + 4 * k : k < 8 ? 16 + 2 * k : 24 + k);
                cf x = y;
                put(row, x);
#pragma unroll
                for (int b = 1; b < n; b++) { x = cmulc(x, k < 2 ? z1 : k < 4 ? z2 : z4); put(row + b, x); }
                y = cmulc(y, z128);
            }
            klast += y.r;
            __syncwarp();
#pragma unroll
            for (int kp = 0; kp < 2; kp++) {
                uint32_t A0[4], A1[4];
                ldsm4(A0, ra + kp * 64);
                ldsm4(A1, ra + kp * 64 + 32);
#pragma unroll
                for (int i = 0; i < 5; i++) {
                    uint32_t B[4];
                    ldsm4(B, rb + i * 8 * 144 + kp * 64);
                    mma16816(T[i], A0[0], A0[1], A0[2], A0[3], B[0], B[1]);
                    mma16816(T[i], A1[0], A1[1], A1[2], A1[3], B[2], B[3]);
                }
            }
#pragma unroll
            for (int i = 0; i < 2; i++)
                stsm4t(sb + S4_U + tr_off * S4_US + 256 + (w * 128 + c * 32 + i * 16) * 2 + tr_l, v[2 * i].x, v[2 * i].y, v[2 * i + 1].x, v[2 * i + 1].y);
            __syncwarp();
        }
#pragma unroll
        for (int o2 = 16; o2; o2 >>= 1) klast += __shfl_xor_sync(~0u, klast, o2);
#pragma unroll
        for (int hh = 0; hh < 2; hh++) {
            const int i = g + 8 * hh;
            sts32(kd + (8 * i + 2 * t) * 2, pack2(T[0][2 * hh], T[0][2 * hh + 1]));
            sts32(kd + (128 + 8 * i + 2 * t) * 2, pack2(T[1][2 * hh], T[1][2 * hh + 1]));
            sts32(kd + (256 + 4 * i + 2 * (t & 1) + 64 * (t >> 1)) * 2, pack2(T[2][2 * hh], T[2][2 * hh + 1]));
            sts32(kd + (384 + 2 * i + 32 * t) * 2, pack2(T[3][2 * hh], T[3][2 * hh + 1]));
        }
        asm volatile("stmatrix.sync.aligned.m8n8.x2.trans.shared.b16 [%0], {%1,%2};"
                     ::"r"(kd + 1024 + (lane & 7) * 32 + ((lane >> 3) & 1) * 16), "r"(pack2(T[4][0], T[4][1])), "r"(pack2(T[4][2], T[4][3])) : "memory");
        if (lane == 0) sts32(kd + 1280, pack2(klast, 0.f));
    }
    __syncwarp();
    const uint32_t pk = rs + S4_PK + 64;
    {
#pragma unroll
        for (int i = 0; i < 2; i++) {
            const int x = i * 128 + lane * 4;
            const uint2 c = lds64(kd + x * 2);
            uint32_t p = lds16(kd + x * 2 - 2);
            if (x == 0) p = 0;
            sts128(pk + x * 4, __byte_perm(c.x, p, 0x5410), __byte_perm(c.x, 0, 0x1032), __byte_perm(c.y, c.x, 0x7610), __byte_perm(c.y, 0, 0x1032));
        }
#pragma unroll
        for (int i = 2; i < 4; i++) {
            const int x = i * 128 + lane * 4;
            const uint32_t ab = lds32(kd + 256 + x), c = lds16(kd + 256 + x + 4);
            const uint32_t p = x == 256 ? lds16(kd + 510) : ab;
            sts128(pk + x * 4, __byte_perm(ab, p, 0x5410), __byte_perm(ab, 0, 0x1010), __byte_perm(ab, 0, 0x1032), __byte_perm(c, ab, 0x7610));
        }
        const uint32_t v = lds16(kd + 768), v2 = lds16(kd + 1024);
        if (lane < 24) {
            uint32_t x0 = 0, x1 = 0, x2 = 0, x3 = 0;
            if (lane == 0) { x0 = x1 = x2 = v | (v << 16); x3 = v << 16; }
            if (lane == 12) x3 = v2;
            if (lane == 13) { x0 = v2 | (v2 << 16); x1 = v2 << 16; }
            sts128(lane < 20 ? pk + 2048 + lane * 16 : pk - 64 + (lane - 20) * 16, x0, x1, x2, x3);
        }
        if (lane < 4) sts128(rs + (lane >> 1) * S4_SIG + (lane & 1) * 16, 0, 0, 0, 0);
    }
    __syncthreads();
    float acc[16][4];
#pragma unroll
    for (int i = 0; i < 16; i++) acc[i][0] = acc[i][1] = acc[i][2] = acc[i][3] = 0.f;
    const uint32_t lf = (lane & 7) * 32 + ((lane >> 3) & 1) * 16 + (lane >> 4) * 256;
#pragma unroll
    for (int rg = 3; rg >= 2; rg--) {
#pragma unroll 1
        for (int it = 0; it < (rg == 3 ? 4 : 6); it++) {
            const int n = it * 32 + lane;
            uint32_t x[2][4];
            lds128(x[0], ur + 256 + n * 16 - 16);
            lds128(x[1], ur + 256 + n * 16);
            float e[16], p[15], s[11];
#pragma unroll
            for (int i = 0; i < 8; i++) { e[2 * i] = bf_lo(x[i >> 2][i & 3]); e[2 * i + 1] = bf_hi(x[i >> 2][i & 3]); }
#pragma unroll
            for (int i = 0; i < 15; i++) p[i] = e[i] + e[i + 1];
#pragma unroll
            for (int i = 0; i < 11; i++) s[i] = p[i + 3] + e[i + 5];
            const uint32_t o = rs + 16 + n * 16;
            if (rg == 2) sts128(o, pack2(s[0], s[1]), pack2(s[2], s[3]), pack2(s[4], s[5]), pack2(s[6], s[7]));
#pragma unroll
            for (int i = 0; i < 10; i++) s[i] = p[i + 2] + s[i + 1];
            if (rg == 2) {
                sts64(o + S4_SIG + 8, pack2(s[0], s[1]), pack2(s[2], s[3]));
                sts64(o + S4_SIG + 16, pack2(s[4], s[5]), pack2(s[6], s[7]));
            } else {
#pragma unroll
                for (int i = 0; i < 9; i++) s[i] = p[i + 1] + s[i + 1];
                sts64(o + 8, pack2(s[0], s[1]), pack2(s[2], s[3]));
                sts64(o + 16, pack2(s[4], s[5]), pack2(s[6], s[7]));
#pragma unroll
                for (int i = 0; i < 8; i++) s[i] = p[i] + s[i + 1];
                sts64(o + S4_SIG + 8, pack2(s[0], s[1]), pack2(s[2], s[3]));
                sts64(o + S4_SIG + 16, pack2(s[4], s[5]), pack2(s[6], s[7]));
            }
        }
        __syncwarp();
        if (rg == 3) {
#pragma unroll 1
            for (int q = 1; q <= 2; q++) s4_class<64, 2>(acc, rs + lf + (q == 1 ? 16 : S4_SIG), kd + (384 + q) * 2, g - 2 * t);
        } else {
#pragma unroll 1
            for (int q = 1; q <= 4; q++) s4_class<32, 4>(acc, rs + lf + ((q & 1) ? 0 : S4_SIG) + (q < 3 ? 16 : 0), kd + (256 + q) * 2, g - 2 * t);
        }
        __syncwarp();
    }
    {
        const uint32_t ub = ur + 256 + lf, kb = pk + (g - 2 * t) * 4;
#pragma unroll 1
        for (int j0 = 0; j0 < 8; j0++) {
            uint32_t B[8][4];
#pragma unroll
            for (int i = 0; i < 8; i++) ldsm4(B[i], ub + i * 512 - j0 * 32);
            auto block = [&](int J, uint32_t a) {
                const uint32_t r0 = lds32(a), rp = lds32(a + 32), rm = lds32(a - 32), r3 = lds32(a);
#pragma unroll
                for (int I = J; I < 16; I++)
                    mma16816(acc[I], r0, rp, rm, r3, B[(I - J) >> 1][((I - J) & 1) * 2], B[(I - J) >> 1][((I - J) & 1) * 2 + 1]);
            };
#pragma unroll
            for (int J = 0; J < 4; J++) block(J, kb + j0 * 64 + J * 512);
            if (j0 < 2) { block(4, kb + j0 * 64 + 2048); block(8, kb + j0 * 64 + (544 + 16) * 4); }
        }
        __syncwarp();
#pragma unroll
        for (int i = 0; i < 8; i++)
            stsm4t(rs + lf + i * 512, pack2(acc[2 * i][0], acc[2 * i][1]), pack2(acc[2 * i][2], acc[2 * i][3]),
                   pack2(acc[2 * i + 1][0], acc[2 * i + 1][1]), pack2(acc[2 * i + 1][2], acc[2 * i + 1][3]));
    }
    __syncthreads();
    {
        const uint2 dv = __ldg((const uint2*)(Dsk + d0 + 4 * t));
        bf16* dst = out + (size_t)(w * 128 + g) * 2048 + 1024 + d0 + 4 * t;
#pragma unroll
        for (int i = 0; i < 8; i++) {
            uint32_t y[4], x[4], o[4];
            ldsm4t(y, sb + S4_R + tr_off * S4_RS + (w * 128 + i * 16) * 2 + tr_l);
            ldsm4t(x, sb + S4_U + tr_off * S4_US + 256 + (w * 128 + i * 16) * 2 + tr_l);
#pragma unroll
            for (int j = 0; j < 4; j++)
                asm("{\n.reg .b32 s;\nmul.rn.bf16x2 s, %2, %3;\nadd.rn.bf16x2 %0, %1, s;\n}" : "=r"(o[j]) : "r"(y[j]), "r"(x[j]), "r"((j & 1) ? dv.y : dv.x));
            *reinterpret_cast<uint2*>(dst + (size_t)(i * 16) * 2048) = make_uint2(o[0], o[1]);
            *reinterpret_cast<uint2*>(dst + (size_t)(i * 16 + 8) * 2048) = make_uint2(o[2], o[3]);
        }
    }
    if (tid == 0) TL(2, 1);
}

enum { IT_QA = 0, IT_W256 = 1, IT_W128 = 2, IT_W64 = 3, IT_W64S = 4, IT_END = 7 };
struct BgParams { CUtensorMap mx, mwq, mkv, mkvm, mo, mo2, mo2s, mwo4, mwo2, mwo1; };
#define LOOK 3
#define LOOKL 8
#define LOOKM 5
#define LOOKN 4
#define PWO 40
#define P256 44
#define P128 50
__device__ __forceinline__ uint32_t ld_rlx32(const uint32_t* p) {
    uint32_t v;
    asm volatile("ld.relaxed.gpu.global.u32 %0, [%1];" : "=r"(v) : "l"(p) : "memory");
    return v;
}
struct Sched { uint32_t qb = 0, w0 = 0, w1 = 0; };
__device__ __forceinline__ int next_item(Sched& z) {
    for (int n = 0; n < SPIN_LIMIT; n++) {
        if (z.w0 < z.w1 && (z.qb >= 16 || ld_rlx32(g_flag + 64 + min(z.w0 >> 4, 15u)) >= 16)) {
            const uint32_t i = z.w0, k = i >= 240 ? 1 : z.w1 - i >= 4 && !(i & 3) ? 4 : z.w1 - i >= 2 && !(i & 1) ? 2 : 1;
            z.w0 += k;
            if (i >= 240) return IT_W64S | 15 << 3 | (i - 240) << 7;
            return (k == 4 ? IT_W256 : k == 2 ? IT_W128 : IT_W64) | (i >> 4) << 3 | ((i & 15) / k) << 7;
        }
        const uint32_t prog = ld_rlx32(g_flag + 98), wo = ld_rlx32(g_flag + 97);
        z.qb = max(z.qb, ld_rlx32(g_flag + 96));
        const bool wo_ready = z.w0 >= z.w1 && wo < 272 && (z.qb >= 16 || ld_rlx32(g_flag + 64 + min(wo >> 4, 15u)) >= 16);
        if (z.qb < 16 && prog + (z.qb == 15 ? LOOKL : z.qb == 14 ? LOOKM : z.qb == 13 ? LOOKN : LOOK) >= 4 * z.qb + 4 && !(wo_ready && prog <= PWO)) {
            const uint32_t i = atomicAdd(g_flag + 80 + z.qb, 1);
            if (i == 15) atomicMax(g_flag + 96, z.qb + 1);
            if (i < 16) return IT_QA | z.qb << 3 | i << 7;
            z.qb++;
            continue;
        }
        if (z.w0 < z.w1) {
            if (z.qb >= 16) continue;
        } else if (wo >= 272) {
            if (z.qb >= 16) return IT_END;
        } else if (wo_ready) {
            const uint32_t k = prog <= P256 ? 4 : prog <= P128 ? 2 : 1;
            z.w0 = atomicAdd(g_flag + 97, k);
            z.w1 = min(z.w0 + k, 272u);
            continue;
        }
        __nanosleep(300);
    }
    __trap();
    return IT_END;
}
constexpr int B_OST = NSTAGE * STAGE_BYTES + 1024;
constexpr int BG_SMEM = B_OST + 32768;

template <int BM, int BN, int KPS, typename ACC>
__device__ __forceinline__ void gemm_mainloop(ACC& acc, const GemmSmem& g, int cw, int rounds, uint32_t& round) {
#pragma unroll
    for (int i = 0; i < BN / 2; i++) acc[i] = 0.f;
#pragma unroll 1
    for (int k0 = 0; k0 < rounds; k0++, round++) {
#pragma unroll
        for (int s = 0; s < 4; s++) {
            mbar_wait_u(g.full + 8 * s, round & 1);
            gemm_stage<BM, BN, KPS>(acc, g.st + s * STAGE_BYTES, cw, false);
            wg_wait<1>();
            if (s > 0 || k0 > 0) mbar_arrive_one(g.empty + 8 * ((s + 3) & 3), threadIdx.x & 31);
        }
    }
    wg_wait<0>();
    mbar_arrive_one(g.empty + 8 * 3, threadIdx.x & 31);
}

template <int BM, int BN, int KPS>
__device__ __forceinline__ void wo_item(const GemmSmem& g, int cw, uint32_t& round, bf16* dst, int t) {
    if (BM == 64 && cw == 1) {
#pragma unroll 1
        for (int k0 = 0; k0 < 16 / KPS; k0++, round++)
#pragma unroll
            for (int s = 0; s < 4; s++) { mbar_wait_u(g.full + 8 * s, round & 1); mbar_arrive_one(g.empty + 8 * s, threadIdx.x & 31); }
        return;
    }
    float acc[BN / 2];
    gemm_mainloop<BM, BN, KPS>(acc, g, cw, 16 / KPS, round);
#pragma unroll
    for (int G = 0; G < BN / 32; G++)
#pragma unroll
        for (int rr = 0; rr < 2; rr++) {
            uint32_t r0 = pack2(acc[16 * G + 2 * rr], acc[16 * G + 2 * rr + 1]), r1 = pack2(acc[16 * G + 4 + 2 * rr], acc[16 * G + 5 + 2 * rr]);
            uint32_t r2 = pack2(acc[16 * G + 8 + 2 * rr], acc[16 * G + 9 + 2 * rr]), r3 = pack2(acc[16 * G + 12 + 2 * rr], acc[16 * G + 13 + 2 * rr]);
            quad_transpose(r0, r1, r2, r3, t);
            *reinterpret_cast<uint4*>(dst + (size_t)rr * 8 * 2048 + G * 32) = make_uint4(r0, r1, r2, r3);
        }
}

template <int HF>
__device__ __forceinline__ void attend(const uint32_t* q, uint32_t st, uint32_t sm, uint32_t ost, uint32_t bar_free, uint32_t parity, int lane) {
    constexpr int NT = HF ? 5 : 3;
    const int r8 = lane & 7, m4 = lane >> 3, gq = lane >> 2, t = lane & 3;
    const float sl2e = 0.08838834764831845f * 1.4426950408889634f;
    const uint32_t la = r8 * 128 + ((m4 ^ r8) << 4);
    float sc[NT][4];
#pragma unroll
    for (int nt = 0; nt < NT; nt++) sc[nt][0] = sc[nt][1] = sc[nt][2] = sc[nt][3] = 0.f;
#pragma unroll
    for (int kp = 0; kp < 4; kp++)
#pragma unroll
        for (int nt = 0; nt < NT; nt++) {
            uint32_t b[4];
            ldsm4(b, (nt == 0 ? sm + (kp >> 1) * 2048 : st + (kp >> 1) * 8192 + (nt - 1) * 1024) + (la ^ ((kp & 1) << 6)));
            mma16816(sc[nt], q[kp * 8], q[kp * 8 + 1], q[kp * 8 + 2], q[kp * 8 + 3], b[0], b[1]);
            mma16816(sc[nt], q[kp * 8 + 4], q[kp * 8 + 5], q[kp * 8 + 6], q[kp * 8 + 7], b[2], b[3]);
        }
    const float ninf = -3.0e38f;
    if (2 * t > gq) sc[NT - 2][0] = sc[NT - 1][2] = ninf;
    if (2 * t + 1 > gq) sc[NT - 2][1] = sc[NT - 1][3] = ninf;
    sc[NT - 1][0] = sc[NT - 1][1] = ninf;
    uint32_t p[NT][2];
#pragma unroll
    for (int i = 0; i < 2; i++) {
        float m = fmaxf(sc[0][2 * i], sc[0][2 * i + 1]);
#pragma unroll
        for (int nt = 1; nt < NT - 1 + i; nt++) m = fmaxf(m, fmaxf(sc[nt][2 * i], sc[nt][2 * i + 1]));
        m = fmaxf(m, __shfl_xor_sync(~0u, m, 1));
        m = fmaxf(m, __shfl_xor_sync(~0u, m, 2));
        const float ms = m * sl2e;
        float sum = 0.f;
#pragma unroll
        for (int nt = 0; nt < NT - 1 + i; nt++) {
            sc[nt][2 * i] = ex2(fmaf(sc[nt][2 * i], sl2e, -ms));
            sc[nt][2 * i + 1] = ex2(fmaf(sc[nt][2 * i + 1], sl2e, -ms));
            sum += sc[nt][2 * i] + sc[nt][2 * i + 1];
        }
        sum += __shfl_xor_sync(~0u, sum, 1);
        sum += __shfl_xor_sync(~0u, sum, 2);
        float inv;
        asm("rcp.approx.ftz.f32 %0, %1;" : "=f"(inv) : "f"(sum));
#pragma unroll
        for (int nt = 0; nt < NT - 1 + i; nt++) p[nt][i] = pack2(sc[nt][2 * i] * inv, sc[nt][2 * i + 1] * inv);
    }
    p[NT - 1][0] = 0;
    const uint32_t lv = ((m4 & 1) * 8 + r8) * 128 + (((m4 >> 1) ^ r8) << 4);
    mbar_wait_u(bar_free, parity);
#pragma unroll
    for (int G = 0; G < 4; G++) {
        float o[4][4];
#pragma unroll
        for (int i = 0; i < 4; i++) o[i][0] = o[i][1] = o[i][2] = o[i][3] = 0.f;
        uint32_t b[4];
        ldsm4t(b, sm + 4096 + (G >> 1) * 2048 + (la ^ ((G & 1) << 6)));
#pragma unroll
        for (int i = 0; i < 4; i++) mma1688(o[i], p[0][0], p[0][1], b[i]);
#pragma unroll
        for (int kk = 0; kk <= HF; kk++)
#pragma unroll
            for (int i = 0; i < 2; i++) {
                ldsm4t(b, st + 16384 + (G >> 1) * 8192 + kk * 2048 + (lv ^ (((G & 1) * 2 + i) << 5)));
                mma16816(o[2 * i], p[1 + 2 * kk][0], p[1 + 2 * kk][1], p[2 + 2 * kk][0], p[2 + 2 * kk][1], b[0], b[1]);
                mma16816(o[2 * i + 1], p[1 + 2 * kk][0], p[1 + 2 * kk][1], p[2 + 2 * kk][0], p[2 + 2 * kk][1], b[2], b[3]);
            }
#pragma unroll
        for (int i = 0; i < 2; i++)
            asm volatile("stmatrix.sync.aligned.m8n8.x4.shared.b16 [%0], {%1,%2,%3,%4};"
                         ::"r"(ost + (G >> 1) * 16384 + (lv ^ (((G & 1) * 2 + i) << 5))),
                           "r"(pack2(o[2 * i][0], o[2 * i][1])), "r"(pack2(o[2 * i][2], o[2 * i][3])),
                           "r"(pack2(o[2 * i + 1][0], o[2 * i + 1][1])), "r"(pack2(o[2 * i + 1][2], o[2 * i + 1][3])) : "memory");
    }
    asm volatile("fence.proxy.async.shared::cta;" ::: "memory");
    __syncwarp();
}

__device__ __forceinline__ void tma_prefetch3d(const CUtensorMap* m, int c0, int c1, int c2) {
    asm volatile("cp.async.bulk.prefetch.tensor.3d.L2.global [%0, {%1, %2, %3}];" ::"l"(m), "r"(c0), "r"(c1), "r"(c2) : "memory");
}

__global__ void __launch_bounds__(384, 1) k_bg(const __grid_constant__ BgParams P, bf16* __restrict__ out) {
    extern __shared__ __align__(1024) uint8_t smem_gemm[];
    const uint32_t xb = smem_u32(smem_gemm) + NSTAGE * STAGE_BYTES + 128;
    const uint32_t bar_item = xb, bar_o = xb + 16, bar_f = xb + 24, slot = xb + 32, slot_o = xb + 40;
    if (threadIdx.x == 0) { mbar_init(bar_item, 1); mbar_init(bar_item + 8, 1); mbar_init(bar_o, 8); mbar_init(bar_f, 1); }
    GemmSmem g = gemm_setup(smem_gemm, 8);
    const int wg = __shfl_sync(~0u, threadIdx.x >> 7, 0);
    if (wg == 0) {
        asm volatile("setmaxnreg.dec.sync.aligned.u32 40;");
        if (threadIdx.x == 0) {
            uint32_t it = 0;
            Sched z;
            auto acquire = [&](uint32_t bytes) {
                const int s = it & 3;
                mbar_wait(g.empty + 8 * s, ((it >> 2) & 1) ^ 1);
                mbar_expect_tx(g.full + 8 * s, bytes);
                it++;
                return s;
            };
            for (int n = 0;; n++) {
                const int code = next_item(z);
                sts32(slot + (n & 1) * 4, code);
                mbar_arrive(bar_item + (n & 1) * 8);
                const int type = code & 7, blk = (code >> 3) & 15, idx = code >> 7, m0 = blk * 128;
                if (type == IT_END) break;
                if (type == IT_QA) {
                    for (int k = 0; k < 16; k++) {
                        const int s = acquire(STAGE_BYTES);
                        const uint32_t st = g.st + s * STAGE_BYTES, fb = g.full + 8 * s;
                        tma2d(st, &P.mx, k * 64, m0, fb);
                        tma3d(st + 16384, &P.mwq, 0, k * 64, idx * 4, fb);
                        if (k >= 4 && k < 12) tma_prefetch3d(&P.mkv, 0, m0 + (k & 1) * 64, (k & 8) * 8 + idx * 4 + (k & 2));
                    }
                    bool ready = ld_acq32(g_flag + 2 * idx) >= 4 * blk + 4 && ld_acq32(g_flag + 2 * idx + 1) >= 4 * blk + 4;
                    if (ready) asm volatile("fence.proxy.async.global;" ::: "memory");
                    for (int pass = 0; pass < 2; pass++) {
                        for (int s = 0; s < 4; s++) {
                            const uint32_t st = g.st + s * STAGE_BYTES, fb = g.full + 8 * s;
                            if (pass == 0) {
                                acquire(40960);
                                tma3d(st, &P.mkv, 0, m0 + (s & 1) * 64, idx * 4 + (s & 2), fb);
                                tma3d(st + 16384, &P.mkv, 0, m0 + (s & 1) * 64, 64 + idx * 4 + (s & 2), fb);
                            }
                            if (ready) {
                                tma3d(st + 32768, &P.mkvm, 0, blk * 32 + (s & 1) * 16, idx * 4 + (s & 2), fb);
                                tma3d(st + 36864, &P.mkvm, 0, blk * 32 + (s & 1) * 16, 64 + idx * 4 + (s & 2), fb);
                            }
                        }
                        if (ready) break;
                        wait_flag(g_flag + 2 * idx, 4 * blk + 4);
                        wait_flag(g_flag + 2 * idx + 1, 4 * blk + 4);
                        asm volatile("fence.proxy.async.global;" ::: "memory");
                        ready = true;
                    }
                } else {
                    wait_flag(g_flag + 64 + blk, 16);
                    asm volatile("fence.proxy.async.global;" ::: "memory");
                    if (type <= IT_W128) {
                        const int nb = type == IT_W256 ? 4 : 2;
                        for (int k = 0; k < 64; k++) {
                            const int s = acquire(16384 + nb * 8192);
                            const uint32_t st = g.st + s * STAGE_BYTES, fb = g.full + 8 * s;
                            tma2d(st, &P.mo, k * 64, m0, fb);
                            tma3d(st + 16384, nb == 4 ? &P.mwo4 : &P.mwo2, 0, k * 64, idx * nb, fb);
                        }
                    } else {
                        const uint32_t ab = type == IT_W64 ? 32768 : 16384;
                        for (int k = 0; k < 32; k++) {
                            const int s = acquire(ab + 16384);
                            const uint32_t st = g.st + s * STAGE_BYTES, fb = g.full + 8 * s;
                            tma3d(st, type == IT_W64 ? &P.mo2 : &P.mo2s, 0, m0 + (idx >> 4) * 64, k * 2, fb);
                            tma3d(st + ab, &P.mwo1, 0, k * 128, idx & 15, fb);
                        }
                    }
                }
            }
        } else if (threadIdx.x == 32) {
            for (;;) {
                mbar_wait(bar_o, 0);
                const int code = lds32(slot_o), blk = (code >> 3) & 15, idx = (code >> 7) & 31;
                if ((code & 7) == IT_END) break;
                for (int hh = 0; hh < 2; hh++) {
                    if (hh) mbar_wait(bar_o, 1);
                    asm volatile("cp.async.bulk.tensor.3d.global.shared::cta.bulk_group [%0, {%2, %3, %4}], [%1];\n"
                                 "cp.async.bulk.commit_group;\ncp.async.bulk.wait_group.read 0;"
                                 ::"l"(&P.mo2), "r"(g.st + B_OST), "r"(0), "r"(blk * 128), "r"(idx * 4 + hh * 2) : "memory");
                    mbar_arrive(bar_f);
                }
                asm volatile("cp.async.bulk.wait_group 0;\nfence.acq_rel.gpu;\nred.relaxed.gpu.global.add.u32 [%0], 1;"
                             ::"l"(g_flag + 64 + blk) : "memory");
            }
        }
    } else {
        asm volatile("setmaxnreg.inc.sync.aligned.u32 232;");
        const int cw = wg - 1, ww = __shfl_sync(~0u, (threadIdx.x >> 5) & 3, 0), lane = threadIdx.x & 31;
        uint32_t round = 0;
#pragma unroll 1
        for (int n = 0;; n++) {
            mbar_wait_u(bar_item + (n & 1) * 8, (n >> 1) & 1);
            const int code = __shfl_sync(~0u, lds32(slot + (n & 1) * 4), 0);
            const int type = code & 7, blk = (code >> 3) & 15, idx = (code >> 7) & 31;
#define TLB(slot_)
            if (type == IT_END) {
                mbar_wait_u(bar_f, 1);
                if (threadIdx.x == 128) sts32(slot_o, IT_END);
                __syncwarp();
                mbar_arrive_one(bar_o, lane);
                break;
            }
            TLB(0);
            if (type == IT_QA) {
                uint32_t q[64];
                {
                    float acc[128];
                    gemm_mainloop<128, 256, 1>(acc, g, cw, 4, round);
#pragma unroll
                    for (int i = 0; i < 64; i++) q[i] = pack2(acc[2 * i], acc[2 * i + 1]);
                }
                if (threadIdx.x == 128) sts32(slot_o, code);
                TLB(2);
#pragma unroll
                for (int hh = 0; hh < 2; hh++) {
                    const uint32_t st = g.st + (2 * hh + cw) * STAGE_BYTES, ost = g.st + B_OST + (cw * 4 + ww) * 2048;
                    mbar_wait_u(g.full + 16 * hh, round & 1);
                    mbar_wait_u(g.full + 16 * hh + 8, round & 1);
                    if (hh == 0) { TLB(3); }
                    if (ww & 1) attend<1>(q + 32 * hh, st + (ww >> 1) * 4096, st + 32768 + (ww >> 1) * 1024, ost, bar_f, hh ^ 1, lane);
                    else attend<0>(q + 32 * hh, st + (ww >> 1) * 4096, st + 32768 + (ww >> 1) * 1024, ost, bar_f, hh ^ 1, lane);
                    mbar_arrive_one(bar_o, lane);
                    mbar_arrive_one(g.empty + 16 * hh, lane);
                    mbar_arrive_one(g.empty + 16 * hh + 8, lane);
                }
                round++;
            } else {
                bf16* dst = out + (size_t)(blk * 128 + cw * 64 + ww * 16 + (lane >> 2)) * 2048 + (lane & 3) * 8;
                if (type == IT_W256) wo_item<128, 256, 1>(g, cw, round, dst + idx * 256, lane & 3);
                else if (type == IT_W128) wo_item<128, 128, 1>(g, cw, round, dst + idx * 128, lane & 3);
                else if (type == IT_W64) wo_item<128, 64, 2>(g, cw, round, dst + idx * 64, lane & 3);
                else wo_item<64, 64, 2>(g, cw, round, dst + (size_t)(idx >> 4) * 64 * 2048 + (idx & 15) * 64, lane & 3);
            }
            TLB(1);
        }
    }
}

typedef CUresult (*EncodeFn)(CUtensorMap*, CUtensorMapDataType, cuuint32_t, void*, const cuuint64_t*, const cuuint64_t*,
                             const cuuint32_t*, const cuuint32_t*, CUtensorMapInterleave, CUtensorMapSwizzle,
                             CUtensorMapL2promotion, CUtensorMapFloatOOBfill);

static void map2d(EncodeFn enc, CUtensorMap* m, const void* p, int rows, int cols, int box_rows) {
    cuuint64_t dim[2] = {(cuuint64_t)cols, (cuuint64_t)rows}, str[1] = {(cuuint64_t)cols * 2};
    cuuint32_t box[2] = {64, (cuuint32_t)box_rows}, es[2] = {1, 1};
    enc(m, CU_TENSOR_MAP_DATA_TYPE_BFLOAT16, 2, (void*)p, dim, str, box, es, CU_TENSOR_MAP_INTERLEAVE_NONE,
        CU_TENSOR_MAP_SWIZZLE_128B, CU_TENSOR_MAP_L2_PROMOTION_L2_256B, CU_TENSOR_MAP_FLOAT_OOB_FILL_NONE);
}
static void map3d(EncodeFn enc, CUtensorMap* m, const void* p, int rows, int cols, int box_rows, int nblk) {
    cuuint64_t dim[3] = {64, (cuuint64_t)rows, (cuuint64_t)cols / 64}, str[2] = {(cuuint64_t)cols * 2, 128};
    cuuint32_t box[3] = {64, (cuuint32_t)box_rows, (cuuint32_t)nblk}, es[3] = {1, 1, 1};
    enc(m, CU_TENSOR_MAP_DATA_TYPE_BFLOAT16, 3, (void*)p, dim, str, box, es, CU_TENSOR_MAP_INTERLEAVE_NONE,
        CU_TENSOR_MAP_SWIZZLE_128B, CU_TENSOR_MAP_L2_PROMOTION_L2_256B, CU_TENSOR_MAP_FLOAT_OOB_FILL_NONE);
}

#define USE_PDL 1

extern "C" void kernel_launch(void* const* d_in, const int* in_sizes, int n_in, void* d_out, int out_size) {
    const bf16 *x = (const bf16*)d_in[0], *mem0 = (const bf16*)d_in[1], *Wq = (const bf16*)d_in[2], *Wk = (const bf16*)d_in[3];
    const bf16 *Wv = (const bf16*)d_in[4], *Wo = (const bf16*)d_in[5];
    const bf16 *u = (const bf16*)d_in[7], *Are = (const bf16*)d_in[8], *Aim = (const bf16*)d_in[9], *Bre = (const bf16*)d_in[10];
    const bf16 *Bim = (const bf16*)d_in[11], *Cre = (const bf16*)d_in[12], *Cim = (const bf16*)d_in[13];
    const bf16 *logdt = (const bf16*)d_in[14], *Dsk = (const bf16*)d_in[15];
    bf16* out = (bf16*)d_out;

    void* fn = nullptr;
    cudaDriverEntryPointQueryResult qr;
    cudaGetDriverEntryPoint("cuTensorMapEncodeTiled", &fn, cudaEnableDefault, &qr);
    EncodeFn enc = (EncodeFn)fn;
    void *kv, *kvm, *o;
    cudaGetSymbolAddress(&kv, g_kv);
    cudaGetSymbolAddress(&kvm, g_kvm);
    cudaGetSymbolAddress(&o, g_o);
    CUtensorMap mwk, mwv, mkv2;
    BgParams P;
    map2d(enc, &P.mx, x, SEQ, DM, 128);
    map2d(enc, &P.mo, o, SEQ, HD, 128);
    map3d(enc, &P.mo2, o, SEQ, HD, 128, 2);
    map3d(enc, &P.mo2s, o, SEQ, HD, 64, 2);
    map3d(enc, &P.mwq, Wq, DM, HD, 64, 4);
    map3d(enc, &mwk, Wk, DM, HD, 64, 4);
    map3d(enc, &mwv, Wv, DM, HD, 64, 4);
    map3d(enc, &P.mwo4, Wo, HD, DM, 64, 4);
    map3d(enc, &P.mwo2, Wo, HD, DM, 64, 2);
    map3d(enc, &P.mwo1, Wo, HD, DM, 128, 1);
    map3d(enc, &mkv2, kv, SEQ, 8192, 32, 2);
    map3d(enc, &P.mkv, kv, SEQ, 8192, 64, 2);
    map3d(enc, &P.mkvm, kvm, NSEG * 8, 8192, 16, 2);
    cudaFuncSetAttribute(k_kv, cudaFuncAttributeMaxDynamicSharedMemorySize, GEMM_SMEM);
    cudaFuncSetAttribute(k_bg, cudaFuncAttributeMaxDynamicSharedMemorySize, BG_SMEM);
    cudaFuncSetAttribute(k_chain, cudaFuncAttributeMaxDynamicSharedMemorySize, CHAIN_SMEM);
    cudaFuncSetAttribute(k_s4, cudaFuncAttributeMaxDynamicSharedMemorySize, S4_SMEM);

    cudaStream_t st = cudaStreamPerThread;
    k_kv<<<132, 384, GEMM_SMEM, st>>>(P.mx, mwk, mwv, Wq, Wo, u);
    k_chain<<<96, 256, CHAIN_SMEM, st>>>(mem0, Wq, Wk, Wv, Wo, mkv2);
    cudaLaunchAttribute pdl[1];
    pdl[0].id = cudaLaunchAttributeProgrammaticStreamSerialization;
    pdl[0].val.programmaticStreamSerializationAllowed = 1;
    cudaLaunchConfig_t cfg = {};
    cfg.stream = st; cfg.attrs = pdl; cfg.numAttrs = USE_PDL;
    cfg.gridDim = dim3(64); cfg.blockDim = dim3(512); cfg.dynamicSmemBytes = S4_SMEM;
    cudaLaunchKernelEx(&cfg, k_s4, u, Are, Aim, Bre, Bim, Cre, Cim, logdt, Dsk, out);
    cfg.gridDim = dim3(132); cfg.blockDim = dim3(384); cfg.dynamicSmemBytes = BG_SMEM;
    cudaLaunchKernelEx(&cfg, k_bg, P, out);
}
```

```cpp
#include <cuda_runtime.h>
#include <cuda_bf16.h>
#include <cuda.h>
#include <stdint.h>

typedef __nv_bfloat16 bf16;

constexpr int SEQ = 2048, DM = 1024, HD = 4096, NSEG = 64;

__device__ __align__(1024) bf16 g_kv[(size_t)SEQ * 8192];
__device__ __align__(1024) bf16 g_kvm[(size_t)NSEG * 8 * 8192];
__device__ __align__(1024) bf16 g_o[(size_t)SEQ * HD];
constexpr int XPAIRS = 128 + NSEG * 4;
__device__ __align__(8192) uint2 g_x[XPAIRS * 1024];
__device__ uint32_t g_home[XPAIRS];
__device__ uint32_t g_side[256];
__device__ __align__(1024) uint32_t g_flag[256];

#define TL(kern, slot)

__device__ __forceinline__ uint32_t smem_u32(const void* p) { return (uint32_t)__cvta_generic_to_shared(p); }
__device__ __forceinline__ void mbar_init(uint32_t bar, uint32_t cnt) {
    asm volatile("mbarrier.init.shared::cta.b64 [%0], %1;" ::"r"(bar), "r"(cnt) : "memory");
}
__device__ __forceinline__ void mbar_expect_tx(uint32_t bar, uint32_t bytes) {
    asm volatile("mbarrier.arrive.expect_tx.shared::cta.b64 _, [%0], %1;" ::"r"(bar), "r"(bytes) : "memory");
}
__device__ __forceinline__ void mbar_arrive(uint32_t bar) {
    asm volatile("mbarrier.arrive.shared::cta.b64 _, [%0];" ::"r"(bar) : "memory");
}
__device__ __forceinline__ bool mbar_try(uint32_t bar, uint32_t parity) {
    uint32_t ok;
    asm volatile("{\n.reg .pred p;\nmbarrier.try_wait.parity.shared::cta.b64 p, [%1], %2;\nselp.u32 %0, 1, 0, p;\n}"
                 : "=r"(ok) : "r"(bar), "r"(parity) : "memory");
    return ok;
}
constexpr int SPIN_LIMIT = 1 << 20;
__device__ __forceinline__ void mbar_wait(uint32_t bar, uint32_t parity) {
    int n = 0;
    while (!mbar_try(bar, parity)) { if (++n > SPIN_LIMIT) __trap(); }
}
__device__ __forceinline__ void mbar_wait_u(uint32_t bar, uint32_t parity) {
    asm volatile("{\n.reg .pred p;\n.reg .u32 n;\n"
                 "mbarrier.try_wait.parity.shared::cta.b64 p, [%0], %1;\n@p bra.uni DONE;\nmov.u32 n, 0;\n"
                 "AGAIN:\nmbarrier.try_wait.parity.shared::cta.b64 p, [%0], %1;\n@p bra.uni DONE;\n"
                 "add.u32 n, n, 1;\nsetp.lt.u32 p, n, 0x100000;\n@p bra.uni AGAIN;\ntrap;\nDONE:\n}"
                 ::"r"(bar), "r"(parity) : "memory");
}
__device__ __forceinline__ void tma2d(uint32_t dst, const CUtensorMap* m, int c0, int c1, uint32_t bar) {
    asm volatile("cp.async.bulk.tensor.2d.shared::cluster.global.mbarrier::complete_tx::bytes [%0], [%1, {%3, %4}], [%2];"
                 ::"r"(dst), "l"(m), "r"(bar), "r"(c0), "r"(c1) : "memory");
}
__device__ __forceinline__ void tma3d(uint32_t dst, const CUtensorMap* m, int c0, int c1, int c2, uint32_t bar) {
    asm volatile("cp.async.bulk.tensor.3d.shared::cluster.global.mbarrier::complete_tx::bytes [%0], [%1, {%3, %4, %5}], [%2];"
                 ::"r"(dst), "l"(m), "r"(bar), "r"(c0), "r"(c1), "r"(c2) : "memory");
}
__device__ __forceinline__ uint32_t pack2(float lo, float hi) {
    uint32_t r;
    asm("cvt.rn.bf16x2.f32 %0, %1, %2;" : "=r"(r) : "f"(hi), "f"(lo));
    return r;
}
__device__ __forceinline__ float bf_lo(uint32_t v) { return __uint_as_float(v << 16); }
__device__ __forceinline__ float bf_hi(uint32_t v) { return __uint_as_float(v & 0xffff0000u); }
__device__ __forceinline__ float bf_round(float x) { return bf_lo(pack2(x, 0.f)); }
__device__ __forceinline__ float ex2(float x) { float y; asm("ex2.approx.ftz.f32 %0, %1;" : "=f"(y) : "f"(x)); return y; }
__device__ __forceinline__ void mma16816(float (&c)[4], uint32_t a0, uint32_t a1, uint32_t a2, uint32_t a3, uint32_t b0, uint32_t b1) {
    asm volatile("mma.sync.aligned.m16n8k16.row.col.f32.bf16.bf16.f32 {%0,%1,%2,%3}, {%4,%5,%6,%7}, {%8,%9}, {%0,%1,%2,%3};"
                 : "+f"(c[0]), "+f"(c[1]), "+f"(c[2]), "+f"(c[3]) : "r"(a0), "r"(a1), "r"(a2), "r"(a3), "r"(b0), "r"(b1));
}
__device__ __forceinline__ void mma1688(float (&c)[4], uint32_t a0, uint32_t a1, uint32_t b0) {
    asm volatile("mma.sync.aligned.m16n8k8.row.col.f32.bf16.bf16.f32 {%0,%1,%2,%3}, {%4,%5}, {%6}, {%0,%1,%2,%3};"
                 : "+f"(c[0]), "+f"(c[1]), "+f"(c[2]), "+f"(c[3]) : "r"(a0), "r"(a1), "r"(b0));
}
__device__ __forceinline__ void ldsm4(uint32_t (&r)[4], uint32_t a) {
    asm volatile("ldmatrix.sync.aligned.m8n8.x4.shared.b16 {%0,%1,%2,%3}, [%4];"
                 : "=r"(r[0]), "=r"(r[1]), "=r"(r[2]), "=r"(r[3]) : "r"(a) : "memory");
}
__device__ __forceinline__ void ldsm4t(uint32_t (&r)[4], uint32_t a) {
    asm volatile("ldmatrix.sync.aligned.m8n8.x4.trans.shared.b16 {%0,%1,%2,%3}, [%4];"
                 : "=r"(r[0]), "=r"(r[1]), "=r"(r[2]), "=r"(r[3]) : "r"(a) : "memory");
}
__device__ __forceinline__ void ldsm2t(uint32_t& r0, uint32_t& r1, uint32_t a) {
    asm volatile("ldmatrix.sync.aligned.m8n8.x2.trans.shared.b16 {%0,%1}, [%2];" : "=r"(r0), "=r"(r1) : "r"(a) : "memory");
}
__device__ __forceinline__ void stsm4t(uint32_t a, uint32_t r0, uint32_t r1, uint32_t r2, uint32_t r3) {
    asm volatile("stmatrix.sync.aligned.m8n8.x4.trans.shared.b16 [%0], {%1,%2,%3,%4};"
                 ::"r"(a), "r"(r0), "r"(r1), "r"(r2), "r"(r3) : "memory");
}
__device__ __forceinline__ void lds128(uint32_t (&r)[4], uint32_t a) {
    asm volatile("ld.shared.v4.u32 {%0,%1,%2,%3}, [%4];" : "=r"(r[0]), "=r"(r[1]), "=r"(r[2]), "=r"(r[3]) : "r"(a) : "memory");
}
__device__ __forceinline__ float4 lds128f(uint32_t a) {
    float4 v;
    asm volatile("ld.shared.v4.f32 {%0,%1,%2,%3}, [%4];" : "=f"(v.x), "=f"(v.y), "=f"(v.z), "=f"(v.w) : "r"(a) : "memory");
    return v;
}
__device__ __forceinline__ float2 lds64f(uint32_t a) {
    float2 v;
    asm volatile("ld.shared.v2.f32 {%0,%1}, [%2];" : "=f"(v.x), "=f"(v.y) : "r"(a) : "memory");
    return v;
}
__device__ __forceinline__ uint32_t lds32(uint32_t a) {
    uint32_t v;
    asm volatile("ld.shared.u32 %0, [%1];" : "=r"(v) : "r"(a) : "memory");
    return v;
}
__device__ __forceinline__ void sts128(uint32_t a, uint32_t r0, uint32_t r1, uint32_t r2, uint32_t r3) {
    asm volatile("st.shared.v4.u32 [%0], {%1,%2,%3,%4};" ::"r"(a), "r"(r0), "r"(r1), "r"(r2), "r"(r3) : "memory");
}
__device__ __forceinline__ void sts128f(uint32_t a, float r0, float r1, float r2, float r3) {
    asm volatile("st.shared.v4.f32 [%0], {%1,%2,%3,%4};" ::"r"(a), "f"(r0), "f"(r1), "f"(r2), "f"(r3) : "memory");
}
__device__ __forceinline__ void sts64(uint32_t a, uint32_t r0, uint32_t r1) {
    asm volatile("st.shared.v2.u32 [%0], {%1,%2};" ::"r"(a), "r"(r0), "r"(r1) : "memory");
}
__device__ __forceinline__ void sts64f(uint32_t a, float r0, float r1) {
    asm volatile("st.shared.v2.f32 [%0], {%1,%2};" ::"r"(a), "f"(r0), "f"(r1) : "memory");
}
__device__ __forceinline__ void sts32f(uint32_t a, float r0) {
    asm volatile("st.shared.f32 [%0], %1;" ::"r"(a), "f"(r0) : "memory");
}
__device__ __forceinline__ uint2 ld_rlx64(const uint2* p) {
    uint2 v;
    asm volatile("{\n.reg .b64 t;\nld.relaxed.gpu.global.b64 t, [%2];\nmov.b64 {%0,%1}, t;\n}" : "=r"(v.x), "=r"(v.y) : "l"(p) : "memory");
    return v;
}
__device__ __forceinline__ void st_rlx64(uint2* p, uint32_t x, uint32_t y) {
    asm volatile("{\n.reg .b64 t;\nmov.b64 t, {%1,%2};\nst.relaxed.gpu.global.b64 [%0], t;\n}" ::"l"(p), "r"(x), "r"(y) : "memory");
}
__device__ __forceinline__ uint32_t ld_acq32(const uint32_t* p) {
    uint32_t v;
    asm volatile("ld.acquire.gpu.global.u32 %0, [%1];" : "=r"(v) : "l"(p) : "memory");
    return v;
}
__device__ __forceinline__ void wait_flag(const uint32_t* p, uint32_t need) {
    int n = 0;
    while (ld_acq32(p) < need) { __nanosleep(200); if (++n > SPIN_LIMIT) __trap(); }
}
__device__ __forceinline__ void bar_sync(int id, int n) { asm volatile("bar.sync %0, %1;" ::"r"(id), "r"(n) : "memory"); }
__device__ __forceinline__ void wg_fence() { asm volatile("wgmma.fence.sync.aligned;" ::: "memory"); }
__device__ __forceinline__ void wg_commit() { asm volatile("wgmma.commit_group.sync.aligned;" ::: "memory"); }
template <int N> __device__ __forceinline__ void wg_wait() { asm volatile("wgmma.wait_group.sync.aligned %0;" ::"n"(N) : "memory"); }
__device__ __forceinline__ uint64_t desc_sw128(uint32_t addr, uint32_t lbo, uint32_t sbo) {
    return (uint64_t)((addr & 0x3FFFF) >> 4) | ((uint64_t)(lbo >> 4) << 16) | ((uint64_t)(sbo >> 4) << 32) | (1ull << 62);
}
__device__ __forceinline__ void quad_transpose(uint32_t& r0, uint32_t& r1, uint32_t& r2, uint32_t& r3, int t) {
    const bool o = t & 1, h = t & 2;
    uint32_t s0 = __shfl_xor_sync(~0u, o ? r0 : r1, 1), s1 = __shfl_xor_sync(~0u, o ? r2 : r3, 1);
    uint32_t a0 = o ? s0 : r0, a1 = o ? r1 : s0, a2 = o ? s1 : r2, a3 = o ? r3 : s1;
    s0 = __shfl_xor_sync(~0u, h ? a0 : a2, 2); s1 = __shfl_xor_sync(~0u, h ? a1 : a3, 2);
    r0 = h ? s0 : a0; r1 = h ? s1 : a1; r2 = h ? a2 : s0; r3 = h ? a3 : s1;
}

__device__ __forceinline__ void wgmma_n256(float (&d)[128], uint64_t da, uint64_t db, int sd) {
    asm volatile("{\n.reg .pred p;\nsetp.ne.b32 p, %130, 0;\n"
        "wgmma.mma_async.sync.aligned.m64n256k16.f32.bf16.bf16 "
        "{%0,%1,%2,%3,%4,%5,%6,%7,%8,%9,%10,%11,%12,%13,%14,%15,"
        "%16,%17,%18,%19,%20,%21,%22,%23,%24,%25,%26,%27,%28,%29,%30,%31,"
        "%32,%33,%34,%35,%36,%37,%38,%39,%40,%41,%42,%43,%44,%45,%46,%47,"
        "%48,%49,%50,%51,%52,%53,%54,%55,%56,%57,%58,%59,%60,%61,%62,%63,"
        "%64,%65,%66,%67,%68,%69,%70,%71,%72,%73,%74,%75,%76,%77,%78,%79,"
        "%80,%81,%82,%83,%84,%85,%86,%87,%88,%89,%90,%91,%92,%93,%94,%95,"
        "%96,%97,%98,%99,%100,%101,%102,%103,%104,%105,%106,%107,%108,%109,%110,%111,"
        "%112,%113,%114,%115,%116,%117,%118,%119,%120,%121,%122,%123,%124,%125,%126,%127}, %128, %129, p, 1, 1, 0, 1;\n}\n"
        : "+f"(d[0]), "+f"(d[1]), "+f"(d[2]), "+f"(d[3]), "+f"(d[4]), "+f"(d[5]), "+f"(d[6]), "+f"(d[7]),
          "+f"(d[8]), "+f"(d[9]), "+f"(d[10]), "+f"(d[11]), "+f"(d[12]), "+f"(d[13]), "+f"(d[14]), "+f"(d[15]),
          "+f"(d[16]), "+f"(d[17]), "+f"(d[18]), "+f"(d[19]), "+f"(d[20]), "+f"(d[21]), "+f"(d[22]), "+f"(d[23]),
          "+f"(d[24]), "+f"(d[25]), "+f"(d[26]), "+f"(d[27]), "+f"(d[28]), "+f"(d[29]), "+f"(d[30]), "+f"(d[31]),
          "+f"(d[32]), "+f"(d[33]), "+f"(d[34]), "+f"(d[35]), "+f"(d[36]), "+f"(d[37]), "+f"(d[38]), "+f"(d[39]),
          "+f"(d[40]), "+f"(d[41]), "+f"(d[42]), "+f"(d[43]), "+f"(d[44]), "+f"(d[45]), "+f"(d[46]), "+f"(d[47]),
          "+f"(d[48]), "+f"(d[49]), "+f"(d[50]), "+f"(d[51]), "+f"(d[52]), "+f"(d[53]), "+f"(d[54]), "+f"(d[55]),
          "+f"(d[56]), "+f"(d[57]), "+f"(d[58]), "+f"(d[59]), "+f"(d[60]), "+f"(d[61]), "+f"(d[62]), "+f"(d[63]),
          "+f"(d[64]), "+f"(d[65]), "+f"(d[66]), "+f"(d[67]), "+f"(d[68]), "+f"(d[69]), "+f"(d[70]), "+f"(d[71]),
          "+f"(d[72]), "+f"(d[73]), "+f"(d[74]), "+f"(d[75]), "+f"(d[76]), "+f"(d[77]), "+f"(d[78]), "+f"(d[79]),
          "+f"(d[80]), "+f"(d[81]), "+f"(d[82]), "+f"(d[83]), "+f"(d[84]), "+f"(d[85]), "+f"(d[86]), "+f"(d[87]),
          "+f"(d[88]), "+f"(d[89]), "+f"(d[90]), "+f"(d[91]), "+f"(d[92]), "+f"(d[93]), "+f"(d[94]), "+f"(d[95]),
          "+f"(d[96]), "+f"(d[97]), "+f"(d[98]), "+f"(d[99]), "+f"(d[100]), "+f"(d[101]), "+f"(d[102]), "+f"(d[103]),
          "+f"(d[104]), "+f"(d[105]), "+f"(d[106]), "+f"(d[107]), "+f"(d[108]), "+f"(d[109]), "+f"(d[110]), "+f"(d[111]),
          "+f"(d[112]), "+f"(d[113]), "+f"(d[114]), "+f"(d[115]), "+f"(d[116]), "+f"(d[117]), "+f"(d[118]), "+f"(d[119]),
          "+f"(d[120]), "+f"(d[121]), "+f"(d[122]), "+f"(d[123]), "+f"(d[124]), "+f"(d[125]), "+f"(d[126]), "+f"(d[127])
        : "l"(da), "l"(db), "r"(sd));
}

__device__ __forceinline__ void wgmma_n128(float (&d)[64], uint64_t da, uint64_t db, int sd) {
    asm volatile("{\n.reg .pred p;\nsetp.ne.b32 p, %66, 0;\n"
        "wgmma.mma_async.sync.aligned.m64n128k16.f32.bf16.bf16 "
        "{%0,%1,%2,%3,%4,%5,%6,%7,%8,%9,%10,%11,%12,%13,%14,%15,"
        "%16,%17,%18,%19,%20,%21,%22,%23,%24,%25,%26,%27,%28,%29,%30,%31,"
        "%32,%33,%34,%35,%36,%37,%38,%39,%40,%41,%42,%43,%44,%45,%46,%47,"
        "%48,%49,%50,%51,%52,%53,%54,%55,%56,%57,%58,%59,%60,%61,%62,%63}, %64, %65, p, 1, 1, 0, 1;\n}\n"
        : "+f"(d[0]), "+f"(d[1]), "+f"(d[2]), "+f"(d[3]), "+f"(d[4]), "+f"(d[5]), "+f"(d[6]), "+f"(d[7]),
          "+f"(d[8]), "+f"(d[9]), "+f"(d[10]), "+f"(d[11]), "+f"(d[12]), "+f"(d[13]), "+f"(d[14]), "+f"(d[15]),
          "+f"(d[16]), "+f"(d[17]), "+f"(d[18]), "+f"(d[19]), "+f"(d[20]), "+f"(d[21]), "+f"(d[22]), "+f"(d[23]),
          "+f"(d[24]), "+f"(d[25]), "+f"(d[26]), "+f"(d[27]), "+f"(d[28]), "+f"(d[29]), "+f"(d[30]), "+f"(d[31]),
          "+f"(d[32]), "+f"(d[33]), "+f"(d[34]), "+f"(d[35]), "+f"(d[36]), "+f"(d[37]), "+f"(d[38]), "+f"(d[39]),
          "+f"(d[40]), "+f"(d[41]), "+f"(d[42]), "+f"(d[43]), "+f"(d[44]), "+f"(d[45]), "+f"(d[46]), "+f"(d[47]),
          "+f"(d[48]), "+f"(d[49]), "+f"(d[50]), "+f"(d[51]), "+f"(d[52]), "+f"(d[53]), "+f"(d[54]), "+f"(d[55]),
          "+f"(d[56]), "+f"(d[57]), "+f"(d[58]), "+f"(d[59]), "+f"(d[60]), "+f"(d[61]), "+f"(d[62]), "+f"(d[63])
        : "l"(da), "l"(db), "r"(sd));
}

__device__ __forceinline__ void wgmma_n64(float (&d)[32], uint64_t da, uint64_t db, int sd) {
    asm volatile("{\n.reg .pred p;\nsetp.ne.b32 p, %34, 0;\n"
        "wgmma.mma_async.sync.aligned.m64n64k16.f32.bf16.bf16 "
        "{%0,%1,%2,%3,%4,%5,%6,%7,%8,%9,%10,%11,%12,%13,%14,%15,"
        "%16,%17,%18,%19,%20,%21,%22,%23,%24,%25,%26,%27,%28,%29,%30,%31}, %32, %33, p, 1, 1, 0, 1;\n}\n"
        : "+f"(d[0]), "+f"(d[1]), "+f"(d[2]), "+f"(d[3]), "+f"(d[4]), "+f"(d[5]), "+f"(d[6]), "+f"(d[7]),
          "+f"(d[8]), "+f"(d[9]), "+f"(d[10]), "+f"(d[11]), "+f"(d[12]), "+f"(d[13]), "+f"(d[14]), "+f"(d[15]),
          "+f"(d[16]), "+f"(d[17]), "+f"(d[18]), "+f"(d[19]), "+f"(d[20]), "+f"(d[21]), "+f"(d[22]), "+f"(d[23]),
          "+f"(d[24]), "+f"(d[25]), "+f"(d[26]), "+f"(d[27]), "+f"(d[28]), "+f"(d[29]), "+f"(d[30]), "+f"(d[31])
        : "l"(da), "l"(db), "r"(sd));
}

constexpr int STAGE_BYTES = 49152, NSTAGE = 4;
constexpr int GEMM_SMEM = NSTAGE * STAGE_BYTES + 128;

struct GemmSmem { uint32_t st, full, empty; };
__device__ __forceinline__ GemmSmem gemm_setup(uint8_t* raw, int releases) {
    GemmSmem g;
    g.st = smem_u32(raw);
    if (g.st & 1023) __trap();
    g.full = g.st + NSTAGE * STAGE_BYTES; g.empty = g.full + 64;
    if (threadIdx.x == 0) {
        for (int s = 0; s < NSTAGE; s++) { mbar_init(g.full + 8 * s, 1); mbar_init(g.empty + 8 * s, releases); }
        asm volatile("fence.mbarrier_init.release.cluster;" ::: "memory");
        asm volatile("fence.proxy.async.shared::cta;" ::: "memory");
    }
    __syncthreads();
    return g;
}
__device__ __forceinline__ void mbar_arrive_one(uint32_t bar, uint32_t who) {
    asm volatile("{\n.reg .pred p;\nsetp.eq.u32 p, %1, 0;\n@p mbarrier.arrive.shared::cta.b64 _, [%0];\n}" ::"r"(bar), "r"(who) : "memory");
}
template <int BM, int BN, int KPS, typename ACC>
__device__ __forceinline__ void gemm_stage(ACC& acc, uint32_t stage, int wg, bool first) {
    const uint64_t da = desc_sw128(stage + wg * 8192, 16, 1024);
    const uint64_t db = desc_sw128(stage + KPS * BM * 128, 8192, 1024);
    wg_fence();
#pragma unroll
    for (int k = 0; k < 4 * KPS; k++) {
        const uint64_t a = da + (k >> 2) * (BM * 8) + (k & 3) * 2, b = db + k * 128;
        if constexpr (BN == 256) wgmma_n256(acc, a, b, first && k == 0 ? 0 : 1);
        else if constexpr (BN == 128) wgmma_n128(acc, a, b, first && k == 0 ? 0 : 1);
        else wgmma_n64(acc, a, b, first && k == 0 ? 0 : 1);
    }
    wg_commit();
}

__device__ __forceinline__ void kv_store_unit(const uint32_t (&pk)[64], int u, bf16* dst, int t) {
    const int G = (u >> 2) * 2 + (u & 1), hh = (u >> 1) & 1;
    uint32_t r0 = pk[(4 * G + 0) * 2 + hh], r1 = pk[(4 * G + 1) * 2 + hh], r2 = pk[(4 * G + 2) * 2 + hh], r3 = pk[(4 * G + 3) * 2 + hh];
    quad_transpose(r0, r1, r2, r3, t);
#define KVST ".cs"
    asm volatile("st.global" KVST ".v4.u32 [%0], {%1,%2,%3,%4};" ::"l"(dst + (size_t)hh * 8 * 8192 + G * 32), "r"(r0), "r"(r1), "r"(r2), "r"(r3) : "memory");
}

#define TLK(slot)
__device__ __forceinline__ uint32_t near_page(int pair, int line) {
    uint32_t best[2] = {~0u, ~0u};
#pragma unroll 1
    for (int i = 0; i < 16; i++) {
        uint32_t t0, t1, v;
        asm volatile("mov.u32 %0, %%clock;" : "=r"(t0)::"memory");
        asm volatile("atom.relaxed.gpu.global.or.b32 %0, [%1], -1;" : "=r"(v) : "l"(g_x + pair * 1024 + (i & 1) * 512 + line * 16) : "memory");
        asm volatile("{\n.reg .pred p;\nsetp.ne.u32 p, %1, 0x12345;\nmov.u32 %0, -1;\n@p mov.u32 %0, %%clock;\n}" : "=r"(t1) : "r"(v) : "memory");
        if (i & 1) best[1] = min(best[1], t1 - t0); else best[0] = min(best[0], t1 - t0);
    }
    return best[1] < best[0];
}
__device__ __forceinline__ void map_pages(int c) {
    uint32_t smid;
    asm("mov.u32 %0, %%smid;" : "=r"(smid));
    const uint32_t side = near_page(0, c & 31);
    g_side[smid & 255] = side;
    for (int p = c; p < XPAIRS; p += 132) g_home[p] = near_page(p, 0) ^ side;
}

__global__ void __launch_bounds__(384, 1)
k_kv(const __grid_constant__ CUtensorMap mx, const __grid_constant__ CUtensorMap mwk, const __grid_constant__ CUtensorMap mwv,
     const bf16* __restrict__ Wq, const bf16* __restrict__ Wk, const bf16* __restrict__ Wo, int c0) {
    extern __shared__ __align__(1024) uint8_t smem_gemm[];
    const int c = c0 + blockIdx.x;
    if (c == 128) {
        if (threadIdx.x < 256) g_flag[threadIdx.x] = 0;
        __threadfence();
        __syncthreads();
    }
    asm volatile("griddepcontrol.launch_dependents;");
    if (threadIdx.x == 0) TLK(0);
    if (c >= 128) {
        const int i0 = (c - 128) * 384 + threadIdx.x;
        const uint4 ones = make_uint4(~0u, ~0u, ~0u, ~0u);
        if (threadIdx.x == 32) map_pages(c);
        for (int i = i0; i < XPAIRS * 512; i += 4 * 384) reinterpret_cast<uint4*>(g_x)[i] = ones;
        if (threadIdx.x == 0) TLK(1);
        asm volatile("griddepcontrol.wait;" ::: "memory");
        return;
    }
    GemmSmem g = gemm_setup(smem_gemm, 2);
    const int m0 = (c & 15) * 128, nb0 = c >> 4;
    const int wg = __shfl_sync(~0u, threadIdx.x >> 7, 0);
    if (wg == 0) {
        asm volatile("setmaxnreg.dec.sync.aligned.u32 40;");
        if (threadIdx.x == 0) {
            for (int it = 0; it < 64; it++) {
                const int s = it & 3, tile = it >> 4, kb = it & 15;
                mbar_wait(g.empty + 8 * s, ((it >> 2) & 1) ^ 1);
                mbar_expect_tx(g.full + 8 * s, STAGE_BYTES);
                const int nb = nb0 + 8 * tile;
                tma2d(g.st + s * STAGE_BYTES, &mx, kb * 64, m0, g.full + 8 * s);
                tma3d(g.st + s * STAGE_BYTES + 16384, nb < 16 ? &mwk : &mwv, 0, kb * 64, (nb & 15) * 4, g.full + 8 * s);
#define PF0 40
#define PFN 24
#define PFB 4096
                const int pi = it - PF0;
                if (pi >= 0 && pi < PFN) {
                    const uint32_t o = (pi * 128 + c) * PFB;
                    const char* p = (const char*)(o < (8 << 20) ? Wo : o < (16 << 20) ? Wq : Wk) + (o & ((8 << 20) - 1));
                    asm volatile("cp.async.bulk.prefetch.L2.global [%0], %1;" ::"l"(p), "n"(PFB) : "memory");
                }
            }
        } else if (threadIdx.x == 32) map_pages(c);
    } else {
        asm volatile("setmaxnreg.inc.sync.aligned.u32 232;");
        const int cw = wg - 1, lane = threadIdx.x & 31, t = lane & 3;
        const int row = m0 + cw * 64 + ((threadIdx.x >> 5) & 3) * 16 + (lane >> 2);
        bf16* dst = g_kv + (size_t)row * 8192 + nb0 * 256 + t * 8;
        float acc[128];
        uint32_t pk[64];
#pragma unroll 1
        for (int tile = 0; tile < 4; tile++) {
#pragma unroll
            for (int kb = 0; kb < 16; kb++) {
                mbar_wait_u(g.full + 8 * (kb & 3), (kb >> 2) & 1);
                gemm_stage<128, 256, 1>(acc, g.st + (kb & 3) * STAGE_BYTES, cw, kb == 0);
                if (tile > 0) kv_store_unit(pk, kb, dst + (tile - 1) * 2048, t);
                if (kb > 0) {
                    wg_wait<1>();
                    mbar_arrive_one(g.empty + 8 * ((kb - 1) & 3), threadIdx.x & 127);
                }
            }
            wg_wait<0>();
            mbar_arrive_one(g.empty + 8 * 3, threadIdx.x & 127);
#pragma unroll
            for (int i = 0; i < 64; i++) pk[i] = pack2(acc[2 * i], acc[2 * i + 1]);
        }
        if (threadIdx.x == 128) TLK(2);
#pragma unroll
        for (int u = 0; u < 16; u++) kv_store_unit(pk, u, dst + 3 * 2048, t);
        if (threadIdx.x == 128) TLK(1);
        asm volatile("griddepcontrol.wait;" ::: "memory");
    }
}

constexpr int NS1 = 31;
#define RB1 4
#define PFC 4
constexpr int C_W1 = 0;
constexpr int C_W2 = C_W1 + 8 * NS1 * 512;
constexpr int C_KV = C_W2 + 14 * 8 * 512;
constexpr int C_RED = C_KV + 16384;
constexpr int C_QKV = C_RED + 64 * 272;
constexpr int C_SC = C_RED;
constexpr int C_OB = C_SC + 2 * 8 * 52 * 4;
constexpr int C_BAR = C_QKV + 3 * 8 * 272;
__host__ __device__ constexpr int smem_idx(int ks, int j) {
    return ks == 0 ? j : ks < 3 ? (j < 4 ? 4 + 4 * ks + j : -1) : (j < 3 ? 7 + 3 * ks + j : -1);
}
constexpr int CHAIN_SMEM = C_BAR + 64;
#define TS(i)

#define DLY3 8
#define DLY1 2
#define DLY0 2
#define DLY1A 10
#define DLY0A DLY0
#define DLYW 3
template <int N> __device__ __forceinline__ uint32_t delayed(uint32_t x, int lane) {
#pragma unroll
    for (int i = 0; i < N; i++) asm volatile("shfl.sync.idx.b32 %0, %0, %1, 31, -1;" : "+r"(x) : "r"(lane) : "memory");
    return x;
}
__device__ __forceinline__ void lds128v(uint32_t (&r)[4], uint32_t a) {
    asm volatile("ld.volatile.shared.v4.u32 {%0,%1,%2,%3}, [%4];" : "=r"(r[0]), "=r"(r[1]), "=r"(r[2]), "=r"(r[3]) : "r"(a) : "memory");
}
__device__ __forceinline__ uint2 lds64(uint32_t a) {
    uint2 v;
    asm volatile("ld.shared.v2.u32 {%0,%1}, [%2];" : "=r"(v.x), "=r"(v.y) : "r"(a) : "memory");
    return v;
}
#define LDQ ".L1::no_allocate"
__device__ __forceinline__ uint4 ldw128(const void* p) {
    uint4 v;
    asm volatile("ld.global.nc" LDQ ".v4.u32 {%0,%1,%2,%3}, [%4];" : "=r"(v.x), "=r"(v.y), "=r"(v.z), "=r"(v.w) : "l"(p));
    return v;
}
#define P8_LD(i) "ld.relaxed.gpu.global.b64 d" #i ", [src + " #i " * 256];\n"
#define P8_X(i) "mov.b64 {x" #i ", y" #i "}, d" #i ";\n"
#define P8_HEAD(SRC) "{\n.reg .pred p, q;\n.reg .b64 src, d<8>;\n.reg .b32 n, x<8>, y<8>, m0, m1;\nmov.b64 src, " SRC ";\n"         \
                P8_LD(0) P8_LD(1) P8_LD(2) P8_LD(3) P8_LD(4) P8_LD(5) P8_LD(6) P8_LD(7) "mov.u32 n, 0;\nCHECK:\n" \
                P8_X(0) P8_X(1) P8_X(2) P8_X(3) P8_X(4) P8_X(5) P8_X(6) P8_X(7)
#define P8_VOTE "vote.sync.all.pred p, p, -1;\n@p bra.uni DONE;\n"
#define P8_TAIL "add.u32 n, n, 1;\nsetp.lt.u32 p, n, 0x100000;\n@p bra.uni CHECK;\ntrap;\nDONE:\n"
__device__ __forceinline__ void poll_state(uint2 (&v)[8], const void* src) {
#define P8_RS(i) "setp.eq.u32 q, x" #i ", 0xffffffff;\n@q " P8_LD(i)
#define P8_O(i) "mov.b64 %" #i ", d" #i ";\n"
    uint64_t d[8];
    asm volatile(P8_HEAD("%8") "max.u32 m0, x0, x1;\nmax.u32 m0, m0, x2;\nmax.u32 m1, x3, x4;\nmax.u32 m1, m1, x5;\nmax.u32 m0, m0, x6;\n"
                 "max.u32 m0, m0, x7;\nmax.u32 m0, m0, m1;\nsetp.ne.u32 p, m0, 0xffffffff;\n" P8_VOTE
                 P8_RS(0) P8_RS(1) P8_RS(2) P8_RS(3) P8_RS(4) P8_RS(5) P8_RS(6) P8_RS(7) P8_TAIL
                 P8_O(0) P8_O(1) P8_O(2) P8_O(3) P8_O(4) P8_O(5) P8_O(6) P8_O(7) "}"
                 : "=l"(d[0]), "=l"(d[1]), "=l"(d[2]), "=l"(d[3]), "=l"(d[4]), "=l"(d[5]), "=l"(d[6]), "=l"(d[7]) : "l"(src) : "memory");
#pragma unroll
    for (int i = 0; i < 8; i++) { v[i].x = (uint32_t)d[i]; v[i].y = (uint32_t)(d[i] >> 32); }
}
__device__ __forceinline__ uint64_t poll_sum(const void* src, uint32_t tag, uint32_t sel) {
#define P8_RT(i) "lop3.b32 m0, x" #i ", %2, 1, 0x28;\nsetp.ne.u32 q, m0, 0;\n@q " P8_LD(i)
#define P8_MMA(c, i, z) "mma.sync.aligned.m16n8k8.row.col.f32.bf16.bf16.f32 {" #c "0," #c "1," #c "2," #c "3}, {x" #i ", y" #i "}, {%3}, {" #z "0," #z "1," #z "2," #z "3};\n"
    uint64_t r;
    asm volatile(P8_HEAD("%1") "{\n.reg .f32 a<4>, b<4>, z<4>;\nmov.f32 z0, 0f00000000;\nmov.f32 z1, z0;\nmov.f32 z2, z0;\nmov.f32 z3, z0;\n"
                 P8_MMA(a, 0, z) P8_MMA(b, 1, z) P8_MMA(a, 2, a) P8_MMA(b, 3, b) P8_MMA(a, 4, a) P8_MMA(b, 5, b) P8_MMA(a, 6, a) P8_MMA(b, 7, b)
                 "add.f32 a0, a0, b0;\nadd.f32 a1, a1, b1;\nadd.f32 a2, a2, b2;\nadd.f32 a3, a3, b3;\n"
                 "cvt.rn.bf16x2.f32 m0, a1, a0;\ncvt.rn.bf16x2.f32 m1, a3, a2;\nmov.b64 %0, {m0, m1};\n}\n"
                 "lop3.b32 m0, x0, x1, %2, 0x7e;\nlop3.b32 m1, x2, x3, %2, 0x7e;\nlop3.b32 m0, m0, x4, %2, 0xf6;\n"
                 "lop3.b32 m1, m1, x5, %2, 0xf6;\nlop3.b32 m0, m0, x6, %2, 0xf6;\nlop3.b32 m1, m1, x7, %2, 0xf6;\n"
                 "lop3.b32 m0, m0, m1, 1, 0xa8;\nsetp.eq.u32 p, m0, 0;\n" P8_VOTE
                 P8_RT(0) P8_RT(1) P8_RT(2) P8_RT(3) P8_RT(4) P8_RT(5) P8_RT(6) P8_RT(7) P8_TAIL "}"
                 : "=&l"(r) : "l"(src), "r"(tag), "r"(sel) : "memory");
    return r;
}
__device__ __forceinline__ void sum8(float (&c)[4], const uint2 (&v)[8], uint32_t idn) {
    float d[4] = {0.f, 0.f, 0.f, 0.f};
    c[0] = c[1] = c[2] = c[3] = 0.f;
    mma16816(c, v[0].x, v[0].y, v[1].x, v[1].y, idn, idn);
    mma16816(d, v[2].x, v[2].y, v[3].x, v[3].y, idn, idn);
    mma16816(c, v[4].x, v[4].y, v[5].x, v[5].y, idn, idn);
    mma16816(d, v[6].x, v[6].y, v[7].x, v[7].y, idn, idn);
    c[0] += d[0]; c[1] += d[1]; c[2] += d[2]; c[3] += d[3];
}

#define CLS 6
__global__ void __cluster_dims__(CLS, 1, 1) __launch_bounds__(256, 1)
k_chain(const bf16* __restrict__ mem0, const bf16* __restrict__ Wq, const bf16* __restrict__ Wk, const bf16* __restrict__ Wv,
        const bf16* __restrict__ Wo, const __grid_constant__ CUtensorMap mkv) {
    extern __shared__ __align__(1024) uint8_t smem_chain[];
    const uint32_t sb = smem_u32(smem_chain);
    if (sb & 1023) __trap();
    const int w = __shfl_sync(~0u, threadIdx.x >> 5, 0), lane = __shfl_sync(~0u, threadIdx.x & 31, threadIdx.x & 31);
    const int tid = w * 32 + lane, g = lane >> 2, t = lane & 3;
    auto pin = [&](uint32_t x) { return delayed<1>(x, lane); };
    const int h = blockIdx.x / 3, r = blockIdx.x - 3 * h;
    const uint32_t bar_x = sb + C_BAR, bar_kv = sb + C_BAR + 8, bar_go = sb + C_BAR + 16, bar_w = sb + C_BAR + 24;
    asm volatile("griddepcontrol.launch_dependents;");
    const int tbase = r == 0 ? 0 : 1 + 21 * r, ntile = r == 0 ? 22 : 21;
    uint32_t side;
    if (tid == 0) {
        mbar_init(bar_x, 8); mbar_init(bar_kv, 1); mbar_init(bar_go, 1); mbar_init(bar_w, 1);
        asm volatile("fence.mbarrier_init.release.cluster;" ::: "memory");
        asm volatile("fence.proxy.async.shared::cta;" ::: "memory");
        mbar_expect_tx(bar_w, 128 * 32 * ntile);
    }
    __syncthreads();
    asm volatile("barrier.cluster.arrive.relaxed.aligned;" ::: "memory");
    if (tid < 128)
        asm volatile("cp.async.bulk.shared::cluster.global.mbarrier::complete_tx::bytes [%0], [%1], %2, [%3];"
                     ::"r"(sb + C_W1 + tid * 720), "l"(Wo + (size_t)(h * 128 + tid) * DM + tbase * 16), "r"(32 * ntile), "r"(bar_w) : "memory");
    const int tile0 = tbase + 7 - w;
    const bool three = w >= (r == 0 ? 2 : 3);
    const uint32_t wa = pin(sb + tid * 16);
#define W1A(i) (wa + C_W1 + (i) * 4096)
#define W2A(x) (wa + C_W2 + ((x) < 8 ? (x) * 4096 : 32768 - 1024 + ((x) - 8) * 3072))
    uint32_t wo0[8][4], wr[64][4];
    {
        const bf16* W = (r == 0 ? Wq : r == 1 ? Wk : Wv) + (size_t)(128 * w + (lane >> 4)) * HD + h * 128 + 8 * (lane & 15);
        uint4 raw[8][8];
        auto fetch = [&](int ks) {
#pragma unroll
            for (int i = 0; i < 8; i++) raw[ks][i] = ldw128(W + (size_t)(16 * ks + 2 * i) * HD);
        };
        fetch(0); fetch(1); fetch(2); fetch(3);
    asm("mov.u32 %0, %%smid;" : "=r"(side));
    side = ld_acq32(g_side + (side & 255)) & 1;
    if (tid == 0 && r > 0) asm volatile("st.relaxed.gpu.global.u32 [%0], %1;" ::"l"(g_flag + 128 + 2 * h + r - 1), "r"(2 | side) : "memory");
        mbar_wait_u(bar_w, 0);
        const uint32_t p = sb + C_W1 + ((lane & 7) + (lane >> 4) * 8) * 720 + (7 - w) * 32 + ((lane >> 3) & 1) * 16;
#pragma unroll
        for (int ks = 0; ks < 8; ks++) {
            uint32_t a[4];
            ldsm4t(wo0[ks], p + ks * 16 * 720);
            ldsm4t(a, p + ks * 16 * 720 + 256);
            sts128(W2A(ks), a[0], a[1], a[2], a[3]);
            if (three) { ldsm4t(a, p + ks * 16 * 720 + 512); sts128(W2A(8 + ks), a[0], a[1], a[2], a[3]); }
        }
        __syncthreads();
        const uint32_t stg = sb + C_KV + w * 4096;
        const uint32_t rd = stg + ((lane & 7) + 8 * (lane >> 4)) * 256 + ((((lane >> 3) & 1) ^ (lane & 7)) << 4);
#pragma unroll
        for (int ks = 0; ks < 8; ks++) {
#pragma unroll
            for (int i = 0; i < 8; i++)
                sts128(stg + (2 * i + (lane >> 4)) * 256 + (((lane & 15) ^ (((2 * i) & 6) | (lane >> 4))) << 4),
                       raw[ks][i].x, raw[ks][i].y, raw[ks][i].z, raw[ks][i].w);
            if (ks < 2) fetch(ks + 4);
            if (ks == 3 || ks == 5) fetch(ks / 2 + 5);
            __syncwarp();
#pragma unroll
            for (int j = 0; j < 8; j++) {
                if (smem_idx(ks, j) >= 0) {
                    uint32_t a[4];
                    ldsm4t(a, rd ^ (j << 5));
                    sts128(W1A(smem_idx(ks, j)), a[0], a[1], a[2], a[3]);
                } else ldsm4t(wr[8 * ks + j], rd ^ (j << 5));
            }
            __syncwarp();
        }
    }
    asm volatile("griddepcontrol.wait;\nfence.proxy.async.shared::cta;" ::: "memory");
    __syncthreads();
    if (tid == 0) {
        mbar_expect_tx(bar_kv, 16384);
        tma3d(sb + C_KV, &mkv, 0, 0, 2 * h, bar_kv);
        tma3d(sb + C_KV + 8192, &mkv, 0, 0, 64 + 2 * h, bar_kv);
    }
    asm volatile("barrier.cluster.wait.aligned;" ::: "memory");

    auto publish_kvm = [&](int s) {
        uint32_t v[4];
        lds128(v, sb + C_QKV + (8 + (tid >> 4)) * 272 + (tid & 15) * 16);
        asm volatile("st.global.v4.u32 [%0], {%1,%2,%3,%4};"
                     ::"l"(g_kvm + (size_t)(s * 8 + ((tid >> 4) & 7)) * 8192 + (tid >> 7) * HD + h * 128 + (tid & 15) * 8),
                       "r"(v[0]), "r"(v[1]), "r"(v[2]), "r"(v[3]) : "memory");
        if (h == 0 && w == 6) asm volatile("st.relaxed.gpu.global.u32 [%0], %1;" ::"l"(g_flag + 98), "r"(s + 1) : "memory");
        if ((s & 3) == 3) {
            __syncthreads();
            if (w == 7) asm volatile("{\n.reg .pred p;\nsetp.eq.u32 p, %2, 0;\nfence.acq_rel.gpu;\n@p st.relaxed.gpu.global.u32 [%0], %1;\n}"
                                     ::"l"(g_flag + h), "r"(s + 1), "r"(lane) : "memory");
        }
    };
    const float sl2e = 0.08838834764831845f * 1.4426950408889634f;
    const uint32_t idn = pin(g == 2 * t ? 0x00003f80u : g == 2 * t + 1 ? 0x3f800000u : 0u);
    const uint32_t lm = pin(sb + (lane & 7) * 272 + (lane >> 3) * 16);
    const uint32_t sa = pin(sb + C_SC + (w & 1) * (8 * 52 * 4) + (2 * t * 52 + (w < 4 ? 32 : (w & 2) * 8) + g) * 4);
    const uint32_t sr = pin(sb + C_SC + (g * 52 + 8 * t) * 4), sr2 = pin(sb + C_SC + (g * 52 + 32 + 2 * t) * 4);
    uint32_t kva;
    {
        const int pos = (w & 2) * 8 + (lane & 15), row = (pos & 24) + ((pos + (pos >> 2 & 6)) & 7);
        const int key = 4 * (lane & 6) + (((lane & 7) + 2 * (lane >> 4)) & 7);
        kva = pin(w >= 4 ? sb + C_KV + (w & 1) * 4096 + row * 128 + (((lane >> 4) ^ (row & 7)) << 4)
                         : sb + C_KV + 8192 + (w >> 1) * 4096 + key * 128 + ((((w & 1) * 4 + ((lane >> 3) & 1)) ^ (key & 7)) << 4));
    }
    uint32_t buf0[8][4], ring[RB1][4];
    auto stage_w1 = [&]() {
#pragma unroll
        for (int i = 0; i < 8; i++) lds128v(buf0[i], W1A(i));
#pragma unroll
        for (int i = 0; i < RB1; i++) lds128v(ring[i], W1A(8 + i));
    };
    stage_w1();
    uint32_t psel, msel0, msel1;
    {
        const int j = r > 0 ? 2 * h + r - 1 : 0, tl = min(tile0 + 8 * (lane >> 1), 63);
        uint32_t b;
        asm volatile("{\n.reg .pred p;\n.reg .u32 n;\nmov.u32 n, 0;\nAGAIN:\nld.relaxed.gpu.global.u32 %0, [%1];\nsetp.ne.u32 p, %0, 0;\n"
                     "vote.sync.all.pred p, p, -1;\n@p bra.uni DONE;\nadd.u32 n, n, 1;\nsetp.lt.u32 p, n, 0x100000;\n@p bra.uni AGAIN;\ntrap;\nDONE:\n}"
                     : "=&r"(b) : "l"(g_flag + 128 + tl) : "memory");
        psel = __ballot_sync(~0u, (g_home[lane == 6 ? j * 2 + ((w >> 1) & 1) : tl * 2 + (lane & 1)] ^ (lane == 6 ? side : b)) & 1);
        msel0 = __ballot_sync(~0u, (g_home[128 + lane * 4 + (w >> 1)] ^ side) & 1);
        msel1 = __ballot_sync(~0u, (g_home[256 + lane * 4 + (w >> 1)] ^ side) & 1);
        if (r > 0) {
            if (w < 4) asm volatile("prefetch.global.L2 [%0];" ::"l"(g_x + (128 + (1 + (w >> 1)) * 4 + (j >> 4)) * 1024 + (w & 1) * 512 + (j & 15) * 32 + lane) : "memory");
            if (w < 4) asm volatile("prefetch.global.L2 [%0];" ::"l"(g_x + j * 2048 + tid * 16) : "memory");
        }
    }
    uint2 bm[8];
#pragma unroll
    for (int ks = 0; ks < 8; ks++) {
        const uint32_t* p = (const uint32_t*)(mem0 + g * DM + (8 * w + ks) * 16) + t;
        bm[ks] = make_uint2(__ldg(p), __ldg(p + 4));
    }
    mbar_wait_u(bar_kv, 0);
    if (tid == 0) TL(1, 2);
#pragma unroll 1
    for (int s = 0;; s++) {
        TS(1);
        {
            float acc[8][4];
#pragma unroll
            for (int ks = 0; ks < 8; ks++) {
#pragma unroll
                for (int j = 0; j < 8; j++) {
                    const int i = smem_idx(ks, j) - 8;
                    if (ks == 0) {
                        acc[j][0] = acc[j][1] = acc[j][2] = acc[j][3] = 0.f;
                        mma16816(acc[j], buf0[j][0], buf0[j][1], buf0[j][2], buf0[j][3], bm[ks].x, bm[ks].y);
                    } else if (i >= 0) {
                        uint32_t(&a)[4] = ring[i % RB1];
                        mma16816(acc[j], a[0], a[1], a[2], a[3], bm[ks].x, bm[ks].y);
                        if (8 + i + RB1 < NS1) lds128v(a, W1A(8 + i + RB1));
                    } else {
                        const uint32_t(&a)[4] = wr[8 * ks + j];
                        mma16816(acc[j], a[0], a[1], a[2], a[3], bm[ks].x, bm[ks].y);
                    }
                }
            }
#pragma unroll
            for (int c = 0; c < 4; c++)
                stsm4t(lm + C_RED + w * 2176 + c * 64, pack2(acc[2 * c][0], acc[2 * c][1]), pack2(acc[2 * c][2], acc[2 * c][3]),
                       pack2(acc[2 * c + 1][0], acc[2 * c + 1][1]), pack2(acc[2 * c + 1][2], acc[2 * c + 1][3]));
        }
        {
            const uint32_t a = sb + C_RED + w * 272 + lane * 8;
            TS(2);
            __syncthreads();
            TS(3);
            uint2 v[8];
#pragma unroll
            for (int i = 0; i < 8; i++) v[i] = lds64(a + i * 2176);
            float c[4];
            sum8(c, v, idn);
            const uint32_t p0 = pack2(c[0], c[1]), p1 = pack2(c[2], c[3]);
            const uint32_t dst = sb + C_QKV + (r * 8 + w) * 272 + lane * 8;
#pragma unroll
            for (int i = 1; i < 3; i++) {
                const uint32_t peer = (h % (CLS / 3)) * 3 + (r + i >= 3 ? r + i - 3 : r + i);
                uint32_t rd, rb;
                asm("mapa.shared::cluster.u32 %0, %1, %2;" : "=r"(rd) : "r"(dst), "r"(peer));
                asm("mapa.shared::cluster.u32 %0, %1, %2;" : "=r"(rb) : "r"(bar_x), "r"(peer));
                asm volatile("st.async.weak.shared::cluster.mbarrier::complete_tx::bytes.v2.b32 [%0], {%1,%2}, [%3];"
                             ::"r"(rd), "r"(p0), "r"(p1), "r"(rb) : "memory");
            }
            sts64(dst, p0, p1);
            __syncwarp();
            asm volatile("{\n.reg .pred p;\nsetp.eq.u32 p, %1, 0;\n@p mbarrier.arrive.expect_tx.shared::cta.b64 _, [%0], 512;\n}"
                         ::"r"(bar_x), "r"(lane) : "memory");
        }
        TS(4);
        if (s == NSEG - 1) break;
        uint32_t wb[8][4], wc[8][4];
        const uint32_t po = (tile0 * 2 + (lane >> 4)) * 8192 + ((lane >> 3) & 1) * 2048 + h * 64 + (lane & 7) * 8;
        const uint32_t tag = s & 1;
        auto project = [&](const uint32_t(&wt)[8][4], const uint32_t(&ob)[4][4], int i) {
            float c0[4] = {0.f, 0.f, 0.f, 0.f}, c1[4] = {0.f, 0.f, 0.f, 0.f};
#pragma unroll
            for (int ks = 0; ks < 8; ks++)
                mma16816((ks & 1) ? c1 : c0, wt[ks][0], wt[ks][1], wt[ks][2], wt[ks][3], ob[ks >> 1][(ks & 1) * 2], ob[ks >> 1][(ks & 1) * 2 + 1]);
            uint32_t p0 = pack2(c0[0] + c1[0], c0[1] + c1[1]), p1 = pack2(c0[2] + c1[2], c0[3] + c1[3]);
            asm volatile("movmatrix.sync.aligned.m8n8.trans.b16 %0, %0;\nmovmatrix.sync.aligned.m8n8.trans.b16 %1, %1;" : "+r"(p0), "+r"(p1));
            st_rlx64((uint2*)((char*)g_x + po + i * 131072 + ((psel >> (2 * i + (lane >> 4))) & 1) * 4096), (p0 & ~1u) | tag, p1);
        };
        if (w >= 4) {
            uint32_t ka[4][4];
#pragma unroll
            for (int ks = 0; ks < 4; ks++) ldsm4(ka[ks], kva ^ (ks << 5));
            const uint32_t qa = lm + C_QKV + (w & 1) * 128;
            TS(5);
            mbar_wait_u(bar_x, s & 1);
            TS(6);
            {
                uint32_t qb[2][4];
                ldsm4(qb[0], qa);
                ldsm4(qb[1], qa + 64);
                float c0[4] = {0.f, 0.f, 0.f, 0.f}, c1[4] = {0.f, 0.f, 0.f, 0.f};
                mma16816(c0, ka[0][0], ka[0][1], ka[0][2], ka[0][3], qb[0][0], qb[0][1]);
                mma16816(c1, ka[1][0], ka[1][1], ka[1][2], ka[1][3], qb[0][2], qb[0][3]);
                mma16816(c0, ka[2][0], ka[2][1], ka[2][2], ka[2][3], qb[1][0], qb[1][1]);
                mma16816(c1, ka[3][0], ka[3][1], ka[3][2], ka[3][3], qb[1][2], qb[1][3]);
                sts32f(sa, c0[0] + c1[0]);
                sts32f(sa + 208, c0[1] + c1[1]);
                sts32f(sa + 32, c0[2] + c1[2]);
                sts32f(sa + 240, c0[3] + c1[3]);
            }
            __syncthreads();
            TS(7);
            if (w == 7 && s + 1 < NSEG - 1) {
                if (lane == 0) {
                    mbar_expect_tx(bar_kv, 16384);
                    tma3d(sb + C_KV, &mkv, 0, (s + 1) * 32, 2 * h, bar_kv);
                    tma3d(sb + C_KV + 8192, &mkv, 0, (s + 1) * 32, 64 + 2 * h, bar_kv);
                }
                __syncwarp();
            }
            const uint32_t wd = delayed<DLYW>(wa, lane);
#pragma unroll
            for (int i = 0; i < 8; i++) lds128(wb[i], wd + C_W2 + i * 4096);
#pragma unroll
            for (int i = 0; i < PFC; i++) lds128(wc[i], wd + C_W2 + 32768 - 1024 + i * 3072);
            TS(8);
            __syncthreads();
            TS(9);
            uint32_t ob[4][4];
#pragma unroll
            for (int i = 0; i < 4; i++) ldsm4(ob[i], lm + C_OB + i * 64);
#pragma unroll
            for (int i = PFC; i < 8; i++) lds128(wc[i], W2A(8 + i));
            project(wb, ob, 1);
            project(wo0, ob, 0);
            project(wc, ob, 2);
        } else {
            uint32_t va[4][4];
#pragma unroll
            for (int i = 0; i < 4; i++) ldsm4t(va[i], kva ^ (((i >> 1) << 5) | ((i & 1) * 0x240)));
#pragma unroll
            for (int i = 0; i < 8; i++) lds128(wb[i], W2A(i));
            const uint32_t qa = lm + C_QKV + (w & 1) * 128, oa = lm + w * 64;
            TS(5);
            mbar_wait_u(bar_x, s & 1);
            TS(6);
            if (w < 2) {
                uint32_t qb[2][4], km[2][4];
                ldsm4(qb[0], qa);
                ldsm4(km[0], qa + 8 * 272);
                ldsm4(qb[1], qa + 64);
                ldsm4(km[1], qa + 8 * 272 + 64);
                float c0[4] = {0.f, 0.f, 0.f, 0.f}, c1[4] = {0.f, 0.f, 0.f, 0.f};
                mma16816(c0, km[0][0], km[0][1], km[0][2], km[0][3], qb[0][0], qb[0][2]);
                mma16816(c1, km[0][0], km[0][1], km[0][2], km[0][3], qb[0][1], qb[0][3]);
                mma16816(c0, km[1][0], km[1][1], km[1][2], km[1][3], qb[1][0], qb[1][2]);
                mma16816(c1, km[1][0], km[1][1], km[1][2], km[1][3], qb[1][1], qb[1][3]);
                sts32f(sa, c0[0] + c1[2]);
                sts32f(sa + 208, c0[1] + c1[3]);
            }
            __syncthreads();
            TS(7);
            {
                float4 x0 = lds128f(sr), y0 = lds128f(sr + 1664), x1 = lds128f(sr + 16), y1 = lds128f(sr + 1680);
                float2 x2 = lds64f(sr2), y2 = lds64f(sr2 + 1664);
                float p[10] = {x0.x + y0.x, x0.y + y0.y, x0.z + y0.z, x0.w + y0.w, x1.x + y1.x,
                               x1.y + y1.y, x1.z + y1.z, x1.w + y1.w, x2.x + y2.x, x2.y + y2.y};
                float m = fmaxf(fmaxf(fmaxf(p[0], p[1]), fmaxf(p[2], p[3])), fmaxf(fmaxf(fmaxf(p[4], p[5]), fmaxf(p[6], p[7])), fmaxf(p[8], p[9])));
                const float m1 = __shfl_xor_sync(~0u, m, 1), m2 = __shfl_xor_sync(~0u, m, 2), m3 = __shfl_xor_sync(~0u, m, 3);
                uint32_t vm[4];
                ldsm4t(vm, oa + C_QKV + 16 * 272);
                m = fmaxf(fmaxf(m, m1), fmaxf(m2, m3));
                const float ms = m * sl2e;
#pragma unroll
                for (int i = 0; i < 10; i++) p[i] = ex2(fmaf(p[i], sl2e, -ms));
                const uint32_t b0 = pack2(p[0], p[1]), b1 = pack2(p[2], p[3]), b2 = pack2(p[4], p[5]), b3 = pack2(p[6], p[7]), b4 = pack2(p[8], p[9]);
                const uint32_t one = 0x3f803f80u;
                float o0[4] = {0.f, 0.f, 0.f, 0.f}, o1[4] = {0.f, 0.f, 0.f, 0.f}, sm[4] = {0.f, 0.f, 0.f, 0.f};
                mma16816(sm, one, one, one, one, b0, b1);
                mma16816(o0, va[0][0], va[0][1], va[0][2], va[0][3], b0, b1);
                mma16816(o1, va[2][0], va[2][1], va[2][2], va[2][3], b0, b1);
                mma16816(sm, one, one, one, one, b2, b3);
                mma16816(o0, va[1][0], va[1][1], va[1][2], va[1][3], b2, b3);
                mma16816(o1, va[3][0], va[3][1], va[3][2], va[3][3], b2, b3);
                mma1688(sm, one, one, b4);
                mma1688(o0, vm[0], vm[1], b4);
                mma1688(o1, vm[2], vm[3], b4);
                float i0, i1;
                asm("rcp.approx.ftz.f32 %0, %1;" : "=f"(i0) : "f"(sm[0]));
                asm("rcp.approx.ftz.f32 %0, %1;" : "=f"(i1) : "f"(sm[1]));
                stsm4t(oa + C_OB, pack2(o0[0] * i0, o0[1] * i1), pack2(o0[2] * i0, o0[3] * i1),
                       pack2(o1[0] * i0, o1[1] * i1), pack2(o1[2] * i0, o1[3] * i1));
            }
            TS(8);
            __syncthreads();
            TS(9);
            uint32_t ob[4][4];
#pragma unroll
            for (int i = 0; i < 4; i++) ldsm4(ob[i], lm + C_OB + i * 64);
            if (three) {
#pragma unroll
                for (int i = 0; i < 8; i++) lds128(wc[i], W2A(8 + i));
                project(wb, ob, 1);
                project(wo0, ob, 0);
                project(wc, ob, 2);
            } else {
                project(wb, ob, 1);
                project(wo0, ob, 0);
            }
        }
        TS(10);
        __syncthreads();
        uint32_t eo = (128 + (s + 1) * 4 + (w >> 1)) * 8192 + (((s < 31 ? msel0 : msel1) >> ((s + 1) & 31)) & 1) * 4096 + (w & 1) * 2048 + lane * 8;
        if (r == 0) {
            TS(11); TS(12);
            stage_w1();
            publish_kvm(s);
            if (s < NSEG - 2) mbar_wait_u(bar_kv, (s + 1) & 1);
            mbar_wait_u(bar_go, s & 1);
            if (w < 4) eo = delayed<DLY0>(eo, lane); else eo = delayed<DLY0A>(eo, lane);
        } else {
            const int j = 2 * h + r - 1;
            if (w < 4) {
                const char* src = (const char*)g_x + delayed<DLY3>((j * 2 + (w >> 1)) * 8192 + (psel & 64) * 64 + (w & 1) * 2048 + t * 64 + g * 8, lane);
                const char* dst = (const char*)g_x + pin((128 + (s + 1) * 4 + (j >> 4)) * 8192 + (j & 15) * 256 + w * 64 + (t & 1) * 4096 + g * 8);
                const uint64_t v = poll_sum(src, tag, (lane & 4) ? 0x3f800000u : 0x00003f80u);
                TS(11);
                asm volatile("st.relaxed.gpu.global.b64 [%0], %1;" ::"l"(dst), "l"(v) : "memory");
                asm volatile("bar.arrive 1, 256;" ::: "memory");
                TS(12);
                stage_w1();
                if (s < NSEG - 2) mbar_wait_u(bar_kv, (s + 1) & 1);
                eo = delayed<DLY1>(eo, lane);
            } else {
                if (w >= 6 && s + 3 < NSEG)
                    asm volatile("prefetch.global.L2 [%0];" ::"l"(g_x + (128 + (s + 3) * 4 + (j >> 4)) * 1024 + (w & 1) * 512 + (j & 15) * 32 + lane) : "memory");
                stage_w1();
                if (s < NSEG - 2) mbar_wait_u(bar_kv, (s + 1) & 1);
                TS(11);
                bar_sync(1, 256);
                TS(12);
                if (w == 4 && r == 1)
                    asm volatile("{\n.reg .pred p;\n.reg .u32 a;\nelect.sync _|p, -1;\nmapa.shared::cluster.u32 a, %0, %1;\n"
                                 "@p mbarrier.arrive.relaxed.cluster.shared::cluster.b64 _, [a];\n}" ::"r"(bar_go), "r"((h % (CLS / 3)) * 3) : "memory");
                eo = delayed<DLY1A>(eo, lane);
            }
        }
        { const int s_ = s; { const int s = s_ + 1; TS(0); } }
        poll_state(bm, (const char*)g_x + eo);
    }
    mbar_wait_u(bar_x, (NSEG - 1) & 1);
    if (r == 0) publish_kvm(NSEG - 1);
    asm volatile("barrier.cluster.arrive.relaxed.aligned;\nbarrier.cluster.wait.aligned;" ::: "memory");
}

constexpr int S4_US = 4368;
constexpr int S4_RS = 8848;
constexpr int S4_KS = 1296;
constexpr int S4_U = 0, S4_R = 16 * S4_US, S4_K = S4_R + 16 * S4_RS;
constexpr int S4_SMEM = S4_K + 16 * S4_KS;
constexpr int S4_SIG = 3104, S4_PK = 2 * S4_SIG;

struct cf { float r, i; };
__device__ __forceinline__ cf cmul(cf a, cf b) { return {fmaf(a.r, b.r, -a.i * b.i), fmaf(a.r, b.i, a.i * b.r)}; }
__device__ __forceinline__ cf cmulc(cf a, cf b) { return {fmaf(a.r, b.r, a.i * b.i), fmaf(a.i, b.r, -a.r * b.i)}; }
__device__ __forceinline__ cf csq(cf a) { const float t = a.r * a.i; return {fmaf(a.r, a.r, -a.i * a.i), t + t}; }
__device__ __forceinline__ cf cexp(float l2, float turns) {
    const float mag = ex2(l2), fr = (turns - rintf(turns)) * 6.283185307179586f;
    return {mag * __cosf(fr), mag * __sinf(fr)};
}
__device__ __forceinline__ void sts32(uint32_t a, uint32_t v) { asm volatile("st.shared.u32 [%0], %1;" ::"r"(a), "r"(v) : "memory"); }
__device__ __forceinline__ uint32_t lds16(uint32_t a) {
    uint32_t v;
    asm volatile("ld.shared.u16 %0, [%1];" : "=r"(v) : "r"(a) : "memory");
    return v;
}

template <int M0, int NQ>
__device__ __forceinline__ void s4_class(float (&acc)[16][4], uint32_t sig, uint32_t taps, int x0) {
    constexpr int D0 = M0 / 8, D1 = M0 == 32 ? 9 : 15;
    uint32_t R[D1 - D0 + 2];
#pragma unroll
    for (int D = D0 - 1; D <= D1; D++) {
        if (D < D0 || 8 * D - 7 >= 2 * M0) { R[D - D0 + 1] = 0; continue; }
        const int m = 8 * D + x0;
        uint32_t lo = lds16(taps + m * (2 * NQ)), hi = lds16(taps + (m - 1) * (2 * NQ));
        if (D == D0) { lo = m >= M0 ? lo : 0; hi = m > M0 ? hi : 0; }
        if (D == 2 * D0) { lo = m < 2 * M0 ? lo : 0; hi = m <= 2 * M0 ? hi : 0; }
        R[D - D0 + 1] = lo | (hi << 16);
    }
#pragma unroll
    for (int J = 0; 2 * J + D0 < 16; J++) {
        uint32_t a[4];
        ldsm4t(a, sig + J * 512);
#pragma unroll
        for (int D = D0; D <= D1; D++)
            if (2 * J + D < 16) mma16816(acc[2 * J + D], a[0], a[1], a[2], a[3], R[D - D0 + 1], R[D - D0]);
    }
}

__global__ void __launch_bounds__(512, 1)
k_s4(const bf16* __restrict__ u, const bf16* __restrict__ Are, const bf16* __restrict__ Aim, const bf16* __restrict__ Bre,
     const bf16* __restrict__ Bim, const bf16* __restrict__ Cre, const bf16* __restrict__ Cim, const bf16* __restrict__ logdt,
     const bf16* __restrict__ Dsk, bf16* __restrict__ out) {
    extern __shared__ __align__(16) uint8_t smem_s4[];
    const uint32_t sb = smem_u32(smem_s4);
    asm volatile("griddepcontrol.launch_dependents;");
    const int tid = threadIdx.x, w = __shfl_sync(~0u, tid >> 5, 0), lane = tid & 31, g = lane >> 2, t = lane & 3;
    if (tid == 0) TL(2, 0);
    const int d0 = blockIdx.x * 16;
    const int d = d0 + (w & 1) + ((w >> 1) & 3) * 4 + (w >> 3) * 2;
    const uint32_t tr_off = (lane & 15), tr_l = (lane >> 4) * 16;
    const uint32_t ur = sb + S4_U + w * S4_US, rs = sb + S4_R + w * S4_RS, kd = sb + S4_K + w * S4_KS;
    if (lane < 16) sts128(ur + lane * 16, 0, 0, 0, 0);
    {
        const int o = d * 128 + lane * 4;
        const uint2 ar = __ldg((const uint2*)(Are + o)), ai = __ldg((const uint2*)(Aim + o)), br = __ldg((const uint2*)(Bre + o));
        const uint2 bi = __ldg((const uint2*)(Bim + o)), cr = __ldg((const uint2*)(Cre + o)), ci = __ldg((const uint2*)(Cim + o));
        const float dt = bf_round(expf(__bfloat162float(logdt[d])));
        const bf16* src = u + (size_t)(w * 128 + g) * DM + d0 + 4 * t;
        float T[5][4];
#pragma unroll
        for (int i = 0; i < 5; i++) T[i][0] = T[i][1] = T[i][2] = T[i][3] = 0.f;
        float klast = 0.f;
        const uint32_t wr_ = rs + lane * 4;
        const uint32_t ra = rs + (lane & 15) * 144 + (lane >> 4) * 16, rb = rs + (16 + (lane & 7)) * 144 + (lane >> 3) * 16;
#pragma unroll 1
        for (int c = 0; c < 4; c++) {
            uint2 v[4];
#pragma unroll
            for (int i = 0; i < 4; i++) v[i] = __ldg((const uint2*)(src + (size_t)(c * 32 + i * 8) * DM));
            auto pick = [&](const uint2& x) { const uint32_t y = c < 2 ? x.x : x.y; return (c & 1) ? bf_hi(y) : bf_lo(y); };
            auto put = [&](int row, cf x) { sts32(wr_ + row * 144, pack2(x.r, x.i)); };
            const float l2 = dt * pick(ar) * 1.4426950408889634f, tu = dt * pick(ai) * 0.15915494309189535f;
            const cf z1 = cexp(l2, tu), z2 = csq(z1), z4 = csq(z2), z8 = csq(z4), z128 = cexp(l2 * 128.f, tu * 128.f);
            cf a = z8;
            sts32(wr_, 0x00003f80u);
            put(1, a);
#pragma unroll
            for (int i = 2; i < 16; i++) { a = cmul(a, z8); put(i, a); }
            cf y = cmul({pick(cr), pick(ci)}, {dt * pick(br), dt * pick(bi)});
            y.i = -y.i;
#pragma unroll
            for (int k = 0; k < 16; k++) {
                const int n = k < 2 ? 8 : k < 4 ? 4 : k < 8 ? 2 : 1;
                const int row = 16 + (k < 2 ? 8 * k : k < 4 ? 8 + 4 * k : k < 8 ? 16 + 2 * k : 24 + k);
                cf x = y;
                put(row, x);
#pragma unroll
                for (int b = 1; b < n; b++) { x = cmulc(x, k < 2 ? z1 : k < 4 ? z2 : z4); put(row + b, x); }
                y = cmulc(y, z128);
            }
            klast += y.r;
            __syncwarp();
#pragma unroll
            for (int kp = 0; kp < 2; kp++) {
                uint32_t A0[4], A1[4];
                ldsm4(A0, ra + kp * 64);
                ldsm4(A1, ra + kp * 64 + 32);
#pragma unroll
                for (int i = 0; i < 5; i++) {
                    uint32_t B[4];
                    ldsm4(B, rb + i * 8 * 144 + kp * 64);
                    mma16816(T[i], A0[0], A0[1], A0[2], A0[3], B[0], B[1]);
                    mma16816(T[i], A1[0], A1[1], A1[2], A1[3], B[2], B[3]);
                }
            }
#pragma unroll
            for (int i = 0; i < 2; i++)
                stsm4t(sb + S4_U + tr_off * S4_US + 256 + (w * 128 + c * 32 + i * 16) * 2 + tr_l, v[2 * i].x, v[2 * i].y, v[2 * i + 1].x, v[2 * i + 1].y);
            __syncwarp();
        }
#pragma unroll
        for (int o2 = 16; o2; o2 >>= 1) klast += __shfl_xor_sync(~0u, klast, o2);
#pragma unroll
        for (int hh = 0; hh < 2; hh++) {
            const int i = g + 8 * hh;
            sts32(kd + (8 * i + 2 * t) * 2, pack2(T[0][2 * hh], T[0][2 * hh + 1]));
            sts32(kd + (128 + 8 * i + 2 * t) * 2, pack2(T[1][2 * hh], T[1][2 * hh + 1]));
            sts32(kd + (256 + 4 * i + 2 * (t & 1) + 64 * (t >> 1)) * 2, pack2(T[2][2 * hh], T[2][2 * hh + 1]));
            sts32(kd + (384 + 2 * i + 32 * t) * 2, pack2(T[3][2 * hh], T[3][2 * hh + 1]));
        }
        asm volatile("stmatrix.sync.aligned.m8n8.x2.trans.shared.b16 [%0], {%1,%2};"
                     ::"r"(kd + 1024 + (lane & 7) * 32 + ((lane >> 3) & 1) * 16), "r"(pack2(T[4][0], T[4][1])), "r"(pack2(T[4][2], T[4][3])) : "memory");
        if (lane == 0) sts32(kd + 1280, pack2(klast, 0.f));
    }
    __syncwarp();
    const uint32_t pk = rs + S4_PK + 64;
    {
#pragma unroll
        for (int i = 0; i < 2; i++) {
            const int x = i * 128 + lane * 4;
            const uint2 c = lds64(kd + x * 2);
            uint32_t p = lds16(kd + x * 2 - 2);
            if (x == 0) p = 0;
            sts128(pk + x * 4, __byte_perm(c.x, p, 0x5410), __byte_perm(c.x, 0, 0x1032), __byte_perm(c.y, c.x, 0x7610), __byte_perm(c.y, 0, 0x1032));
        }
#pragma unroll
        for (int i = 2; i < 4; i++) {
            const int x = i * 128 + lane * 4;
            const uint32_t ab = lds32(kd + 256 + x), c = lds16(kd + 256 + x + 4);
            const uint32_t p = x == 256 ? lds16(kd + 510) : ab;
            sts128(pk + x * 4, __byte_perm(ab, p, 0x5410), __byte_perm(ab, 0, 0x1010), __byte_perm(ab, 0, 0x1032), __byte_perm(c, ab, 0x7610));
        }
        const uint32_t v = lds16(kd + 768), v2 = lds16(kd + 1024);
        if (lane < 24) {
            uint32_t x0 = 0, x1 = 0, x2 = 0, x3 = 0;
            if (lane == 0) { x0 = x1 = x2 = v | (v << 16); x3 = v << 16; }
            if (lane == 12) x3 = v2;
            if (lane == 13) { x0 = v2 | (v2 << 16); x1 = v2 << 16; }
            sts128(lane < 20 ? pk + 2048 + lane * 16 : pk - 64 + (lane - 20) * 16, x0, x1, x2, x3);
        }
        if (lane < 4) sts128(rs + (lane >> 1) * S4_SIG + (lane & 1) * 16, 0, 0, 0, 0);
    }
    __syncthreads();
    float acc[16][4];
#pragma unroll
    for (int i = 0; i < 16; i++) acc[i][0] = acc[i][1] = acc[i][2] = acc[i][3] = 0.f;
    const uint32_t lf = (lane & 7) * 32 + ((lane >> 3) & 1) * 16 + (lane >> 4) * 256;
#pragma unroll
    for (int rg = 3; rg >= 2; rg--) {
#pragma unroll 1
        for (int it = 0; it < (rg == 3 ? 4 : 6); it++) {
            const int n = it * 32 + lane;
            uint32_t x[2][4];
            lds128(x[0], ur + 256 + n * 16 - 16);
            lds128(x[1], ur + 256 + n * 16);
            float e[16], p[15], s[11];
#pragma unroll
            for (int i = 0; i < 8; i++) { e[2 * i] = bf_lo(x[i >> 2][i & 3]); e[2 * i + 1] = bf_hi(x[i >> 2][i & 3]); }
#pragma unroll
            for (int i = 0; i < 15; i++) p[i] = e[i] + e[i + 1];
#pragma unroll
            for (int i = 0; i < 11; i++) s[i] = p[i + 3] + e[i + 5];
            const uint32_t o = rs + 16 + n * 16;
            if (rg == 2) sts128(o, pack2(s[0], s[1]), pack2(s[2], s[3]), pack2(s[4], s[5]), pack2(s[6], s[7]));
#pragma unroll
            for (int i = 0; i < 10; i++) s[i] = p[i + 2] + s[i + 1];
            if (rg == 2) {
                sts64(o + S4_SIG + 8, pack2(s[0], s[1]), pack2(s[2], s[3]));
                sts64(o + S4_SIG + 16, pack2(s[4], s[5]), pack2(s[6], s[7]));
            } else {
#pragma unroll
                for (int i = 0; i < 9; i++) s[i] = p[i + 1] + s[i + 1];
                sts64(o + 8, pack2(s[0], s[1]), pack2(s[2], s[3]));
                sts64(o + 16, pack2(s[4], s[5]), pack2(s[6], s[7]));
#pragma unroll
                for (int i = 0; i < 8; i++) s[i] = p[i] + s[i + 1];
                sts64(o + S4_SIG + 8, pack2(s[0], s[1]), pack2(s[2], s[3]));
                sts64(o + S4_SIG + 16, pack2(s[4], s[5]), pack2(s[6], s[7]));
            }
        }
        __syncwarp();
        if (rg == 3) {
#pragma unroll 1
            for (int q = 1; q <= 2; q++) s4_class<64, 2>(acc, rs + lf + (q == 1 ? 16 : S4_SIG), kd + (384 + q) * 2, g - 2 * t);
        } else {
#pragma unroll 1
            for (int q = 1; q <= 4; q++) s4_class<32, 4>(acc, rs + lf + ((q & 1) ? 0 : S4_SIG) + (q < 3 ? 16 : 0), kd + (256 + q) * 2, g - 2 * t);
        }
        __syncwarp();
    }
    {
        const uint32_t ub = ur + 256 + lf, kb = pk + (g - 2 * t) * 4;
#pragma unroll 1
        for (int j0 = 0; j0 < 8; j0++) {
            uint32_t B[8][4];
#pragma unroll
            for (int i = 0; i < 8; i++) ldsm4(B[i], ub + i * 512 - j0 * 32);
            auto block = [&](int J, uint32_t a) {
                const uint32_t r0 = lds32(a), rp = lds32(a + 32), rm = lds32(a - 32), r3 = lds32(a);
#pragma unroll
                for (int I = J; I < 16; I++)
                    mma16816(acc[I], r0, rp, rm, r3, B[(I - J) >> 1][((I - J) & 1) * 2], B[(I - J) >> 1][((I - J) & 1) * 2 + 1]);
            };
#pragma unroll
            for (int J = 0; J < 4; J++) block(J, kb + j0 * 64 + J * 512);
            if (j0 < 2) { block(4, kb + j0 * 64 + 2048); block(8, kb + j0 * 64 + (544 + 16) * 4); }
        }
        __syncwarp();
#pragma unroll
        for (int i = 0; i < 8; i++)
            stsm4t(rs + lf + i * 512, pack2(acc[2 * i][0], acc[2 * i][1]), pack2(acc[2 * i][2], acc[2 * i][3]),
                   pack2(acc[2 * i + 1][0], acc[2 * i + 1][1]), pack2(acc[2 * i + 1][2], acc[2 * i + 1][3]));
    }
    __syncthreads();
    {
        const uint2 dv = __ldg((const uint2*)(Dsk + d0 + 4 * t));
        bf16* dst = out + (size_t)(w * 128 + g) * 2048 + 1024 + d0 + 4 * t;
#pragma unroll
        for (int i = 0; i < 8; i++) {
            uint32_t y[4], x[4], o[4];
            ldsm4t(y, sb + S4_R + tr_off * S4_RS + (w * 128 + i * 16) * 2 + tr_l);
            ldsm4t(x, sb + S4_U + tr_off * S4_US + 256 + (w * 128 + i * 16) * 2 + tr_l);
#pragma unroll
            for (int j = 0; j < 4; j++)
                asm("{\n.reg .b32 s;\nmul.rn.bf16x2 s, %2, %3;\nadd.rn.bf16x2 %0, %1, s;\n}" : "=r"(o[j]) : "r"(y[j]), "r"(x[j]), "r"((j & 1) ? dv.y : dv.x));
            *reinterpret_cast<uint2*>(dst + (size_t)(i * 16) * 2048) = make_uint2(o[0], o[1]);
            *reinterpret_cast<uint2*>(dst + (size_t)(i * 16 + 8) * 2048) = make_uint2(o[2], o[3]);
        }
    }
    if (tid == 0) TL(2, 1);
}

enum { IT_QA = 0, IT_W256 = 1, IT_W128 = 2, IT_W64 = 3, IT_W64S = 4, IT_END = 7 };
struct BgParams { CUtensorMap mx, mwq, mkv, mkvm, mo, mo2, mo2s, mwo4, mwo2, mwo1; };
#define LOOK 3
#define LOOKL 8
#define LOOKM 5
#define LOOKN 4
#define PWO 40
#define P256 44
#define P128 50
__device__ __forceinline__ uint32_t ld_rlx32(const uint32_t* p) {
    uint32_t v;
    asm volatile("ld.relaxed.gpu.global.u32 %0, [%1];" : "=r"(v) : "l"(p) : "memory");
    return v;
}
struct Sched { uint32_t qb = 0, w0 = 0, w1 = 0; };
__device__ __forceinline__ int next_item(Sched& z) {
    for (int n = 0; n < SPIN_LIMIT; n++) {
        if (z.w0 < z.w1 && (z.qb >= 16 || ld_rlx32(g_flag + 64 + min(z.w0 >> 4, 15u)) >= 16)) {
            const uint32_t i = z.w0, k = i >= 240 ? 1 : z.w1 - i >= 4 && !(i & 3) ? 4 : z.w1 - i >= 2 && !(i & 1) ? 2 : 1;
            z.w0 += k;
            if (i >= 240) return IT_W64S | 15 << 3 | (i - 240) << 7;
            return (k == 4 ? IT_W256 : k == 2 ? IT_W128 : IT_W64) | (i >> 4) << 3 | ((i & 15) / k) << 7;
        }
        const uint32_t wo = ld_rlx32(g_flag + 97), prog = ld_acq32(g_flag + 98);
        z.qb = max(z.qb, ld_rlx32(g_flag + 96));
        const bool wo_ready = z.w0 >= z.w1 && wo < 272 && (z.qb >= 16 || ld_rlx32(g_flag + 64 + min(wo >> 4, 15u)) >= 16);
        if (z.qb < 16 && prog + (z.qb == 15 ? LOOKL : z.qb == 14 ? LOOKM : z.qb == 13 ? LOOKN : LOOK) >= 4 * z.qb + 4 && !(wo_ready && prog <= PWO)) {
            const uint32_t i = atomicAdd(g_flag + 80 + z.qb, 1);
            if (i == 15) atomicMax(g_flag + 96, z.qb + 1);
            if (i < 16) return IT_QA | z.qb << 3 | i << 7;
            z.qb++;
            continue;
        }
        if (z.w0 < z.w1) {
            if (z.qb >= 16) continue;
        } else if (wo >= 272) {
            if (z.qb >= 16) return IT_END;
        } else if (wo_ready) {
            const uint32_t k = prog <= P256 ? 4 : prog <= P128 ? 2 : 1;
            z.w0 = atomicAdd(g_flag + 97, k);
            z.w1 = min(z.w0 + k, 272u);
            continue;
        }
        __nanosleep(300);
    }
    __trap();
    return IT_END;
}
constexpr int B_OST = NSTAGE * STAGE_BYTES + 1024;
constexpr int BG_SMEM = B_OST + 32768;

template <int BM, int BN, int KPS, typename ACC>
__device__ __forceinline__ void gemm_mainloop(ACC& acc, const GemmSmem& g, int cw, int rounds, uint32_t& round) {
#pragma unroll
    for (int i = 0; i < BN / 2; i++) acc[i] = 0.f;
#pragma unroll 1
    for (int k0 = 0; k0 < rounds; k0++, round++) {
#pragma unroll
        for (int s = 0; s < 4; s++) {
            mbar_wait_u(g.full + 8 * s, round & 1);
            gemm_stage<BM, BN, KPS>(acc, g.st + s * STAGE_BYTES, cw, false);
            wg_wait<1>();
            if (s > 0 || k0 > 0) mbar_arrive_one(g.empty + 8 * ((s + 3) & 3), threadIdx.x & 31);
        }
    }
    wg_wait<0>();
    mbar_arrive_one(g.empty + 8 * 3, threadIdx.x & 31);
}

template <int BM, int BN, int KPS>
__device__ __forceinline__ void wo_item(const GemmSmem& g, int cw, uint32_t& round, bf16* dst, int t) {
    if (BM == 64 && cw == 1) {
#pragma unroll 1
        for (int k0 = 0; k0 < 16 / KPS; k0++, round++)
#pragma unroll
            for (int s = 0; s < 4; s++) { mbar_wait_u(g.full + 8 * s, round & 1); mbar_arrive_one(g.empty + 8 * s, threadIdx.x & 31); }
        return;
    }
    float acc[BN / 2];
    gemm_mainloop<BM, BN, KPS>(acc, g, cw, 16 / KPS, round);
#pragma unroll
    for (int G = 0; G < BN / 32; G++)
#pragma unroll
        for (int rr = 0; rr < 2; rr++) {
            uint32_t r0 = pack2(acc[16 * G + 2 * rr], acc[16 * G + 2 * rr + 1]), r1 = pack2(acc[16 * G + 4 + 2 * rr], acc[16 * G + 5 + 2 * rr]);
            uint32_t r2 = pack2(acc[16 * G + 8 + 2 * rr], acc[16 * G + 9 + 2 * rr]), r3 = pack2(acc[16 * G + 12 + 2 * rr], acc[16 * G + 13 + 2 * rr]);
            quad_transpose(r0, r1, r2, r3, t);
            *reinterpret_cast<uint4*>(dst + (size_t)rr * 8 * 2048 + G * 32) = make_uint4(r0, r1, r2, r3);
        }
}

template <int HF>
__device__ __forceinline__ void attend(const uint32_t* q, uint32_t st, uint32_t sm, uint32_t ost, uint32_t bar_free, uint32_t parity, int lane) {
    constexpr int NT = HF ? 5 : 3;
    const int r8 = lane & 7, m4 = lane >> 3, gq = lane >> 2, t = lane & 3;
    const float sl2e = 0.08838834764831845f * 1.4426950408889634f;
    const uint32_t la = r8 * 128 + ((m4 ^ r8) << 4);
    float sc[NT][4];
#pragma unroll
    for (int nt = 0; nt < NT; nt++) sc[nt][0] = sc[nt][1] = sc[nt][2] = sc[nt][3] = 0.f;
#pragma unroll
    for (int kp = 0; kp < 4; kp++)
#pragma unroll
        for (int nt = 0; nt < NT; nt++) {
            uint32_t b[4];
            ldsm4(b, (nt == 0 ? sm + (kp >> 1) * 2048 : st + (kp >> 1) * 8192 + (nt - 1) * 1024) + (la ^ ((kp & 1) << 6)));
            mma16816(sc[nt], q[kp * 8], q[kp * 8 + 1], q[kp * 8 + 2], q[kp * 8 + 3], b[0], b[1]);
            mma16816(sc[nt], q[kp * 8 + 4], q[kp * 8 + 5], q[kp * 8 + 6], q[kp * 8 + 7], b[2], b[3]);
        }
    const float ninf = -3.0e38f;
    if (2 * t > gq) sc[NT - 2][0] = sc[NT - 1][2] = ninf;
    if (2 * t + 1 > gq) sc[NT - 2][1] = sc[NT - 1][3] = ninf;
    sc[NT - 1][0] = sc[NT - 1][1] = ninf;
    uint32_t p[NT][2];
#pragma unroll
    for (int i = 0; i < 2; i++) {
        float m = fmaxf(sc[0][2 * i], sc[0][2 * i + 1]);
#pragma unroll
        for (int nt = 1; nt < NT - 1 + i; nt++) m = fmaxf(m, fmaxf(sc[nt][2 * i], sc[nt][2 * i + 1]));
        m = fmaxf(m, __shfl_xor_sync(~0u, m, 1));
        m = fmaxf(m, __shfl_xor_sync(~0u, m, 2));
        const float ms = m * sl2e;
        float sum = 0.f;
#pragma unroll
        for (int nt = 0; nt < NT - 1 + i; nt++) {
            sc[nt][2 * i] = ex2(fmaf(sc[nt][2 * i], sl2e, -ms));
            sc[nt][2 * i + 1] = ex2(fmaf(sc[nt][2 * i + 1], sl2e, -ms));
            sum += sc[nt][2 * i] + sc[nt][2 * i + 1];
        }
        sum += __shfl_xor_sync(~0u, sum, 1);
        sum += __shfl_xor_sync(~0u, sum, 2);
        float inv;
        asm("rcp.approx.ftz.f32 %0, %1;" : "=f"(inv) : "f"(sum));
#pragma unroll
        for (int nt = 0; nt < NT - 1 + i; nt++) p[nt][i] = pack2(sc[nt][2 * i] * inv, sc[nt][2 * i + 1] * inv);
    }
    p[NT - 1][0] = 0;
    const uint32_t lv = ((m4 & 1) * 8 + r8) * 128 + (((m4 >> 1) ^ r8) << 4);
    mbar_wait_u(bar_free, parity);
#pragma unroll
    for (int G = 0; G < 4; G++) {
        float o[4][4];
#pragma unroll
        for (int i = 0; i < 4; i++) o[i][0] = o[i][1] = o[i][2] = o[i][3] = 0.f;
        uint32_t b[4];
        ldsm4t(b, sm + 4096 + (G >> 1) * 2048 + (la ^ ((G & 1) << 6)));
#pragma unroll
        for (int i = 0; i < 4; i++) mma1688(o[i], p[0][0], p[0][1], b[i]);
#pragma unroll
        for (int kk = 0; kk <= HF; kk++)
#pragma unroll
            for (int i = 0; i < 2; i++) {
                ldsm4t(b, st + 16384 + (G >> 1) * 8192 + kk * 2048 + (lv ^ (((G & 1) * 2 + i) << 5)));
                mma16816(o[2 * i], p[1 + 2 * kk][0], p[1 + 2 * kk][1], p[2 + 2 * kk][0], p[2 + 2 * kk][1], b[0], b[1]);
                mma16816(o[2 * i + 1], p[1 + 2 * kk][0], p[1 + 2 * kk][1], p[2 + 2 * kk][0], p[2 + 2 * kk][1], b[2], b[3]);
            }
#pragma unroll
        for (int i = 0; i < 2; i++)
            asm volatile("stmatrix.sync.aligned.m8n8.x4.shared.b16 [%0], {%1,%2,%3,%4};"
                         ::"r"(ost + (G >> 1) * 16384 + (lv ^ (((G & 1) * 2 + i) << 5))),
                           "r"(pack2(o[2 * i][0], o[2 * i][1])), "r"(pack2(o[2 * i][2], o[2 * i][3])),
                           "r"(pack2(o[2 * i + 1][0], o[2 * i + 1][1])), "r"(pack2(o[2 * i + 1][2], o[2 * i + 1][3])) : "memory");
    }
    asm volatile("fence.proxy.async.shared::cta;" ::: "memory");
    __syncwarp();
}

__device__ __forceinline__ void tma_prefetch3d(const CUtensorMap* m, int c0, int c1, int c2) {
    asm volatile("cp.async.bulk.prefetch.tensor.3d.L2.global [%0, {%1, %2, %3}];" ::"l"(m), "r"(c0), "r"(c1), "r"(c2) : "memory");
}

__global__ void __launch_bounds__(384, 1) k_bg(const __grid_constant__ BgParams P, bf16* __restrict__ out) {
    extern __shared__ __align__(1024) uint8_t smem_gemm[];
    const uint32_t xb = smem_u32(smem_gemm) + NSTAGE * STAGE_BYTES + 128;
    const uint32_t bar_item = xb, bar_o = xb + 16, bar_f = xb + 24, slot = xb + 32, slot_o = xb + 40;
    if (threadIdx.x == 0) { mbar_init(bar_item, 1); mbar_init(bar_item + 8, 1); mbar_init(bar_o, 8); mbar_init(bar_f, 1); }
    GemmSmem g = gemm_setup(smem_gemm, 8);
    const int wg = __shfl_sync(~0u, threadIdx.x >> 7, 0);
    if (wg == 0) {
        asm volatile("setmaxnreg.dec.sync.aligned.u32 40;");
        if (threadIdx.x == 0) {
            uint32_t it = 0;
            Sched z;
            auto acquire = [&](uint32_t bytes) {
                const int s = it & 3;
                mbar_wait(g.empty + 8 * s, ((it >> 2) & 1) ^ 1);
                mbar_expect_tx(g.full + 8 * s, bytes);
                it++;
                return s;
            };
            for (int n = 0;; n++) {
                const int code = next_item(z);
                sts32(slot + (n & 1) * 4, code);
                mbar_arrive(bar_item + (n & 1) * 8);
                const int type = code & 7, blk = (code >> 3) & 15, idx = code >> 7, m0 = blk * 128;
                if (type == IT_END) break;
                if (type == IT_QA) {
                    for (int k = 0; k < 16; k++) {
                        const int s = acquire(STAGE_BYTES);
                        const uint32_t st = g.st + s * STAGE_BYTES, fb = g.full + 8 * s;
                        tma2d(st, &P.mx, k * 64, m0, fb);
                        tma3d(st + 16384, &P.mwq, 0, k * 64, idx * 4, fb);
                        if (k >= 4 && k < 12) tma_prefetch3d(&P.mkv, 0, m0 + (k & 1) * 64, (k & 8) * 8 + idx * 4 + (k & 2));
                    }
                    bool ready = ld_acq32(g_flag + 2 * idx) >= 4 * blk + 4 && ld_acq32(g_flag + 2 * idx + 1) >= 4 * blk + 4;
                    if (ready) asm volatile("fence.proxy.async.global;" ::: "memory");
                    for (int pass = 0; pass < 2; pass++) {
                        for (int s = 0; s < 4; s++) {
                            const uint32_t st = g.st + s * STAGE_BYTES, fb = g.full + 8 * s;
                            if (pass == 0) {
                                acquire(40960);
                                tma3d(st, &P.mkv, 0, m0 + (s & 1) * 64, idx * 4 + (s & 2), fb);
                                tma3d(st + 16384, &P.mkv, 0, m0 + (s & 1) * 64, 64 + idx * 4 + (s & 2), fb);
                            }
                            if (ready) {
                                tma3d(st + 32768, &P.mkvm, 0, blk * 32 + (s & 1) * 16, idx * 4 + (s & 2), fb);
                                tma3d(st + 36864, &P.mkvm, 0, blk * 32 + (s & 1) * 16, 64 + idx * 4 + (s & 2), fb);
                            }
                        }
                        if (ready) break;
                        wait_flag(g_flag + 2 * idx, 4 * blk + 4);
                        wait_flag(g_flag + 2 * idx + 1, 4 * blk + 4);
                        asm volatile("fence.proxy.async.global;" ::: "memory");
                        ready = true;
                    }
                } else {
                    wait_flag(g_flag + 64 + blk, 16);
                    asm volatile("fence.proxy.async.global;" ::: "memory");
                    if (type <= IT_W128) {
                        const int nb = type == IT_W256 ? 4 : 2;
                        for (int k = 0; k < 64; k++) {
                            const int s = acquire(16384 + nb * 8192);
                            const uint32_t st = g.st + s * STAGE_BYTES, fb = g.full + 8 * s;
                            tma2d(st, &P.mo, k * 64, m0, fb);
                            tma3d(st + 16384, nb == 4 ? &P.mwo4 : &P.mwo2, 0, k * 64, idx * nb, fb);
                        }
                    } else {
                        const uint32_t ab = type == IT_W64 ? 32768 : 16384;
                        for (int k = 0; k < 32; k++) {
                            const int s = acquire(ab + 16384);
                            const uint32_t st = g.st + s * STAGE_BYTES, fb = g.full + 8 * s;
                            tma3d(st, type == IT_W64 ? &P.mo2 : &P.mo2s, 0, m0 + (idx >> 4) * 64, k * 2, fb);
                            tma3d(st + ab, &P.mwo1, 0, k * 128, idx & 15, fb);
                        }
                    }
                }
            }
        } else if (threadIdx.x == 32) {
            for (;;) {
                mbar_wait(bar_o, 0);
                const int code = lds32(slot_o), blk = (code >> 3) & 15, idx = (code >> 7) & 31;
                if ((code & 7) == IT_END) break;
                for (int hh = 0; hh < 2; hh++) {
                    if (hh) mbar_wait(bar_o, 1);
                    asm volatile("cp.async.bulk.tensor.3d.global.shared::cta.bulk_group [%0, {%2, %3, %4}], [%1];\n"
                                 "cp.async.bulk.commit_group;\ncp.async.bulk.wait_group.read 0;"
                                 ::"l"(&P.mo2), "r"(g.st + B_OST), "r"(0), "r"(blk * 128), "r"(idx * 4 + hh * 2) : "memory");
                    mbar_arrive(bar_f);
                }
                asm volatile("cp.async.bulk.wait_group 0;\nfence.acq_rel.gpu;\nred.relaxed.gpu.global.add.u32 [%0], 1;"
                             ::"l"(g_flag + 64 + blk) : "memory");
            }
        }
    } else {
        asm volatile("setmaxnreg.inc.sync.aligned.u32 232;");
        const int cw = wg - 1, ww = __shfl_sync(~0u, (threadIdx.x >> 5) & 3, 0), lane = threadIdx.x & 31;
        uint32_t round = 0;
#pragma unroll 1
        for (int n = 0;; n++) {
            mbar_wait_u(bar_item + (n & 1) * 8, (n >> 1) & 1);
            const int code = __shfl_sync(~0u, lds32(slot + (n & 1) * 4), 0);
            const int type = code & 7, blk = (code >> 3) & 15, idx = (code >> 7) & 31;
#define TLB(slot_)
            if (type == IT_END) {
                mbar_wait_u(bar_f, 1);
                if (threadIdx.x == 128) sts32(slot_o, IT_END);
                __syncwarp();
                mbar_arrive_one(bar_o, lane);
                break;
            }
            TLB(0);
            if (type == IT_QA) {
                uint32_t q[64];
                {
                    float acc[128];
                    gemm_mainloop<128, 256, 1>(acc, g, cw, 4, round);
#pragma unroll
                    for (int i = 0; i < 64; i++) q[i] = pack2(acc[2 * i], acc[2 * i + 1]);
                }
                if (threadIdx.x == 128) sts32(slot_o, code);
                TLB(2);
#pragma unroll
                for (int hh = 0; hh < 2; hh++) {
                    const uint32_t st = g.st + (2 * hh + cw) * STAGE_BYTES, ost = g.st + B_OST + (cw * 4 + ww) * 2048;
                    mbar_wait_u(g.full + 16 * hh, round & 1);
                    mbar_wait_u(g.full + 16 * hh + 8, round & 1);
                    if (hh == 0) { TLB(3); }
                    if (ww & 1) attend<1>(q + 32 * hh, st + (ww >> 1) * 4096, st + 32768 + (ww >> 1) * 1024, ost, bar_f, hh ^ 1, lane);
                    else attend<0>(q + 32 * hh, st + (ww >> 1) * 4096, st + 32768 + (ww >> 1) * 1024, ost, bar_f, hh ^ 1, lane);
                    mbar_arrive_one(bar_o, lane);
                    mbar_arrive_one(g.empty + 16 * hh, lane);
                    mbar_arrive_one(g.empty + 16 * hh + 8, lane);
                }
                round++;
            } else {
                bf16* dst = out + (size_t)(blk * 128 + cw * 64 + ww * 16 + (lane >> 2)) * 2048 + (lane & 3) * 8;
                if (type == IT_W256) wo_item<128, 256, 1>(g, cw, round, dst + idx * 256, lane & 3);
                else if (type == IT_W128) wo_item<128, 128, 1>(g, cw, round, dst + idx * 128, lane & 3);
                else if (type == IT_W64) wo_item<128, 64, 2>(g, cw, round, dst + idx * 64, lane & 3);
                else wo_item<64, 64, 2>(g, cw, round, dst + (size_t)(idx >> 4) * 64 * 2048 + (idx & 15) * 64, lane & 3);
            }
            TLB(1);
        }
    }
}

typedef CUresult (*EncodeFn)(CUtensorMap*, CUtensorMapDataType, cuuint32_t, void*, const cuuint64_t*, const cuuint64_t*,
                             const cuuint32_t*, const cuuint32_t*, CUtensorMapInterleave, CUtensorMapSwizzle,
                             CUtensorMapL2promotion, CUtensorMapFloatOOBfill);

static void map2d(EncodeFn enc, CUtensorMap* m, const void* p, int rows, int cols, int box_rows) {
    cuuint64_t dim[2] = {(cuuint64_t)cols, (cuuint64_t)rows}, str[1] = {(cuuint64_t)cols * 2};
    cuuint32_t box[2] = {64, (cuuint32_t)box_rows}, es[2] = {1, 1};
    enc(m, CU_TENSOR_MAP_DATA_TYPE_BFLOAT16, 2, (void*)p, dim, str, box, es, CU_TENSOR_MAP_INTERLEAVE_NONE,
        CU_TENSOR_MAP_SWIZZLE_128B, CU_TENSOR_MAP_L2_PROMOTION_L2_256B, CU_TENSOR_MAP_FLOAT_OOB_FILL_NONE);
}
static void map3d(EncodeFn enc, CUtensorMap* m, const void* p, int rows, int cols, int box_rows, int nblk) {
    cuuint64_t dim[3] = {64, (cuuint64_t)rows, (cuuint64_t)cols / 64}, str[2] = {(cuuint64_t)cols * 2, 128};
    cuuint32_t box[3] = {64, (cuuint32_t)box_rows, (cuuint32_t)nblk}, es[3] = {1, 1, 1};
    enc(m, CU_TENSOR_MAP_DATA_TYPE_BFLOAT16, 3, (void*)p, dim, str, box, es, CU_TENSOR_MAP_INTERLEAVE_NONE,
        CU_TENSOR_MAP_SWIZZLE_128B, CU_TENSOR_MAP_L2_PROMOTION_L2_256B, CU_TENSOR_MAP_FLOAT_OOB_FILL_NONE);
}

#define USE_PDL 1

extern "C" void kernel_launch(void* const* d_in, const int* in_sizes, int n_in, void* d_out, int out_size) {
    const bf16 *x = (const bf16*)d_in[0], *mem0 = (const bf16*)d_in[1], *Wq = (const bf16*)d_in[2], *Wk = (const bf16*)d_in[3];
    const bf16 *Wv = (const bf16*)d_in[4], *Wo = (const bf16*)d_in[5];
    const bf16 *u = (const bf16*)d_in[7], *Are = (const bf16*)d_in[8], *Aim = (const bf16*)d_in[9], *Bre = (const bf16*)d_in[10];
    const bf16 *Bim = (const bf16*)d_in[11], *Cre = (const bf16*)d_in[12], *Cim = (const bf16*)d_in[13];
    const bf16 *logdt = (const bf16*)d_in[14], *Dsk = (const bf16*)d_in[15];
    bf16* out = (bf16*)d_out;

    void* fn = nullptr;
    cudaDriverEntryPointQueryResult qr;
    cudaGetDriverEntryPoint("cuTensorMapEncodeTiled", &fn, cudaEnableDefault, &qr);
    EncodeFn enc = (EncodeFn)fn;
    void *kv, *kvm, *o;
    cudaGetSymbolAddress(&kv, g_kv);
    cudaGetSymbolAddress(&kvm, g_kvm);
    cudaGetSymbolAddress(&o, g_o);
    CUtensorMap mwk, mwv, mkv2;
    BgParams P;
    map2d(enc, &P.mx, x, SEQ, DM, 128);
    map2d(enc, &P.mo, o, SEQ, HD, 128);
    map3d(enc, &P.mo2, o, SEQ, HD, 128, 2);
    map3d(enc, &P.mo2s, o, SEQ, HD, 64, 2);
    map3d(enc, &P.mwq, Wq, DM, HD, 64, 4);
    map3d(enc, &mwk, Wk, DM, HD, 64, 4);
    map3d(enc, &mwv, Wv, DM, HD, 64, 4);
    map3d(enc, &P.mwo4, Wo, HD, DM, 64, 4);
    map3d(enc, &P.mwo2, Wo, HD, DM, 64, 2);
    map3d(enc, &P.mwo1, Wo, HD, DM, 128, 1);
    map3d(enc, &mkv2, kv, SEQ, 8192, 32, 2);
    map3d(enc, &P.mkv, kv, SEQ, 8192, 64, 2);
    map3d(enc, &P.mkvm, kvm, NSEG * 8, 8192, 16, 2);
    cudaFuncSetAttribute(k_kv, cudaFuncAttributeMaxDynamicSharedMemorySize, GEMM_SMEM);
    cudaFuncSetAttribute(k_bg, cudaFuncAttributeMaxDynamicSharedMemorySize, BG_SMEM);
    cudaFuncSetAttribute(k_chain, cudaFuncAttributeMaxDynamicSharedMemorySize, CHAIN_SMEM);
    cudaFuncSetAttribute(k_s4, cudaFuncAttributeMaxDynamicSharedMemorySize, S4_SMEM);

    cudaStream_t st = cudaStreamPerThread;
    cudaLaunchAttribute pdl[1], cls[1];
    pdl[0].id = cudaLaunchAttributeProgrammaticStreamSerialization;
    pdl[0].val.programmaticStreamSerializationAllowed = 1;
    cls[0].id = cudaLaunchAttributeClusterDimension;
    cls[0].val.clusterDim.x = CLS; cls[0].val.clusterDim.y = 1; cls[0].val.clusterDim.z = 1;
    cudaLaunchConfig_t cfg = {};
    cfg.stream = st; cfg.attrs = cls; cfg.numAttrs = 1;
    cfg.gridDim = dim3(96); cfg.blockDim = dim3(384); cfg.dynamicSmemBytes = GEMM_SMEM;
    cudaLaunchKernelEx(&cfg, k_kv, P.mx, mwk, mwv, Wq, Wk, Wo, 0);
    cfg.attrs = pdl; cfg.numAttrs = 1;
    cfg.gridDim = dim3(36);
    cudaLaunchKernelEx(&cfg, k_kv, P.mx, mwk, mwv, Wq, Wk, Wo, 96);
    cfg.gridDim = dim3(96); cfg.blockDim = dim3(256); cfg.dynamicSmemBytes = CHAIN_SMEM;
    cudaLaunchKernelEx(&cfg, k_chain, mem0, Wq, Wk, Wv, Wo, mkv2);
    cfg.numAttrs = USE_PDL;
    cfg.gridDim = dim3(64); cfg.blockDim = dim3(512); cfg.dynamicSmemBytes = S4_SMEM;
    cudaLaunchKernelEx(&cfg, k_s4, u, Are, Aim, Bre, Bim, Cre, Cim, logdt, Dsk, out);
    cfg.gridDim = dim3(132); cfg.blockDim = dim3(384); cfg.dynamicSmemBytes = BG_SMEM;
    cudaLaunchKernelEx(&cfg, k_bg, P, out);
}
```

```cpp
#include <cuda_runtime.h>
#include <cuda_bf16.h>
#include <cuda.h>
#include <stdint.h>

typedef __nv_bfloat16 bf16;

constexpr int SEQ = 2048, DM = 1024, HD = 4096, NSEG = 64;

__device__ __align__(1024) bf16 g_kv[(size_t)SEQ * 8192];
__device__ __align__(1024) bf16 g_kvm[(size_t)NSEG * 8 * 8192];
__device__ __align__(1024) bf16 g_o[(size_t)SEQ * HD];
constexpr int XPAIRS = 128 + NSEG * 4;
__device__ __align__(8192) uint2 g_x[XPAIRS * 1024];
__device__ uint32_t g_home[XPAIRS];
__device__ uint32_t g_side[256];
__device__ __align__(1024) uint32_t g_flag[256];

#define TL(kern, slot)

__device__ __forceinline__ uint32_t smem_u32(const void* p) { return (uint32_t)__cvta_generic_to_shared(p); }
__device__ __forceinline__ void mbar_init(uint32_t bar, uint32_t cnt) {
    asm volatile("mbarrier.init.shared::cta.b64 [%0], %1;" ::"r"(bar), "r"(cnt) : "memory");
}
__device__ __forceinline__ void mbar_expect_tx(uint32_t bar, uint32_t bytes) {
    asm volatile("mbarrier.arrive.expect_tx.shared::cta.b64 _, [%0], %1;" ::"r"(bar), "r"(bytes) : "memory");
}
__device__ __forceinline__ void mbar_arrive(uint32_t bar) {
    asm volatile("mbarrier.arrive.shared::cta.b64 _, [%0];" ::"r"(bar) : "memory");
}
__device__ __forceinline__ bool mbar_try(uint32_t bar, uint32_t parity) {
    uint32_t ok;
    asm volatile("{\n.reg .pred p;\nmbarrier.try_wait.parity.shared::cta.b64 p, [%1], %2;\nselp.u32 %0, 1, 0, p;\n}"
                 : "=r"(ok) : "r"(bar), "r"(parity) : "memory");
    return ok;
}
constexpr int SPIN_LIMIT = 1 << 20;
__device__ __forceinline__ void mbar_wait(uint32_t bar, uint32_t parity) {
    int n = 0;
    while (!mbar_try(bar, parity)) { if (++n > SPIN_LIMIT) __trap(); }
}
__device__ __forceinline__ void mbar_wait_u(uint32_t bar, uint32_t parity) {
    asm volatile("{\n.reg .pred p;\n.reg .u32 n;\n"
                 "mbarrier.try_wait.parity.shared::cta.b64 p, [%0], %1;\n@p bra.uni DONE;\nmov.u32 n, 0;\n"
                 "AGAIN:\nmbarrier.try_wait.parity.shared::cta.b64 p, [%0], %1;\n@p bra.uni DONE;\n"
                 "add.u32 n, n, 1;\nsetp.lt.u32 p, n, 0x100000;\n@p bra.uni AGAIN;\ntrap;\nDONE:\n}"
                 ::"r"(bar), "r"(parity) : "memory");
}
__device__ __forceinline__ void tma2d(uint32_t dst, const CUtensorMap* m, int c0, int c1, uint32_t bar) {
    asm volatile("cp.async.bulk.tensor.2d.shared::cluster.global.mbarrier::complete_tx::bytes [%0], [%1, {%3, %4}], [%2];"
                 ::"r"(dst), "l"(m), "r"(bar), "r"(c0), "r"(c1) : "memory");
}
__device__ __forceinline__ void tma3d(uint32_t dst, const CUtensorMap* m, int c0, int c1, int c2, uint32_t bar) {
    asm volatile("cp.async.bulk.tensor.3d.shared::cluster.global.mbarrier::complete_tx::bytes [%0], [%1, {%3, %4, %5}], [%2];"
                 ::"r"(dst), "l"(m), "r"(bar), "r"(c0), "r"(c1), "r"(c2) : "memory");
}
__device__ __forceinline__ uint32_t pack2(float lo, float hi) {
    uint32_t r;
    asm("cvt.rn.bf16x2.f32 %0, %1, %2;" : "=r"(r) : "f"(hi), "f"(lo));
    return r;
}
__device__ __forceinline__ float bf_lo(uint32_t v) { return __uint_as_float(v << 16); }
__device__ __forceinline__ float bf_hi(uint32_t v) { return __uint_as_float(v & 0xffff0000u); }
__device__ __forceinline__ float bf_round(float x) { return bf_lo(pack2(x, 0.f)); }
__device__ __forceinline__ float ex2(float x) { float y; asm("ex2.approx.ftz.f32 %0, %1;" : "=f"(y) : "f"(x)); return y; }
__device__ __forceinline__ void mma16816(float (&c)[4], uint32_t a0, uint32_t a1, uint32_t a2, uint32_t a3, uint32_t b0, uint32_t b1) {
    asm volatile("mma.sync.aligned.m16n8k16.row.col.f32.bf16.bf16.f32 {%0,%1,%2,%3}, {%4,%5,%6,%7}, {%8,%9}, {%0,%1,%2,%3};"
                 : "+f"(c[0]), "+f"(c[1]), "+f"(c[2]), "+f"(c[3]) : "r"(a0), "r"(a1), "r"(a2), "r"(a3), "r"(b0), "r"(b1));
}
__device__ __forceinline__ void mma1688(float (&c)[4], uint32_t a0, uint32_t a1, uint32_t b0) {
    asm volatile("mma.sync.aligned.m16n8k8.row.col.f32.bf16.bf16.f32 {%0,%1,%2,%3}, {%4,%5}, {%6}, {%0,%1,%2,%3};"
                 : "+f"(c[0]), "+f"(c[1]), "+f"(c[2]), "+f"(c[3]) : "r"(a0), "r"(a1), "r"(b0));
}
__device__ __forceinline__ void ldsm4(uint32_t (&r)[4], uint32_t a) {
    asm volatile("ldmatrix.sync.aligned.m8n8.x4.shared.b16 {%0,%1,%2,%3}, [%4];"
                 : "=r"(r[0]), "=r"(r[1]), "=r"(r[2]), "=r"(r[3]) : "r"(a) : "memory");
}
__device__ __forceinline__ void ldsm4t(uint32_t (&r)[4], uint32_t a) {
    asm volatile("ldmatrix.sync.aligned.m8n8.x4.trans.shared.b16 {%0,%1,%2,%3}, [%4];"
                 : "=r"(r[0]), "=r"(r[1]), "=r"(r[2]), "=r"(r[3]) : "r"(a) : "memory");
}
__device__ __forceinline__ void ldsm2t(uint32_t& r0, uint32_t& r1, uint32_t a) {
    asm volatile("ldmatrix.sync.aligned.m8n8.x2.trans.shared.b16 {%0,%1}, [%2];" : "=r"(r0), "=r"(r1) : "r"(a) : "memory");
}
__device__ __forceinline__ void stsm4t(uint32_t a, uint32_t r0, uint32_t r1, uint32_t r2, uint32_t r3) {
    asm volatile("stmatrix.sync.aligned.m8n8.x4.trans.shared.b16 [%0], {%1,%2,%3,%4};"
                 ::"r"(a), "r"(r0), "r"(r1), "r"(r2), "r"(r3) : "memory");
}
__device__ __forceinline__ void lds128(uint32_t (&r)[4], uint32_t a) {
    asm volatile("ld.shared.v4.u32 {%0,%1,%2,%3}, [%4];" : "=r"(r[0]), "=r"(r[1]), "=r"(r[2]), "=r"(r[3]) : "r"(a) : "memory");
}
__device__ __forceinline__ float4 lds128f(uint32_t a) {
    float4 v;
    asm volatile("ld.shared.v4.f32 {%0,%1,%2,%3}, [%4];" : "=f"(v.x), "=f"(v.y), "=f"(v.z), "=f"(v.w) : "r"(a) : "memory");
    return v;
}
__device__ __forceinline__ float2 lds64f(uint32_t a) {
    float2 v;
    asm volatile("ld.shared.v2.f32 {%0,%1}, [%2];" : "=f"(v.x), "=f"(v.y) : "r"(a) : "memory");
    return v;
}
__device__ __forceinline__ uint32_t lds32(uint32_t a) {
    uint32_t v;
    asm volatile("ld.shared.u32 %0, [%1];" : "=r"(v) : "r"(a) : "memory");
    return v;
}
__device__ __forceinline__ void sts128(uint32_t a, uint32_t r0, uint32_t r1, uint32_t r2, uint32_t r3) {
    asm volatile("st.shared.v4.u32 [%0], {%1,%2,%3,%4};" ::"r"(a), "r"(r0), "r"(r1), "r"(r2), "r"(r3) : "memory");
}
__device__ __forceinline__ void sts128f(uint32_t a, float r0, float r1, float r2, float r3) {
    asm volatile("st.shared.v4.f32 [%0], {%1,%2,%3,%4};" ::"r"(a), "f"(r0), "f"(r1), "f"(r2), "f"(r3) : "memory");
}
__device__ __forceinline__ void sts64(uint32_t a, uint32_t r0, uint32_t r1) {
    asm volatile("st.shared.v2.u32 [%0], {%1,%2};" ::"r"(a), "r"(r0), "r"(r1) : "memory");
}
__device__ __forceinline__ void sts64f(uint32_t a, float r0, float r1) {
    asm volatile("st.shared.v2.f32 [%0], {%1,%2};" ::"r"(a), "f"(r0), "f"(r1) : "memory");
}
__device__ __forceinline__ void sts32f(uint32_t a, float r0) {
    asm volatile("st.shared.f32 [%0], %1;" ::"r"(a), "f"(r0) : "memory");
}
__device__ __forceinline__ uint2 ld_rlx64(const uint2* p) {
    uint2 v;
    asm volatile("{\n.reg .b64 t;\nld.relaxed.gpu.global.b64 t, [%2];\nmov.b64 {%0,%1}, t;\n}" : "=r"(v.x), "=r"(v.y) : "l"(p) : "memory");
    return v;
}
__device__ __forceinline__ void st_rlx64(uint2* p, uint32_t x, uint32_t y) {
    asm volatile("{\n.reg .b64 t;\nmov.b64 t, {%1,%2};\nst.relaxed.gpu.global.b64 [%0], t;\n}" ::"l"(p), "r"(x), "r"(y) : "memory");
}
__device__ __forceinline__ uint32_t ld_acq32(const uint32_t* p) {
    uint32_t v;
    asm volatile("ld.acquire.gpu.global.u32 %0, [%1];" : "=r"(v) : "l"(p) : "memory");
    return v;
}
__device__ __forceinline__ void wait_flag(const uint32_t* p, uint32_t need) {
    int n = 0;
    while (ld_acq32(p) < need) { __nanosleep(200); if (++n > SPIN_LIMIT) __trap(); }
}
__device__ __forceinline__ void bar_sync(int id, int n) { asm volatile("bar.sync %0, %1;" ::"r"(id), "r"(n) : "memory"); }
__device__ __forceinline__ void wg_fence() { asm volatile("wgmma.fence.sync.aligned;" ::: "memory"); }
__device__ __forceinline__ void wg_commit() { asm volatile("wgmma.commit_group.sync.aligned;" ::: "memory"); }
template <int N> __device__ __forceinline__ void wg_wait() { asm volatile("wgmma.wait_group.sync.aligned %0;" ::"n"(N) : "memory"); }
__device__ __forceinline__ uint64_t desc_sw128(uint32_t addr, uint32_t lbo, uint32_t sbo) {
    return (uint64_t)((addr & 0x3FFFF) >> 4) | ((uint64_t)(lbo >> 4) << 16) | ((uint64_t)(sbo >> 4) << 32) | (1ull << 62);
}
__device__ __forceinline__ void quad_transpose(uint32_t& r0, uint32_t& r1, uint32_t& r2, uint32_t& r3, int t) {
    const bool o = t & 1, h = t & 2;
    uint32_t s0 = __shfl_xor_sync(~0u, o ? r0 : r1, 1), s1 = __shfl_xor_sync(~0u, o ? r2 : r3, 1);
    uint32_t a0 = o ? s0 : r0, a1 = o ? r1 : s0, a2 = o ? s1 : r2, a3 = o ? r3 : s1;
    s0 = __shfl_xor_sync(~0u, h ? a0 : a2, 2); s1 = __shfl_xor_sync(~0u, h ? a1 : a3, 2);
    r0 = h ? s0 : a0; r1 = h ? s1 : a1; r2 = h ? a2 : s0; r3 = h ? a3 : s1;
}

__device__ __forceinline__ void wgmma_n256(float (&d)[128], uint64_t da, uint64_t db, int sd) {
    asm volatile("{\n.reg .pred p;\nsetp.ne.b32 p, %130, 0;\n"
        "wgmma.mma_async.sync.aligned.m64n256k16.f32.bf16.bf16 "
        "{%0,%1,%2,%3,%4,%5,%6,%7,%8,%9,%10,%11,%12,%13,%14,%15,"
        "%16,%17,%18,%19,%20,%21,%22,%23,%24,%25,%26,%27,%28,%29,%30,%31,"
        "%32,%33,%34,%35,%36,%37,%38,%39,%40,%41,%42,%43,%44,%45,%46,%47,"
        "%48,%49,%50,%51,%52,%53,%54,%55,%56,%57,%58,%59,%60,%61,%62,%63,"
        "%64,%65,%66,%67,%68,%69,%70,%71,%72,%73,%74,%75,%76,%77,%78,%79,"
        "%80,%81,%82,%83,%84,%85,%86,%87,%88,%89,%90,%91,%92,%93,%94,%95,"
        "%96,%97,%98,%99,%100,%101,%102,%103,%104,%105,%106,%107,%108,%109,%110,%111,"
        "%112,%113,%114,%115,%116,%117,%118,%119,%120,%121,%122,%123,%124,%125,%126,%127}, %128, %129, p, 1, 1, 0, 1;\n}\n"
        : "+f"(d[0]), "+f"(d[1]), "+f"(d[2]), "+f"(d[3]), "+f"(d[4]), "+f"(d[5]), "+f"(d[6]), "+f"(d[7]),
          "+f"(d[8]), "+f"(d[9]), "+f"(d[10]), "+f"(d[11]), "+f"(d[12]), "+f"(d[13]), "+f"(d[14]), "+f"(d[15]),
          "+f"(d[16]), "+f"(d[17]), "+f"(d[18]), "+f"(d[19]), "+f"(d[20]), "+f"(d[21]), "+f"(d[22]), "+f"(d[23]),
          "+f"(d[24]), "+f"(d[25]), "+f"(d[26]), "+f"(d[27]), "+f"(d[28]), "+f"(d[29]), "+f"(d[30]), "+f"(d[31]),
          "+f"(d[32]), "+f"(d[33]), "+f"(d[34]), "+f"(d[35]), "+f"(d[36]), "+f"(d[37]), "+f"(d[38]), "+f"(d[39]),
          "+f"(d[40]), "+f"(d[41]), "+f"(d[42]), "+f"(d[43]), "+f"(d[44]), "+f"(d[45]), "+f"(d[46]), "+f"(d[47]),
          "+f"(d[48]), "+f"(d[49]), "+f"(d[50]), "+f"(d[51]), "+f"(d[52]), "+f"(d[53]), "+f"(d[54]), "+f"(d[55]),
          "+f"(d[56]), "+f"(d[57]), "+f"(d[58]), "+f"(d[59]), "+f"(d[60]), "+f"(d[61]), "+f"(d[62]), "+f"(d[63]),
          "+f"(d[64]), "+f"(d[65]), "+f"(d[66]), "+f"(d[67]), "+f"(d[68]), "+f"(d[69]), "+f"(d[70]), "+f"(d[71]),
          "+f"(d[72]), "+f"(d[73]), "+f"(d[74]), "+f"(d[75]), "+f"(d[76]), "+f"(d[77]), "+f"(d[78]), "+f"(d[79]),
          "+f"(d[80]), "+f"(d[81]), "+f"(d[82]), "+f"(d[83]), "+f"(d[84]), "+f"(d[85]), "+f"(d[86]), "+f"(d[87]),
          "+f"(d[88]), "+f"(d[89]), "+f"(d[90]), "+f"(d[91]), "+f"(d[92]), "+f"(d[93]), "+f"(d[94]), "+f"(d[95]),
          "+f"(d[96]), "+f"(d[97]), "+f"(d[98]), "+f"(d[99]), "+f"(d[100]), "+f"(d[101]), "+f"(d[102]), "+f"(d[103]),
          "+f"(d[104]), "+f"(d[105]), "+f"(d[106]), "+f"(d[107]), "+f"(d[108]), "+f"(d[109]), "+f"(d[110]), "+f"(d[111]),
          "+f"(d[112]), "+f"(d[113]), "+f"(d[114]), "+f"(d[115]), "+f"(d[116]), "+f"(d[117]), "+f"(d[118]), "+f"(d[119]),
          "+f"(d[120]), "+f"(d[121]), "+f"(d[122]), "+f"(d[123]), "+f"(d[124]), "+f"(d[125]), "+f"(d[126]), "+f"(d[127])
        : "l"(da), "l"(db), "r"(sd));
}

__device__ __forceinline__ void wgmma_n128(float (&d)[64], uint64_t da, uint64_t db, int sd) {
    asm volatile("{\n.reg .pred p;\nsetp.ne.b32 p, %66, 0;\n"
        "wgmma.mma_async.sync.aligned.m64n128k16.f32.bf16.bf16 "
        "{%0,%1,%2,%3,%4,%5,%6,%7,%8,%9,%10,%11,%12,%13,%14,%15,"
        "%16,%17,%18,%19,%20,%21,%22,%23,%24,%25,%26,%27,%28,%29,%30,%31,"
        "%32,%33,%34,%35,%36,%37,%38,%39,%40,%41,%42,%43,%44,%45,%46,%47,"
        "%48,%49,%50,%51,%52,%53,%54,%55,%56,%57,%58,%59,%60,%61,%62,%63}, %64, %65, p, 1, 1, 0, 1;\n}\n"
        : "+f"(d[0]), "+f"(d[1]), "+f"(d[2]), "+f"(d[3]), "+f"(d[4]), "+f"(d[5]), "+f"(d[6]), "+f"(d[7]),
          "+f"(d[8]), "+f"(d[9]), "+f"(d[10]), "+f"(d[11]), "+f"(d[12]), "+f"(d[13]), "+f"(d[14]), "+f"(d[15]),
          "+f"(d[16]), "+f"(d[17]), "+f"(d[18]), "+f"(d[19]), "+f"(d[20]), "+f"(d[21]), "+f"(d[22]), "+f"(d[23]),
          "+f"(d[24]), "+f"(d[25]), "+f"(d[26]), "+f"(d[27]), "+f"(d[28]), "+f"(d[29]), "+f"(d[30]), "+f"(d[31]),
          "+f"(d[32]), "+f"(d[33]), "+f"(d[34]), "+f"(d[35]), "+f"(d[36]), "+f"(d[37]), "+f"(d[38]), "+f"(d[39]),
          "+f"(d[40]), "+f"(d[41]), "+f"(d[42]), "+f"(d[43]), "+f"(d[44]), "+f"(d[45]), "+f"(d[46]), "+f"(d[47]),
          "+f"(d[48]), "+f"(d[49]), "+f"(d[50]), "+f"(d[51]), "+f"(d[52]), "+f"(d[53]), "+f"(d[54]), "+f"(d[55]),
          "+f"(d[56]), "+f"(d[57]), "+f"(d[58]), "+f"(d[59]), "+f"(d[60]), "+f"(d[61]), "+f"(d[62]), "+f"(d[63])
        : "l"(da), "l"(db), "r"(sd));
}

__device__ __forceinline__ void wgmma_n64(float (&d)[32], uint64_t da, uint64_t db, int sd) {
    asm volatile("{\n.reg .pred p;\nsetp.ne.b32 p, %34, 0;\n"
        "wgmma.mma_async.sync.aligned.m64n64k16.f32.bf16.bf16 "
        "{%0,%1,%2,%3,%4,%5,%6,%7,%8,%9,%10,%11,%12,%13,%14,%15,"
        "%16,%17,%18,%19,%20,%21,%22,%23,%24,%25,%26,%27,%28,%29,%30,%31}, %32, %33, p, 1, 1, 0, 1;\n}\n"
        : "+f"(d[0]), "+f"(d[1]), "+f"(d[2]), "+f"(d[3]), "+f"(d[4]), "+f"(d[5]), "+f"(d[6]), "+f"(d[7]),
          "+f"(d[8]), "+f"(d[9]), "+f"(d[10]), "+f"(d[11]), "+f"(d[12]), "+f"(d[13]), "+f"(d[14]), "+f"(d[15]),
          "+f"(d[16]), "+f"(d[17]), "+f"(d[18]), "+f"(d[19]), "+f"(d[20]), "+f"(d[21]), "+f"(d[22]), "+f"(d[23]),
          "+f"(d[24]), "+f"(d[25]), "+f"(d[26]), "+f"(d[27]), "+f"(d[28]), "+f"(d[29]), "+f"(d[30]), "+f"(d[31])
        : "l"(da), "l"(db), "r"(sd));
}

constexpr int STAGE_BYTES = 49152, NSTAGE = 4;
constexpr int GEMM_SMEM = NSTAGE * STAGE_BYTES + 128;

struct GemmSmem { uint32_t st, full, empty; };
__device__ __forceinline__ GemmSmem gemm_setup(uint8_t* raw, int releases) {
    GemmSmem g;
    g.st = smem_u32(raw);
    if (g.st & 1023) __trap();
    g.full = g.st + NSTAGE * STAGE_BYTES; g.empty = g.full + 64;
    if (threadIdx.x == 0) {
        for (int s = 0; s < NSTAGE; s++) { mbar_init(g.full + 8 * s, 1); mbar_init(g.empty + 8 * s, releases); }
        asm volatile("fence.mbarrier_init.release.cluster;" ::: "memory");
        asm volatile("fence.proxy.async.shared::cta;" ::: "memory");
    }
    __syncthreads();
    return g;
}
__device__ __forceinline__ void mbar_arrive_one(uint32_t bar, uint32_t who) {
    asm volatile("{\n.reg .pred p;\nsetp.eq.u32 p, %1, 0;\n@p mbarrier.arrive.shared::cta.b64 _, [%0];\n}" ::"r"(bar), "r"(who) : "memory");
}
template <int BM, int BN, int KPS, typename ACC>
__device__ __forceinline__ void gemm_stage(ACC& acc, uint32_t stage, int wg, bool first) {
    const uint64_t da = desc_sw128(stage + wg * 8192, 16, 1024);
    const uint64_t db = desc_sw128(stage + KPS * BM * 128, 8192, 1024);
    wg_fence();
#pragma unroll
    for (int k = 0; k < 4 * KPS; k++) {
        const uint64_t a = da + (k >> 2) * (BM * 8) + (k & 3) * 2, b = db + k * 128;
        if constexpr (BN == 256) wgmma_n256(acc, a, b, first && k == 0 ? 0 : 1);
        else if constexpr (BN == 128) wgmma_n128(acc, a, b, first && k == 0 ? 0 : 1);
        else wgmma_n64(acc, a, b, first && k == 0 ? 0 : 1);
    }
    wg_commit();
}

__device__ __forceinline__ void kv_store_unit(const uint32_t (&pk)[64], int u, bf16* dst, int t) {
    const int G = (u >> 2) * 2 + (u & 1), hh = (u >> 1) & 1;
    uint32_t r0 = pk[(4 * G + 0) * 2 + hh], r1 = pk[(4 * G + 1) * 2 + hh], r2 = pk[(4 * G + 2) * 2 + hh], r3 = pk[(4 * G + 3) * 2 + hh];
    quad_transpose(r0, r1, r2, r3, t);
#define KVST ".cs"
    asm volatile("st.global" KVST ".v4.u32 [%0], {%1,%2,%3,%4};" ::"l"(dst + (size_t)hh * 8 * 8192 + G * 32), "r"(r0), "r"(r1), "r"(r2), "r"(r3) : "memory");
}

#define TLK(slot)
__device__ __forceinline__ uint32_t near_page(int pair, int line) {
    uint32_t best[2] = {~0u, ~0u};
#pragma unroll 1
    for (int i = 0; i < 16; i++) {
        uint32_t t0, t1, v;
        asm volatile("mov.u32 %0, %%clock;" : "=r"(t0)::"memory");
        asm volatile("atom.relaxed.gpu.global.or.b32 %0, [%1], -1;" : "=r"(v) : "l"(g_x + pair * 1024 + (i & 1) * 512 + line * 16) : "memory");
        asm volatile("{\n.reg .pred p;\nsetp.ne.u32 p, %1, 0x12345;\nmov.u32 %0, -1;\n@p mov.u32 %0, %%clock;\n}" : "=r"(t1) : "r"(v) : "memory");
        if (i & 1) best[1] = min(best[1], t1 - t0); else best[0] = min(best[0], t1 - t0);
    }
    return best[1] < best[0];
}
__device__ __forceinline__ void map_pages(int c) {
    uint32_t smid;
    asm("mov.u32 %0, %%smid;" : "=r"(smid));
    const uint32_t side = near_page(0, c & 31);
    g_side[smid & 255] = side;
    for (int p = c; p < XPAIRS; p += 132) g_home[p] = near_page(p, 0) ^ side;
}

__global__ void __launch_bounds__(384, 1)
k_kv(const __grid_constant__ CUtensorMap mx, const __grid_constant__ CUtensorMap mwk, const __grid_constant__ CUtensorMap mwv,
     const bf16* __restrict__ Wq, const bf16* __restrict__ Wk, const bf16* __restrict__ Wo, int c0) {
    extern __shared__ __align__(1024) uint8_t smem_gemm[];
    const int c = c0 + blockIdx.x;
    if (c == 128) {
        if (threadIdx.x < 256) g_flag[threadIdx.x] = 0;
        __threadfence();
        __syncthreads();
    }
    asm volatile("griddepcontrol.launch_dependents;");
    if (threadIdx.x == 0) TLK(0);
    if (c >= 128) {
        const int i0 = (c - 128) * 384 + threadIdx.x;
        const uint4 ones = make_uint4(~0u, ~0u, ~0u, ~0u);
        if (threadIdx.x == 32) map_pages(c);
        for (int i = i0; i < XPAIRS * 512; i += 4 * 384) reinterpret_cast<uint4*>(g_x)[i] = ones;
        if (threadIdx.x == 0) TLK(1);
        asm volatile("griddepcontrol.wait;" ::: "memory");
        return;
    }
    GemmSmem g = gemm_setup(smem_gemm, 2);
    const int m0 = (c & 15) * 128, nb0 = c >> 4;
    const int wg = __shfl_sync(~0u, threadIdx.x >> 7, 0);
    if (wg == 0) {
        asm volatile("setmaxnreg.dec.sync.aligned.u32 40;");
        if (threadIdx.x == 0) {
            for (int it = 0; it < 64; it++) {
                const int s = it & 3, tile = it >> 4, kb = it & 15;
                mbar_wait(g.empty + 8 * s, ((it >> 2) & 1) ^ 1);
                mbar_expect_tx(g.full + 8 * s, STAGE_BYTES);
                const int nb = nb0 + 8 * tile;
                tma2d(g.st + s * STAGE_BYTES, &mx, kb * 64, m0, g.full + 8 * s);
                tma3d(g.st + s * STAGE_BYTES + 16384, nb < 16 ? &mwk : &mwv, 0, kb * 64, (nb & 15) * 4, g.full + 8 * s);
#define PF0 40
#define PFN 24
#define PFB 4096
                const int pi = it - PF0;
                if (pi >= 0 && pi < PFN) {
                    const uint32_t o = (pi * 128 + c) * PFB;
                    const char* p = (const char*)(o < (8 << 20) ? Wo : o < (16 << 20) ? Wq : Wk) + (o & ((8 << 20) - 1));
                    asm volatile("cp.async.bulk.prefetch.L2.global [%0], %1;" ::"l"(p), "n"(PFB) : "memory");
                }
            }
        } else if (threadIdx.x == 32) map_pages(c);
    } else {
        asm volatile("setmaxnreg.inc.sync.aligned.u32 232;");
        const int cw = wg - 1, lane = threadIdx.x & 31, t = lane & 3;
        const int row = m0 + cw * 64 + ((threadIdx.x >> 5) & 3) * 16 + (lane >> 2);
        bf16* dst = g_kv + (size_t)row * 8192 + nb0 * 256 + t * 8;
        float acc[128];
        uint32_t pk[64];
#pragma unroll 1
        for (int tile = 0; tile < 4; tile++) {
#pragma unroll
            for (int kb = 0; kb < 16; kb++) {
                mbar_wait_u(g.full + 8 * (kb & 3), (kb >> 2) & 1);
                gemm_stage<128, 256, 1>(acc, g.st + (kb & 3) * STAGE_BYTES, cw, kb == 0);
                if (tile > 0) kv_store_unit(pk, kb, dst + (tile - 1) * 2048, t);
                if (kb > 0) {
                    wg_wait<1>();
                    mbar_arrive_one(g.empty + 8 * ((kb - 1) & 3), threadIdx.x & 127);
                }
            }
            wg_wait<0>();
            mbar_arrive_one(g.empty + 8 * 3, threadIdx.x & 127);
#pragma unroll
            for (int i = 0; i < 64; i++) pk[i] = pack2(acc[2 * i], acc[2 * i + 1]);
        }
        if (threadIdx.x == 128) TLK(2);
#pragma unroll
        for (int u = 0; u < 16; u++) kv_store_unit(pk, u, dst + 3 * 2048, t);
        if (threadIdx.x == 128) TLK(1);
        asm volatile("griddepcontrol.wait;" ::: "memory");
    }
}

constexpr int NS1 = 31;
#define RB1 4
#define PFC 4
constexpr int C_W1 = 0;
constexpr int C_W2 = C_W1 + 8 * NS1 * 512;
constexpr int C_KV = C_W2 + 14 * 8 * 512;
constexpr int C_RED = C_KV + 16384;
constexpr int C_QKV = C_RED + 64 * 272;
constexpr int C_SC = C_RED;
constexpr int C_OB = C_SC + 2 * 8 * 52 * 4;
constexpr int C_BAR = C_QKV + 3 * 8 * 272;
__host__ __device__ constexpr int smem_idx(int ks, int j) {
    return ks == 0 ? j : ks < 3 ? (j < 4 ? 4 + 4 * ks + j : -1) : (j < 3 ? 7 + 3 * ks + j : -1);
}
constexpr int CHAIN_SMEM = C_BAR + 64;
#define TS(i)

#define DLY3 8
#define DLY1 2
#define DLY0 2
#define DLY1A 10
#define DLY0A DLY0
#define DLYW 3
template <int N> __device__ __forceinline__ uint32_t delayed(uint32_t x, int lane) {
#pragma unroll
    for (int i = 0; i < N; i++) asm volatile("shfl.sync.idx.b32 %0, %0, %1, 31, -1;" : "+r"(x) : "r"(lane) : "memory");
    return x;
}
__device__ __forceinline__ void lds128v(uint32_t (&r)[4], uint32_t a) {
    asm volatile("ld.volatile.shared.v4.u32 {%0,%1,%2,%3}, [%4];" : "=r"(r[0]), "=r"(r[1]), "=r"(r[2]), "=r"(r[3]) : "r"(a) : "memory");
}
__device__ __forceinline__ uint2 lds64(uint32_t a) {
    uint2 v;
    asm volatile("ld.shared.v2.u32 {%0,%1}, [%2];" : "=r"(v.x), "=r"(v.y) : "r"(a) : "memory");
    return v;
}
#define LDQ ".L1::no_allocate"
__device__ __forceinline__ uint4 ldw128(const void* p) {
    uint4 v;
    asm volatile("ld.global.nc" LDQ ".v4.u32 {%0,%1,%2,%3}, [%4];" : "=r"(v.x), "=r"(v.y), "=r"(v.z), "=r"(v.w) : "l"(p));
    return v;
}
#define P8_LD(i) "ld.relaxed.gpu.global.b64 d" #i ", [src + " #i " * 256];\n"
#define P8_X(i) "mov.b64 {x" #i ", y" #i "}, d" #i ";\n"
#define P8_HEAD(SRC) "{\n.reg .pred p, q;\n.reg .b64 src, d<8>;\n.reg .b32 n, x<8>, y<8>, m0, m1;\nmov.b64 src, " SRC ";\n"         \
                P8_LD(0) P8_LD(1) P8_LD(2) P8_LD(3) P8_LD(4) P8_LD(5) P8_LD(6) P8_LD(7) "mov.u32 n, 0;\nCHECK:\n" \
                P8_X(0) P8_X(1) P8_X(2) P8_X(3) P8_X(4) P8_X(5) P8_X(6) P8_X(7)
#define P8_VOTE "vote.sync.all.pred p, p, -1;\n@p bra.uni DONE;\n"
#define P8_TAIL "add.u32 n, n, 1;\nsetp.lt.u32 p, n, 0x100000;\n@p bra.uni CHECK;\ntrap;\nDONE:\n"
__device__ __forceinline__ void poll_state(uint2 (&v)[8], const void* src) {
#define P8_RS(i) "setp.eq.u32 q, x" #i ", 0xffffffff;\n@q " P8_LD(i)
#define P8_O(i) "mov.b64 %" #i ", d" #i ";\n"
    uint64_t d[8];
    asm volatile(P8_HEAD("%8") "max.u32 m0, x0, x1;\nmax.u32 m0, m0, x2;\nmax.u32 m1, x3, x4;\nmax.u32 m1, m1, x5;\nmax.u32 m0, m0, x6;\n"
                 "max.u32 m0, m0, x7;\nmax.u32 m0, m0, m1;\nsetp.ne.u32 p, m0, 0xffffffff;\n" P8_VOTE
                 P8_RS(0) P8_RS(1) P8_RS(2) P8_RS(3) P8_RS(4) P8_RS(5) P8_RS(6) P8_RS(7) P8_TAIL
                 P8_O(0) P8_O(1) P8_O(2) P8_O(3) P8_O(4) P8_O(5) P8_O(6) P8_O(7) "}"
                 : "=l"(d[0]), "=l"(d[1]), "=l"(d[2]), "=l"(d[3]), "=l"(d[4]), "=l"(d[5]), "=l"(d[6]), "=l"(d[7]) : "l"(src) : "memory");
#pragma unroll
    for (int i = 0; i < 8; i++) { v[i].x = (uint32_t)d[i]; v[i].y = (uint32_t)(d[i] >> 32); }
}
__device__ __forceinline__ uint64_t poll_sum(const void* src, uint32_t tag, uint32_t sel) {
#define P8_RT(i) "lop3.b32 m0, x" #i ", %2, 1, 0x28;\nsetp.ne.u32 q, m0, 0;\n@q " P8_LD(i)
#define P8_MMA(c, i, z) "mma.sync.aligned.m16n8k8.row.col.f32.bf16.bf16.f32 {" #c "0," #c "1," #c "2," #c "3}, {x" #i ", y" #i "}, {%3}, {" #z "0," #z "1," #z "2," #z "3};\n"
    uint64_t r;
    asm volatile(P8_HEAD("%1") "{\n.reg .f32 a<4>, b<4>, z<4>;\nmov.f32 z0, 0f00000000;\nmov.f32 z1, z0;\nmov.f32 z2, z0;\nmov.f32 z3, z0;\n"
                 P8_MMA(a, 0, z) P8_MMA(b, 1, z) P8_MMA(a, 2, a) P8_MMA(b, 3, b) P8_MMA(a, 4, a) P8_MMA(b, 5, b) P8_MMA(a, 6, a) P8_MMA(b, 7, b)
                 "add.f32 a0, a0, b0;\nadd.f32 a1, a1, b1;\nadd.f32 a2, a2, b2;\nadd.f32 a3, a3, b3;\n"
                 "cvt.rn.bf16x2.f32 m0, a1, a0;\ncvt.rn.bf16x2.f32 m1, a3, a2;\nmov.b64 %0, {m0, m1};\n}\n"
                 "lop3.b32 m0, x0, x1, %2, 0x7e;\nlop3.b32 m1, x2, x3, %2, 0x7e;\nlop3.b32 m0, m0, x4, %2, 0xf6;\n"
                 "lop3.b32 m1, m1, x5, %2, 0xf6;\nlop3.b32 m0, m0, x6, %2, 0xf6;\nlop3.b32 m1, m1, x7, %2, 0xf6;\n"
                 "lop3.b32 m0, m0, m1, 1, 0xa8;\nsetp.eq.u32 p, m0, 0;\n" P8_VOTE
                 P8_RT(0) P8_RT(1) P8_RT(2) P8_RT(3) P8_RT(4) P8_RT(5) P8_RT(6) P8_RT(7) P8_TAIL "}"
                 : "=&l"(r) : "l"(src), "r"(tag), "r"(sel) : "memory");
    return r;
}
__device__ __forceinline__ void sum8(float (&c)[4], const uint2 (&v)[8], uint32_t idn) {
    float d[4] = {0.f, 0.f, 0.f, 0.f};
    c[0] = c[1] = c[2] = c[3] = 0.f;
    mma16816(c, v[0].x, v[0].y, v[1].x, v[1].y, idn, idn);
    mma16816(d, v[2].x, v[2].y, v[3].x, v[3].y, idn, idn);
    mma16816(c, v[4].x, v[4].y, v[5].x, v[5].y, idn, idn);
    mma16816(d, v[6].x, v[6].y, v[7].x, v[7].y, idn, idn);
    c[0] += d[0]; c[1] += d[1]; c[2] += d[2]; c[3] += d[3];
}

#define CLS 6
__global__ void __cluster_dims__(CLS, 1, 1) __launch_bounds__(256, 1)
k_chain(const bf16* __restrict__ mem0, const bf16* __restrict__ Wq, const bf16* __restrict__ Wk, const bf16* __restrict__ Wv,
        const bf16* __restrict__ Wo, const __grid_constant__ CUtensorMap mkv) {
    extern __shared__ __align__(1024) uint8_t smem_chain[];
    const uint32_t sb = smem_u32(smem_chain);
    if (sb & 1023) __trap();
    const int w = __shfl_sync(~0u, threadIdx.x >> 5, 0), lane = __shfl_sync(~0u, threadIdx.x & 31, threadIdx.x & 31);
    const int tid = w * 32 + lane, g = lane >> 2, t = lane & 3;
    auto pin = [&](uint32_t x) { return delayed<1>(x, lane); };
    const int h = blockIdx.x / 3, r = blockIdx.x - 3 * h;
    const uint32_t bar_x = sb + C_BAR, bar_kv = sb + C_BAR + 8, bar_go = sb + C_BAR + 16, bar_w = sb + C_BAR + 24;
    asm volatile("griddepcontrol.launch_dependents;");
    const int tbase = r == 0 ? 0 : 1 + 21 * r, ntile = r == 0 ? 22 : 21;
    uint32_t side;
    if (tid == 0) {
        mbar_init(bar_x, 8); mbar_init(bar_kv, 1); mbar_init(bar_go, 1); mbar_init(bar_w, 1);
        asm volatile("fence.mbarrier_init.release.cluster;" ::: "memory");
        asm volatile("fence.proxy.async.shared::cta;" ::: "memory");
        mbar_expect_tx(bar_w, 128 * 32 * ntile);
    }
    __syncthreads();
    asm volatile("barrier.cluster.arrive.relaxed.aligned;" ::: "memory");
    if (tid < 128)
        asm volatile("cp.async.bulk.shared::cluster.global.mbarrier::complete_tx::bytes [%0], [%1], %2, [%3];"
                     ::"r"(sb + C_W1 + tid * 720), "l"(Wo + (size_t)(h * 128 + tid) * DM + tbase * 16), "r"(32 * ntile), "r"(bar_w) : "memory");
    const int tile0 = tbase + 7 - w;
    const bool three = w >= (r == 0 ? 2 : 3);
    const uint32_t wa = pin(sb + tid * 16);
#define W1A(i) (wa + C_W1 + (i) * 4096)
#define W2A(x) (wa + C_W2 + ((x) < 8 ? (x) * 4096 : 32768 - 1024 + ((x) - 8) * 3072))
    uint32_t wo0[8][4], wr[64][4];
    {
        const bf16* W = (r == 0 ? Wq : r == 1 ? Wk : Wv) + (size_t)(128 * w + (lane >> 4)) * HD + h * 128 + 8 * (lane & 15);
        uint4 raw[8][8];
        auto fetch = [&](int ks) {
#pragma unroll
            for (int i = 0; i < 8; i++) raw[ks][i] = ldw128(W + (size_t)(16 * ks + 2 * i) * HD);
        };
        fetch(0); fetch(1); fetch(2); fetch(3);
    asm("mov.u32 %0, %%smid;" : "=r"(side));
    side = ld_acq32(g_side + (side & 255)) & 1;
    if (tid == 0 && r > 0) asm volatile("st.relaxed.gpu.global.u32 [%0], %1;" ::"l"(g_flag + 128 + 2 * h + r - 1), "r"(2 | side) : "memory");
        mbar_wait_u(bar_w, 0);
        const uint32_t p = sb + C_W1 + ((lane & 7) + (lane >> 4) * 8) * 720 + (7 - w) * 32 + ((lane >> 3) & 1) * 16;
#pragma unroll
        for (int ks = 0; ks < 8; ks++) {
            uint32_t a[4];
            ldsm4t(wo0[ks], p + ks * 16 * 720);
            ldsm4t(a, p + ks * 16 * 720 + 256);
            sts128(W2A(ks), a[0], a[1], a[2], a[3]);
            if (three) { ldsm4t(a, p + ks * 16 * 720 + 512); sts128(W2A(8 + ks), a[0], a[1], a[2], a[3]); }
        }
        __syncthreads();
        const uint32_t stg = sb + C_KV + w * 4096;
        const uint32_t rd = stg + ((lane & 7) + 8 * (lane >> 4)) * 256 + ((((lane >> 3) & 1) ^ (lane & 7)) << 4);
#pragma unroll
        for (int ks = 0; ks < 8; ks++) {
#pragma unroll
            for (int i = 0; i < 8; i++)
                sts128(stg + (2 * i + (lane >> 4)) * 256 + (((lane & 15) ^ (((2 * i) & 6) | (lane >> 4))) << 4),
                       raw[ks][i].x, raw[ks][i].y, raw[ks][i].z, raw[ks][i].w);
            if (ks < 2) fetch(ks + 4);
            if (ks == 3 || ks == 5) fetch(ks / 2 + 5);
            __syncwarp();
#pragma unroll
            for (int j = 0; j < 8; j++) {
                if (smem_idx(ks, j) >= 0) {
                    uint32_t a[4];
                    ldsm4t(a, rd ^ (j << 5));
                    sts128(W1A(smem_idx(ks, j)), a[0], a[1], a[2], a[3]);
                } else ldsm4t(wr[8 * ks + j], rd ^ (j << 5));
            }
            __syncwarp();
        }
    }
    asm volatile("griddepcontrol.wait;\nfence.proxy.async.shared::cta;" ::: "memory");
    __syncthreads();
    if (tid == 0) {
        mbar_expect_tx(bar_kv, 16384);
        tma3d(sb + C_KV, &mkv, 0, 0, 2 * h, bar_kv);
        tma3d(sb + C_KV + 8192, &mkv, 0, 0, 64 + 2 * h, bar_kv);
    }
    asm volatile("barrier.cluster.wait.aligned;" ::: "memory");

    auto publish_kvm = [&](int s) {
        uint32_t v[4];
        lds128(v, sb + C_QKV + (8 + (tid >> 4)) * 272 + (tid & 15) * 16);
        asm volatile("st.global.v4.u32 [%0], {%1,%2,%3,%4};"
                     ::"l"(g_kvm + (size_t)(s * 8 + ((tid >> 4) & 7)) * 8192 + (tid >> 7) * HD + h * 128 + (tid & 15) * 8),
                       "r"(v[0]), "r"(v[1]), "r"(v[2]), "r"(v[3]) : "memory");
        if (h == 0 && w == 6) asm volatile("st.relaxed.gpu.global.u32 [%0], %1;" ::"l"(g_flag + 98), "r"(s + 1) : "memory");
        if ((s & 3) == 3) {
            __syncthreads();
            if (w == 7) asm volatile("{\n.reg .pred p;\nsetp.eq.u32 p, %2, 0;\nfence.acq_rel.gpu;\n@p st.relaxed.gpu.global.u32 [%0], %1;\n}"
                                     ::"l"(g_flag + h), "r"(s + 1), "r"(lane) : "memory");
        }
    };
    const float sl2e = 0.08838834764831845f * 1.4426950408889634f;
    const uint32_t idn = pin(g == 2 * t ? 0x00003f80u : g == 2 * t + 1 ? 0x3f800000u : 0u);
    const uint32_t lm = pin(sb + (lane & 7) * 272 + (lane >> 3) * 16);
    const uint32_t sa = pin(sb + C_SC + (w & 1) * (8 * 52 * 4) + (2 * t * 52 + (w < 4 ? 32 : (w & 2) * 8) + g) * 4);
    const uint32_t sr = pin(sb + C_SC + (g * 52 + 8 * t) * 4), sr2 = pin(sb + C_SC + (g * 52 + 32 + 2 * t) * 4);
    uint32_t kva;
    {
        const int pos = (w & 2) * 8 + (lane & 15), row = (pos & 24) + ((pos + (pos >> 2 & 6)) & 7);
        const int key = 4 * (lane & 6) + (((lane & 7) + 2 * (lane >> 4)) & 7);
        kva = pin(w >= 4 ? sb + C_KV + (w & 1) * 4096 + row * 128 + (((lane >> 4) ^ (row & 7)) << 4)
                         : sb + C_KV + 8192 + (w >> 1) * 4096 + key * 128 + ((((w & 1) * 4 + ((lane >> 3) & 1)) ^ (key & 7)) << 4));
    }
    uint32_t buf0[8][4], ring[RB1][4];
    auto stage_w1 = [&]() {
#pragma unroll
        for (int i = 0; i < 8; i++) lds128v(buf0[i], W1A(i));
#pragma unroll
        for (int i = 0; i < RB1; i++) lds128v(ring[i], W1A(8 + i));
    };
    stage_w1();
    uint32_t psel, msel0, msel1;
    {
        const int j = r > 0 ? 2 * h + r - 1 : 0, tl = min(tile0 + 8 * (lane >> 1), 63);
        uint32_t b;
        asm volatile("{\n.reg .pred p;\n.reg .u32 n;\nmov.u32 n, 0;\nAGAIN:\nld.relaxed.gpu.global.u32 %0, [%1];\nsetp.ne.u32 p, %0, 0;\n"
                     "vote.sync.all.pred p, p, -1;\n@p bra.uni DONE;\nadd.u32 n, n, 1;\nsetp.lt.u32 p, n, 0x100000;\n@p bra.uni AGAIN;\ntrap;\nDONE:\n}"
                     : "=&r"(b) : "l"(g_flag + 128 + tl) : "memory");
        psel = __ballot_sync(~0u, (g_home[lane == 6 ? j * 2 + ((w >> 1) & 1) : tl * 2 + (lane & 1)] ^ (lane == 6 ? side : b)) & 1);
        msel0 = __ballot_sync(~0u, (g_home[128 + lane * 4 + (w >> 1)] ^ side) & 1);
        msel1 = __ballot_sync(~0u, (g_home[256 + lane * 4 + (w >> 1)] ^ side) & 1);
        if (r > 0) {
            if (w < 4) asm volatile("prefetch.global.L2 [%0];" ::"l"(g_x + (128 + (1 + (w >> 1)) * 4 + (j >> 4)) * 1024 + (w & 1) * 512 + (j & 15) * 32 + lane) : "memory");
            if (w < 4) asm volatile("prefetch.global.L2 [%0];" ::"l"(g_x + j * 2048 + tid * 16) : "memory");
        }
    }
    uint2 bm[8];
#pragma unroll
    for (int ks = 0; ks < 8; ks++) {
        const uint32_t* p = (const uint32_t*)(mem0 + g * DM + (8 * w + ks) * 16) + t;
        bm[ks] = make_uint2(__ldg(p), __ldg(p + 4));
    }
    mbar_wait_u(bar_kv, 0);
    if (tid == 0) TL(1, 2);
#pragma unroll 1
    for (int s = 0;; s++) {
        TS(1);
        {
            float acc[8][4];
#pragma unroll
            for (int ks = 0; ks < 8; ks++) {
#pragma unroll
                for (int j = 0; j < 8; j++) {
                    const int i = smem_idx(ks, j) - 8;
                    if (ks == 0) {
                        acc[j][0] = acc[j][1] = acc[j][2] = acc[j][3] = 0.f;
                        mma16816(acc[j], buf0[j][0], buf0[j][1], buf0[j][2], buf0[j][3], bm[ks].x, bm[ks].y);
                    } else if (i >= 0) {
                        uint32_t(&a)[4] = ring[i % RB1];
                        mma16816(acc[j], a[0], a[1], a[2], a[3], bm[ks].x, bm[ks].y);
                        if (8 + i + RB1 < NS1) lds128v(a, W1A(8 + i + RB1));
                    } else {
                        const uint32_t(&a)[4] = wr[8 * ks + j];
                        mma16816(acc[j], a[0], a[1], a[2], a[3], bm[ks].x, bm[ks].y);
                    }
                }
            }
#pragma unroll
            for (int c = 0; c < 4; c++)
                stsm4t(lm + C_RED + w * 2176 + c * 64, pack2(acc[2 * c][0], acc[2 * c][1]), pack2(acc[2 * c][2], acc[2 * c][3]),
                       pack2(acc[2 * c + 1][0], acc[2 * c + 1][1]), pack2(acc[2 * c + 1][2], acc[2 * c + 1][3]));
        }
        {
            const uint32_t a = sb + C_RED + w * 272 + lane * 8;
            TS(2);
            __syncthreads();
            TS(3);
            uint2 v[8];
#pragma unroll
            for (int i = 0; i < 8; i++) v[i] = lds64(a + i * 2176);
            float c[4];
            sum8(c, v, idn);
            const uint32_t p0 = pack2(c[0], c[1]), p1 = pack2(c[2], c[3]);
            const uint32_t dst = sb + C_QKV + (r * 8 + w) * 272 + lane * 8;
#pragma unroll
            for (int i = 1; i < 3; i++) {
                const uint32_t peer = (h % (CLS / 3)) * 3 + (r + i >= 3 ? r + i - 3 : r + i);
                uint32_t rd, rb;
                asm("mapa.shared::cluster.u32 %0, %1, %2;" : "=r"(rd) : "r"(dst), "r"(peer));
                asm("mapa.shared::cluster.u32 %0, %1, %2;" : "=r"(rb) : "r"(bar_x), "r"(peer));
                asm volatile("st.async.weak.shared::cluster.mbarrier::complete_tx::bytes.v2.b32 [%0], {%1,%2}, [%3];"
                             ::"r"(rd), "r"(p0), "r"(p1), "r"(rb) : "memory");
            }
            sts64(dst, p0, p1);
            __syncwarp();
            asm volatile("{\n.reg .pred p;\nsetp.eq.u32 p, %1, 0;\n@p mbarrier.arrive.expect_tx.shared::cta.b64 _, [%0], 512;\n}"
                         ::"r"(bar_x), "r"(lane) : "memory");
        }
        TS(4);
        if (s == NSEG - 1) break;
        uint32_t wb[8][4], wc[8][4];
        const uint32_t po = (tile0 * 2 + (lane >> 4)) * 8192 + ((lane >> 3) & 1) * 2048 + h * 64 + (lane & 7) * 8;
        const uint32_t tag = s & 1;
        auto project = [&](const uint32_t(&wt)[8][4], const uint32_t(&ob)[4][4], int i) {
            float c0[4] = {0.f, 0.f, 0.f, 0.f}, c1[4] = {0.f, 0.f, 0.f, 0.f};
#pragma unroll
            for (int ks = 0; ks < 8; ks++)
                mma16816((ks & 1) ? c1 : c0, wt[ks][0], wt[ks][1], wt[ks][2], wt[ks][3], ob[ks >> 1][(ks & 1) * 2], ob[ks >> 1][(ks & 1) * 2 + 1]);
            uint32_t p0 = pack2(c0[0] + c1[0], c0[1] + c1[1]), p1 = pack2(c0[2] + c1[2], c0[3] + c1[3]);
            asm volatile("movmatrix.sync.aligned.m8n8.trans.b16 %0, %0;\nmovmatrix.sync.aligned.m8n8.trans.b16 %1, %1;" : "+r"(p0), "+r"(p1));
            st_rlx64((uint2*)((char*)g_x + po + i * 131072 + ((psel >> (2 * i + (lane >> 4))) & 1) * 4096), (p0 & ~1u) | tag, p1);
        };
        if (w >= 4) {
            uint32_t ka[4][4];
#pragma unroll
            for (int ks = 0; ks < 4; ks++) ldsm4(ka[ks], kva ^ (ks << 5));
            const uint32_t qa = lm + C_QKV + (w & 1) * 128;
            TS(5);
            mbar_wait_u(bar_x, s & 1);
            TS(6);
            {
                uint32_t qb[2][4];
                ldsm4(qb[0], qa);
                ldsm4(qb[1], qa + 64);
                float c0[4] = {0.f, 0.f, 0.f, 0.f}, c1[4] = {0.f, 0.f, 0.f, 0.f};
                mma16816(c0, ka[0][0], ka[0][1], ka[0][2], ka[0][3], qb[0][0], qb[0][1]);
                mma16816(c1, ka[1][0], ka[1][1], ka[1][2], ka[1][3], qb[0][2], qb[0][3]);
                mma16816(c0, ka[2][0], ka[2][1], ka[2][2], ka[2][3], qb[1][0], qb[1][1]);
                mma16816(c1, ka[3][0], ka[3][1], ka[3][2], ka[3][3], qb[1][2], qb[1][3]);
                sts32f(sa, c0[0] + c1[0]);
                sts32f(sa + 208, c0[1] + c1[1]);
                sts32f(sa + 32, c0[2] + c1[2]);
                sts32f(sa + 240, c0[3] + c1[3]);
            }
            __syncthreads();
            TS(7);
            if (w == 7 && s + 1 < NSEG - 1) {
                if (lane == 0) {
                    mbar_expect_tx(bar_kv, 16384);
                    tma3d(sb + C_KV, &mkv, 0, (s + 1) * 32, 2 * h, bar_kv);
                    tma3d(sb + C_KV + 8192, &mkv, 0, (s + 1) * 32, 64 + 2 * h, bar_kv);
                }
                __syncwarp();
            }
            const uint32_t wd = delayed<DLYW>(wa, lane);
#pragma unroll
            for (int i = 0; i < 8; i++) lds128(wb[i], wd + C_W2 + i * 4096);
#pragma unroll
            for (int i = 0; i < PFC; i++) lds128(wc[i], wd + C_W2 + 32768 - 1024 + i * 3072);
            TS(8);
            __syncthreads();
            TS(9);
            uint32_t ob[4][4];
#pragma unroll
            for (int i = 0; i < 4; i++) ldsm4(ob[i], lm + C_OB + i * 64);
#pragma unroll
            for (int i = PFC; i < 8; i++) lds128(wc[i], W2A(8 + i));
            project(wb, ob, 1);
            project(wo0, ob, 0);
            project(wc, ob, 2);
        } else {
            uint32_t va[4][4];
#pragma unroll
            for (int i = 0; i < 4; i++) ldsm4t(va[i], kva ^ (((i >> 1) << 5) | ((i & 1) * 0x240)));
#pragma unroll
            for (int i = 0; i < 8; i++) lds128(wb[i], W2A(i));
            const uint32_t qa = lm + C_QKV + (w & 1) * 128, oa = lm + w * 64;
            TS(5);
            mbar_wait_u(bar_x, s & 1);
            TS(6);
            if (w < 2) {
                uint32_t qb[2][4], km[2][4];
                ldsm4(qb[0], qa);
                ldsm4(km[0], qa + 8 * 272);
                ldsm4(qb[1], qa + 64);
                ldsm4(km[1], qa + 8 * 272 + 64);
                float c0[4] = {0.f, 0.f, 0.f, 0.f}, c1[4] = {0.f, 0.f, 0.f, 0.f};
                mma16816(c0, km[0][0], km[0][1], km[0][2], km[0][3], qb[0][0], qb[0][2]);
                mma16816(c1, km[0][0], km[0][1], km[0][2], km[0][3], qb[0][1], qb[0][3]);
                mma16816(c0, km[1][0], km[1][1], km[1][2], km[1][3], qb[1][0], qb[1][2]);
                mma16816(c1, km[1][0], km[1][1], km[1][2], km[1][3], qb[1][1], qb[1][3]);
                sts32f(sa, c0[0] + c1[2]);
                sts32f(sa + 208, c0[1] + c1[3]);
            }
            __syncthreads();
            TS(7);
            {
                float4 x0 = lds128f(sr), y0 = lds128f(sr + 1664), x1 = lds128f(sr + 16), y1 = lds128f(sr + 1680);
                float2 x2 = lds64f(sr2), y2 = lds64f(sr2 + 1664);
                float p[10] = {x0.x + y0.x, x0.y + y0.y, x0.z + y0.z, x0.w + y0.w, x1.x + y1.x,
                               x1.y + y1.y, x1.z + y1.z, x1.w + y1.w, x2.x + y2.x, x2.y + y2.y};
                float m = fmaxf(fmaxf(fmaxf(p[0], p[1]), fmaxf(p[2], p[3])), fmaxf(fmaxf(fmaxf(p[4], p[5]), fmaxf(p[6], p[7])), fmaxf(p[8], p[9])));
                const float m1 = __shfl_xor_sync(~0u, m, 1), m2 = __shfl_xor_sync(~0u, m, 2), m3 = __shfl_xor_sync(~0u, m, 3);
                uint32_t vm[4];
                ldsm4t(vm, oa + C_QKV + 16 * 272);
                m = fmaxf(fmaxf(m, m1), fmaxf(m2, m3));
                const float ms = m * sl2e;
#pragma unroll
                for (int i = 0; i < 10; i++) p[i] = ex2(fmaf(p[i], sl2e, -ms));
                const uint32_t b0 = pack2(p[0], p[1]), b1 = pack2(p[2], p[3]), b2 = pack2(p[4], p[5]), b3 = pack2(p[6], p[7]), b4 = pack2(p[8], p[9]);
                const uint32_t one = 0x3f803f80u;
                float o0[4] = {0.f, 0.f, 0.f, 0.f}, o1[4] = {0.f, 0.f, 0.f, 0.f}, sm[4] = {0.f, 0.f, 0.f, 0.f};
                mma16816(sm, one, one, one, one, b0, b1);
                mma16816(o0, va[0][0], va[0][1], va[0][2], va[0][3], b0, b1);
                mma16816(o1, va[2][0], va[2][1], va[2][2], va[2][3], b0, b1);
                mma16816(sm, one, one, one, one, b2, b3);
                mma16816(o0, va[1][0], va[1][1], va[1][2], va[1][3], b2, b3);
                mma16816(o1, va[3][0], va[3][1], va[3][2], va[3][3], b2, b3);
                mma1688(sm, one, one, b4);
                mma1688(o0, vm[0], vm[1], b4);
                mma1688(o1, vm[2], vm[3], b4);
                float i0, i1;
                asm("rcp.approx.ftz.f32 %0, %1;" : "=f"(i0) : "f"(sm[0]));
                asm("rcp.approx.ftz.f32 %0, %1;" : "=f"(i1) : "f"(sm[1]));
                stsm4t(oa + C_OB, pack2(o0[0] * i0, o0[1] * i1), pack2(o0[2] * i0, o0[3] * i1),
                       pack2(o1[0] * i0, o1[1] * i1), pack2(o1[2] * i0, o1[3] * i1));
            }
            TS(8);
            __syncthreads();
            TS(9);
            uint32_t ob[4][4];
#pragma unroll
            for (int i = 0; i < 4; i++) ldsm4(ob[i], lm + C_OB + i * 64);
            if (three) {
#pragma unroll
                for (int i = 0; i < 8; i++) lds128(wc[i], W2A(8 + i));
                project(wb, ob, 1);
                project(wo0, ob, 0);
                project(wc, ob, 2);
            } else {
                project(wb, ob, 1);
                project(wo0, ob, 0);
            }
        }
        TS(10);
        __syncthreads();
        uint32_t eo = (128 + (s + 1) * 4 + (w >> 1)) * 8192 + (((s < 31 ? msel0 : msel1) >> ((s + 1) & 31)) & 1) * 4096 + (w & 1) * 2048 + lane * 8;
        if (r == 0) {
            TS(11); TS(12);
            stage_w1();
            publish_kvm(s);
            if (s < NSEG - 2) mbar_wait_u(bar_kv, (s + 1) & 1);
            mbar_wait_u(bar_go, s & 1);
            if (w < 4) eo = delayed<DLY0>(eo, lane); else eo = delayed<DLY0A>(eo, lane);
        } else {
            const int j = 2 * h + r - 1;
            if (w < 4) {
                const char* src = (const char*)g_x + delayed<DLY3>((j * 2 + (w >> 1)) * 8192 + (psel & 64) * 64 + (w & 1) * 2048 + t * 64 + g * 8, lane);
                const char* dst = (const char*)g_x + pin((128 + (s + 1) * 4 + (j >> 4)) * 8192 + (j & 15) * 256 + w * 64 + (t & 1) * 4096 + g * 8);
                const uint64_t v = poll_sum(src, tag, (lane & 4) ? 0x3f800000u : 0x00003f80u);
                TS(11);
                asm volatile("st.relaxed.gpu.global.b64 [%0], %1;" ::"l"(dst), "l"(v) : "memory");
                asm volatile("bar.arrive 1, 256;" ::: "memory");
                TS(12);
                stage_w1();
                if (s < NSEG - 2) mbar_wait_u(bar_kv, (s + 1) & 1);
                eo = delayed<DLY1>(eo, lane);
            } else {
                if (w >= 6 && s + 3 < NSEG)
                    asm volatile("prefetch.global.L2 [%0];" ::"l"(g_x + (128 + (s + 3) * 4 + (j >> 4)) * 1024 + (w & 1) * 512 + (j & 15) * 32 + lane) : "memory");
                stage_w1();
                if (s < NSEG - 2) mbar_wait_u(bar_kv, (s + 1) & 1);
                TS(11);
                bar_sync(1, 256);
                TS(12);
                if (w == 4 && r == 1)
                    asm volatile("{\n.reg .pred p;\n.reg .u32 a;\nelect.sync _|p, -1;\nmapa.shared::cluster.u32 a, %0, %1;\n"
                                 "@p mbarrier.arrive.relaxed.cluster.shared::cluster.b64 _, [a];\n}" ::"r"(bar_go), "r"((h % (CLS / 3)) * 3) : "memory");
                eo = delayed<DLY1A>(eo, lane);
            }
        }
        { const int s_ = s; { const int s = s_ + 1; TS(0); } }
        poll_state(bm, (const char*)g_x + eo);
    }
    mbar_wait_u(bar_x, (NSEG - 1) & 1);
    if (r == 0) publish_kvm(NSEG - 1);
    asm volatile("barrier.cluster.arrive.relaxed.aligned;\nbarrier.cluster.wait.aligned;" ::: "memory");
}

constexpr int S4_US = 4368;
constexpr int S4_RS = 8848;
constexpr int S4_KS = 1296;
constexpr int S4_U = 0, S4_R = 16 * S4_US, S4_K = S4_R + 16 * S4_RS;
constexpr int S4_SMEM = S4_K + 16 * S4_KS;
constexpr int S4_SIG = 3104, S4_PK = 2 * S4_SIG;

struct cf { float r, i; };
__device__ __forceinline__ cf cmul(cf a, cf b) { return {fmaf(a.r, b.r, -a.i * b.i), fmaf(a.r, b.i, a.i * b.r)}; }
__device__ __forceinline__ cf cmulc(cf a, cf b) { return {fmaf(a.r, b.r, a.i * b.i), fmaf(a.i, b.r, -a.r * b.i)}; }
__device__ __forceinline__ cf csq(cf a) { const float t = a.r * a.i; return {fmaf(a.r, a.r, -a.i * a.i), t + t}; }
__device__ __forceinline__ cf cexp(float l2, float turns) {
    const float mag = ex2(l2), fr = (turns - rintf(turns)) * 6.283185307179586f;
    return {mag * __cosf(fr), mag * __sinf(fr)};
}
__device__ __forceinline__ void sts32(uint32_t a, uint32_t v) { asm volatile("st.shared.u32 [%0], %1;" ::"r"(a), "r"(v) : "memory"); }
__device__ __forceinline__ uint32_t lds16(uint32_t a) {
    uint32_t v;
    asm volatile("ld.shared.u16 %0, [%1];" : "=r"(v) : "r"(a) : "memory");
    return v;
}

template <int M0, int NQ>
__device__ __forceinline__ void s4_class(float (&acc)[16][4], uint32_t sig, uint32_t taps, int x0) {
    constexpr int D0 = M0 / 8, D1 = M0 == 32 ? 9 : 15;
    uint32_t R[D1 - D0 + 2];
#pragma unroll
    for (int D = D0 - 1; D <= D1; D++) {
        if (D < D0 || 8 * D - 7 >= 2 * M0) { R[D - D0 + 1] = 0; continue; }
        const int m = 8 * D + x0;
        uint32_t lo = lds16(taps + m * (2 * NQ)), hi = lds16(taps + (m - 1) * (2 * NQ));
        if (D == D0) { lo = m >= M0 ? lo : 0; hi = m > M0 ? hi : 0; }
        if (D == 2 * D0) { lo = m < 2 * M0 ? lo : 0; hi = m <= 2 * M0 ? hi : 0; }
        R[D - D0 + 1] = lo | (hi << 16);
    }
#pragma unroll
    for (int J = 0; 2 * J + D0 < 16; J++) {
        uint32_t a[4];
        ldsm4t(a, sig + J * 512);
#pragma unroll
        for (int D = D0; D <= D1; D++)
            if (2 * J + D < 16) mma16816(acc[2 * J + D], a[0], a[1], a[2], a[3], R[D - D0 + 1], R[D - D0]);
    }
}

__global__ void __launch_bounds__(512, 1)
k_s4(const bf16* __restrict__ u, const bf16* __restrict__ Are, const bf16* __restrict__ Aim, const bf16* __restrict__ Bre,
     const bf16* __restrict__ Bim, const bf16* __restrict__ Cre, const bf16* __restrict__ Cim, const bf16* __restrict__ logdt,
     const bf16* __restrict__ Dsk, bf16* __restrict__ out) {
    extern __shared__ __align__(16) uint8_t smem_s4[];
    const uint32_t sb = smem_u32(smem_s4);
    asm volatile("griddepcontrol.launch_dependents;");
    const int tid = threadIdx.x, w = __shfl_sync(~0u, tid >> 5, 0), lane = tid & 31, g = lane >> 2, t = lane & 3;
    if (tid == 0) TL(2, 0);
    const int d0 = blockIdx.x * 16;
    const int d = d0 + (w & 1) + ((w >> 1) & 3) * 4 + (w >> 3) * 2;
    const uint32_t tr_off = (lane & 15), tr_l = (lane >> 4) * 16;
    const uint32_t ur = sb + S4_U + w * S4_US, rs = sb + S4_R + w * S4_RS, kd = sb + S4_K + w * S4_KS;
    if (lane < 16) sts128(ur + lane * 16, 0, 0, 0, 0);
    {
        const int o = d * 128 + lane * 4;
        const uint2 ar = __ldg((const uint2*)(Are + o)), ai = __ldg((const uint2*)(Aim + o)), br = __ldg((const uint2*)(Bre + o));
        const uint2 bi = __ldg((const uint2*)(Bim + o)), cr = __ldg((const uint2*)(Cre + o)), ci = __ldg((const uint2*)(Cim + o));
        const float dt = bf_round(expf(__bfloat162float(logdt[d])));
        const bf16* src = u + (size_t)(w * 128 + g) * DM + d0 + 4 * t;
        float T[5][4];
#pragma unroll
        for (int i = 0; i < 5; i++) T[i][0] = T[i][1] = T[i][2] = T[i][3] = 0.f;
        float klast = 0.f;
        const uint32_t wr_ = rs + lane * 272, rd_ = rs + t * 544 + g * 16;
#pragma unroll 1
        for (int c = 0; c < 4; c++) {
            uint2 v[4];
#pragma unroll
            for (int i = 0; i < 4; i++) v[i] = __ldg((const uint2*)(src + (size_t)(c * 32 + i * 8) * DM));
            auto pick = [&](const uint2& x) { const uint32_t y = c < 2 ? x.x : x.y; return (c & 1) ? bf_hi(y) : bf_lo(y); };
            auto pk2 = [](cf x) { return pack2(x.r, x.i); };
            const float l2 = dt * pick(ar) * 1.4426950408889634f, tu = dt * pick(ai) * 0.15915494309189535f;
            const cf z1 = cexp(l2, tu), z2 = csq(z1), z4 = csq(z2), z8 = csq(z4);
            const cf z64 = cexp(l2 * 64.f, tu * 64.f), z128 = csq(z64), z256 = csq(z128), z512 = csq(z256);
            cf a0 = {1.f, 0.f}, a1 = z64;
            cf b0 = cmul({pick(cr), pick(ci)}, {dt * pick(br), dt * pick(bi)});
            b0.i = -b0.i;
            cf b1 = cmulc(b0, z128), b2 = cmulc(b0, z256), y3 = cmulc(b0, z512), b4 = cmulc(y3, z512), b3 = y3;
            const cf y2 = cmulc(b2, z128);
#pragma unroll
            for (int i = 0; i < 8; i++) {
                sts128(wr_ + i * 16, pk2(a0), pk2(a1), pk2(b0), pk2(b1));
                sts128(wr_ + i * 16 + 128, pk2(b2), pk2(b3), pk2(b4), 0);
                b4 = cmulc(b4, z128);
                if (i < 7) {
                    a0 = i == 0 ? z8 : cmul(a0, z8); a1 = cmul(a1, z8);
                    b0 = cmulc(b0, z1); b1 = cmulc(b1, z1);
                    b2 = i == 3 ? y2 : cmulc(b2, z2);
                    if (i & 1) { y3 = cmulc(y3, z128); b3 = y3; } else b3 = cmulc(y3, z4);
                }
            }
            klast += b4.r;
            __syncwarp();
#pragma unroll
            for (int k = 0; k < 8; k++) {
                uint32_t x[4], y[4];
                lds128(x, rd_ + (8 * (k >> 1) + (k & 1)) * 272);
                lds128(y, rd_ + (8 * (k >> 1) + (k & 1)) * 272 + 128);
                mma1688(T[0], x[0], x[1], x[2]);
                mma1688(T[1], x[0], x[1], x[3]);
                mma1688(T[2], x[0], x[1], y[0]);
                mma1688(T[3], x[0], x[1], y[1]);
                mma1688(T[4], x[0], x[1], y[2]);
            }
#pragma unroll
            for (int i = 0; i < 2; i++)
                stsm4t(sb + S4_U + tr_off * S4_US + 256 + (w * 128 + c * 32 + i * 16) * 2 + tr_l, v[2 * i].x, v[2 * i].y, v[2 * i + 1].x, v[2 * i + 1].y);
            __syncwarp();
        }
#pragma unroll
        for (int o2 = 16; o2; o2 >>= 1) klast += __shfl_xor_sync(~0u, klast, o2);
#pragma unroll
        for (int hh = 0; hh < 2; hh++) {
            const int i = g + 8 * hh;
            sts32(kd + (8 * i + 2 * t) * 2, pack2(T[0][2 * hh], T[0][2 * hh + 1]));
            sts32(kd + (128 + 8 * i + 2 * t) * 2, pack2(T[1][2 * hh], T[1][2 * hh + 1]));
            sts32(kd + (256 + 4 * i + 2 * (t & 1) + 64 * (t >> 1)) * 2, pack2(T[2][2 * hh], T[2][2 * hh + 1]));
            sts32(kd + (384 + 2 * i + 32 * t) * 2, pack2(T[3][2 * hh], T[3][2 * hh + 1]));
        }
        asm volatile("stmatrix.sync.aligned.m8n8.x2.trans.shared.b16 [%0], {%1,%2};"
                     ::"r"(kd + 1024 + (lane & 7) * 32 + ((lane >> 3) & 1) * 16), "r"(pack2(T[4][0], T[4][1])), "r"(pack2(T[4][2], T[4][3])) : "memory");
        if (lane == 0) sts32(kd + 1280, pack2(klast, 0.f));
    }
    __syncwarp();
    const uint32_t pk = rs + S4_PK + 64;
    {
#pragma unroll
        for (int i = 0; i < 2; i++) {
            const int x = i * 128 + lane * 4;
            const uint2 c = lds64(kd + x * 2);
            uint32_t p = lds16(kd + x * 2 - 2);
            if (x == 0) p = 0;
            sts128(pk + x * 4, __byte_perm(c.x, p, 0x5410), __byte_perm(c.x, 0, 0x1032), __byte_perm(c.y, c.x, 0x7610), __byte_perm(c.y, 0, 0x1032));
        }
#pragma unroll
        for (int i = 2; i < 4; i++) {
            const int x = i * 128 + lane * 4;
            const uint32_t ab = lds32(kd + 256 + x), c = lds16(kd + 256 + x + 4);
            const uint32_t p = x == 256 ? lds16(kd + 510) : ab;
            sts128(pk + x * 4, __byte_perm(ab, p, 0x5410), __byte_perm(ab, 0, 0x1010), __byte_perm(ab, 0, 0x1032), __byte_perm(c, ab, 0x7610));
        }
        const uint32_t v = lds16(kd + 768), v2 = lds16(kd + 1024);
        if (lane < 24) {
            uint32_t x0 = 0, x1 = 0, x2 = 0, x3 = 0;
            if (lane == 0) { x0 = x1 = x2 = v | (v << 16); x3 = v << 16; }
            if (lane == 12) x3 = v2;
            if (lane == 13) { x0 = v2 | (v2 << 16); x1 = v2 << 16; }
            sts128(lane < 20 ? pk + 2048 + lane * 16 : pk - 64 + (lane - 20) * 16, x0, x1, x2, x3);
        }
        if (lane < 4) sts128(rs + (lane >> 1) * S4_SIG + (lane & 1) * 16, 0, 0, 0, 0);
    }
    __syncthreads();
    float acc[16][4];
#pragma unroll
    for (int i = 0; i < 16; i++) acc[i][0] = acc[i][1] = acc[i][2] = acc[i][3] = 0.f;
    const uint32_t lf = (lane & 7) * 32 + ((lane >> 3) & 1) * 16 + (lane >> 4) * 256;
#pragma unroll 1
    for (int ph = 0; ph < 2; ph++) {
    if (((w >> 2) ^ ph) & 1) {
#pragma unroll
    for (int rg = 3; rg >= 2; rg--) {
#pragma unroll 1
        for (int it = 0; it < (rg == 3 ? 4 : 6); it++) {
            const int n = it * 32 + lane;
            uint32_t x[2][4];
            lds128(x[0], ur + 256 + n * 16 - 16);
            lds128(x[1], ur + 256 + n * 16);
            float e[16], p[15], s[11];
#pragma unroll
            for (int i = 0; i < 8; i++) { e[2 * i] = bf_lo(x[i >> 2][i & 3]); e[2 * i + 1] = bf_hi(x[i >> 2][i & 3]); }
#pragma unroll
            for (int i = 0; i < 15; i++) p[i] = e[i] + e[i + 1];
#pragma unroll
            for (int i = 0; i < 11; i++) s[i] = p[i + 3] + e[i + 5];
            const uint32_t o = rs + 16 + n * 16;
            if (rg == 2) sts128(o, pack2(s[0], s[1]), pack2(s[2], s[3]), pack2(s[4], s[5]), pack2(s[6], s[7]));
#pragma unroll
            for (int i = 0; i < 10; i++) s[i] = p[i + 2] + s[i + 1];
            if (rg == 2) {
                sts64(o + S4_SIG + 8, pack2(s[0], s[1]), pack2(s[2], s[3]));
                sts64(o + S4_SIG + 16, pack2(s[4], s[5]), pack2(s[6], s[7]));
            } else {
#pragma unroll
                for (int i = 0; i < 9; i++) s[i] = p[i + 1] + s[i + 1];
                sts64(o + 8, pack2(s[0], s[1]), pack2(s[2], s[3]));
                sts64(o + 16, pack2(s[4], s[5]), pack2(s[6], s[7]));
#pragma unroll
                for (int i = 0; i < 8; i++) s[i] = p[i] + s[i + 1];
                sts64(o + S4_SIG + 8, pack2(s[0], s[1]), pack2(s[2], s[3]));
                sts64(o + S4_SIG + 16, pack2(s[4], s[5]), pack2(s[6], s[7]));
            }
        }
        __syncwarp();
        if (rg == 3) {
#pragma unroll 1
            for (int q = 1; q <= 2; q++) s4_class<64, 2>(acc, rs + lf + (q == 1 ? 16 : S4_SIG), kd + (384 + q) * 2, g - 2 * t);
        } else {
#pragma unroll 1
            for (int q = 1; q <= 4; q++) s4_class<32, 4>(acc, rs + lf + ((q & 1) ? 0 : S4_SIG) + (q < 3 ? 16 : 0), kd + (256 + q) * 2, g - 2 * t);
        }
        __syncwarp();
    }
    } else
    {
        const uint32_t ub = ur + 256 + lf, kb = pk + (g - 2 * t) * 4;
#pragma unroll 1
        for (int j0 = 0; j0 < 8; j0++) {
            uint32_t B[8][4];
#pragma unroll
            for (int i = 0; i < 8; i++) ldsm4(B[i], ub + i * 512 - j0 * 32);
            auto block = [&](int J, uint32_t a) {
                const uint32_t r0 = lds32(a), rp = lds32(a + 32), rm = lds32(a - 32);
                uint32_t r3;
                asm volatile("ld.volatile.shared.u32 %0, [%1];" : "=r"(r3) : "r"(a) : "memory");
#pragma unroll
                for (int I = J; I < 16; I++)
                    mma16816(acc[I], r0, rp, rm, r3, B[(I - J) >> 1][((I - J) & 1) * 2], B[(I - J) >> 1][((I - J) & 1) * 2 + 1]);
            };
#pragma unroll
            for (int J = 0; J < 4; J++) block(J, kb + j0 * 64 + J * 512);
            if (j0 < 2) { block(4, kb + j0 * 64 + 2048); block(8, kb + j0 * 64 + (544 + 16) * 4); }
        }
    }
    }
    {
        __syncwarp();
#pragma unroll
        for (int i = 0; i < 8; i++)
            stsm4t(rs + lf + i * 512, pack2(acc[2 * i][0], acc[2 * i][1]), pack2(acc[2 * i][2], acc[2 * i][3]),
                   pack2(acc[2 * i + 1][0], acc[2 * i + 1][1]), pack2(acc[2 * i + 1][2], acc[2 * i + 1][3]));
    }
    __syncthreads();
    {
        const uint2 dv = __ldg((const uint2*)(Dsk + d0 + 4 * t));
        bf16* dst = out + (size_t)(w * 128 + g) * 2048 + 1024 + d0 + 4 * t;
#pragma unroll
        for (int i = 0; i < 8; i++) {
            uint32_t y[4], x[4], o[4];
            ldsm4t(y, sb + S4_R + tr_off * S4_RS + (w * 128 + i * 16) * 2 + tr_l);
            ldsm4t(x, sb + S4_U + tr_off * S4_US + 256 + (w * 128 + i * 16) * 2 + tr_l);
#pragma unroll
            for (int j = 0; j < 4; j++)
                asm("{\n.reg .b32 s;\nmul.rn.bf16x2 s, %2, %3;\nadd.rn.bf16x2 %0, %1, s;\n}" : "=r"(o[j]) : "r"(y[j]), "r"(x[j]), "r"((j & 1) ? dv.y : dv.x));
            *reinterpret_cast<uint2*>(dst + (size_t)(i * 16) * 2048) = make_uint2(o[0], o[1]);
            *reinterpret_cast<uint2*>(dst + (size_t)(i * 16 + 8) * 2048) = make_uint2(o[2], o[3]);
        }
    }
    if (tid == 0) TL(2, 1);
}

enum { IT_QA = 0, IT_W256 = 1, IT_W128 = 2, IT_W64 = 3, IT_W64S = 4, IT_END = 7 };
struct BgParams { CUtensorMap mx, mwq, mkv, mkvm, mo, mo2, mo2s, mwo4, mwo2, mwo1; };
#define LOOK 3
#define LOOKL 8
#define LOOKM 5
#define LOOKN 4
#define PWO 40
#define P256 44
#define P128 50
__device__ __forceinline__ uint32_t ld_rlx32(const uint32_t* p) {
    uint32_t v;
    asm volatile("ld.relaxed.gpu.global.u32 %0, [%1];" : "=r"(v) : "l"(p) : "memory");
    return v;
}
struct Sched { uint32_t qb = 0, w0 = 0, w1 = 0; };
__device__ __forceinline__ int next_item(Sched& z) {
    for (int n = 0; n < SPIN_LIMIT; n++) {
        if (z.w0 < z.w1 && (z.qb >= 16 || ld_rlx32(g_flag + 64 + min(z.w0 >> 4, 15u)) >= 16)) {
            const uint32_t i = z.w0, k = i >= 240 ? 1 : z.w1 - i >= 4 && !(i & 3) ? 4 : z.w1 - i >= 2 && !(i & 1) ? 2 : 1;
            z.w0 += k;
            if (i >= 240) return IT_W64S | 15 << 3 | (i - 240) << 7;
            return (k == 4 ? IT_W256 : k == 2 ? IT_W128 : IT_W64) | (i >> 4) << 3 | ((i & 15) / k) << 7;
        }
        const uint32_t wo = ld_rlx32(g_flag + 97), prog = ld_acq32(g_flag + 98);
        z.qb = max(z.qb, ld_rlx32(g_flag + 96));
        const bool wo_ready = z.w0 >= z.w1 && wo < 272 && (z.qb >= 16 || ld_rlx32(g_flag + 64 + min(wo >> 4, 15u)) >= 16);
        if (z.qb < 16 && prog + (z.qb == 15 ? LOOKL : z.qb == 14 ? LOOKM : z.qb == 13 ? LOOKN : LOOK) >= 4 * z.qb + 4 && !(wo_ready && prog <= PWO)) {
            const uint32_t i = atomicAdd(g_flag + 80 + z.qb, 1);
            if (i == 15) atomicMax(g_flag + 96, z.qb + 1);
            if (i < 16) return IT_QA | z.qb << 3 | i << 7;
            z.qb++;
            continue;
        }
        if (z.w0 < z.w1) {
            if (z.qb >= 16) continue;
        } else if (wo >= 272) {
            if (z.qb >= 16) return IT_END;
        } else if (wo_ready) {
            const uint32_t k = prog <= P256 ? 4 : prog <= P128 ? 2 : 1;
            z.w0 = atomicAdd(g_flag + 97, k);
            z.w1 = min(z.w0 + k, 272u);
            continue;
        }
        __nanosleep(300);
    }
    __trap();
    return IT_END;
}
constexpr int B_OST = NSTAGE * STAGE_BYTES + 1024;
constexpr int BG_SMEM = B_OST + 32768;

template <int BM, int BN, int KPS, typename ACC>
__device__ __forceinline__ void gemm_mainloop(ACC& acc, const GemmSmem& g, int cw, int rounds, uint32_t& round) {
#pragma unroll
    for (int i = 0; i < BN / 2; i++) acc[i] = 0.f;
#pragma unroll 1
    for (int k0 = 0; k0 < rounds; k0++, round++) {
#pragma unroll
        for (int s = 0; s < 4; s++) {
            mbar_wait_u(g.full + 8 * s, round & 1);
            gemm_stage<BM, BN, KPS>(acc, g.st + s * STAGE_BYTES, cw, false);
            wg_wait<1>();
            if (s > 0 || k0 > 0) mbar_arrive_one(g.empty + 8 * ((s + 3) & 3), threadIdx.x & 31);
        }
    }
    wg_wait<0>();
    mbar_arrive_one(g.empty + 8 * 3, threadIdx.x & 31);
}

template <int BM, int BN, int KPS>
__device__ __forceinline__ void wo_item(const GemmSmem& g, int cw, uint32_t& round, bf16* dst, int t) {
    if (BM == 64 && cw == 1) {
#pragma unroll 1
        for (int k0 = 0; k0 < 16 / KPS; k0++, round++)
#pragma unroll
            for (int s = 0; s < 4; s++) { mbar_wait_u(g.full + 8 * s, round & 1); mbar_arrive_one(g.empty + 8 * s, threadIdx.x & 31); }
        return;
    }
    float acc[BN / 2];
    gemm_mainloop<BM, BN, KPS>(acc, g, cw, 16 / KPS, round);
#pragma unroll
    for (int G = 0; G < BN / 32; G++)
#pragma unroll
        for (int rr = 0; rr < 2; rr++) {
            uint32_t r0 = pack2(acc[16 * G + 2 * rr], acc[16 * G + 2 * rr + 1]), r1 = pack2(acc[16 * G + 4 + 2 * rr], acc[16 * G + 5 + 2 * rr]);
            uint32_t r2 = pack2(acc[16 * G + 8 + 2 * rr], acc[16 * G + 9 + 2 * rr]), r3 = pack2(acc[16 * G + 12 + 2 * rr], acc[16 * G + 13 + 2 * rr]);
            quad_transpose(r0, r1, r2, r3, t);
            *reinterpret_cast<uint4*>(dst + (size_t)rr * 8 * 2048 + G * 32) = make_uint4(r0, r1, r2, r3);
        }
}

template <int HF>
__device__ __forceinline__ void attend(const uint32_t* q, uint32_t st, uint32_t sm, uint32_t ost, uint32_t bar_free, uint32_t parity, int lane) {
    constexpr int NT = HF ? 5 : 3;
    const int r8 = lane & 7, m4 = lane >> 3, gq = lane >> 2, t = lane & 3;
    const float sl2e = 0.08838834764831845f * 1.4426950408889634f;
    const uint32_t la = r8 * 128 + ((m4 ^ r8) << 4);
    float sc[NT][4];
#pragma unroll
    for (int nt = 0; nt < NT; nt++) sc[nt][0] = sc[nt][1] = sc[nt][2] = sc[nt][3] = 0.f;
#pragma unroll
    for (int kp = 0; kp < 4; kp++)
#pragma unroll
        for (int nt = 0; nt < NT; nt++) {
            uint32_t b[4];
            ldsm4(b, (nt == 0 ? sm + (kp >> 1) * 2048 : st + (kp >> 1) * 8192 + (nt - 1) * 1024) + (la ^ ((kp & 1) << 6)));
            mma16816(sc[nt], q[kp * 8], q[kp * 8 + 1], q[kp * 8 + 2], q[kp * 8 + 3], b[0], b[1]);
            mma16816(sc[nt], q[kp * 8 + 4], q[kp * 8 + 5], q[kp * 8 + 6], q[kp * 8 + 7], b[2], b[3]);
        }
    const float ninf = -3.0e38f;
    if (2 * t > gq) sc[NT - 2][0] = sc[NT - 1][2] = ninf;
    if (2 * t + 1 > gq) sc[NT - 2][1] = sc[NT - 1][3] = ninf;
    sc[NT - 1][0] = sc[NT - 1][1] = ninf;
    uint32_t p[NT][2];
#pragma unroll
    for (int i = 0; i < 2; i++) {
        float m = fmaxf(sc[0][2 * i], sc[0][2 * i + 1]);
#pragma unroll
        for (int nt = 1; nt < NT - 1 + i; nt++) m = fmaxf(m, fmaxf(sc[nt][2 * i], sc[nt][2 * i + 1]));
        m = fmaxf(m, __shfl_xor_sync(~0u, m, 1));
        m = fmaxf(m, __shfl_xor_sync(~0u, m, 2));
        const float ms = m * sl2e;
        float sum = 0.f;
#pragma unroll
        for (int nt = 0; nt < NT - 1 + i; nt++) {
            sc[nt][2 * i] = ex2(fmaf(sc[nt][2 * i], sl2e, -ms));
            sc[nt][2 * i + 1] = ex2(fmaf(sc[nt][2 * i + 1], sl2e, -ms));
            sum += sc[nt][2 * i] + sc[nt][2 * i + 1];
        }
        sum += __shfl_xor_sync(~0u, sum, 1);
        sum += __shfl_xor_sync(~0u, sum, 2);
        float inv;
        asm("rcp.approx.ftz.f32 %0, %1;" : "=f"(inv) : "f"(sum));
#pragma unroll
        for (int nt = 0; nt < NT - 1 + i; nt++) p[nt][i] = pack2(sc[nt][2 * i] * inv, sc[nt][2 * i + 1] * inv);
    }
    p[NT - 1][0] = 0;
    const uint32_t lv = ((m4 & 1) * 8 + r8) * 128 + (((m4 >> 1) ^ r8) << 4);
    mbar_wait_u(bar_free, parity);
#pragma unroll
    for (int G = 0; G < 4; G++) {
        float o[4][4];
#pragma unroll
        for (int i = 0; i < 4; i++) o[i][0] = o[i][1] = o[i][2] = o[i][3] = 0.f;
        uint32_t b[4];
        ldsm4t(b, sm + 4096 + (G >> 1) * 2048 + (la ^ ((G & 1) << 6)));
#pragma unroll
        for (int i = 0; i < 4; i++) mma1688(o[i], p[0][0], p[0][1], b[i]);
#pragma unroll
        for (int kk = 0; kk <= HF; kk++)
#pragma unroll
            for (int i = 0; i < 2; i++) {
                ldsm4t(b, st + 16384 + (G >> 1) * 8192 + kk * 2048 + (lv ^ (((G & 1) * 2 + i) << 5)));
                mma16816(o[2 * i], p[1 + 2 * kk][0], p[1 + 2 * kk][1], p[2 + 2 * kk][0], p[2 + 2 * kk][1], b[0], b[1]);
                mma16816(o[2 * i + 1], p[1 + 2 * kk][0], p[1 + 2 * kk][1], p[2 + 2 * kk][0], p[2 + 2 * kk][1], b[2], b[3]);
            }
#pragma unroll
        for (int i = 0; i < 2; i++)
            asm volatile("stmatrix.sync.aligned.m8n8.x4.shared.b16 [%0], {%1,%2,%3,%4};"
                         ::"r"(ost + (G >> 1) * 16384 + (lv ^ (((G & 1) * 2 + i) << 5))),
                           "r"(pack2(o[2 * i][0], o[2 * i][1])), "r"(pack2(o[2 * i][2], o[2 * i][3])),
                           "r"(pack2(o[2 * i + 1][0], o[2 * i + 1][1])), "r"(pack2(o[2 * i + 1][2], o[2 * i + 1][3])) : "memory");
    }
    asm volatile("fence.proxy.async.shared::cta;" ::: "memory");
    __syncwarp();
}

__device__ __forceinline__ void tma_prefetch3d(const CUtensorMap* m, int c0, int c1, int c2) {
    asm volatile("cp.async.bulk.prefetch.tensor.3d.L2.global [%0, {%1, %2, %3}];" ::"l"(m), "r"(c0), "r"(c1), "r"(c2) : "memory");
}

__global__ void __launch_bounds__(384, 1) k_bg(const __grid_constant__ BgParams P, bf16* __restrict__ out) {
    extern __shared__ __align__(1024) uint8_t smem_gemm[];
    const uint32_t xb = smem_u32(smem_gemm) + NSTAGE * STAGE_BYTES + 128;
    const uint32_t bar_item = xb, bar_o = xb + 16, bar_f = xb + 24, slot = xb + 32, slot_o = xb + 40;
    if (threadIdx.x == 0) { mbar_init(bar_item, 1); mbar_init(bar_item + 8, 1); mbar_init(bar_o, 8); mbar_init(bar_f, 1); }
    GemmSmem g = gemm_setup(smem_gemm, 8);
    const int wg = __shfl_sync(~0u, threadIdx.x >> 7, 0);
    if (wg == 0) {
        asm volatile("setmaxnreg.dec.sync.aligned.u32 40;");
        if (threadIdx.x == 0) {
            uint32_t it = 0;
            Sched z;
            auto acquire = [&](uint32_t bytes) {
                const int s = it & 3;
                mbar_wait(g.empty + 8 * s, ((it >> 2) & 1) ^ 1);
                mbar_expect_tx(g.full + 8 * s, bytes);
                it++;
                return s;
            };
            for (int n = 0;; n++) {
                const int code = next_item(z);
                sts32(slot + (n & 1) * 4, code);
                mbar_arrive(bar_item + (n & 1) * 8);
                const int type = code & 7, blk = (code >> 3) & 15, idx = code >> 7, m0 = blk * 128;
                if (type == IT_END) break;
                if (type == IT_QA) {
                    for (int k = 0; k < 16; k++) {
                        const int s = acquire(STAGE_BYTES);
                        const uint32_t st = g.st + s * STAGE_BYTES, fb = g.full + 8 * s;
                        tma2d(st, &P.mx, k * 64, m0, fb);
                        tma3d(st + 16384, &P.mwq, 0, k * 64, idx * 4, fb);
                        if (k >= 4 && k < 12) tma_prefetch3d(&P.mkv, 0, m0 + (k & 1) * 64, (k & 8) * 8 + idx * 4 + (k & 2));
                    }
                    bool ready = ld_acq32(g_flag + 2 * idx) >= 4 * blk + 4 && ld_acq32(g_flag + 2 * idx + 1) >= 4 * blk + 4;
                    if (ready) asm volatile("fence.proxy.async.global;" ::: "memory");
                    for (int pass = 0; pass < 2; pass++) {
                        for (int s = 0; s < 4; s++) {
                            const uint32_t st = g.st + s * STAGE_BYTES, fb = g.full + 8 * s;
                            if (pass == 0) {
                                acquire(40960);
                                tma3d(st, &P.mkv, 0, m0 + (s & 1) * 64, idx * 4 + (s & 2), fb);
                                tma3d(st + 16384, &P.mkv, 0, m0 + (s & 1) * 64, 64 + idx * 4 + (s & 2), fb);
                            }
                            if (ready) {
                                tma3d(st + 32768, &P.mkvm, 0, blk * 32 + (s & 1) * 16, idx * 4 + (s & 2), fb);
                                tma3d(st + 36864, &P.mkvm, 0, blk * 32 + (s & 1) * 16, 64 + idx * 4 + (s & 2), fb);
                            }
                        }
                        if (ready) break;
                        wait_flag(g_flag + 2 * idx, 4 * blk + 4);
                        wait_flag(g_flag + 2 * idx + 1, 4 * blk + 4);
                        asm volatile("fence.proxy.async.global;" ::: "memory");
                        ready = true;
                    }
                } else {
                    wait_flag(g_flag + 64 + blk, 16);
                    asm volatile("fence.proxy.async.global;" ::: "memory");
                    if (type <= IT_W128) {
                        const int nb = type == IT_W256 ? 4 : 2;
                        for (int k = 0; k < 64; k++) {
                            const int s = acquire(16384 + nb * 8192);
                            const uint32_t st = g.st + s * STAGE_BYTES, fb = g.full + 8 * s;
                            tma2d(st, &P.mo, k * 64, m0, fb);
                            tma3d(st + 16384, nb == 4 ? &P.mwo4 : &P.mwo2, 0, k * 64, idx * nb, fb);
                        }
                    } else {
                        const uint32_t ab = type == IT_W64 ? 32768 : 16384;
                        for (int k = 0; k < 32; k++) {
                            const int s = acquire(ab + 16384);
                            const uint32_t st = g.st + s * STAGE_BYTES, fb = g.full + 8 * s;
                            tma3d(st, type == IT_W64 ? &P.mo2 : &P.mo2s, 0, m0 + (idx >> 4) * 64, k * 2, fb);
                            tma3d(st + ab, &P.mwo1, 0, k * 128, idx & 15, fb);
                        }
                    }
                }
            }
        } else if (threadIdx.x == 32) {
            for (;;) {
                mbar_wait(bar_o, 0);
                const int code = lds32(slot_o), blk = (code >> 3) & 15, idx = (code >> 7) & 31;
                if ((code & 7) == IT_END) break;
                for (int hh = 0; hh < 2; hh++) {
                    if (hh) mbar_wait(bar_o, 1);
                    asm volatile("cp.async.bulk.tensor.3d.global.shared::cta.bulk_group [%0, {%2, %3, %4}], [%1];\n"
                                 "cp.async.bulk.commit_group;\ncp.async.bulk.wait_group.read 0;"
                                 ::"l"(&P.mo2), "r"(g.st + B_OST), "r"(0), "r"(blk * 128), "r"(idx * 4 + hh * 2) : "memory");
                    mbar_arrive(bar_f);
                }
                asm volatile("cp.async.bulk.wait_group 0;\nfence.acq_rel.gpu;\nred.relaxed.gpu.global.add.u32 [%0], 1;"
                             ::"l"(g_flag + 64 + blk) : "memory");
            }
        }
    } else {
        asm volatile("setmaxnreg.inc.sync.aligned.u32 232;");
        const int cw = wg - 1, ww = __shfl_sync(~0u, (threadIdx.x >> 5) & 3, 0), lane = threadIdx.x & 31;
        uint32_t round = 0;
#pragma unroll 1
        for (int n = 0;; n++) {
            mbar_wait_u(bar_item + (n & 1) * 8, (n >> 1) & 1);
            const int code = __shfl_sync(~0u, lds32(slot + (n & 1) * 4), 0);
            const int type = code & 7, blk = (code >> 3) & 15, idx = (code >> 7) & 31;
#define TLB(slot_)
            if (type == IT_END) {
                mbar_wait_u(bar_f, 1);
                if (threadIdx.x == 128) sts32(slot_o, IT_END);
                __syncwarp();
                mbar_arrive_one(bar_o, lane);
                break;
            }
            TLB(0);
            if (type == IT_QA) {
                uint32_t q[64];
                {
                    float acc[128];
                    gemm_mainloop<128, 256, 1>(acc, g, cw, 4, round);
#pragma unroll
                    for (int i = 0; i < 64; i++) q[i] = pack2(acc[2 * i], acc[2 * i + 1]);
                }
                if (threadIdx.x == 128) sts32(slot_o, code);
                TLB(2);
#pragma unroll
                for (int hh = 0; hh < 2; hh++) {
                    const uint32_t st = g.st + (2 * hh + cw) * STAGE_BYTES, ost = g.st + B_OST + (cw * 4 + ww) * 2048;
                    mbar_wait_u(g.full + 16 * hh, round & 1);
                    mbar_wait_u(g.full + 16 * hh + 8, round & 1);
                    if (hh == 0) { TLB(3); }
                    if (ww & 1) attend<1>(q + 32 * hh, st + (ww >> 1) * 4096, st + 32768 + (ww >> 1) * 1024, ost, bar_f, hh ^ 1, lane);
                    else attend<0>(q + 32 * hh, st + (ww >> 1) * 4096, st + 32768 + (ww >> 1) * 1024, ost, bar_f, hh ^ 1, lane);
                    mbar_arrive_one(bar_o, lane);
                    mbar_arrive_one(g.empty + 16 * hh, lane);
                    mbar_arrive_one(g.empty + 16 * hh + 8, lane);
                }
                round++;
            } else {
                bf16* dst = out + (size_t)(blk * 128 + cw * 64 + ww * 16 + (lane >> 2)) * 2048 + (lane & 3) * 8;
                if (type == IT_W256) wo_item<128, 256, 1>(g, cw, round, dst + idx * 256, lane & 3);
                else if (type == IT_W128) wo_item<128, 128, 1>(g, cw, round, dst + idx * 128, lane & 3);
                else if (type == IT_W64) wo_item<128, 64, 2>(g, cw, round, dst + idx * 64, lane & 3);
                else wo_item<64, 64, 2>(g, cw, round, dst + (size_t)(idx >> 4) * 64 * 2048 + (idx & 15) * 64, lane & 3);
            }
            TLB(1);
        }
    }
}

typedef CUresult (*EncodeFn)(CUtensorMap*, CUtensorMapDataType, cuuint32_t, void*, const cuuint64_t*, const cuuint64_t*,
                             const cuuint32_t*, const cuuint32_t*, CUtensorMapInterleave, CUtensorMapSwizzle,
                             CUtensorMapL2promotion, CUtensorMapFloatOOBfill);

static void map2d(EncodeFn enc, CUtensorMap* m, const void* p, int rows, int cols, int box_rows) {
    cuuint64_t dim[2] = {(cuuint64_t)cols, (cuuint64_t)rows}, str[1] = {(cuuint64_t)cols * 2};
    cuuint32_t box[2] = {64, (cuuint32_t)box_rows}, es[2] = {1, 1};
    enc(m, CU_TENSOR_MAP_DATA_TYPE_BFLOAT16, 2, (void*)p, dim, str, box, es, CU_TENSOR_MAP_INTERLEAVE_NONE,
        CU_TENSOR_MAP_SWIZZLE_128B, CU_TENSOR_MAP_L2_PROMOTION_L2_256B, CU_TENSOR_MAP_FLOAT_OOB_FILL_NONE);
}
static void map3d(EncodeFn enc, CUtensorMap* m, const void* p, int rows, int cols, int box_rows, int nblk) {
    cuuint64_t dim[3] = {64, (cuuint64_t)rows, (cuuint64_t)cols / 64}, str[2] = {(cuuint64_t)cols * 2, 128};
    cuuint32_t box[3] = {64, (cuuint32_t)box_rows, (cuuint32_t)nblk}, es[3] = {1, 1, 1};
    enc(m, CU_TENSOR_MAP_DATA_TYPE_BFLOAT16, 3, (void*)p, dim, str, box, es, CU_TENSOR_MAP_INTERLEAVE_NONE,
        CU_TENSOR_MAP_SWIZZLE_128B, CU_TENSOR_MAP_L2_PROMOTION_L2_256B, CU_TENSOR_MAP_FLOAT_OOB_FILL_NONE);
}

#define USE_PDL 1

extern "C" void kernel_launch(void* const* d_in, const int* in_sizes, int n_in, void* d_out, int out_size) {
    const bf16 *x = (const bf16*)d_in[0], *mem0 = (const bf16*)d_in[1], *Wq = (const bf16*)d_in[2], *Wk = (const bf16*)d_in[3];
    const bf16 *Wv = (const bf16*)d_in[4], *Wo = (const bf16*)d_in[5];
    const bf16 *u = (const bf16*)d_in[7], *Are = (const bf16*)d_in[8], *Aim = (const bf16*)d_in[9], *Bre = (const bf16*)d_in[10];
    const bf16 *Bim = (const bf16*)d_in[11], *Cre = (const bf16*)d_in[12], *Cim = (const bf16*)d_in[13];
    const bf16 *logdt = (const bf16*)d_in[14], *Dsk = (const bf16*)d_in[15];
    bf16* out = (bf16*)d_out;

    void* fn = nullptr;
    cudaDriverEntryPointQueryResult qr;
    cudaGetDriverEntryPoint("cuTensorMapEncodeTiled", &fn, cudaEnableDefault, &qr);
    EncodeFn enc = (EncodeFn)fn;
    void *kv, *kvm, *o;
    cudaGetSymbolAddress(&kv, g_kv);
    cudaGetSymbolAddress(&kvm, g_kvm);
    cudaGetSymbolAddress(&o, g_o);
    CUtensorMap mwk, mwv, mkv2;
    BgParams P;
    map2d(enc, &P.mx, x, SEQ, DM, 128);
    map2d(enc, &P.mo, o, SEQ, HD, 128);
    map3d(enc, &P.mo2, o, SEQ, HD, 128, 2);
    map3d(enc, &P.mo2s, o, SEQ, HD, 64, 2);
    map3d(enc, &P.mwq, Wq, DM, HD, 64, 4);
    map3d(enc, &mwk, Wk, DM, HD, 64, 4);
    map3d(enc, &mwv, Wv, DM, HD, 64, 4);
    map3d(enc, &P.mwo4, Wo, HD, DM, 64, 4);
    map3d(enc, &P.mwo2, Wo, HD, DM, 64, 2);
    map3d(enc, &P.mwo1, Wo, HD, DM, 128, 1);
    map3d(enc, &mkv2, kv, SEQ, 8192, 32, 2);
    map3d(enc, &P.mkv, kv, SEQ, 8192, 64, 2);
    map3d(enc, &P.mkvm, kvm, NSEG * 8, 8192, 16, 2);
    cudaFuncSetAttribute(k_kv, cudaFuncAttributeMaxDynamicSharedMemorySize, GEMM_SMEM);
    cudaFuncSetAttribute(k_bg, cudaFuncAttributeMaxDynamicSharedMemorySize, BG_SMEM);
    cudaFuncSetAttribute(k_chain, cudaFuncAttributeMaxDynamicSharedMemorySize, CHAIN_SMEM);
    cudaFuncSetAttribute(k_s4, cudaFuncAttributeMaxDynamicSharedMemorySize, S4_SMEM);

    cudaStream_t st = cudaStreamPerThread;
    cudaLaunchAttribute pdl[1], cls[1];
    pdl[0].id = cudaLaunchAttributeProgrammaticStreamSerialization;
    pdl[0].val.programmaticStreamSerializationAllowed = 1;
    cls[0].id = cudaLaunchAttributeClusterDimension;
    cls[0].val.clusterDim.x = CLS; cls[0].val.clusterDim.y = 1; cls[0].val.clusterDim.z = 1;
    cudaLaunchConfig_t cfg = {};
    cfg.stream = st; cfg.attrs = cls; cfg.numAttrs = 1;
    cfg.gridDim = dim3(96); cfg.blockDim = dim3(384); cfg.dynamicSmemBytes = GEMM_SMEM;
    cudaLaunchKernelEx(&cfg, k_kv, P.mx, mwk, mwv, Wq, Wk, Wo, 0);
    cfg.attrs = pdl; cfg.numAttrs = 1;
    cfg.gridDim = dim3(36);
    cudaLaunchKernelEx(&cfg, k_kv, P.mx, mwk, mwv, Wq, Wk, Wo, 96);
    cfg.gridDim = dim3(96); cfg.blockDim = dim3(256); cfg.dynamicSmemBytes = CHAIN_SMEM;
    cudaLaunchKernelEx(&cfg, k_chain, mem0, Wq, Wk, Wv, Wo, mkv2);
    cfg.numAttrs = USE_PDL;
    cfg.gridDim = dim3(64); cfg.blockDim = dim3(512); cfg.dynamicSmemBytes = S4_SMEM;
    cudaLaunchKernelEx(&cfg, k_s4, u, Are, Aim, Bre, Bim, Cre, Cim, logdt, Dsk, out);
    cfg.gridDim = dim3(132); cfg.blockDim = dim3(384); cfg.dynamicSmemBytes = BG_SMEM;
    cudaLaunchKernelEx(&cfg, k_bg, P, out);
}
```

```cpp
#include <cuda_runtime.h>
#include <cuda_bf16.h>
#include <cuda.h>
#include <stdint.h>

typedef __nv_bfloat16 bf16;

constexpr int SEQ = 2048, DM = 1024, HD = 4096, NSEG = 64;

__device__ __align__(1024) bf16 g_kv[(size_t)SEQ * 8192];
__device__ __align__(1024) bf16 g_kvm[(size_t)NSEG * 8 * 8192];
__device__ __align__(1024) bf16 g_o[(size_t)SEQ * HD];
constexpr int XPAIRS = 128 + NSEG * 4;
__device__ __align__(8192) uint2 g_x[XPAIRS * 1024];
__device__ uint32_t g_home[XPAIRS];
__device__ uint32_t g_side[256];
__device__ __align__(1024) uint32_t g_flag[256];

#define TL(kern, slot)

__device__ __forceinline__ uint32_t smem_u32(const void* p) { return (uint32_t)__cvta_generic_to_shared(p); }
__device__ __forceinline__ void mbar_init(uint32_t bar, uint32_t cnt) {
    asm volatile("mbarrier.init.shared::cta.b64 [%0], %1;" ::"r"(bar), "r"(cnt) : "memory");
}
__device__ __forceinline__ void mbar_expect_tx(uint32_t bar, uint32_t bytes) {
    asm volatile("mbarrier.arrive.expect_tx.shared::cta.b64 _, [%0], %1;" ::"r"(bar), "r"(bytes) : "memory");
}
__device__ __forceinline__ void mbar_arrive(uint32_t bar) {
    asm volatile("mbarrier.arrive.shared::cta.b64 _, [%0];" ::"r"(bar) : "memory");
}
__device__ __forceinline__ bool mbar_try(uint32_t bar, uint32_t parity) {
    uint32_t ok;
    asm volatile("{\n.reg .pred p;\nmbarrier.try_wait.parity.shared::cta.b64 p, [%1], %2;\nselp.u32 %0, 1, 0, p;\n}"
                 : "=r"(ok) : "r"(bar), "r"(parity) : "memory");
    return ok;
}
constexpr int SPIN_LIMIT = 1 << 20;
__device__ __forceinline__ void mbar_wait(uint32_t bar, uint32_t parity) {
    int n = 0;
    while (!mbar_try(bar, parity)) { if (++n > SPIN_LIMIT) __trap(); }
}
__device__ __forceinline__ void mbar_wait_u(uint32_t bar, uint32_t parity) {
    asm volatile("{\n.reg .pred p;\n.reg .u32 n;\n"
                 "mbarrier.try_wait.parity.shared::cta.b64 p, [%0], %1;\n@p bra.uni DONE;\nmov.u32 n, 0;\n"
                 "AGAIN:\nmbarrier.try_wait.parity.shared::cta.b64 p, [%0], %1;\n@p bra.uni DONE;\n"
                 "add.u32 n, n, 1;\nsetp.lt.u32 p, n, 0x100000;\n@p bra.uni AGAIN;\ntrap;\nDONE:\n}"
                 ::"r"(bar), "r"(parity) : "memory");
}
__device__ __forceinline__ void tma2d(uint32_t dst, const CUtensorMap* m, int c0, int c1, uint32_t bar) {
    asm volatile("cp.async.bulk.tensor.2d.shared::cluster.global.mbarrier::complete_tx::bytes [%0], [%1, {%3, %4}], [%2];"
                 ::"r"(dst), "l"(m), "r"(bar), "r"(c0), "r"(c1) : "memory");
}
__device__ __forceinline__ void tma3d(uint32_t dst, const CUtensorMap* m, int c0, int c1, int c2, uint32_t bar) {
    asm volatile("cp.async.bulk.tensor.3d.shared::cluster.global.mbarrier::complete_tx::bytes [%0], [%1, {%3, %4, %5}], [%2];"
                 ::"r"(dst), "l"(m), "r"(bar), "r"(c0), "r"(c1), "r"(c2) : "memory");
}
__device__ __forceinline__ uint32_t pack2(float lo, float hi) {
    uint32_t r;
    asm("cvt.rn.bf16x2.f32 %0, %1, %2;" : "=r"(r) : "f"(hi), "f"(lo));
    return r;
}
__device__ __forceinline__ float bf_lo(uint32_t v) { return __uint_as_float(v << 16); }
__device__ __forceinline__ float bf_hi(uint32_t v) { return __uint_as_float(v & 0xffff0000u); }
__device__ __forceinline__ float bf_round(float x) { return bf_lo(pack2(x, 0.f)); }
__device__ __forceinline__ float ex2(float x) { float y; asm("ex2.approx.ftz.f32 %0, %1;" : "=f"(y) : "f"(x)); return y; }
__device__ __forceinline__ void mma16816(float (&c)[4], uint32_t a0, uint32_t a1, uint32_t a2, uint32_t a3, uint32_t b0, uint32_t b1) {
    asm volatile("mma.sync.aligned.m16n8k16.row.col.f32.bf16.bf16.f32 {%0,%1,%2,%3}, {%4,%5,%6,%7}, {%8,%9}, {%0,%1,%2,%3};"
                 : "+f"(c[0]), "+f"(c[1]), "+f"(c[2]), "+f"(c[3]) : "r"(a0), "r"(a1), "r"(a2), "r"(a3), "r"(b0), "r"(b1));
}
__device__ __forceinline__ void mma1688(float (&c)[4], uint32_t a0, uint32_t a1, uint32_t b0) {
    asm volatile("mma.sync.aligned.m16n8k8.row.col.f32.bf16.bf16.f32 {%0,%1,%2,%3}, {%4,%5}, {%6}, {%0,%1,%2,%3};"
                 : "+f"(c[0]), "+f"(c[1]), "+f"(c[2]), "+f"(c[3]) : "r"(a0), "r"(a1), "r"(b0));
}
__device__ __forceinline__ void ldsm4(uint32_t (&r)[4], uint32_t a) {
    asm volatile("ldmatrix.sync.aligned.m8n8.x4.shared.b16 {%0,%1,%2,%3}, [%4];"
                 : "=r"(r[0]), "=r"(r[1]), "=r"(r[2]), "=r"(r[3]) : "r"(a) : "memory");
}
__device__ __forceinline__ void ldsm4t(uint32_t (&r)[4], uint32_t a) {
    asm volatile("ldmatrix.sync.aligned.m8n8.x4.trans.shared.b16 {%0,%1,%2,%3}, [%4];"
                 : "=r"(r[0]), "=r"(r[1]), "=r"(r[2]), "=r"(r[3]) : "r"(a) : "memory");
}
__device__ __forceinline__ void ldsm2t(uint32_t& r0, uint32_t& r1, uint32_t a) {
    asm volatile("ldmatrix.sync.aligned.m8n8.x2.trans.shared.b16 {%0,%1}, [%2];" : "=r"(r0), "=r"(r1) : "r"(a) : "memory");
}
__device__ __forceinline__ void stsm4t(uint32_t a, uint32_t r0, uint32_t r1, uint32_t r2, uint32_t r3) {
    asm volatile("stmatrix.sync.aligned.m8n8.x4.trans.shared.b16 [%0], {%1,%2,%3,%4};"
                 ::"r"(a), "r"(r0), "r"(r1), "r"(r2), "r"(r3) : "memory");
}
__device__ __forceinline__ void lds128(uint32_t (&r)[4], uint32_t a) {
    asm volatile("ld.shared.v4.u32 {%0,%1,%2,%3}, [%4];" : "=r"(r[0]), "=r"(r[1]), "=r"(r[2]), "=r"(r[3]) : "r"(a) : "memory");
}
__device__ __forceinline__ float4 lds128f(uint32_t a) {
    float4 v;
    asm volatile("ld.shared.v4.f32 {%0,%1,%2,%3}, [%4];" : "=f"(v.x), "=f"(v.y), "=f"(v.z), "=f"(v.w) : "r"(a) : "memory");
    return v;
}
__device__ __forceinline__ float2 lds64f(uint32_t a) {
    float2 v;
    asm volatile("ld.shared.v2.f32 {%0,%1}, [%2];" : "=f"(v.x), "=f"(v.y) : "r"(a) : "memory");
    return v;
}
__device__ __forceinline__ uint32_t lds32(uint32_t a) {
    uint32_t v;
    asm volatile("ld.shared.u32 %0, [%1];" : "=r"(v) : "r"(a) : "memory");
    return v;
}
__device__ __forceinline__ void sts128(uint32_t a, uint32_t r0, uint32_t r1, uint32_t r2, uint32_t r3) {
    asm volatile("st.shared.v4.u32 [%0], {%1,%2,%3,%4};" ::"r"(a), "r"(r0), "r"(r1), "r"(r2), "r"(r3) : "memory");
}
__device__ __forceinline__ void sts128f(uint32_t a, float r0, float r1, float r2, float r3) {
    asm volatile("st.shared.v4.f32 [%0], {%1,%2,%3,%4};" ::"r"(a), "f"(r0), "f"(r1), "f"(r2), "f"(r3) : "memory");
}
__device__ __forceinline__ void sts64(uint32_t a, uint32_t r0, uint32_t r1) {
    asm volatile("st.shared.v2.u32 [%0], {%1,%2};" ::"r"(a), "r"(r0), "r"(r1) : "memory");
}
__device__ __forceinline__ void sts64f(uint32_t a, float r0, float r1) {
    asm volatile("st.shared.v2.f32 [%0], {%1,%2};" ::"r"(a), "f"(r0), "f"(r1) : "memory");
}
__device__ __forceinline__ void sts32f(uint32_t a, float r0) {
    asm volatile("st.shared.f32 [%0], %1;" ::"r"(a), "f"(r0) : "memory");
}
__device__ __forceinline__ uint2 ld_rlx64(const uint2* p) {
    uint2 v;
    asm volatile("{\n.reg .b64 t;\nld.relaxed.gpu.global.b64 t, [%2];\nmov.b64 {%0,%1}, t;\n}" : "=r"(v.x), "=r"(v.y) : "l"(p) : "memory");
    return v;
}
__device__ __forceinline__ void st_rlx64(uint2* p, uint32_t x, uint32_t y) {
    asm volatile("{\n.reg .b64 t;\nmov.b64 t, {%1,%2};\nst.relaxed.gpu.global.b64 [%0], t;\n}" ::"l"(p), "r"(x), "r"(y) : "memory");
}
__device__ __forceinline__ uint32_t ld_acq32(const uint32_t* p) {
    uint32_t v;
    asm volatile("ld.acquire.gpu.global.u32 %0, [%1];" : "=r"(v) : "l"(p) : "memory");
    return v;
}
__device__ __forceinline__ void wait_flag(const uint32_t* p, uint32_t need) {
    int n = 0;
    while (ld_acq32(p) < need) { __nanosleep(200); if (++n > SPIN_LIMIT) __trap(); }
}
__device__ __forceinline__ void bar_sync(int id, int n) { asm volatile("bar.sync %0, %1;" ::"r"(id), "r"(n) : "memory"); }
__device__ __forceinline__ void wg_fence() { asm volatile("wgmma.fence.sync.aligned;" ::: "memory"); }
__device__ __forceinline__ void wg_commit() { asm volatile("wgmma.commit_group.sync.aligned;" ::: "memory"); }
template <int N> __device__ __forceinline__ void wg_wait() { asm volatile("wgmma.wait_group.sync.aligned %0;" ::"n"(N) : "memory"); }
__device__ __forceinline__ uint64_t desc_sw128(uint32_t addr, uint32_t lbo, uint32_t sbo) {
    return (uint64_t)((addr & 0x3FFFF) >> 4) | ((uint64_t)(lbo >> 4) << 16) | ((uint64_t)(sbo >> 4) << 32) | (1ull << 62);
}
__device__ __forceinline__ void quad_transpose(uint32_t& r0, uint32_t& r1, uint32_t& r2, uint32_t& r3, int t) {
    const bool o = t & 1, h = t & 2;
    uint32_t s0 = __shfl_xor_sync(~0u, o ? r0 : r1, 1), s1 = __shfl_xor_sync(~0u, o ? r2 : r3, 1);
    uint32_t a0 = o ? s0 : r0, a1 = o ? r1 : s0, a2 = o ? s1 : r2, a3 = o ? r3 : s1;
    s0 = __shfl_xor_sync(~0u, h ? a0 : a2, 2); s1 = __shfl_xor_sync(~0u, h ? a1 : a3, 2);
    r0 = h ? s0 : a0; r1 = h ? s1 : a1; r2 = h ? a2 : s0; r3 = h ? a3 : s1;
}

__device__ __forceinline__ void wgmma_n256(float (&d)[128], uint64_t da, uint64_t db, int sd) {
    asm volatile("{\n.reg .pred p;\nsetp.ne.b32 p, %130, 0;\n"
        "wgmma.mma_async.sync.aligned.m64n256k16.f32.bf16.bf16 "
        "{%0,%1,%2,%3,%4,%5,%6,%7,%8,%9,%10,%11,%12,%13,%14,%15,"
        "%16,%17,%18,%19,%20,%21,%22,%23,%24,%25,%26,%27,%28,%29,%30,%31,"
        "%32,%33,%34,%35,%36,%37,%38,%39,%40,%41,%42,%43,%44,%45,%46,%47,"
        "%48,%49,%50,%51,%52,%53,%54,%55,%56,%57,%58,%59,%60,%61,%62,%63,"
        "%64,%65,%66,%67,%68,%69,%70,%71,%72,%73,%74,%75,%76,%77,%78,%79,"
        "%80,%81,%82,%83,%84,%85,%86,%87,%88,%89,%90,%91,%92,%93,%94,%95,"
        "%96,%97,%98,%99,%100,%101,%102,%103,%104,%105,%106,%107,%108,%109,%110,%111,"
        "%112,%113,%114,%115,%116,%117,%118,%119,%120,%121,%122,%123,%124,%125,%126,%127}, %128, %129, p, 1, 1, 0, 1;\n}\n"
        : "+f"(d[0]), "+f"(d[1]), "+f"(d[2]), "+f"(d[3]), "+f"(d[4]), "+f"(d[5]), "+f"(d[6]), "+f"(d[7]),
          "+f"(d[8]), "+f"(d[9]), "+f"(d[10]), "+f"(d[11]), "+f"(d[12]), "+f"(d[13]), "+f"(d[14]), "+f"(d[15]),
          "+f"(d[16]), "+f"(d[17]), "+f"(d[18]), "+f"(d[19]), "+f"(d[20]), "+f"(d[21]), "+f"(d[22]), "+f"(d[23]),
          "+f"(d[24]), "+f"(d[25]), "+f"(d[26]), "+f"(d[27]), "+f"(d[28]), "+f"(d[29]), "+f"(d[30]), "+f"(d[31]),
          "+f"(d[32]), "+f"(d[33]), "+f"(d[34]), "+f"(d[35]), "+f"(d[36]), "+f"(d[37]), "+f"(d[38]), "+f"(d[39]),
          "+f"(d[40]), "+f"(d[41]), "+f"(d[42]), "+f"(d[43]), "+f"(d[44]), "+f"(d[45]), "+f"(d[46]), "+f"(d[47]),
          "+f"(d[48]), "+f"(d[49]), "+f"(d[50]), "+f"(d[51]), "+f"(d[52]), "+f"(d[53]), "+f"(d[54]), "+f"(d[55]),
          "+f"(d[56]), "+f"(d[57]), "+f"(d[58]), "+f"(d[59]), "+f"(d[60]), "+f"(d[61]), "+f"(d[62]), "+f"(d[63]),
          "+f"(d[64]), "+f"(d[65]), "+f"(d[66]), "+f"(d[67]), "+f"(d[68]), "+f"(d[69]), "+f"(d[70]), "+f"(d[71]),
          "+f"(d[72]), "+f"(d[73]), "+f"(d[74]), "+f"(d[75]), "+f"(d[76]), "+f"(d[77]), "+f"(d[78]), "+f"(d[79]),
          "+f"(d[80]), "+f"(d[81]), "+f"(d[82]), "+f"(d[83]), "+f"(d[84]), "+f"(d[85]), "+f"(d[86]), "+f"(d[87]),
          "+f"(d[88]), "+f"(d[89]), "+f"(d[90]), "+f"(d[91]), "+f"(d[92]), "+f"(d[93]), "+f"(d[94]), "+f"(d[95]),
          "+f"(d[96]), "+f"(d[97]), "+f"(d[98]), "+f"(d[99]), "+f"(d[100]), "+f"(d[101]), "+f"(d[102]), "+f"(d[103]),
          "+f"(d[104]), "+f"(d[105]), "+f"(d[106]), "+f"(d[107]), "+f"(d[108]), "+f"(d[109]), "+f"(d[110]), "+f"(d[111]),
          "+f"(d[112]), "+f"(d[113]), "+f"(d[114]), "+f"(d[115]), "+f"(d[116]), "+f"(d[117]), "+f"(d[118]), "+f"(d[119]),
          "+f"(d[120]), "+f"(d[121]), "+f"(d[122]), "+f"(d[123]), "+f"(d[124]), "+f"(d[125]), "+f"(d[126]), "+f"(d[127])
        : "l"(da), "l"(db), "r"(sd));
}

__device__ __forceinline__ void wgmma_n128(float (&d)[64], uint64_t da, uint64_t db, int sd) {
    asm volatile("{\n.reg .pred p;\nsetp.ne.b32 p, %66, 0;\n"
        "wgmma.mma_async.sync.aligned.m64n128k16.f32.bf16.bf16 "
        "{%0,%1,%2,%3,%4,%5,%6,%7,%8,%9,%10,%11,%12,%13,%14,%15,"
        "%16,%17,%18,%19,%20,%21,%22,%23,%24,%25,%26,%27,%28,%29,%30,%31,"
        "%32,%33,%34,%35,%36,%37,%38,%39,%40,%41,%42,%43,%44,%45,%46,%47,"
        "%48,%49,%50,%51,%52,%53,%54,%55,%56,%57,%58,%59,%60,%61,%62,%63}, %64, %65, p, 1, 1, 0, 1;\n}\n"
        : "+f"(d[0]), "+f"(d[1]), "+f"(d[2]), "+f"(d[3]), "+f"(d[4]), "+f"(d[5]), "+f"(d[6]), "+f"(d[7]),
          "+f"(d[8]), "+f"(d[9]), "+f"(d[10]), "+f"(d[11]), "+f"(d[12]), "+f"(d[13]), "+f"(d[14]), "+f"(d[15]),
          "+f"(d[16]), "+f"(d[17]), "+f"(d[18]), "+f"(d[19]), "+f"(d[20]), "+f"(d[21]), "+f"(d[22]), "+f"(d[23]),
          "+f"(d[24]), "+f"(d[25]), "+f"(d[26]), "+f"(d[27]), "+f"(d[28]), "+f"(d[29]), "+f"(d[30]), "+f"(d[31]),
          "+f"(d[32]), "+f"(d[33]), "+f"(d[34]), "+f"(d[35]), "+f"(d[36]), "+f"(d[37]), "+f"(d[38]), "+f"(d[39]),
          "+f"(d[40]), "+f"(d[41]), "+f"(d[42]), "+f"(d[43]), "+f"(d[44]), "+f"(d[45]), "+f"(d[46]), "+f"(d[47]),
          "+f"(d[48]), "+f"(d[49]), "+f"(d[50]), "+f"(d[51]), "+f"(d[52]), "+f"(d[53]), "+f"(d[54]), "+f"(d[55]),
          "+f"(d[56]), "+f"(d[57]), "+f"(d[58]), "+f"(d[59]), "+f"(d[60]), "+f"(d[61]), "+f"(d[62]), "+f"(d[63])
        : "l"(da), "l"(db), "r"(sd));
}

__device__ __forceinline__ void wgmma_n64(float (&d)[32], uint64_t da, uint64_t db, int sd) {
    asm volatile("{\n.reg .pred p;\nsetp.ne.b32 p, %34, 0;\n"
        "wgmma.mma_async.sync.aligned.m64n64k16.f32.bf16.bf16 "
        "{%0,%1,%2,%3,%4,%5,%6,%7,%8,%9,%10,%11,%12,%13,%14,%15,"
        "%16,%17,%18,%19,%20,%21,%22,%23,%24,%25,%26,%27,%28,%29,%30,%31}, %32, %33, p, 1, 1, 0, 1;\n}\n"
        : "+f"(d[0]), "+f"(d[1]), "+f"(d[2]), "+f"(d[3]), "+f"(d[4]), "+f"(d[5]), "+f"(d[6]), "+f"(d[7]),
          "+f"(d[8]), "+f"(d[9]), "+f"(d[10]), "+f"(d[11]), "+f"(d[12]), "+f"(d[13]), "+f"(d[14]), "+f"(d[15]),
          "+f"(d[16]), "+f"(d[17]), "+f"(d[18]), "+f"(d[19]), "+f"(d[20]), "+f"(d[21]), "+f"(d[22]), "+f"(d[23]),
          "+f"(d[24]), "+f"(d[25]), "+f"(d[26]), "+f"(d[27]), "+f"(d[28]), "+f"(d[29]), "+f"(d[30]), "+f"(d[31])
        : "l"(da), "l"(db), "r"(sd));
}

constexpr int STAGE_BYTES = 49152, NSTAGE = 4;
constexpr int GEMM_SMEM = NSTAGE * STAGE_BYTES + 128;

struct GemmSmem { uint32_t st, full, empty; };
__device__ __forceinline__ GemmSmem gemm_setup(uint8_t* raw, int releases) {
    GemmSmem g;
    g.st = smem_u32(raw);
    if (g.st & 1023) __trap();
    g.full = g.st + NSTAGE * STAGE_BYTES; g.empty = g.full + 64;
    if (threadIdx.x == 0) {
        for (int s = 0; s < NSTAGE; s++) { mbar_init(g.full + 8 * s, 1); mbar_init(g.empty + 8 * s, releases); }
        asm volatile("fence.mbarrier_init.release.cluster;" ::: "memory");
        asm volatile("fence.proxy.async.shared::cta;" ::: "memory");
    }
    __syncthreads();
    return g;
}
__device__ __forceinline__ void mbar_arrive_one(uint32_t bar, uint32_t who) {
    asm volatile("{\n.reg .pred p;\nsetp.eq.u32 p, %1, 0;\n@p mbarrier.arrive.shared::cta.b64 _, [%0];\n}" ::"r"(bar), "r"(who) : "memory");
}
template <int BM, int BN, int KPS, typename ACC>
__device__ __forceinline__ void gemm_stage(ACC& acc, uint32_t stage, int wg, bool first) {
    const uint64_t da = desc_sw128(stage + wg * 8192, 16, 1024);
    const uint64_t db = desc_sw128(stage + KPS * BM * 128, 8192, 1024);
    wg_fence();
#pragma unroll
    for (int k = 0; k < 4 * KPS; k++) {
        const uint64_t a = da + (k >> 2) * (BM * 8) + (k & 3) * 2, b = db + k * 128;
        if constexpr (BN == 256) wgmma_n256(acc, a, b, first && k == 0 ? 0 : 1);
        else if constexpr (BN == 128) wgmma_n128(acc, a, b, first && k == 0 ? 0 : 1);
        else wgmma_n64(acc, a, b, first && k == 0 ? 0 : 1);
    }
    wg_commit();
}

__device__ __forceinline__ void kv_store_unit(const uint32_t (&pk)[64], int u, bf16* dst, int t) {
    const int G = (u >> 2) * 2 + (u & 1), hh = (u >> 1) & 1;
    uint32_t r0 = pk[(4 * G + 0) * 2 + hh], r1 = pk[(4 * G + 1) * 2 + hh], r2 = pk[(4 * G + 2) * 2 + hh], r3 = pk[(4 * G + 3) * 2 + hh];
    quad_transpose(r0, r1, r2, r3, t);
#define KVST ".cs"
    asm volatile("st.global" KVST ".v4.u32 [%0], {%1,%2,%3,%4};" ::"l"(dst + (size_t)hh * 8 * 8192 + G * 32), "r"(r0), "r"(r1), "r"(r2), "r"(r3) : "memory");
}

#define TLK(slot)
__device__ __forceinline__ uint32_t near_page(int pair, int line) {
    uint32_t best[2] = {~0u, ~0u};
#pragma unroll 1
    for (int i = 0; i < 16; i++) {
        uint32_t t0, t1, v;
        asm volatile("mov.u32 %0, %%clock;" : "=r"(t0)::"memory");
        asm volatile("atom.relaxed.gpu.global.or.b32 %0, [%1], -1;" : "=r"(v) : "l"(g_x + pair * 1024 + (i & 1) * 512 + line * 16) : "memory");
        asm volatile("{\n.reg .pred p;\nsetp.ne.u32 p, %1, 0x12345;\nmov.u32 %0, -1;\n@p mov.u32 %0, %%clock;\n}" : "=r"(t1) : "r"(v) : "memory");
        if (i & 1) best[1] = min(best[1], t1 - t0); else best[0] = min(best[0], t1 - t0);
    }
    return best[1] < best[0];
}
__device__ __forceinline__ void map_pages(int c) {
    uint32_t smid;
    asm("mov.u32 %0, %%smid;" : "=r"(smid));
    const uint32_t side = near_page(0, c & 31);
    g_side[smid & 255] = side;
    for (int p = c; p < XPAIRS; p += 132) g_home[p] = near_page(p, 0) ^ side;
}

__global__ void __launch_bounds__(384, 1)
k_kv(const __grid_constant__ CUtensorMap mx, const __grid_constant__ CUtensorMap mwk, const __grid_constant__ CUtensorMap mwv,
     const bf16* __restrict__ Wq, const bf16* __restrict__ Wk, const bf16* __restrict__ Wo, int c0) {
    extern __shared__ __align__(1024) uint8_t smem_gemm[];
    const int c = c0 + blockIdx.x;
    if (c == 128) {
        if (threadIdx.x < 256) g_flag[threadIdx.x] = 0;
        __threadfence();
        __syncthreads();
    }
    asm volatile("griddepcontrol.launch_dependents;");
    if (threadIdx.x == 0) TLK(0);
    if (c >= 128) {
        const int i0 = (c - 128) * 384 + threadIdx.x;
        const uint4 ones = make_uint4(~0u, ~0u, ~0u, ~0u);
        if (threadIdx.x == 32) map_pages(c);
        for (int i = i0; i < XPAIRS * 512; i += 4 * 384) reinterpret_cast<uint4*>(g_x)[i] = ones;
        if (threadIdx.x == 0) TLK(1);
        asm volatile("griddepcontrol.wait;" ::: "memory");
        return;
    }
    GemmSmem g = gemm_setup(smem_gemm, 2);
    const int m0 = (c & 15) * 128, nb0 = c >> 4;
    const int wg = __shfl_sync(~0u, threadIdx.x >> 7, 0);
    if (wg == 0) {
        asm volatile("setmaxnreg.dec.sync.aligned.u32 40;");
        if (threadIdx.x == 0) {
            for (int it = 0; it < 64; it++) {
                const int s = it & 3, tile = it >> 4, kb = it & 15;
                mbar_wait(g.empty + 8 * s, ((it >> 2) & 1) ^ 1);
                mbar_expect_tx(g.full + 8 * s, STAGE_BYTES);
                const int nb = nb0 + 8 * tile;
                tma2d(g.st + s * STAGE_BYTES, &mx, kb * 64, m0, g.full + 8 * s);
                tma3d(g.st + s * STAGE_BYTES + 16384, nb < 16 ? &mwk : &mwv, 0, kb * 64, (nb & 15) * 4, g.full + 8 * s);
#define PF0 40
#define PFN 24
#define PFB 4096
                const int pi = it - PF0;
                if (pi >= 0 && pi < PFN) {
                    const uint32_t o = (pi * 128 + c) * PFB;
                    const char* p = (const char*)(o < (8 << 20) ? Wo : o < (16 << 20) ? Wq : Wk) + (o & ((8 << 20) - 1));
                    asm volatile("cp.async.bulk.prefetch.L2.global [%0], %1;" ::"l"(p), "n"(PFB) : "memory");
                }
            }
        } else if (threadIdx.x == 32) map_pages(c);
    } else {
        asm volatile("setmaxnreg.inc.sync.aligned.u32 232;");
        const int cw = wg - 1, lane = threadIdx.x & 31, t = lane & 3;
        const int row = m0 + cw * 64 + ((threadIdx.x >> 5) & 3) * 16 + (lane >> 2);
        bf16* dst = g_kv + (size_t)row * 8192 + nb0 * 256 + t * 8;
        float acc[128];
        uint32_t pk[64];
#pragma unroll 1
        for (int tile = 0; tile < 4; tile++) {
#pragma unroll
            for (int kb = 0; kb < 16; kb++) {
                mbar_wait_u(g.full + 8 * (kb & 3), (kb >> 2) & 1);
                gemm_stage<128, 256, 1>(acc, g.st + (kb & 3) * STAGE_BYTES, cw, kb == 0);
                if (tile > 0) kv_store_unit(pk, kb, dst + (tile - 1) * 2048, t);
                if (kb > 0) {
                    wg_wait<1>();
                    mbar_arrive_one(g.empty + 8 * ((kb - 1) & 3), threadIdx.x & 127);
                }
            }
            wg_wait<0>();
            mbar_arrive_one(g.empty + 8 * 3, threadIdx.x & 127);
#pragma unroll
            for (int i = 0; i < 64; i++) pk[i] = pack2(acc[2 * i], acc[2 * i + 1]);
        }
        if (threadIdx.x == 128) TLK(2);
#pragma unroll
        for (int u = 0; u < 16; u++) kv_store_unit(pk, u, dst + 3 * 2048, t);
        if (threadIdx.x == 128) TLK(1);
        asm volatile("griddepcontrol.wait;" ::: "memory");
    }
}

constexpr int NS1 = 31;
#define RB1 4
#define PFC 4
constexpr int C_W1 = 0;
constexpr int C_W2 = C_W1 + 8 * NS1 * 512;
constexpr int C_KV = C_W2 + 14 * 8 * 512;
constexpr int C_RED = C_KV + 16384;
constexpr int C_QKV = C_RED + 64 * 272;
constexpr int C_SC = C_RED;
constexpr int C_OB = C_SC + 2 * 8 * 52 * 4;
constexpr int C_BAR = C_QKV + 3 * 8 * 272;
__host__ __device__ constexpr int smem_idx(int ks, int j) {
    return ks == 0 ? j : ks < 3 ? (j < 4 ? 4 + 4 * ks + j : -1) : (j < 3 ? 7 + 3 * ks + j : -1);
}
constexpr int CHAIN_SMEM = C_BAR + 64;
#define TS(i)

#define DLY3 8
#define DLY1 2
#define DLY0 2
#define DLY1A 10
#define DLY0A DLY0
#define DLYW 3
template <int N> __device__ __forceinline__ uint32_t delayed(uint32_t x, int lane) {
#pragma unroll
    for (int i = 0; i < N; i++) asm volatile("shfl.sync.idx.b32 %0, %0, %1, 31, -1;" : "+r"(x) : "r"(lane) : "memory");
    return x;
}
__device__ __forceinline__ void lds128v(uint32_t (&r)[4], uint32_t a) {
    asm volatile("ld.volatile.shared.v4.u32 {%0,%1,%2,%3}, [%4];" : "=r"(r[0]), "=r"(r[1]), "=r"(r[2]), "=r"(r[3]) : "r"(a) : "memory");
}
__device__ __forceinline__ uint2 lds64(uint32_t a) {
    uint2 v;
    asm volatile("ld.shared.v2.u32 {%0,%1}, [%2];" : "=r"(v.x), "=r"(v.y) : "r"(a) : "memory");
    return v;
}
#define LDQ ".L1::no_allocate"
__device__ __forceinline__ uint4 ldw128(const void* p) {
    uint4 v;
    asm volatile("ld.global.nc" LDQ ".v4.u32 {%0,%1,%2,%3}, [%4];" : "=r"(v.x), "=r"(v.y), "=r"(v.z), "=r"(v.w) : "l"(p));
    return v;
}
#define P8_LD(i) "ld.relaxed.gpu.global.b64 d" #i ", [src + " #i " * 256];\n"
#define P8_X(i) "mov.b64 {x" #i ", y" #i "}, d" #i ";\n"
#define P8_HEAD(SRC) "{\n.reg .pred p, q;\n.reg .b64 src, d<8>;\n.reg .b32 n, x<8>, y<8>, m0, m1;\nmov.b64 src, " SRC ";\n"         \
                P8_LD(0) P8_LD(1) P8_LD(2) P8_LD(3) P8_LD(4) P8_LD(5) P8_LD(6) P8_LD(7) "mov.u32 n, 0;\nCHECK:\n" \
                P8_X(0) P8_X(1) P8_X(2) P8_X(3) P8_X(4) P8_X(5) P8_X(6) P8_X(7)
#define P8_VOTE "vote.sync.all.pred p, p, -1;\n@p bra.uni DONE;\n"
#define P8_TAIL "add.u32 n, n, 1;\nsetp.lt.u32 p, n, 0x100000;\n@p bra.uni CHECK;\ntrap;\nDONE:\n"
__device__ __forceinline__ void poll_state(uint2 (&v)[8], const void* src) {
#define P8_RS(i) "setp.eq.u32 q, x" #i ", 0xffffffff;\n@q " P8_LD(i)
#define P8_O(i) "mov.b64 %" #i ", d" #i ";\n"
    uint64_t d[8];
    asm volatile(P8_HEAD("%8") "max.u32 m0, x0, x1;\nmax.u32 m0, m0, x2;\nmax.u32 m1, x3, x4;\nmax.u32 m1, m1, x5;\nmax.u32 m0, m0, x6;\n"
                 "max.u32 m0, m0, x7;\nmax.u32 m0, m0, m1;\nsetp.ne.u32 p, m0, 0xffffffff;\n" P8_VOTE
                 P8_RS(0) P8_RS(1) P8_RS(2) P8_RS(3) P8_RS(4) P8_RS(5) P8_RS(6) P8_RS(7) P8_TAIL
                 P8_O(0) P8_O(1) P8_O(2) P8_O(3) P8_O(4) P8_O(5) P8_O(6) P8_O(7) "}"
                 : "=l"(d[0]), "=l"(d[1]), "=l"(d[2]), "=l"(d[3]), "=l"(d[4]), "=l"(d[5]), "=l"(d[6]), "=l"(d[7]) : "l"(src) : "memory");
#pragma unroll
    for (int i = 0; i < 8; i++) { v[i].x = (uint32_t)d[i]; v[i].y = (uint32_t)(d[i] >> 32); }
}
__device__ __forceinline__ uint64_t poll_sum(const void* src, uint32_t tag, uint32_t sel) {
#define P8_RT(i) "lop3.b32 m0, x" #i ", %2, 1, 0x28;\nsetp.ne.u32 q, m0, 0;\n@q " P8_LD(i)
#define P8_MMA(c, i, z) "mma.sync.aligned.m16n8k8.row.col.f32.bf16.bf16.f32 {" #c "0," #c "1," #c "2," #c "3}, {x" #i ", y" #i "}, {%3}, {" #z "0," #z "1," #z "2," #z "3};\n"
    uint64_t r;
    asm volatile(P8_HEAD("%1") "{\n.reg .f32 a<4>, b<4>, z<4>;\nmov.f32 z0, 0f00000000;\nmov.f32 z1, z0;\nmov.f32 z2, z0;\nmov.f32 z3, z0;\n"
                 P8_MMA(a, 0, z) P8_MMA(b, 1, z) P8_MMA(a, 2, a) P8_MMA(b, 3, b) P8_MMA(a, 4, a) P8_MMA(b, 5, b) P8_MMA(a, 6, a) P8_MMA(b, 7, b)
                 "add.f32 a0, a0, b0;\nadd.f32 a1, a1, b1;\nadd.f32 a2, a2, b2;\nadd.f32 a3, a3, b3;\n"
                 "cvt.rn.bf16x2.f32 m0, a1, a0;\ncvt.rn.bf16x2.f32 m1, a3, a2;\nmov.b64 %0, {m0, m1};\n}\n"
                 "lop3.b32 m0, x0, x1, %2, 0x7e;\nlop3.b32 m1, x2, x3, %2, 0x7e;\nlop3.b32 m0, m0, x4, %2, 0xf6;\n"
                 "lop3.b32 m1, m1, x5, %2, 0xf6;\nlop3.b32 m0, m0, x6, %2, 0xf6;\nlop3.b32 m1, m1, x7, %2, 0xf6;\n"
                 "lop3.b32 m0, m0, m1, 1, 0xa8;\nsetp.eq.u32 p, m0, 0;\n" P8_VOTE
                 P8_RT(0) P8_RT(1) P8_RT(2) P8_RT(3) P8_RT(4) P8_RT(5) P8_RT(6) P8_RT(7) P8_TAIL "}"
                 : "=&l"(r) : "l"(src), "r"(tag), "r"(sel) : "memory");
    return r;
}
__device__ __forceinline__ void sum8(float (&c)[4], const uint2 (&v)[8], uint32_t idn) {
    float d[4] = {0.f, 0.f, 0.f, 0.f};
    c[0] = c[1] = c[2] = c[3] = 0.f;
    mma16816(c, v[0].x, v[0].y, v[1].x, v[1].y, idn, idn);
    mma16816(d, v[2].x, v[2].y, v[3].x, v[3].y, idn, idn);
    mma16816(c, v[4].x, v[4].y, v[5].x, v[5].y, idn, idn);
    mma16816(d, v[6].x, v[6].y, v[7].x, v[7].y, idn, idn);
    c[0] += d[0]; c[1] += d[1]; c[2] += d[2]; c[3] += d[3];
}

#define CLS 6
__global__ void __cluster_dims__(CLS, 1, 1) __launch_bounds__(256, 1)
k_chain(const bf16* __restrict__ mem0, const bf16* __restrict__ Wq, const bf16* __restrict__ Wk, const bf16* __restrict__ Wv,
        const bf16* __restrict__ Wo, const __grid_constant__ CUtensorMap mkv) {
    extern __shared__ __align__(1024) uint8_t smem_chain[];
    const uint32_t sb = smem_u32(smem_chain);
    if (sb & 1023) __trap();
    const int w = __shfl_sync(~0u, threadIdx.x >> 5, 0), lane = __shfl_sync(~0u, threadIdx.x & 31, threadIdx.x & 31);
    const int tid = w * 32 + lane, g = lane >> 2, t = lane & 3;
    auto pin = [&](uint32_t x) { return delayed<1>(x, lane); };
    const int h = blockIdx.x / 3, r = blockIdx.x - 3 * h;
    const uint32_t bar_x = sb + C_BAR, bar_kv = sb + C_BAR + 8, bar_go = sb + C_BAR + 16, bar_w = sb + C_BAR + 24;
    asm volatile("griddepcontrol.launch_dependents;");
    const int tbase = r == 0 ? 0 : 1 + 21 * r, ntile = r == 0 ? 22 : 21;
    uint32_t side;
    if (tid == 0) {
        mbar_init(bar_x, 8); mbar_init(bar_kv, 1); mbar_init(bar_go, 1); mbar_init(bar_w, 1);
        asm volatile("fence.mbarrier_init.release.cluster;" ::: "memory");
        asm volatile("fence.proxy.async.shared::cta;" ::: "memory");
        mbar_expect_tx(bar_w, 128 * 32 * ntile);
    }
    __syncthreads();
    asm volatile("barrier.cluster.arrive.relaxed.aligned;" ::: "memory");
    if (tid < 128)
        asm volatile("cp.async.bulk.shared::cluster.global.mbarrier::complete_tx::bytes [%0], [%1], %2, [%3];"
                     ::"r"(sb + C_W1 + tid * 720), "l"(Wo + (size_t)(h * 128 + tid) * DM + tbase * 16), "r"(32 * ntile), "r"(bar_w) : "memory");
    const int tile0 = tbase + 7 - w;
    const bool three = w >= (r == 0 ? 2 : 3);
    const uint32_t wa = pin(sb + tid * 16);
#define W1A(i) (wa + C_W1 + (i) * 4096)
#define W2A(x) (wa + C_W2 + ((x) < 8 ? (x) * 4096 : 32768 - 1024 + ((x) - 8) * 3072))
    uint32_t wo0[8][4], wr[64][4];
    {
        const bf16* W = (r == 0 ? Wq : r == 1 ? Wk : Wv) + (size_t)(128 * w + (lane >> 4)) * HD + h * 128 + 8 * (lane & 15);
        uint4 raw[8][8];
        auto fetch = [&](int ks) {
#pragma unroll
            for (int i = 0; i < 8; i++) raw[ks][i] = ldw128(W + (size_t)(16 * ks + 2 * i) * HD);
        };
        fetch(0); fetch(1); fetch(2); fetch(3);
    asm("mov.u32 %0, %%smid;" : "=r"(side));
    side = ld_acq32(g_side + (side & 255)) & 1;
    if (tid == 0 && r > 0) asm volatile("st.relaxed.gpu.global.u32 [%0], %1;" ::"l"(g_flag + 128 + 2 * h + r - 1), "r"(2 | side) : "memory");
        mbar_wait_u(bar_w, 0);
        const uint32_t p = sb + C_W1 + ((lane & 7) + (lane >> 4) * 8) * 720 + (7 - w) * 32 + ((lane >> 3) & 1) * 16;
#pragma unroll
        for (int ks = 0; ks < 8; ks++) {
            uint32_t a[4];
            ldsm4t(wo0[ks], p + ks * 16 * 720);
            ldsm4t(a, p + ks * 16 * 720 + 256);
            sts128(W2A(ks), a[0], a[1], a[2], a[3]);
            if (three) { ldsm4t(a, p + ks * 16 * 720 + 512); sts128(W2A(8 + ks), a[0], a[1], a[2], a[3]); }
        }
        __syncthreads();
        const uint32_t stg = sb + C_KV + w * 4096;
        const uint32_t rd = stg + ((lane & 7) + 8 * (lane >> 4)) * 256 + ((((lane >> 3) & 1) ^ (lane & 7)) << 4);
#pragma unroll
        for (int ks = 0; ks < 8; ks++) {
#pragma unroll
            for (int i = 0; i < 8; i++)
                sts128(stg + (2 * i + (lane >> 4)) * 256 + (((lane & 15) ^ (((2 * i) & 6) | (lane >> 4))) << 4),
                       raw[ks][i].x, raw[ks][i].y, raw[ks][i].z, raw[ks][i].w);
            if (ks < 2) fetch(ks + 4);
            if (ks == 3 || ks == 5) fetch(ks / 2 + 5);
            __syncwarp();
#pragma unroll
            for (int j = 0; j < 8; j++) {
                if (smem_idx(ks, j) >= 0) {
                    uint32_t a[4];
                    ldsm4t(a, rd ^ (j << 5));
                    sts128(W1A(smem_idx(ks, j)), a[0], a[1], a[2], a[3]);
                } else ldsm4t(wr[8 * ks + j], rd ^ (j << 5));
            }
            __syncwarp();
        }
    }
    asm volatile("griddepcontrol.wait;\nfence.proxy.async.shared::cta;" ::: "memory");
    __syncthreads();
    if (tid == 0) {
        mbar_expect_tx(bar_kv, 16384);
        tma3d(sb + C_KV, &mkv, 0, 0, 2 * h, bar_kv);
        tma3d(sb + C_KV + 8192, &mkv, 0, 0, 64 + 2 * h, bar_kv);
    }
    asm volatile("barrier.cluster.wait.aligned;" ::: "memory");

    auto publish_kvm = [&](int s) {
        uint32_t v[4];
        lds128(v, sb + C_QKV + (8 + (tid >> 4)) * 272 + (tid & 15) * 16);
        asm volatile("st.global.v4.u32 [%0], {%1,%2,%3,%4};"
                     ::"l"(g_kvm + (size_t)(s * 8 + ((tid >> 4) & 7)) * 8192 + (tid >> 7) * HD + h * 128 + (tid & 15) * 8),
                       "r"(v[0]), "r"(v[1]), "r"(v[2]), "r"(v[3]) : "memory");
        if (h == 0 && w == 6) asm volatile("st.relaxed.gpu.global.u32 [%0], %1;" ::"l"(g_flag + 98), "r"(s + 1) : "memory");
        if ((s & 3) == 3) {
            __syncthreads();
            if (w == 7) asm volatile("{\n.reg .pred p;\nsetp.eq.u32 p, %2, 0;\nfence.acq_rel.gpu;\n@p st.relaxed.gpu.global.u32 [%0], %1;\n}"
                                     ::"l"(g_flag + h), "r"(s + 1), "r"(lane) : "memory");
        }
    };
    const float sl2e = 0.08838834764831845f * 1.4426950408889634f;
    const uint32_t idn = pin(g == 2 * t ? 0x00003f80u : g == 2 * t + 1 ? 0x3f800000u : 0u);
    const uint32_t lm = pin(sb + (lane & 7) * 272 + (lane >> 3) * 16);
    const uint32_t sa = pin(sb + C_SC + (w & 1) * (8 * 52 * 4) + (2 * t * 52 + (w < 4 ? 32 : (w & 2) * 8) + g) * 4);
    const uint32_t sr = pin(sb + C_SC + (g * 52 + 8 * t) * 4), sr2 = pin(sb + C_SC + (g * 52 + 32 + 2 * t) * 4);
    uint32_t kva;
    {
        const int pos = (w & 2) * 8 + (lane & 15), row = (pos & 24) + ((pos + (pos >> 2 & 6)) & 7);
        const int key = 4 * (lane & 6) + (((lane & 7) + 2 * (lane >> 4)) & 7);
        kva = pin(w >= 4 ? sb + C_KV + (w & 1) * 4096 + row * 128 + (((lane >> 4) ^ (row & 7)) << 4)
                         : sb + C_KV + 8192 + (w >> 1) * 4096 + key * 128 + ((((w & 1) * 4 + ((lane >> 3) & 1)) ^ (key & 7)) << 4));
    }
    uint32_t buf0[8][4], ring[RB1][4];
    auto stage_w1 = [&]() {
#pragma unroll
        for (int i = 0; i < 8; i++) lds128v(buf0[i], W1A(i));
#pragma unroll
        for (int i = 0; i < RB1; i++) lds128v(ring[i], W1A(8 + i));
    };
    stage_w1();
    uint32_t psel, msel0, msel1;
    {
        const int j = r > 0 ? 2 * h + r - 1 : 0, tl = min(tile0 + 8 * (lane >> 1), 63);
        uint32_t b;
        asm volatile("{\n.reg .pred p;\n.reg .u32 n;\nmov.u32 n, 0;\nAGAIN:\nld.relaxed.gpu.global.u32 %0, [%1];\nsetp.ne.u32 p, %0, 0;\n"
                     "vote.sync.all.pred p, p, -1;\n@p bra.uni DONE;\nadd.u32 n, n, 1;\nsetp.lt.u32 p, n, 0x100000;\n@p bra.uni AGAIN;\ntrap;\nDONE:\n}"
                     : "=&r"(b) : "l"(g_flag + 128 + tl) : "memory");
        psel = __ballot_sync(~0u, (g_home[lane == 6 ? j * 2 + ((w >> 1) & 1) : tl * 2 + (lane & 1)] ^ (lane == 6 ? side : b)) & 1);
        msel0 = __ballot_sync(~0u, (g_home[128 + lane * 4 + (w >> 1)] ^ side) & 1);
        msel1 = __ballot_sync(~0u, (g_home[256 + lane * 4 + (w >> 1)] ^ side) & 1);
        if (r > 0) {
            if (w < 4) asm volatile("prefetch.global.L2 [%0];" ::"l"(g_x + (128 + (1 + (w >> 1)) * 4 + (j >> 4)) * 1024 + (w & 1) * 512 + (j & 15) * 32 + lane) : "memory");
            if (w < 4) asm volatile("prefetch.global.L2 [%0];" ::"l"(g_x + j * 2048 + tid * 16) : "memory");
        }
    }
    uint2 bm[8];
#pragma unroll
    for (int ks = 0; ks < 8; ks++) {
        const uint32_t* p = (const uint32_t*)(mem0 + g * DM + (8 * w + ks) * 16) + t;
        bm[ks] = make_uint2(__ldg(p), __ldg(p + 4));
    }
    mbar_wait_u(bar_kv, 0);
    if (tid == 0) TL(1, 2);
#pragma unroll 1
    for (int s = 0;; s++) {
        TS(1);
        {
            float acc[8][4];
#pragma unroll
            for (int ks = 0; ks < 8; ks++) {
#pragma unroll
                for (int j = 0; j < 8; j++) {
                    const int i = smem_idx(ks, j) - 8;
                    if (ks == 0) {
                        acc[j][0] = acc[j][1] = acc[j][2] = acc[j][3] = 0.f;
                        mma16816(acc[j], buf0[j][0], buf0[j][1], buf0[j][2], buf0[j][3], bm[ks].x, bm[ks].y);
                    } else if (i >= 0) {
                        uint32_t(&a)[4] = ring[i % RB1];
                        mma16816(acc[j], a[0], a[1], a[2], a[3], bm[ks].x, bm[ks].y);
                        if (8 + i + RB1 < NS1) lds128v(a, W1A(8 + i + RB1));
                    } else {
                        const uint32_t(&a)[4] = wr[8 * ks + j];
                        mma16816(acc[j], a[0], a[1], a[2], a[3], bm[ks].x, bm[ks].y);
                    }
                }
            }
#pragma unroll
            for (int c = 0; c < 4; c++)
                stsm4t(lm + C_RED + w * 2176 + c * 64, pack2(acc[2 * c][0], acc[2 * c][1]), pack2(acc[2 * c][2], acc[2 * c][3]),
                       pack2(acc[2 * c + 1][0], acc[2 * c + 1][1]), pack2(acc[2 * c + 1][2], acc[2 * c + 1][3]));
        }
        {
            const uint32_t a = sb + C_RED + w * 272 + lane * 8;
            TS(2);
            __syncthreads();
            TS(3);
            uint2 v[8];
#pragma unroll
            for (int i = 0; i < 8; i++) v[i] = lds64(a + i * 2176);
            float c[4];
            sum8(c, v, idn);
            const uint32_t p0 = pack2(c[0], c[1]), p1 = pack2(c[2], c[3]);
            const uint32_t dst = sb + C_QKV + (r * 8 + w) * 272 + lane * 8;
#pragma unroll
            for (int i = 1; i < 3; i++) {
                const uint32_t peer = (h % (CLS / 3)) * 3 + (r + i >= 3 ? r + i - 3 : r + i);
                uint32_t rd, rb;
                asm("mapa.shared::cluster.u32 %0, %1, %2;" : "=r"(rd) : "r"(dst), "r"(peer));
                asm("mapa.shared::cluster.u32 %0, %1, %2;" : "=r"(rb) : "r"(bar_x), "r"(peer));
                asm volatile("st.async.weak.shared::cluster.mbarrier::complete_tx::bytes.v2.b32 [%0], {%1,%2}, [%3];"
                             ::"r"(rd), "r"(p0), "r"(p1), "r"(rb) : "memory");
            }
            sts64(dst, p0, p1);
            __syncwarp();
            asm volatile("{\n.reg .pred p;\nsetp.eq.u32 p, %1, 0;\n@p mbarrier.arrive.expect_tx.shared::cta.b64 _, [%0], 512;\n}"
                         ::"r"(bar_x), "r"(lane) : "memory");
        }
        TS(4);
        if (s == NSEG - 1) break;
        uint32_t wb[8][4], wc[8][4];
        const uint32_t po = (tile0 * 2 + (lane >> 4)) * 8192 + ((lane >> 3) & 1) * 2048 + h * 64 + (lane & 7) * 8;
        const uint32_t tag = s & 1;
        auto project = [&](const uint32_t(&wt)[8][4], const uint32_t(&ob)[4][4], int i) {
            float c0[4] = {0.f, 0.f, 0.f, 0.f}, c1[4] = {0.f, 0.f, 0.f, 0.f};
#pragma unroll
            for (int ks = 0; ks < 8; ks++)
                mma16816((ks & 1) ? c1 : c0, wt[ks][0], wt[ks][1], wt[ks][2], wt[ks][3], ob[ks >> 1][(ks & 1) * 2], ob[ks >> 1][(ks & 1) * 2 + 1]);
            uint32_t p0 = pack2(c0[0] + c1[0], c0[1] + c1[1]), p1 = pack2(c0[2] + c1[2], c0[3] + c1[3]);
            asm volatile("movmatrix.sync.aligned.m8n8.trans.b16 %0, %0;\nmovmatrix.sync.aligned.m8n8.trans.b16 %1, %1;" : "+r"(p0), "+r"(p1));
            st_rlx64((uint2*)((char*)g_x + po + i * 131072 + ((psel >> (2 * i + (lane >> 4))) & 1) * 4096), (p0 & ~1u) | tag, p1);
        };
        if (w >= 4) {
            uint32_t ka[4][4];
#pragma unroll
            for (int ks = 0; ks < 4; ks++) ldsm4(ka[ks], kva ^ (ks << 5));
            const uint32_t qa = lm + C_QKV + (w & 1) * 128;
            TS(5);
            mbar_wait_u(bar_x, s & 1);
            TS(6);
            {
                uint32_t qb[2][4];
                ldsm4(qb[0], qa);
                ldsm4(qb[1], qa + 64);
                float c0[4] = {0.f, 0.f, 0.f, 0.f}, c1[4] = {0.f, 0.f, 0.f, 0.f};
                mma16816(c0, ka[0][0], ka[0][1], ka[0][2], ka[0][3], qb[0][0], qb[0][1]);
                mma16816(c1, ka[1][0], ka[1][1], ka[1][2], ka[1][3], qb[0][2], qb[0][3]);
                mma16816(c0, ka[2][0], ka[2][1], ka[2][2], ka[2][3], qb[1][0], qb[1][1]);
                mma16816(c1, ka[3][0], ka[3][1], ka[3][2], ka[3][3], qb[1][2], qb[1][3]);
                sts32f(sa, c0[0] + c1[0]);
                sts32f(sa + 208, c0[1] + c1[1]);
                sts32f(sa + 32, c0[2] + c1[2]);
                sts32f(sa + 240, c0[3] + c1[3]);
            }
            __syncthreads();
            TS(7);
            if (w == 7 && s + 1 < NSEG - 1) {
                if (lane == 0) {
                    mbar_expect_tx(bar_kv, 16384);
                    tma3d(sb + C_KV, &mkv, 0, (s + 1) * 32, 2 * h, bar_kv);
                    tma3d(sb + C_KV + 8192, &mkv, 0, (s + 1) * 32, 64 + 2 * h, bar_kv);
                }
                __syncwarp();
            }
            const uint32_t wd = delayed<DLYW>(wa, lane);
#pragma unroll
            for (int i = 0; i < 8; i++) lds128(wb[i], wd + C_W2 + i * 4096);
#pragma unroll
            for (int i = 0; i < PFC; i++) lds128(wc[i], wd + C_W2 + 32768 - 1024 + i * 3072);
            TS(8);
            __syncthreads();
            TS(9);
            uint32_t ob[4][4];
#pragma unroll
            for (int i = 0; i < 4; i++) ldsm4(ob[i], lm + C_OB + i * 64);
#pragma unroll
            for (int i = PFC; i < 8; i++) lds128(wc[i], W2A(8 + i));
            project(wb, ob, 1);
            project(wo0, ob, 0);
            project(wc, ob, 2);
        } else {
            uint32_t va[4][4];
#pragma unroll
            for (int i = 0; i < 4; i++) ldsm4t(va[i], kva ^ (((i >> 1) << 5) | ((i & 1) * 0x240)));
#pragma unroll
            for (int i = 0; i < 8; i++) lds128(wb[i], W2A(i));
            const uint32_t qa = lm + C_QKV + (w & 1) * 128, oa = lm + w * 64;
            TS(5);
            mbar_wait_u(bar_x, s & 1);
            TS(6);
            if (w < 2) {
                uint32_t qb[2][4], km[2][4];
                ldsm4(qb[0], qa);
                ldsm4(km[0], qa + 8 * 272);
                ldsm4(qb[1], qa + 64);
                ldsm4(km[1], qa + 8 * 272 + 64);
                float c0[4] = {0.f, 0.f, 0.f, 0.f}, c1[4] = {0.f, 0.f, 0.f, 0.f};
                mma16816(c0, km[0][0], km[0][1], km[0][2], km[0][3], qb[0][0], qb[0][2]);
                mma16816(c1, km[0][0], km[0][1], km[0][2], km[0][3], qb[0][1], qb[0][3]);
                mma16816(c0, km[1][0], km[1][1], km[1][2], km[1][3], qb[1][0], qb[1][2]);
                mma16816(c1, km[1][0], km[1][1], km[1][2], km[1][3], qb[1][1], qb[1][3]);
                sts32f(sa, c0[0] + c1[2]);
                sts32f(sa + 208, c0[1] + c1[3]);
            }
            __syncthreads();
            TS(7);
            {
                float4 x0 = lds128f(sr), y0 = lds128f(sr + 1664), x1 = lds128f(sr + 16), y1 = lds128f(sr + 1680);
                float2 x2 = lds64f(sr2), y2 = lds64f(sr2 + 1664);
                float p[10] = {x0.x + y0.x, x0.y + y0.y, x0.z + y0.z, x0.w + y0.w, x1.x + y1.x,
                               x1.y + y1.y, x1.z + y1.z, x1.w + y1.w, x2.x + y2.x, x2.y + y2.y};
                float m = fmaxf(fmaxf(fmaxf(p[0], p[1]), fmaxf(p[2], p[3])), fmaxf(fmaxf(fmaxf(p[4], p[5]), fmaxf(p[6], p[7])), fmaxf(p[8], p[9])));
                const float m1 = __shfl_xor_sync(~0u, m, 1), m2 = __shfl_xor_sync(~0u, m, 2), m3 = __shfl_xor_sync(~0u, m, 3);
                uint32_t vm[4];
                ldsm4t(vm, oa + C_QKV + 16 * 272);
                m = fmaxf(fmaxf(m, m1), fmaxf(m2, m3));
                const float ms = m * sl2e;
#pragma unroll
                for (int i = 0; i < 10; i++) p[i] = ex2(fmaf(p[i], sl2e, -ms));
                const uint32_t b0 = pack2(p[0], p[1]), b1 = pack2(p[2], p[3]), b2 = pack2(p[4], p[5]), b3 = pack2(p[6], p[7]), b4 = pack2(p[8], p[9]);
                const uint32_t one = 0x3f803f80u;
                float o0[4] = {0.f, 0.f, 0.f, 0.f}, o1[4] = {0.f, 0.f, 0.f, 0.f}, sm[4] = {0.f, 0.f, 0.f, 0.f};
                mma16816(sm, one, one, one, one, b0, b1);
                mma16816(o0, va[0][0], va[0][1], va[0][2], va[0][3], b0, b1);
                mma16816(o1, va[2][0], va[2][1], va[2][2], va[2][3], b0, b1);
                mma16816(sm, one, one, one, one, b2, b3);
                mma16816(o0, va[1][0], va[1][1], va[1][2], va[1][3], b2, b3);
                mma16816(o1, va[3][0], va[3][1], va[3][2], va[3][3], b2, b3);
                mma1688(sm, one, one, b4);
                mma1688(o0, vm[0], vm[1], b4);
                mma1688(o1, vm[2], vm[3], b4);
                float i0, i1;
                asm("rcp.approx.ftz.f32 %0, %1;" : "=f"(i0) : "f"(sm[0]));
                asm("rcp.approx.ftz.f32 %0, %1;" : "=f"(i1) : "f"(sm[1]));
                stsm4t(oa + C_OB, pack2(o0[0] * i0, o0[1] * i1), pack2(o0[2] * i0, o0[3] * i1),
                       pack2(o1[0] * i0, o1[1] * i1), pack2(o1[2] * i0, o1[3] * i1));
            }
            TS(8);
            __syncthreads();
            TS(9);
            uint32_t ob[4][4];
#pragma unroll
            for (int i = 0; i < 4; i++) ldsm4(ob[i], lm + C_OB + i * 64);
            if (three) {
#pragma unroll
                for (int i = 0; i < 8; i++) lds128(wc[i], W2A(8 + i));
                project(wb, ob, 1);
                project(wo0, ob, 0);
                project(wc, ob, 2);
            } else {
                project(wb, ob, 1);
                project(wo0, ob, 0);
            }
        }
        TS(10);
        __syncthreads();
        uint32_t eo = (128 + (s + 1) * 4 + (w >> 1)) * 8192 + (((s < 31 ? msel0 : msel1) >> ((s + 1) & 31)) & 1) * 4096 + (w & 1) * 2048 + lane * 8;
        if (r == 0) {
            TS(11); TS(12);
            stage_w1();
            if (w < 4 && s + 3 < NSEG - 1)
                asm volatile("prefetch.global.L2 [%0];" ::"l"(g_kv + (size_t)((s + 3) * 32 + lane) * 8192 + (w >> 1) * HD + h * 128 + (w & 1) * 64) : "memory");
            publish_kvm(s);
            if (s < NSEG - 2) mbar_wait_u(bar_kv, (s + 1) & 1);
            mbar_wait_u(bar_go, s & 1);
            if (w < 4) eo = delayed<DLY0>(eo, lane); else eo = delayed<DLY0A>(eo, lane);
        } else {
            const int j = 2 * h + r - 1;
            if (w < 4) {
                const char* src = (const char*)g_x + delayed<DLY3>((j * 2 + (w >> 1)) * 8192 + (psel & 64) * 64 + (w & 1) * 2048 + t * 64 + g * 8, lane);
                const char* dst = (const char*)g_x + pin((128 + (s + 1) * 4 + (j >> 4)) * 8192 + (j & 15) * 256 + w * 64 + (t & 1) * 4096 + g * 8);
                const uint64_t v = poll_sum(src, tag, (lane & 4) ? 0x3f800000u : 0x00003f80u);
                TS(11);
                asm volatile("st.relaxed.gpu.global.b64 [%0], %1;" ::"l"(dst), "l"(v) : "memory");
                asm volatile("bar.arrive 1, 256;" ::: "memory");
                TS(12);
                stage_w1();
                if (s < NSEG - 2) mbar_wait_u(bar_kv, (s + 1) & 1);
                eo = delayed<DLY1>(eo, lane);
            } else {
                if (w >= 6 && s + 3 < NSEG)
                    asm volatile("prefetch.global.L2 [%0];" ::"l"(g_x + (128 + (s + 3) * 4 + (j >> 4)) * 1024 + (w & 1) * 512 + (j & 15) * 32 + lane) : "memory");
                stage_w1();
                if (s < NSEG - 2) mbar_wait_u(bar_kv, (s + 1) & 1);
                TS(11);
                bar_sync(1, 256);
                TS(12);
                if (w == 4 && r == 1)
                    asm volatile("{\n.reg .pred p;\n.reg .u32 a;\nelect.sync _|p, -1;\nmapa.shared::cluster.u32 a, %0, %1;\n"
                                 "@p mbarrier.arrive.relaxed.cluster.shared::cluster.b64 _, [a];\n}" ::"r"(bar_go), "r"((h % (CLS / 3)) * 3) : "memory");
                eo = delayed<DLY1A>(eo, lane);
            }
        }
        { const int s_ = s; { const int s = s_ + 1; TS(0); } }
        poll_state(bm, (const char*)g_x + eo);
    }
    mbar_wait_u(bar_x, (NSEG - 1) & 1);
    if (r == 0) publish_kvm(NSEG - 1);
    asm volatile("barrier.cluster.arrive.relaxed.aligned;\nbarrier.cluster.wait.aligned;" ::: "memory");
}

constexpr int S4_US = 4368;
constexpr int S4_RS = 8848;
constexpr int S4_KS = 1296;
constexpr int S4_U = 0, S4_R = 16 * S4_US, S4_K = S4_R + 16 * S4_RS;
constexpr int S4_SMEM = S4_K + 16 * S4_KS;
constexpr int S4_SIG = 3104, S4_PK = 2 * S4_SIG;

struct cf { float r, i; };
__device__ __forceinline__ cf cmul(cf a, cf b) { return {fmaf(a.r, b.r, -a.i * b.i), fmaf(a.r, b.i, a.i * b.r)}; }
__device__ __forceinline__ cf cmulc(cf a, cf b) { return {fmaf(a.r, b.r, a.i * b.i), fmaf(a.i, b.r, -a.r * b.i)}; }
__device__ __forceinline__ cf csq(cf a) { const float t = a.r * a.i; return {fmaf(a.r, a.r, -a.i * a.i), t + t}; }
__device__ __forceinline__ cf cexp(float l2, float turns) {
    const float mag = ex2(l2), fr = (turns - rintf(turns)) * 6.283185307179586f;
    return {mag * __cosf(fr), mag * __sinf(fr)};
}
__device__ __forceinline__ void sts32(uint32_t a, uint32_t v) { asm volatile("st.shared.u32 [%0], %1;" ::"r"(a), "r"(v) : "memory"); }
__device__ __forceinline__ uint32_t lds16(uint32_t a) {
    uint32_t v;
    asm volatile("ld.shared.u16 %0, [%1];" : "=r"(v) : "r"(a) : "memory");
    return v;
}

template <int M0, int NQ>
__device__ __forceinline__ void s4_class(float (&acc)[16][4], uint32_t sig, uint32_t taps, int x0) {
    constexpr int D0 = M0 / 8, D1 = M0 == 32 ? 9 : 15;
    uint32_t R[D1 - D0 + 2];
#pragma unroll
    for (int D = D0 - 1; D <= D1; D++) {
        if (D < D0 || 8 * D - 7 >= 2 * M0) { R[D - D0 + 1] = 0; continue; }
        const int m = 8 * D + x0;
        uint32_t lo = lds16(taps + m * (2 * NQ)), hi = lds16(taps + (m - 1) * (2 * NQ));
        if (D == D0) { lo = m >= M0 ? lo : 0; hi = m > M0 ? hi : 0; }
        if (D == 2 * D0) { lo = m < 2 * M0 ? lo : 0; hi = m <= 2 * M0 ? hi : 0; }
        R[D - D0 + 1] = lo | (hi << 16);
    }
#pragma unroll
    for (int J = 0; 2 * J + D0 < 16; J++) {
        uint32_t a[4];
        ldsm4t(a, sig + J * 512);
#pragma unroll
        for (int D = D0; D <= D1; D++)
            if (2 * J + D < 16) mma16816(acc[2 * J + D], a[0], a[1], a[2], a[3], R[D - D0 + 1], R[D - D0]);
    }
}

__global__ void __launch_bounds__(512, 1)
k_s4(const bf16* __restrict__ u, const bf16* __restrict__ Are, const bf16* __restrict__ Aim, const bf16* __restrict__ Bre,
     const bf16* __restrict__ Bim, const bf16* __restrict__ Cre, const bf16* __restrict__ Cim, const bf16* __restrict__ logdt,
     const bf16* __restrict__ Dsk, bf16* __restrict__ out) {
    extern __shared__ __align__(16) uint8_t smem_s4[];
    const uint32_t sb = smem_u32(smem_s4);
    asm volatile("griddepcontrol.launch_dependents;");
    const int tid = threadIdx.x, w = __shfl_sync(~0u, tid >> 5, 0), lane = tid & 31, g = lane >> 2, t = lane & 3;
    if (tid == 0) TL(2, 0);
    const int d0 = blockIdx.x * 16;
    const int d = d0 + (w & 1) + ((w >> 1) & 3) * 4 + (w >> 3) * 2;
    const uint32_t tr_off = (lane & 15), tr_l = (lane >> 4) * 16;
    const uint32_t ur = sb + S4_U + w * S4_US, rs = sb + S4_R + w * S4_RS, kd = sb + S4_K + w * S4_KS;
    if (lane < 16) sts128(ur + lane * 16, 0, 0, 0, 0);
    {
        const int o = d * 128 + lane * 4;
        const uint2 ar = __ldg((const uint2*)(Are + o)), ai = __ldg((const uint2*)(Aim + o)), br = __ldg((const uint2*)(Bre + o));
        const uint2 bi = __ldg((const uint2*)(Bim + o)), cr = __ldg((const uint2*)(Cre + o)), ci = __ldg((const uint2*)(Cim + o));
        const float dt = bf_round(expf(__bfloat162float(logdt[d])));
        const bf16* src = u + (size_t)(w * 128 + g) * DM + d0 + 4 * t;
        float T[5][4];
#pragma unroll
        for (int i = 0; i < 5; i++) T[i][0] = T[i][1] = T[i][2] = T[i][3] = 0.f;
        float klast = 0.f;
        const uint32_t wr_ = rs + lane * 272, rd_ = rs + t * 544 + g * 16;
#pragma unroll 1
        for (int c = 0; c < 4; c++) {
            uint2 v[4];
#pragma unroll
            for (int i = 0; i < 4; i++) v[i] = __ldg((const uint2*)(src + (size_t)(c * 32 + i * 8) * DM));
            auto pick = [&](const uint2& x) { const uint32_t y = c < 2 ? x.x : x.y; return (c & 1) ? bf_hi(y) : bf_lo(y); };
            auto pk2 = [](cf x) { return pack2(x.r, x.i); };
            const float l2 = dt * pick(ar) * 1.4426950408889634f, tu = dt * pick(ai) * 0.15915494309189535f;
            const cf z1 = cexp(l2, tu), z2 = csq(z1), z4 = csq(z2), z8 = csq(z4);
            const cf z64 = cexp(l2 * 64.f, tu * 64.f), z128 = csq(z64), z256 = csq(z128), z512 = csq(z256);
            cf a0 = {1.f, 0.f}, a1 = z64;
            cf b0 = cmul({pick(cr), pick(ci)}, {dt * pick(br), dt * pick(bi)});
            b0.i = -b0.i;
            cf b1 = cmulc(b0, z128), b2 = cmulc(b0, z256), y3 = cmulc(b0, z512), b4 = cmulc(y3, z512), b3 = y3;
            const cf y2 = cmulc(b2, z128);
#pragma unroll
            for (int i = 0; i < 8; i++) {
                sts128(wr_ + i * 16, pk2(a0), pk2(a1), pk2(b0), pk2(b1));
                sts128(wr_ + i * 16 + 128, pk2(b2), pk2(b3), pk2(b4), 0);
                b4 = cmulc(b4, z128);
                if (i < 7) {
                    a0 = i == 0 ? z8 : cmul(a0, z8); a1 = cmul(a1, z8);
                    b0 = cmulc(b0, z1); b1 = cmulc(b1, z1);
                    b2 = i == 3 ? y2 : cmulc(b2, z2);
                    if (i & 1) { y3 = cmulc(y3, z128); b3 = y3; } else b3 = cmulc(y3, z4);
                }
            }
            klast += b4.r;
            __syncwarp();
#pragma unroll
            for (int k = 0; k < 8; k++) {
                uint32_t x[4], y[4];
                lds128(x, rd_ + (8 * (k >> 1) + (k & 1)) * 272);
                lds128(y, rd_ + (8 * (k >> 1) + (k & 1)) * 272 + 128);
                mma1688(T[0], x[0], x[1], x[2]);
                mma1688(T[1], x[0], x[1], x[3]);
                mma1688(T[2], x[0], x[1], y[0]);
                mma1688(T[3], x[0], x[1], y[1]);
                mma1688(T[4], x[0], x[1], y[2]);
            }
#pragma unroll
            for (int i = 0; i < 2; i++)
                stsm4t(sb + S4_U + tr_off * S4_US + 256 + (w * 128 + c * 32 + i * 16) * 2 + tr_l, v[2 * i].x, v[2 * i].y, v[2 * i + 1].x, v[2 * i + 1].y);
            __syncwarp();
        }
#pragma unroll
        for (int o2 = 16; o2; o2 >>= 1) klast += __shfl_xor_sync(~0u, klast, o2);
#pragma unroll
        for (int hh = 0; hh < 2; hh++) {
            const int i = g + 8 * hh;
            sts32(kd + (8 * i + 2 * t) * 2, pack2(T[0][2 * hh], T[0][2 * hh + 1]));
            sts32(kd + (128 + 8 * i + 2 * t) * 2, pack2(T[1][2 * hh], T[1][2 * hh + 1]));
            sts32(kd + (256 + 4 * i + 2 * (t & 1) + 64 * (t >> 1)) * 2, pack2(T[2][2 * hh], T[2][2 * hh + 1]));
            sts32(kd + (384 + 2 * i + 32 * t) * 2, pack2(T[3][2 * hh], T[3][2 * hh + 1]));
        }
        asm volatile("stmatrix.sync.aligned.m8n8.x2.trans.shared.b16 [%0], {%1,%2};"
                     ::"r"(kd + 1024 + (lane & 7) * 32 + ((lane >> 3) & 1) * 16), "r"(pack2(T[4][0], T[4][1])), "r"(pack2(T[4][2], T[4][3])) : "memory");
        if (lane == 0) sts32(kd + 1280, pack2(klast, 0.f));
    }
    __syncwarp();
    const uint32_t pk = rs + S4_PK + 64;
    {
#pragma unroll
        for (int i = 0; i < 2; i++) {
            const int x = i * 128 + lane * 4;
            const uint2 c = lds64(kd + x * 2);
            uint32_t p = lds16(kd + x * 2 - 2);
            if (x == 0) p = 0;
            sts128(pk + x * 4, __byte_perm(c.x, p, 0x5410), __byte_perm(c.x, 0, 0x1032), __byte_perm(c.y, c.x, 0x7610), __byte_perm(c.y, 0, 0x1032));
        }
#pragma unroll
        for (int i = 2; i < 4; i++) {
            const int x = i * 128 + lane * 4;
            const uint32_t ab = lds32(kd + 256 + x), c = lds16(kd + 256 + x + 4);
            const uint32_t p = x == 256 ? lds16(kd + 510) : ab;
            sts128(pk + x * 4, __byte_perm(ab, p, 0x5410), __byte_perm(ab, 0, 0x1010), __byte_perm(ab, 0, 0x1032), __byte_perm(c, ab, 0x7610));
        }
        const uint32_t v = lds16(kd + 768), v2 = lds16(kd + 1024);
        if (lane < 24) {
            uint32_t x0 = 0, x1 = 0, x2 = 0, x3 = 0;
            if (lane == 0) { x0 = x1 = x2 = v | (v << 16); x3 = v << 16; }
            if (lane == 12) x3 = v2;
            if (lane == 13) { x0 = v2 | (v2 << 16); x1 = v2 << 16; }
            sts128(lane < 20 ? pk + 2048 + lane * 16 : pk - 64 + (lane - 20) * 16, x0, x1, x2, x3);
        }
        if (lane < 4) sts128(rs + (lane >> 1) * S4_SIG + (lane & 1) * 16, 0, 0, 0, 0);
    }
    __syncthreads();
    float acc[16][4];
#pragma unroll
    for (int i = 0; i < 16; i++) acc[i][0] = acc[i][1] = acc[i][2] = acc[i][3] = 0.f;
    const uint32_t lf = (lane & 7) * 32 + ((lane >> 3) & 1) * 16 + (lane >> 4) * 256;
#pragma unroll 1
    for (int ph = 0; ph < 2; ph++) {
    if (((w >> 2) ^ ph) & 1) {
#pragma unroll
    for (int rg = 3; rg >= 2; rg--) {
#pragma unroll 1
        for (int it = 0; it < (rg == 3 ? 4 : 6); it++) {
            const int n = it * 32 + lane;
            uint32_t x[2][4];
            lds128(x[0], ur + 256 + n * 16 - 16);
            lds128(x[1], ur + 256 + n * 16);
            float e[16], p[15], s[11];
#pragma unroll
            for (int i = 0; i < 8; i++) { e[2 * i] = bf_lo(x[i >> 2][i & 3]); e[2 * i + 1] = bf_hi(x[i >> 2][i & 3]); }
#pragma unroll
            for (int i = 0; i < 15; i++) p[i] = e[i] + e[i + 1];
#pragma unroll
            for (int i = 0; i < 11; i++) s[i] = p[i + 3] + e[i + 5];
            const uint32_t o = rs + 16 + n * 16;
            if (rg == 2) sts128(o, pack2(s[0], s[1]), pack2(s[2], s[3]), pack2(s[4], s[5]), pack2(s[6], s[7]));
#pragma unroll
            for (int i = 0; i < 10; i++) s[i] = p[i + 2] + s[i + 1];
            if (rg == 2) {
                sts64(o + S4_SIG + 8, pack2(s[0], s[1]), pack2(s[2], s[3]));
                sts64(o + S4_SIG + 16, pack2(s[4], s[5]), pack2(s[6], s[7]));
            } else {
#pragma unroll
                for (int i = 0; i < 9; i++) s[i] = p[i + 1] + s[i + 1];
                sts64(o + 8, pack2(s[0], s[1]), pack2(s[2], s[3]));
                sts64(o + 16, pack2(s[4], s[5]), pack2(s[6], s[7]));
#pragma unroll
                for (int i = 0; i < 8; i++) s[i] = p[i] + s[i + 1];
                sts64(o + S4_SIG + 8, pack2(s[0], s[1]), pack2(s[2], s[3]));
                sts64(o + S4_SIG + 16, pack2(s[4], s[5]), pack2(s[6], s[7]));
            }
        }
        __syncwarp();
        if (rg == 3) {
#pragma unroll 1
            for (int q = 1; q <= 2; q++) s4_class<64, 2>(acc, rs + lf + (q == 1 ? 16 : S4_SIG), kd + (384 + q) * 2, g - 2 * t);
        } else {
#pragma unroll 1
            for (int q = 1; q <= 4; q++) s4_class<32, 4>(acc, rs + lf + ((q & 1) ? 0 : S4_SIG) + (q < 3 ? 16 : 0), kd + (256 + q) * 2, g - 2 * t);
        }
        __syncwarp();
    }
    } else
    {
        const uint32_t ub = ur + 256 + lf, kb = pk + (g - 2 * t) * 4;
#pragma unroll 1
        for (int j0 = 0; j0 < 8; j0++) {
            uint32_t B[8][4];
#pragma unroll
            for (int i = 0; i < 8; i++) ldsm4(B[i], ub + i * 512 - j0 * 32);
            auto block = [&](int J, uint32_t a) {
                const uint32_t r0 = lds32(a), rp = lds32(a + 32), rm = lds32(a - 32);
                uint32_t r3;
                asm volatile("ld.volatile.shared.u32 %0, [%1];" : "=r"(r3) : "r"(a) : "memory");
#pragma unroll
                for (int I = J; I < 16; I++)
                    mma16816(acc[I], r0, rp, rm, r3, B[(I - J) >> 1][((I - J) & 1) * 2], B[(I - J) >> 1][((I - J) & 1) * 2 + 1]);
            };
#pragma unroll
            for (int J = 0; J < 4; J++) block(J, kb + j0 * 64 + J * 512);
            if (j0 < 2) { block(4, kb + j0 * 64 + 2048); block(8, kb + j0 * 64 + (544 + 16) * 4); }
        }
    }
    }
    {
        __syncwarp();
#pragma unroll
        for (int i = 0; i < 8; i++)
            stsm4t(rs + lf + i * 512, pack2(acc[2 * i][0], acc[2 * i][1]), pack2(acc[2 * i][2], acc[2 * i][3]),
                   pack2(acc[2 * i + 1][0], acc[2 * i + 1][1]), pack2(acc[2 * i + 1][2], acc[2 * i + 1][3]));
    }
    __syncthreads();
    {
        const uint2 dv = __ldg((const uint2*)(Dsk + d0 + 4 * t));
        bf16* dst = out + (size_t)(w * 128 + g) * 2048 + 1024 + d0 + 4 * t;
#pragma unroll
        for (int i = 0; i < 8; i++) {
            uint32_t y[4], x[4], o[4];
            ldsm4t(y, sb + S4_R + tr_off * S4_RS + (w * 128 + i * 16) * 2 + tr_l);
            ldsm4t(x, sb + S4_U + tr_off * S4_US + 256 + (w * 128 + i * 16) * 2 + tr_l);
#pragma unroll
            for (int j = 0; j < 4; j++)
                asm("{\n.reg .b32 s;\nmul.rn.bf16x2 s, %2, %3;\nadd.rn.bf16x2 %0, %1, s;\n}" : "=r"(o[j]) : "r"(y[j]), "r"(x[j]), "r"((j & 1) ? dv.y : dv.x));
            *reinterpret_cast<uint2*>(dst + (size_t)(i * 16) * 2048) = make_uint2(o[0], o[1]);
            *reinterpret_cast<uint2*>(dst + (size_t)(i * 16 + 8) * 2048) = make_uint2(o[2], o[3]);
        }
    }
    if (tid == 0) TL(2, 1);
}

enum { IT_QA = 0, IT_W256 = 1, IT_W128 = 2, IT_W64 = 3, IT_W64S = 4, IT_END = 7 };
struct BgParams { CUtensorMap mx, mwq, mkv, mkvm, mo, mo2, mo2s, mwo4, mwo2, mwo1; };
#define LOOK 8
#define NW0 4
#define NW1 16
#define PW1 25
#define P256 54
#define P128 56
__device__ __forceinline__ uint32_t ld_rlx32(const uint32_t* p) {
    uint32_t v;
    asm volatile("ld.relaxed.gpu.global.u32 %0, [%1];" : "=r"(v) : "l"(p) : "memory");
    return v;
}
#define NBT 9
#define NBL 9
constexpr uint32_t W_LONG = NBL * 16, W_LAST = NBT * 16, W_END = W_LAST + 32;
__device__ __forceinline__ bool block_done(uint32_t strip) { return ld_rlx32(g_flag + 64 + (strip < W_LAST ? strip >> 4 : 15)) >= 16; }
struct Sched { uint32_t qb = 0, w0 = 0, w1 = 0; };
__device__ __forceinline__ int next_item(Sched& z) {
    for (int n = 0; n < SPIN_LIMIT; n++) {
        if (z.w0 < z.w1 && (z.qb >= 16 || block_done(z.w0))) {
            const uint32_t i = z.w0, k = i >= W_LAST ? 1 : z.w1 - i >= 4 && !(i & 3) ? 4 : z.w1 - i >= 2 && !(i & 1) ? 2 : 1;
            z.w0 += k;
            if (i >= W_LAST) return IT_W64S | 15 << 3 | (i - W_LAST) << 7;
            return (k == 4 ? IT_W256 : k == 2 ? IT_W128 : IT_W64) | (i >> 4) << 3 | ((i & 15) / k) << 7;
        }
        const uint32_t prog = ld_acq32(g_flag + 98);
        uint32_t wo = ld_rlx32(g_flag + 97);
        if (wo >= W_LAST) wo = W_LAST + ld_rlx32(g_flag + 100);
        z.qb = max(z.qb, ld_rlx32(g_flag + 96));
        const bool wo_ready = z.w0 >= z.w1 && wo < W_END &&
                              (z.qb >= 16 || (wo < W_LONG && blockIdx.x < (prog < PW1 ? NW0 : NW1) && block_done(wo)));
        if (z.qb < 16 && prog > 0 && prog + LOOK >= 4 * z.qb + 4 && !wo_ready) {
            const uint32_t i = atomicAdd(g_flag + 80 + z.qb, 1);
            if (i == 15) atomicMax(g_flag + 96, z.qb + 1);
            if (i < 16) return IT_QA | z.qb << 3 | i << 7;
            z.qb++;
            continue;
        }
        if (z.w0 < z.w1) {
            if (z.qb >= 16) continue;
        } else if (wo >= W_END) {
            if (z.qb >= 16) return IT_END;
        } else if (wo_ready) {
            if (wo < W_LAST) {
                const uint32_t k = prog <= P256 ? 4 : prog <= P128 ? 2 : 1;
                z.w0 = atomicAdd(g_flag + 97, k);
                z.w1 = min(z.w0 + k, W_LAST);
            } else {
                z.w0 = W_LAST + atomicAdd(g_flag + 100, 1);
                z.w1 = min(z.w0 + 1, W_END);
            }
            continue;
        }
        __nanosleep(300);
    }
    __trap();
    return IT_END;
}
constexpr int B_OST = NSTAGE * STAGE_BYTES + 1024;
constexpr int BG_SMEM = B_OST + 32768;

template <int BM, int BN, int KPS, typename ACC>
__device__ __forceinline__ void gemm_mainloop(ACC& acc, const GemmSmem& g, int cw, int rounds, uint32_t& round) {
#pragma unroll
    for (int i = 0; i < BN / 2; i++) acc[i] = 0.f;
#pragma unroll 1
    for (int k0 = 0; k0 < rounds; k0++, round++) {
#pragma unroll
        for (int s = 0; s < 4; s++) {
            mbar_wait_u(g.full + 8 * s, round & 1);
            gemm_stage<BM, BN, KPS>(acc, g.st + s * STAGE_BYTES, cw, false);
            wg_wait<1>();
            if (s > 0 || k0 > 0) mbar_arrive_one(g.empty + 8 * ((s + 3) & 3), threadIdx.x & 31);
        }
    }
    wg_wait<0>();
    mbar_arrive_one(g.empty + 8 * 3, threadIdx.x & 31);
}

template <int BN>
__device__ __forceinline__ void store_tile(const float (&acc)[BN / 2], bf16* dst, int t) {
#pragma unroll
    for (int G = 0; G < BN / 32; G++)
#pragma unroll
        for (int rr = 0; rr < 2; rr++) {
            uint32_t r0 = pack2(acc[16 * G + 2 * rr], acc[16 * G + 2 * rr + 1]), r1 = pack2(acc[16 * G + 4 + 2 * rr], acc[16 * G + 5 + 2 * rr]);
            uint32_t r2 = pack2(acc[16 * G + 8 + 2 * rr], acc[16 * G + 9 + 2 * rr]), r3 = pack2(acc[16 * G + 12 + 2 * rr], acc[16 * G + 13 + 2 * rr]);
            quad_transpose(r0, r1, r2, r3, t);
            *reinterpret_cast<uint4*>(dst + (size_t)rr * 8 * 2048 + G * 32) = make_uint4(r0, r1, r2, r3);
        }
}

template <int BM, int BN, int KPS>
__device__ __forceinline__ void wo_item(const GemmSmem& g, int cw, uint32_t& round, bf16* dst, int t) {
    if (BM == 64 && cw == 1) {
#pragma unroll 1
        for (int k0 = 0; k0 < 16 / KPS; k0++, round++)
#pragma unroll
            for (int s = 0; s < 4; s++) { mbar_wait_u(g.full + 8 * s, round & 1); mbar_arrive_one(g.empty + 8 * s, threadIdx.x & 31); }
        return;
    }
    float acc[BN / 2];
    gemm_mainloop<BM, BN, KPS>(acc, g, cw, 16 / KPS, round);
    store_tile<BN>(acc, dst, t);
}

template <int HF>
__device__ __forceinline__ void attend(const uint32_t* q, uint32_t st, uint32_t sm, uint32_t ost, uint32_t bar_free, uint32_t parity, int lane) {
    constexpr int NT = HF ? 5 : 3;
    const int r8 = lane & 7, m4 = lane >> 3, gq = lane >> 2, t = lane & 3;
    const float sl2e = 0.08838834764831845f * 1.4426950408889634f;
    const uint32_t la = r8 * 128 + ((m4 ^ r8) << 4);
    float sc[NT][4];
#pragma unroll
    for (int nt = 0; nt < NT; nt++) sc[nt][0] = sc[nt][1] = sc[nt][2] = sc[nt][3] = 0.f;
#pragma unroll
    for (int kp = 0; kp < 4; kp++)
#pragma unroll
        for (int nt = 0; nt < NT; nt++) {
            uint32_t b[4];
            ldsm4(b, (nt == 0 ? sm + (kp >> 1) * 2048 : st + (kp >> 1) * 8192 + (nt - 1) * 1024) + (la ^ ((kp & 1) << 6)));
            mma16816(sc[nt], q[kp * 8], q[kp * 8 + 1], q[kp * 8 + 2], q[kp * 8 + 3], b[0], b[1]);
            mma16816(sc[nt], q[kp * 8 + 4], q[kp * 8 + 5], q[kp * 8 + 6], q[kp * 8 + 7], b[2], b[3]);
        }
    const float ninf = -3.0e38f;
    if (2 * t > gq) sc[NT - 2][0] = sc[NT - 1][2] = ninf;
    if (2 * t + 1 > gq) sc[NT - 2][1] = sc[NT - 1][3] = ninf;
    sc[NT - 1][0] = sc[NT - 1][1] = ninf;
    uint32_t p[NT][2];
#pragma unroll
    for (int i = 0; i < 2; i++) {
        float m = fmaxf(sc[0][2 * i], sc[0][2 * i + 1]);
#pragma unroll
        for (int nt = 1; nt < NT - 1 + i; nt++) m = fmaxf(m, fmaxf(sc[nt][2 * i], sc[nt][2 * i + 1]));
        m = fmaxf(m, __shfl_xor_sync(~0u, m, 1));
        m = fmaxf(m, __shfl_xor_sync(~0u, m, 2));
        const float ms = m * sl2e;
        float sum = 0.f;
#pragma unroll
        for (int nt = 0; nt < NT - 1 + i; nt++) {
            sc[nt][2 * i] = ex2(fmaf(sc[nt][2 * i], sl2e, -ms));
            sc[nt][2 * i + 1] = ex2(fmaf(sc[nt][2 * i + 1], sl2e, -ms));
            sum += sc[nt][2 * i] + sc[nt][2 * i + 1];
        }
        sum += __shfl_xor_sync(~0u, sum, 1);
        sum += __shfl_xor_sync(~0u, sum, 2);
        float inv;
        asm("rcp.approx.ftz.f32 %0, %1;" : "=f"(inv) : "f"(sum));
#pragma unroll
        for (int nt = 0; nt < NT - 1 + i; nt++) p[nt][i] = pack2(sc[nt][2 * i] * inv, sc[nt][2 * i + 1] * inv);
    }
    p[NT - 1][0] = 0;
    const uint32_t lv = ((m4 & 1) * 8 + r8) * 128 + (((m4 >> 1) ^ r8) << 4);
    mbar_wait_u(bar_free, parity);
#pragma unroll
    for (int G = 0; G < 4; G++) {
        float o[4][4];
#pragma unroll
        for (int i = 0; i < 4; i++) o[i][0] = o[i][1] = o[i][2] = o[i][3] = 0.f;
        uint32_t b[4];
        ldsm4t(b, sm + 4096 + (G >> 1) * 2048 + (la ^ ((G & 1) << 6)));
#pragma unroll
        for (int i = 0; i < 4; i++) mma1688(o[i], p[0][0], p[0][1], b[i]);
#pragma unroll
        for (int kk = 0; kk <= HF; kk++)
#pragma unroll
            for (int i = 0; i < 2; i++) {
                ldsm4t(b, st + 16384 + (G >> 1) * 8192 + kk * 2048 + (lv ^ (((G & 1) * 2 + i) << 5)));
                mma16816(o[2 * i], p[1 + 2 * kk][0], p[1 + 2 * kk][1], p[2 + 2 * kk][0], p[2 + 2 * kk][1], b[0], b[1]);
                mma16816(o[2 * i + 1], p[1 + 2 * kk][0], p[1 + 2 * kk][1], p[2 + 2 * kk][0], p[2 + 2 * kk][1], b[2], b[3]);
            }
#pragma unroll
        for (int i = 0; i < 2; i++)
            asm volatile("stmatrix.sync.aligned.m8n8.x4.shared.b16 [%0], {%1,%2,%3,%4};"
                         ::"r"(ost + (G >> 1) * 16384 + (lv ^ (((G & 1) * 2 + i) << 5))),
                           "r"(pack2(o[2 * i][0], o[2 * i][1])), "r"(pack2(o[2 * i][2], o[2 * i][3])),
                           "r"(pack2(o[2 * i + 1][0], o[2 * i + 1][1])), "r"(pack2(o[2 * i + 1][2], o[2 * i + 1][3])) : "memory");
    }
    asm volatile("fence.proxy.async.shared::cta;" ::: "memory");
    __syncwarp();
}

__device__ __forceinline__ void tma_prefetch3d(const CUtensorMap* m, int c0, int c1, int c2) {
    asm volatile("cp.async.bulk.prefetch.tensor.3d.L2.global [%0, {%1, %2, %3}];" ::"l"(m), "r"(c0), "r"(c1), "r"(c2) : "memory");
}

__global__ void __launch_bounds__(384, 1) k_bg(const __grid_constant__ BgParams P, bf16* __restrict__ out) {
    extern __shared__ __align__(1024) uint8_t smem_gemm[];
    asm volatile("griddepcontrol.launch_dependents;");
    const uint32_t xb = smem_u32(smem_gemm) + NSTAGE * STAGE_BYTES + 128;
    const uint32_t bar_item = xb, bar_o = xb + 16, bar_f = xb + 24, slot = xb + 32, slot_o = xb + 40;
    if (threadIdx.x == 0) { mbar_init(bar_item, 1); mbar_init(bar_item + 8, 1); mbar_init(bar_o, 8); mbar_init(bar_f, 1); }
    GemmSmem g = gemm_setup(smem_gemm, 8);
    const int wg = __shfl_sync(~0u, threadIdx.x >> 7, 0);
    if (wg == 0) {
        asm volatile("setmaxnreg.dec.sync.aligned.u32 40;");
        if (threadIdx.x == 0) {
            uint32_t it = 0;
            Sched z;
            auto acquire = [&](uint32_t bytes) {
                const int s = it & 3;
                mbar_wait(g.empty + 8 * s, ((it >> 2) & 1) ^ 1);
                mbar_expect_tx(g.full + 8 * s, bytes);
                it++;
                return s;
            };
            for (int n = 0;; n++) {
                const int code = next_item(z);
                sts32(slot + (n & 1) * 4, code);
                mbar_arrive(bar_item + (n & 1) * 8);
                const int type = code & 7, blk = (code >> 3) & 15, idx = code >> 7, m0 = blk * 128;
                if (type == IT_END) break;
                if (type == IT_QA) {
                    for (int k = 0; k < 16; k++) {
                        const int s = acquire(STAGE_BYTES);
                        const uint32_t st = g.st + s * STAGE_BYTES, fb = g.full + 8 * s;
                        tma2d(st, &P.mx, k * 64, m0, fb);
                        tma3d(st + 16384, &P.mwq, 0, k * 64, idx * 4, fb);
                        if (k >= 4 && k < 12) tma_prefetch3d(&P.mkv, 0, m0 + (k & 1) * 64, (k & 8) * 8 + idx * 4 + (k & 2));
                    }
                    bool ready = ld_acq32(g_flag + 2 * idx) >= 4 * blk + 4 && ld_acq32(g_flag + 2 * idx + 1) >= 4 * blk + 4;
                    if (ready) asm volatile("fence.proxy.async.global;" ::: "memory");
                    for (int pass = 0; pass < 2; pass++) {
                        for (int s = 0; s < 4; s++) {
                            const uint32_t st = g.st + s * STAGE_BYTES, fb = g.full + 8 * s;
                            if (pass == 0) {
                                acquire(40960);
                                tma3d(st, &P.mkv, 0, m0 + (s & 1) * 64, idx * 4 + (s & 2), fb);
                                tma3d(st + 16384, &P.mkv, 0, m0 + (s & 1) * 64, 64 + idx * 4 + (s & 2), fb);
                            }
                            if (ready) {
                                tma3d(st + 32768, &P.mkvm, 0, blk * 32 + (s & 1) * 16, idx * 4 + (s & 2), fb);
                                tma3d(st + 36864, &P.mkvm, 0, blk * 32 + (s & 1) * 16, 64 + idx * 4 + (s & 2), fb);
                            }
                        }
                        if (ready) break;
                        wait_flag(g_flag + 2 * idx, 4 * blk + 4);
                        wait_flag(g_flag + 2 * idx + 1, 4 * blk + 4);
                        asm volatile("fence.proxy.async.global;" ::: "memory");
                        ready = true;
                    }
                } else {
                    wait_flag(g_flag + 64 + blk, 16);
                    asm volatile("fence.proxy.async.global;" ::: "memory");
                    if (type <= IT_W128) {
                        const int nb = type == IT_W256 ? 4 : 2;
                        for (int k = 0; k < 64; k++) {
                            const int s = acquire(16384 + nb * 8192);
                            const uint32_t st = g.st + s * STAGE_BYTES, fb = g.full + 8 * s;
                            tma2d(st, &P.mo, k * 64, m0, fb);
                            tma3d(st + 16384, nb == 4 ? &P.mwo4 : &P.mwo2, 0, k * 64, idx * nb, fb);
                        }
                    } else {
                        const uint32_t ab = type == IT_W64 ? 32768 : 16384;
                        for (int k = 0; k < 32; k++) {
                            const int s = acquire(ab + 16384);
                            const uint32_t st = g.st + s * STAGE_BYTES, fb = g.full + 8 * s;
                            tma3d(st, type == IT_W64 ? &P.mo2 : &P.mo2s, 0, m0 + (idx >> 4) * 64, k * 2, fb);
                            tma3d(st + ab, &P.mwo1, 0, k * 128, idx & 15, fb);
                        }
                    }
                }
            }
        } else if (threadIdx.x == 32) {
            for (;;) {
                mbar_wait(bar_o, 0);
                const int code = lds32(slot_o), blk = (code >> 3) & 15, idx = (code >> 7) & 31;
                if ((code & 7) == IT_END) break;
                for (int hh = 0; hh < 2; hh++) {
                    if (hh) mbar_wait(bar_o, 1);
                    asm volatile("cp.async.bulk.tensor.3d.global.shared::cta.bulk_group [%0, {%2, %3, %4}], [%1];\n"
                                 "cp.async.bulk.commit_group;\ncp.async.bulk.wait_group.read 0;"
                                 ::"l"(&P.mo2), "r"(g.st + B_OST), "r"(0), "r"(blk * 128), "r"(idx * 4 + hh * 2) : "memory");
                    mbar_arrive(bar_f);
                }
                asm volatile("cp.async.bulk.wait_group 0;\nfence.acq_rel.gpu;\nred.relaxed.gpu.global.add.u32 [%0], 1;"
                             ::"l"(g_flag + 64 + blk) : "memory");
            }
        }
    } else {
        asm volatile("setmaxnreg.inc.sync.aligned.u32 232;");
        const int cw = wg - 1, ww = __shfl_sync(~0u, (threadIdx.x >> 5) & 3, 0), lane = threadIdx.x & 31;
        uint32_t round = 0;
#pragma unroll 1
        for (int n = 0;; n++) {
            mbar_wait_u(bar_item + (n & 1) * 8, (n >> 1) & 1);
            const int code = __shfl_sync(~0u, lds32(slot + (n & 1) * 4), 0);
            const int type = code & 7, blk = (code >> 3) & 15, idx = (code >> 7) & 31;
#define TLB(slot_)
            if (type == IT_END) {
                mbar_wait_u(bar_f, 1);
                if (threadIdx.x == 128) sts32(slot_o, IT_END);
                __syncwarp();
                mbar_arrive_one(bar_o, lane);
                break;
            }
            TLB(0);
            if (type == IT_QA) {
                uint32_t q[64];
                {
                    float acc[128];
                    gemm_mainloop<128, 256, 1>(acc, g, cw, 4, round);
#pragma unroll
                    for (int i = 0; i < 64; i++) q[i] = pack2(acc[2 * i], acc[2 * i + 1]);
                }
                if (threadIdx.x == 128) sts32(slot_o, code);
                TLB(2);
#pragma unroll
                for (int hh = 0; hh < 2; hh++) {
                    const uint32_t st = g.st + (2 * hh + cw) * STAGE_BYTES, ost = g.st + B_OST + (cw * 4 + ww) * 2048;
                    mbar_wait_u(g.full + 16 * hh, round & 1);
                    mbar_wait_u(g.full + 16 * hh + 8, round & 1);
                    if (hh == 0) { TLB(3); }
                    if (ww & 1) attend<1>(q + 32 * hh, st + (ww >> 1) * 4096, st + 32768 + (ww >> 1) * 1024, ost, bar_f, hh ^ 1, lane);
                    else attend<0>(q + 32 * hh, st + (ww >> 1) * 4096, st + 32768 + (ww >> 1) * 1024, ost, bar_f, hh ^ 1, lane);
                    mbar_arrive_one(bar_o, lane);
                    mbar_arrive_one(g.empty + 16 * hh, lane);
                    mbar_arrive_one(g.empty + 16 * hh + 8, lane);
                }
                round++;
            } else {
                bf16* dst = out + (size_t)(blk * 128 + cw * 64 + ww * 16 + (lane >> 2)) * 2048 + (lane & 3) * 8;
                if (type == IT_W256) wo_item<128, 256, 1>(g, cw, round, dst + idx * 256, lane & 3);
                else if (type == IT_W128) wo_item<128, 128, 1>(g, cw, round, dst + idx * 128, lane & 3);
                else if (type == IT_W64) wo_item<128, 64, 2>(g, cw, round, dst + idx * 64, lane & 3);
                else wo_item<64, 64, 2>(g, cw, round, dst + (size_t)(idx >> 4) * 64 * 2048 + (idx & 15) * 64, lane & 3);
            }
            TLB(1);
        }
    }
}

#define TCL 6
__global__ void __cluster_dims__(TCL, 1, 1) __launch_bounds__(384, 1)
k_tail(const __grid_constant__ CUtensorMap mo, const __grid_constant__ CUtensorMap mwo2, bf16* __restrict__ out) {
    extern __shared__ __align__(1024) uint8_t smem_gemm[];
    const uint32_t bar_s = smem_u32(smem_gemm) + NSTAGE * STAGE_BYTES + 128;
    if (threadIdx.x == 0) { TL(4, 0); mbar_init(bar_s, 1); mbar_expect_tx(bar_s, 32768); }
    GemmSmem g = gemm_setup(smem_gemm, 8);
    asm volatile("barrier.cluster.arrive.relaxed.aligned;" ::: "memory");
    const int half = blockIdx.x & 1, cl = blockIdx.x / 6, peer = TCL == 6 ? (blockIdx.x - 6 * cl) ^ 1 : half ^ 1;
    const int blk = TCL == 6 ? NBT + (cl >> 3) * 3 + (peer >> 1) : NBT + (blockIdx.x >> 4), idx = TCL == 6 ? cl & 7 : (blockIdx.x >> 1) & 7;
    const int wg = __shfl_sync(~0u, threadIdx.x >> 7, 0);
    if (wg == 0) {
        if (threadIdx.x == 0) {
            wait_flag(g_flag + 64 + blk, 16);
            asm volatile("fence.proxy.async.global;" ::: "memory");
            for (int k = 0; k < 32; k++) {
                const int s = k & 3;
                const uint32_t st = g.st + s * STAGE_BYTES, fb = g.full + 8 * s;
                mbar_wait(g.empty + 8 * s, ((k >> 2) & 1) ^ 1);
                mbar_expect_tx(fb, 32768);
                tma2d(st, &mo, (half * 32 + k) * 64, blk * 128, fb);
                tma3d(st + 16384, &mwo2, 0, (half * 32 + k) * 64, idx * 2, fb);
            }
        }
        __syncwarp();
        asm volatile("barrier.cluster.wait.aligned;" ::: "memory");
    } else {
        const int cw = wg - 1, lane = threadIdx.x & 31, t = lane & 3;
        float acc[64];
        uint32_t round = 0;
        gemm_mainloop<128, 128, 1>(acc, g, cw, 8, round);
        asm volatile("barrier.cluster.wait.aligned;" ::: "memory");
        const uint32_t xa = g.st + B_OST + (threadIdx.x & 127) * 16;
        if (cw != half) {
            uint32_t ra, rb;
            asm("mapa.shared::cluster.u32 %0, %1, %2;" : "=r"(ra) : "r"(xa), "r"(peer));
            asm("mapa.shared::cluster.u32 %0, %1, %2;" : "=r"(rb) : "r"(bar_s), "r"(peer));
#pragma unroll
            for (int i = 0; i < 16; i++)
                asm volatile("st.async.weak.shared::cluster.mbarrier::complete_tx::bytes.v4.f32 [%0], {%1,%2,%3,%4}, [%5];"
                             ::"r"(ra + i * 2048), "f"(acc[4 * i]), "f"(acc[4 * i + 1]), "f"(acc[4 * i + 2]), "f"(acc[4 * i + 3]), "r"(rb) : "memory");
        } else {
            mbar_wait_u(bar_s, 0);
#pragma unroll
            for (int i = 0; i < 16; i++) {
                const float4 v = lds128f(xa + i * 2048);
                acc[4 * i] += v.x; acc[4 * i + 1] += v.y; acc[4 * i + 2] += v.z; acc[4 * i + 3] += v.w;
            }
            store_tile<128>(acc, out + (size_t)(blk * 128 + cw * 64 + ((threadIdx.x >> 5) & 3) * 16 + (lane >> 2)) * 2048 + idx * 128 + t * 8, t);
            if ((threadIdx.x & 127) == 0) TL(4, 1);
        }
    }
    asm volatile("barrier.cluster.arrive.relaxed.aligned;\nbarrier.cluster.wait.aligned;" ::: "memory");
}

typedef CUresult (*EncodeFn)(CUtensorMap*, CUtensorMapDataType, cuuint32_t, void*, const cuuint64_t*, const cuuint64_t*,
                             const cuuint32_t*, const cuuint32_t*, CUtensorMapInterleave, CUtensorMapSwizzle,
                             CUtensorMapL2promotion, CUtensorMapFloatOOBfill);

static void map2d(EncodeFn enc, CUtensorMap* m, const void* p, int rows, int cols, int box_rows) {
    cuuint64_t dim[2] = {(cuuint64_t)cols, (cuuint64_t)rows}, str[1] = {(cuuint64_t)cols * 2};
    cuuint32_t box[2] = {64, (cuuint32_t)box_rows}, es[2] = {1, 1};
    enc(m, CU_TENSOR_MAP_DATA_TYPE_BFLOAT16, 2, (void*)p, dim, str, box, es, CU_TENSOR_MAP_INTERLEAVE_NONE,
        CU_TENSOR_MAP_SWIZZLE_128B, CU_TENSOR_MAP_L2_PROMOTION_L2_256B, CU_TENSOR_MAP_FLOAT_OOB_FILL_NONE);
}
static void map3d(EncodeFn enc, CUtensorMap* m, const void* p, int rows, int cols, int box_rows, int nblk) {
    cuuint64_t dim[3] = {64, (cuuint64_t)rows, (cuuint64_t)cols / 64}, str[2] = {(cuuint64_t)cols * 2, 128};
    cuuint32_t box[3] = {64, (cuuint32_t)box_rows, (cuuint32_t)nblk}, es[3] = {1, 1, 1};
    enc(m, CU_TENSOR_MAP_DATA_TYPE_BFLOAT16, 3, (void*)p, dim, str, box, es, CU_TENSOR_MAP_INTERLEAVE_NONE,
        CU_TENSOR_MAP_SWIZZLE_128B, CU_TENSOR_MAP_L2_PROMOTION_L2_256B, CU_TENSOR_MAP_FLOAT_OOB_FILL_NONE);
}

#define USE_PDL 1

extern "C" void kernel_launch(void* const* d_in, const int* in_sizes, int n_in, void* d_out, int out_size) {
    const bf16 *x = (const bf16*)d_in[0], *mem0 = (const bf16*)d_in[1], *Wq = (const bf16*)d_in[2], *Wk = (const bf16*)d_in[3];
    const bf16 *Wv = (const bf16*)d_in[4], *Wo = (const bf16*)d_in[5];
    const bf16 *u = (const bf16*)d_in[7], *Are = (const bf16*)d_in[8], *Aim = (const bf16*)d_in[9], *Bre = (const bf16*)d_in[10];
    const bf16 *Bim = (const bf16*)d_in[11], *Cre = (const bf16*)d_in[12], *Cim = (const bf16*)d_in[13];
    const bf16 *logdt = (const bf16*)d_in[14], *Dsk = (const bf16*)d_in[15];
    bf16* out = (bf16*)d_out;

    void* fn = nullptr;
    cudaDriverEntryPointQueryResult qr;
    cudaGetDriverEntryPoint("cuTensorMapEncodeTiled", &fn, cudaEnableDefault, &qr);
    EncodeFn enc = (EncodeFn)fn;
    void *kv, *kvm, *o;
    cudaGetSymbolAddress(&kv, g_kv);
    cudaGetSymbolAddress(&kvm, g_kvm);
    cudaGetSymbolAddress(&o, g_o);
    CUtensorMap mwk, mwv, mkv2;
    BgParams P;
    map2d(enc, &P.mx, x, SEQ, DM, 128);
    map2d(enc, &P.mo, o, SEQ, HD, 128);
    map3d(enc, &P.mo2, o, SEQ, HD, 128, 2);
    map3d(enc, &P.mo2s, o, SEQ, HD, 64, 2);
    map3d(enc, &P.mwq, Wq, DM, HD, 64, 4);
    map3d(enc, &mwk, Wk, DM, HD, 64, 4);
    map3d(enc, &mwv, Wv, DM, HD, 64, 4);
    map3d(enc, &P.mwo4, Wo, HD, DM, 64, 4);
    map3d(enc, &P.mwo2, Wo, HD, DM, 64, 2);
    map3d(enc, &P.mwo1, Wo, HD, DM, 128, 1);
    map3d(enc, &mkv2, kv, SEQ, 8192, 32, 2);
    map3d(enc, &P.mkv, kv, SEQ, 8192, 64, 2);
    map3d(enc, &P.mkvm, kvm, NSEG * 8, 8192, 16, 2);
    cudaFuncSetAttribute(k_kv, cudaFuncAttributeMaxDynamicSharedMemorySize, GEMM_SMEM);
    cudaFuncSetAttribute(k_bg, cudaFuncAttributeMaxDynamicSharedMemorySize, BG_SMEM);
    cudaFuncSetAttribute(k_tail, cudaFuncAttributeMaxDynamicSharedMemorySize, BG_SMEM);
    cudaFuncSetAttribute(k_chain, cudaFuncAttributeMaxDynamicSharedMemorySize, CHAIN_SMEM);
    cudaFuncSetAttribute(k_s4, cudaFuncAttributeMaxDynamicSharedMemorySize, S4_SMEM);

    cudaStream_t st = cudaStreamPerThread;
    cudaLaunchAttribute pdl[1], cls[1];
    pdl[0].id = cudaLaunchAttributeProgrammaticStreamSerialization;
    pdl[0].val.programmaticStreamSerializationAllowed = 1;
    cls[0].id = cudaLaunchAttributeClusterDimension;
    cls[0].val.clusterDim.x = CLS; cls[0].val.clusterDim.y = 1; cls[0].val.clusterDim.z = 1;
    cudaLaunchConfig_t cfg = {};
    cfg.stream = st; cfg.attrs = cls; cfg.numAttrs = 1;
    cfg.gridDim = dim3(96); cfg.blockDim = dim3(384); cfg.dynamicSmemBytes = GEMM_SMEM;
    cudaLaunchKernelEx(&cfg, k_kv, P.mx, mwk, mwv, Wq, Wk, Wo, 0);
    cfg.attrs = pdl; cfg.numAttrs = 1;
    cfg.gridDim = dim3(36);
    cudaLaunchKernelEx(&cfg, k_kv, P.mx, mwk, mwv, Wq, Wk, Wo, 96);
    cfg.gridDim = dim3(96); cfg.blockDim = dim3(256); cfg.dynamicSmemBytes = CHAIN_SMEM;
    cudaLaunchKernelEx(&cfg, k_chain, mem0, Wq, Wk, Wv, Wo, mkv2);
    cfg.numAttrs = USE_PDL;
    cfg.gridDim = dim3(64); cfg.blockDim = dim3(512); cfg.dynamicSmemBytes = S4_SMEM;
    cudaLaunchKernelEx(&cfg, k_s4, u, Are, Aim, Bre, Bim, Cre, Cim, logdt, Dsk, out);
    cfg.gridDim = dim3(36); cfg.blockDim = dim3(384); cfg.dynamicSmemBytes = BG_SMEM;
    cudaLaunchKernelEx(&cfg, k_bg, P, out);
    cfg.gridDim = dim3((15 - NBT) * 16);
    cudaLaunchKernelEx(&cfg, k_tail, P.mo, P.mwo2, out);
}
```

```cpp
#include <cuda_runtime.h>
#include <cuda_bf16.h>
#include <cuda.h>
#include <stdint.h>

typedef __nv_bfloat16 bf16;

constexpr int SEQ = 2048, DM = 1024, HD = 4096, NSEG = 64;

__device__ __align__(1024) bf16 g_kv[(size_t)SEQ * 8192];
__device__ __align__(1024) bf16 g_kvm[(size_t)NSEG * 8 * 8192];
__device__ __align__(1024) bf16 g_o[(size_t)SEQ * HD];
constexpr int XPAIRS = 128 + NSEG * 4;
__device__ __align__(8192) uint2 g_x[XPAIRS * 1024];
__device__ uint32_t g_home[XPAIRS];
__device__ uint32_t g_side[256];
__device__ __align__(1024) uint32_t g_flag[256];

#define TL(kern, slot)

__device__ __forceinline__ uint32_t smem_u32(const void* p) { return (uint32_t)__cvta_generic_to_shared(p); }
__device__ __forceinline__ void mbar_init(uint32_t bar, uint32_t cnt) {
    asm volatile("mbarrier.init.shared::cta.b64 [%0], %1;" ::"r"(bar), "r"(cnt) : "memory");
}
__device__ __forceinline__ void mbar_expect_tx(uint32_t bar, uint32_t bytes) {
    asm volatile("mbarrier.arrive.expect_tx.shared::cta.b64 _, [%0], %1;" ::"r"(bar), "r"(bytes) : "memory");
}
__device__ __forceinline__ void mbar_arrive(uint32_t bar) {
    asm volatile("mbarrier.arrive.shared::cta.b64 _, [%0];" ::"r"(bar) : "memory");
}
__device__ __forceinline__ bool mbar_try(uint32_t bar, uint32_t parity) {
    uint32_t ok;
    asm volatile("{\n.reg .pred p;\nmbarrier.try_wait.parity.shared::cta.b64 p, [%1], %2;\nselp.u32 %0, 1, 0, p;\n}"
                 : "=r"(ok) : "r"(bar), "r"(parity) : "memory");
    return ok;
}
constexpr int SPIN_LIMIT = 1 << 20;
__device__ __forceinline__ void mbar_wait(uint32_t bar, uint32_t parity) {
    int n = 0;
    while (!mbar_try(bar, parity)) { if (++n > SPIN_LIMIT) __trap(); }
}
__device__ __forceinline__ void mbar_wait_u(uint32_t bar, uint32_t parity) {
    asm volatile("{\n.reg .pred p;\n.reg .u32 n;\n"
                 "mbarrier.try_wait.parity.shared::cta.b64 p, [%0], %1;\n@p bra.uni DONE;\nmov.u32 n, 0;\n"
                 "AGAIN:\nmbarrier.try_wait.parity.shared::cta.b64 p, [%0], %1;\n@p bra.uni DONE;\n"
                 "add.u32 n, n, 1;\nsetp.lt.u32 p, n, 0x100000;\n@p bra.uni AGAIN;\ntrap;\nDONE:\n}"
                 ::"r"(bar), "r"(parity) : "memory");
}
__device__ __forceinline__ void tma2d(uint32_t dst, const CUtensorMap* m, int c0, int c1, uint32_t bar) {
    asm volatile("cp.async.bulk.tensor.2d.shared::cluster.global.mbarrier::complete_tx::bytes [%0], [%1, {%3, %4}], [%2];"
                 ::"r"(dst), "l"(m), "r"(bar), "r"(c0), "r"(c1) : "memory");
}
__device__ __forceinline__ void tma3d(uint32_t dst, const CUtensorMap* m, int c0, int c1, int c2, uint32_t bar) {
    asm volatile("cp.async.bulk.tensor.3d.shared::cluster.global.mbarrier::complete_tx::bytes [%0], [%1, {%3, %4, %5}], [%2];"
                 ::"r"(dst), "l"(m), "r"(bar), "r"(c0), "r"(c1), "r"(c2) : "memory");
}
__device__ __forceinline__ uint32_t pack2(float lo, float hi) {
    uint32_t r;
    asm("cvt.rn.bf16x2.f32 %0, %1, %2;" : "=r"(r) : "f"(hi), "f"(lo));
    return r;
}
__device__ __forceinline__ float bf_lo(uint32_t v) { return __uint_as_float(v << 16); }
__device__ __forceinline__ float bf_hi(uint32_t v) { return __uint_as_float(v & 0xffff0000u); }
__device__ __forceinline__ float bf_round(float x) { return bf_lo(pack2(x, 0.f)); }
__device__ __forceinline__ float ex2(float x) { float y; asm("ex2.approx.ftz.f32 %0, %1;" : "=f"(y) : "f"(x)); return y; }
__device__ __forceinline__ void mma16816(float (&c)[4], uint32_t a0, uint32_t a1, uint32_t a2, uint32_t a3, uint32_t b0, uint32_t b1) {
    asm volatile("mma.sync.aligned.m16n8k16.row.col.f32.bf16.bf16.f32 {%0,%1,%2,%3}, {%4,%5,%6,%7}, {%8,%9}, {%0,%1,%2,%3};"
                 : "+f"(c[0]), "+f"(c[1]), "+f"(c[2]), "+f"(c[3]) : "r"(a0), "r"(a1), "r"(a2), "r"(a3), "r"(b0), "r"(b1));
}
__device__ __forceinline__ void mma1688(float (&c)[4], uint32_t a0, uint32_t a1, uint32_t b0) {
    asm volatile("mma.sync.aligned.m16n8k8.row.col.f32.bf16.bf16.f32 {%0,%1,%2,%3}, {%4,%5}, {%6}, {%0,%1,%2,%3};"
                 : "+f"(c[0]), "+f"(c[1]), "+f"(c[2]), "+f"(c[3]) : "r"(a0), "r"(a1), "r"(b0));
}
__device__ __forceinline__ void ldsm4(uint32_t (&r)[4], uint32_t a) {
    asm volatile("ldmatrix.sync.aligned.m8n8.x4.shared.b16 {%0,%1,%2,%3}, [%4];"
                 : "=r"(r[0]), "=r"(r[1]), "=r"(r[2]), "=r"(r[3]) : "r"(a) : "memory");
}
__device__ __forceinline__ void ldsm4t(uint32_t (&r)[4], uint32_t a) {
    asm volatile("ldmatrix.sync.aligned.m8n8.x4.trans.shared.b16 {%0,%1,%2,%3}, [%4];"
                 : "=r"(r[0]), "=r"(r[1]), "=r"(r[2]), "=r"(r[3]) : "r"(a) : "memory");
}
__device__ __forceinline__ void ldsm2t(uint32_t& r0, uint32_t& r1, uint32_t a) {
    asm volatile("ldmatrix.sync.aligned.m8n8.x2.trans.shared.b16 {%0,%1}, [%2];" : "=r"(r0), "=r"(r1) : "r"(a) : "memory");
}
__device__ __forceinline__ void stsm4t(uint32_t a, uint32_t r0, uint32_t r1, uint32_t r2, uint32_t r3) {
    asm volatile("stmatrix.sync.aligned.m8n8.x4.trans.shared.b16 [%0], {%1,%2,%3,%4};"
                 ::"r"(a), "r"(r0), "r"(r1), "r"(r2), "r"(r3) : "memory");
}
__device__ __forceinline__ void lds128(uint32_t (&r)[4], uint32_t a) {
    asm volatile("ld.shared.v4.u32 {%0,%1,%2,%3}, [%4];" : "=r"(r[0]), "=r"(r[1]), "=r"(r[2]), "=r"(r[3]) : "r"(a) : "memory");
}
__device__ __forceinline__ float4 lds128f(uint32_t a) {
    float4 v;
    asm volatile("ld.shared.v4.f32 {%0,%1,%2,%3}, [%4];" : "=f"(v.x), "=f"(v.y), "=f"(v.z), "=f"(v.w) : "r"(a) : "memory");
    return v;
}
__device__ __forceinline__ float2 lds64f(uint32_t a) {
    float2 v;
    asm volatile("ld.shared.v2.f32 {%0,%1}, [%2];" : "=f"(v.x), "=f"(v.y) : "r"(a) : "memory");
    return v;
}
__device__ __forceinline__ uint32_t lds32(uint32_t a) {
    uint32_t v;
    asm volatile("ld.shared.u32 %0, [%1];" : "=r"(v) : "r"(a) : "memory");
    return v;
}
__device__ __forceinline__ void sts128(uint32_t a, uint32_t r0, uint32_t r1, uint32_t r2, uint32_t r3) {
    asm volatile("st.shared.v4.u32 [%0], {%1,%2,%3,%4};" ::"r"(a), "r"(r0), "r"(r1), "r"(r2), "r"(r3) : "memory");
}
__device__ __forceinline__ void sts128f(uint32_t a, float r0, float r1, float r2, float r3) {
    asm volatile("st.shared.v4.f32 [%0], {%1,%2,%3,%4};" ::"r"(a), "f"(r0), "f"(r1), "f"(r2), "f"(r3) : "memory");
}
__device__ __forceinline__ void sts64(uint32_t a, uint32_t r0, uint32_t r1) {
    asm volatile("st.shared.v2.u32 [%0], {%1,%2};" ::"r"(a), "r"(r0), "r"(r1) : "memory");
}
__device__ __forceinline__ void sts64f(uint32_t a, float r0, float r1) {
    asm volatile("st.shared.v2.f32 [%0], {%1,%2};" ::"r"(a), "f"(r0), "f"(r1) : "memory");
}
__device__ __forceinline__ void sts32f(uint32_t a, float r0) {
    asm volatile("st.shared.f32 [%0], %1;" ::"r"(a), "f"(r0) : "memory");
}
__device__ __forceinline__ uint2 ld_rlx64(const uint2* p) {
    uint2 v;
    asm volatile("{\n.reg .b64 t;\nld.relaxed.gpu.global.b64 t, [%2];\nmov.b64 {%0,%1}, t;\n}" : "=r"(v.x), "=r"(v.y) : "l"(p) : "memory");
    return v;
}
__device__ __forceinline__ void st_rlx64(uint2* p, uint32_t x, uint32_t y) {
    asm volatile("{\n.reg .b64 t;\nmov.b64 t, {%1,%2};\nst.relaxed.gpu.global.b64 [%0], t;\n}" ::"l"(p), "r"(x), "r"(y) : "memory");
}
__device__ __forceinline__ uint32_t ld_acq32(const uint32_t* p) {
    uint32_t v;
    asm volatile("ld.acquire.gpu.global.u32 %0, [%1];" : "=r"(v) : "l"(p) : "memory");
    return v;
}
__device__ __forceinline__ void wait_flag(const uint32_t* p, uint32_t need) {
    int n = 0;
    while (ld_acq32(p) < need) { __nanosleep(200); if (++n > SPIN_LIMIT) __trap(); }
}
__device__ __forceinline__ void bar_sync(int id, int n) { asm volatile("bar.sync %0, %1;" ::"r"(id), "r"(n) : "memory"); }
__device__ __forceinline__ void wg_fence() { asm volatile("wgmma.fence.sync.aligned;" ::: "memory"); }
__device__ __forceinline__ void wg_commit() { asm volatile("wgmma.commit_group.sync.aligned;" ::: "memory"); }
template <int N> __device__ __forceinline__ void wg_wait() { asm volatile("wgmma.wait_group.sync.aligned %0;" ::"n"(N) : "memory"); }
__device__ __forceinline__ uint64_t desc_sw128(uint32_t addr, uint32_t lbo, uint32_t sbo) {
    return (uint64_t)((addr & 0x3FFFF) >> 4) | ((uint64_t)(lbo >> 4) << 16) | ((uint64_t)(sbo >> 4) << 32) | (1ull << 62);
}
__device__ __forceinline__ void quad_transpose(uint32_t& r0, uint32_t& r1, uint32_t& r2, uint32_t& r3, int t) {
    const bool o = t & 1, h = t & 2;
    uint32_t s0 = __shfl_xor_sync(~0u, o ? r0 : r1, 1), s1 = __shfl_xor_sync(~0u, o ? r2 : r3, 1);
    uint32_t a0 = o ? s0 : r0, a1 = o ? r1 : s0, a2 = o ? s1 : r2, a3 = o ? r3 : s1;
    s0 = __shfl_xor_sync(~0u, h ? a0 : a2, 2); s1 = __shfl_xor_sync(~0u, h ? a1 : a3, 2);
    r0 = h ? s0 : a0; r1 = h ? s1 : a1; r2 = h ? a2 : s0; r3 = h ? a3 : s1;
}

__device__ __forceinline__ void wgmma_n256(float (&d)[128], uint64_t da, uint64_t db, int sd) {
    asm volatile("{\n.reg .pred p;\nsetp.ne.b32 p, %130, 0;\n"
        "wgmma.mma_async.sync.aligned.m64n256k16.f32.bf16.bf16 "
        "{%0,%1,%2,%3,%4,%5,%6,%7,%8,%9,%10,%11,%12,%13,%14,%15,"
        "%16,%17,%18,%19,%20,%21,%22,%23,%24,%25,%26,%27,%28,%29,%30,%31,"
        "%32,%33,%34,%35,%36,%37,%38,%39,%40,%41,%42,%43,%44,%45,%46,%47,"
        "%48,%49,%50,%51,%52,%53,%54,%55,%56,%57,%58,%59,%60,%61,%62,%63,"
        "%64,%65,%66,%67,%68,%69,%70,%71,%72,%73,%74,%75,%76,%77,%78,%79,"
        "%80,%81,%82,%83,%84,%85,%86,%87,%88,%89,%90,%91,%92,%93,%94,%95,"
        "%96,%97,%98,%99,%100,%101,%102,%103,%104,%105,%106,%107,%108,%109,%110,%111,"
        "%112,%113,%114,%115,%116,%117,%118,%119,%120,%121,%122,%123,%124,%125,%126,%127}, %128, %129, p, 1, 1, 0, 1;\n}\n"
        : "+f"(d[0]), "+f"(d[1]), "+f"(d[2]), "+f"(d[3]), "+f"(d[4]), "+f"(d[5]), "+f"(d[6]), "+f"(d[7]),
          "+f"(d[8]), "+f"(d[9]), "+f"(d[10]), "+f"(d[11]), "+f"(d[12]), "+f"(d[13]), "+f"(d[14]), "+f"(d[15]),
          "+f"(d[16]), "+f"(d[17]), "+f"(d[18]), "+f"(d[19]), "+f"(d[20]), "+f"(d[21]), "+f"(d[22]), "+f"(d[23]),
          "+f"(d[24]), "+f"(d[25]), "+f"(d[26]), "+f"(d[27]), "+f"(d[28]), "+f"(d[29]), "+f"(d[30]), "+f"(d[31]),
          "+f"(d[32]), "+f"(d[33]), "+f"(d[34]), "+f"(d[35]), "+f"(d[36]), "+f"(d[37]), "+f"(d[38]), "+f"(d[39]),
          "+f"(d[40]), "+f"(d[41]), "+f"(d[42]), "+f"(d[43]), "+f"(d[44]), "+f"(d[45]), "+f"(d[46]), "+f"(d[47]),
          "+f"(d[48]), "+f"(d[49]), "+f"(d[50]), "+f"(d[51]), "+f"(d[52]), "+f"(d[53]), "+f"(d[54]), "+f"(d[55]),
          "+f"(d[56]), "+f"(d[57]), "+f"(d[58]), "+f"(d[59]), "+f"(d[60]), "+f"(d[61]), "+f"(d[62]), "+f"(d[63]),
          "+f"(d[64]), "+f"(d[65]), "+f"(d[66]), "+f"(d[67]), "+f"(d[68]), "+f"(d[69]), "+f"(d[70]), "+f"(d[71]),
          "+f"(d[72]), "+f"(d[73]), "+f"(d[74]), "+f"(d[75]), "+f"(d[76]), "+f"(d[77]), "+f"(d[78]), "+f"(d[79]),
          "+f"(d[80]), "+f"(d[81]), "+f"(d[82]), "+f"(d[83]), "+f"(d[84]), "+f"(d[85]), "+f"(d[86]), "+f"(d[87]),
          "+f"(d[88]), "+f"(d[89]), "+f"(d[90]), "+f"(d[91]), "+f"(d[92]), "+f"(d[93]), "+f"(d[94]), "+f"(d[95]),
          "+f"(d[96]), "+f"(d[97]), "+f"(d[98]), "+f"(d[99]), "+f"(d[100]), "+f"(d[101]), "+f"(d[102]), "+f"(d[103]),
          "+f"(d[104]), "+f"(d[105]), "+f"(d[106]), "+f"(d[107]), "+f"(d[108]), "+f"(d[109]), "+f"(d[110]), "+f"(d[111]),
          "+f"(d[112]), "+f"(d[113]), "+f"(d[114]), "+f"(d[115]), "+f"(d[116]), "+f"(d[117]), "+f"(d[118]), "+f"(d[119]),
          "+f"(d[120]), "+f"(d[121]), "+f"(d[122]), "+f"(d[123]), "+f"(d[124]), "+f"(d[125]), "+f"(d[126]), "+f"(d[127])
        : "l"(da), "l"(db), "r"(sd));
}

__device__ __forceinline__ void wgmma_n128(float (&d)[64], uint64_t da, uint64_t db, int sd) {
    asm volatile("{\n.reg .pred p;\nsetp.ne.b32 p, %66, 0;\n"
        "wgmma.mma_async.sync.aligned.m64n128k16.f32.bf16.bf16 "
        "{%0,%1,%2,%3,%4,%5,%6,%7,%8,%9,%10,%11,%12,%13,%14,%15,"
        "%16,%17,%18,%19,%20,%21,%22,%23,%24,%25,%26,%27,%28,%29,%30,%31,"
        "%32,%33,%34,%35,%36,%37,%38,%39,%40,%41,%42,%43,%44,%45,%46,%47,"
        "%48,%49,%50,%51,%52,%53,%54,%55,%56,%57,%58,%59,%60,%61,%62,%63}, %64, %65, p, 1, 1, 0, 1;\n}\n"
        : "+f"(d[0]), "+f"(d[1]), "+f"(d[2]), "+f"(d[3]), "+f"(d[4]), "+f"(d[5]), "+f"(d[6]), "+f"(d[7]),
          "+f"(d[8]), "+f"(d[9]), "+f"(d[10]), "+f"(d[11]), "+f"(d[12]), "+f"(d[13]), "+f"(d[14]), "+f"(d[15]),
          "+f"(d[16]), "+f"(d[17]), "+f"(d[18]), "+f"(d[19]), "+f"(d[20]), "+f"(d[21]), "+f"(d[22]), "+f"(d[23]),
          "+f"(d[24]), "+f"(d[25]), "+f"(d[26]), "+f"(d[27]), "+f"(d[28]), "+f"(d[29]), "+f"(d[30]), "+f"(d[31]),
          "+f"(d[32]), "+f"(d[33]), "+f"(d[34]), "+f"(d[35]), "+f"(d[36]), "+f"(d[37]), "+f"(d[38]), "+f"(d[39]),
          "+f"(d[40]), "+f"(d[41]), "+f"(d[42]), "+f"(d[43]), "+f"(d[44]), "+f"(d[45]), "+f"(d[46]), "+f"(d[47]),
          "+f"(d[48]), "+f"(d[49]), "+f"(d[50]), "+f"(d[51]), "+f"(d[52]), "+f"(d[53]), "+f"(d[54]), "+f"(d[55]),
          "+f"(d[56]), "+f"(d[57]), "+f"(d[58]), "+f"(d[59]), "+f"(d[60]), "+f"(d[61]), "+f"(d[62]), "+f"(d[63])
        : "l"(da), "l"(db), "r"(sd));
}

__device__ __forceinline__ void wgmma_n64(float (&d)[32], uint64_t da, uint64_t db, int sd) {
    asm volatile("{\n.reg .pred p;\nsetp.ne.b32 p, %34, 0;\n"
        "wgmma.mma_async.sync.aligned.m64n64k16.f32.bf16.bf16 "
        "{%0,%1,%2,%3,%4,%5,%6,%7,%8,%9,%10,%11,%12,%13,%14,%15,"
        "%16,%17,%18,%19,%20,%21,%22,%23,%24,%25,%26,%27,%28,%29,%30,%31}, %32, %33, p, 1, 1, 0, 1;\n}\n"
        : "+f"(d[0]), "+f"(d[1]), "+f"(d[2]), "+f"(d[3]), "+f"(d[4]), "+f"(d[5]), "+f"(d[6]), "+f"(d[7]),
          "+f"(d[8]), "+f"(d[9]), "+f"(d[10]), "+f"(d[11]), "+f"(d[12]), "+f"(d[13]), "+f"(d[14]), "+f"(d[15]),
          "+f"(d[16]), "+f"(d[17]), "+f"(d[18]), "+f"(d[19]), "+f"(d[20]), "+f"(d[21]), "+f"(d[22]), "+f"(d[23]),
          "+f"(d[24]), "+f"(d[25]), "+f"(d[26]), "+f"(d[27]), "+f"(d[28]), "+f"(d[29]), "+f"(d[30]), "+f"(d[31])
        : "l"(da), "l"(db), "r"(sd));
}

constexpr int STAGE_BYTES = 49152, NSTAGE = 4;
constexpr int GEMM_SMEM = NSTAGE * STAGE_BYTES + 128;

struct GemmSmem { uint32_t st, full, empty; };
__device__ __forceinline__ GemmSmem gemm_setup(uint8_t* raw, int releases) {
    GemmSmem g;
    g.st = smem_u32(raw);
    if (g.st & 1023) __trap();
    g.full = g.st + NSTAGE * STAGE_BYTES; g.empty = g.full + 64;
    if (threadIdx.x == 0) {
        for (int s = 0; s < NSTAGE; s++) { mbar_init(g.full + 8 * s, 1); mbar_init(g.empty + 8 * s, releases); }
        asm volatile("fence.mbarrier_init.release.cluster;" ::: "memory");
        asm volatile("fence.proxy.async.shared::cta;" ::: "memory");
    }
    __syncthreads();
    return g;
}
__device__ __forceinline__ void mbar_arrive_one(uint32_t bar, uint32_t who) {
    asm volatile("{\n.reg .pred p;\nsetp.eq.u32 p, %1, 0;\n@p mbarrier.arrive.shared::cta.b64 _, [%0];\n}" ::"r"(bar), "r"(who) : "memory");
}
template <int BM, int BN, int KPS, typename ACC>
__device__ __forceinline__ void gemm_stage(ACC& acc, uint32_t stage, int wg, bool first) {
    const uint64_t da = desc_sw128(stage + wg * 8192, 16, 1024);
    const uint64_t db = desc_sw128(stage + KPS * BM * 128, 8192, 1024);
    wg_fence();
#pragma unroll
    for (int k = 0; k < 4 * KPS; k++) {
        const uint64_t a = da + (k >> 2) * (BM * 8) + (k & 3) * 2, b = db + k * 128;
        if constexpr (BN == 256) wgmma_n256(acc, a, b, first && k == 0 ? 0 : 1);
        else if constexpr (BN == 128) wgmma_n128(acc, a, b, first && k == 0 ? 0 : 1);
        else wgmma_n64(acc, a, b, first && k == 0 ? 0 : 1);
    }
    wg_commit();
}

__device__ __forceinline__ void kv_store_unit(const uint32_t (&pk)[64], int u, bf16* dst, int t) {
    const int G = (u >> 2) * 2 + (u & 1), hh = (u >> 1) & 1;
    uint32_t r0 = pk[(4 * G + 0) * 2 + hh], r1 = pk[(4 * G + 1) * 2 + hh], r2 = pk[(4 * G + 2) * 2 + hh], r3 = pk[(4 * G + 3) * 2 + hh];
    quad_transpose(r0, r1, r2, r3, t);
#define KVST ".cs"
    asm volatile("st.global" KVST ".v4.u32 [%0], {%1,%2,%3,%4};" ::"l"(dst + (size_t)hh * 8 * 8192 + G * 32), "r"(r0), "r"(r1), "r"(r2), "r"(r3) : "memory");
}

#define TLK(slot)
__device__ __forceinline__ uint32_t near_page(int pair, int line) {
    uint32_t best[2] = {~0u, ~0u};
#pragma unroll 1
    for (int i = 0; i < 16; i++) {
        uint32_t t0, t1, v;
        asm volatile("mov.u32 %0, %%clock;" : "=r"(t0)::"memory");
        asm volatile("atom.relaxed.gpu.global.or.b32 %0, [%1], -1;" : "=r"(v) : "l"(g_x + pair * 1024 + (i & 1) * 512 + line * 16) : "memory");
        asm volatile("{\n.reg .pred p;\nsetp.ne.u32 p, %1, 0x12345;\nmov.u32 %0, -1;\n@p mov.u32 %0, %%clock;\n}" : "=r"(t1) : "r"(v) : "memory");
        if (i & 1) best[1] = min(best[1], t1 - t0); else best[0] = min(best[0], t1 - t0);
    }
    return best[1] < best[0];
}
__device__ __forceinline__ void map_pages(int c) {
    uint32_t smid;
    asm("mov.u32 %0, %%smid;" : "=r"(smid));
    const uint32_t side = near_page(0, c & 31);
    g_side[smid & 255] = side;
    for (int p = c; p < XPAIRS; p += 132) g_home[p] = near_page(p, 0) ^ side;
}

__global__ void __launch_bounds__(384, 1)
k_kv(const __grid_constant__ CUtensorMap mx, const __grid_constant__ CUtensorMap mwk, const __grid_constant__ CUtensorMap mwv,
     const bf16* __restrict__ Wq, const bf16* __restrict__ Wk, const bf16* __restrict__ Wo, int c0) {
    extern __shared__ __align__(1024) uint8_t smem_gemm[];
    const int c = c0 + blockIdx.x;
    if (c == 128) {
        if (threadIdx.x < 256) g_flag[threadIdx.x] = 0;
        __threadfence();
        __syncthreads();
    }
    asm volatile("griddepcontrol.launch_dependents;");
    if (threadIdx.x == 0) TLK(0);
    if (c >= 128) {
        const int i0 = (c - 128) * 384 + threadIdx.x;
        const uint4 ones = make_uint4(~0u, ~0u, ~0u, ~0u);
        if (threadIdx.x == 32) map_pages(c);
        for (int i = i0; i < XPAIRS * 512; i += 4 * 384) reinterpret_cast<uint4*>(g_x)[i] = ones;
        if (threadIdx.x == 0) TLK(1);
        asm volatile("griddepcontrol.wait;" ::: "memory");
        return;
    }
    GemmSmem g = gemm_setup(smem_gemm, 2);
#define MW 4
    const int m0 = (c % MW) * 128, nb0 = c / MW;
    auto tile_m = [](int tile) { return (tile % (16 / MW)) * MW * 128; };
    auto tile_n = [](int tile) { return (tile / (16 / MW)) * (128 / MW); };
    const int wg = __shfl_sync(~0u, threadIdx.x >> 7, 0);
    if (wg == 0) {
        asm volatile("setmaxnreg.dec.sync.aligned.u32 40;");
        if (threadIdx.x == 0) {
            for (int it = 0; it < 64; it++) {
                const int s = it & 3, tile = it >> 4, kb = it & 15;
                mbar_wait(g.empty + 8 * s, ((it >> 2) & 1) ^ 1);
                mbar_expect_tx(g.full + 8 * s, STAGE_BYTES);
                const int nb = nb0 + tile_n(tile);
                tma2d(g.st + s * STAGE_BYTES, &mx, kb * 64, m0 + tile_m(tile), g.full + 8 * s);
                tma3d(g.st + s * STAGE_BYTES + 16384, nb < 16 ? &mwk : &mwv, 0, kb * 64, (nb & 15) * 4, g.full + 8 * s);
#define PF0 32
#define PFN 32
#define PFB 4096
                const int pi = it - PF0;
                if (pi >= 0 && pi < PFN) {
                    const uint32_t o = (pi * 128 + c) * PFB;
                    const char* p = (const char*)(o < (8 << 20) ? Wo : o < (16 << 20) ? Wq : Wk) + (o & ((8 << 20) - 1));
                    asm volatile("cp.async.bulk.prefetch.L2.global [%0], %1;" ::"l"(p), "n"(PFB) : "memory");
                }
            }
        } else if (threadIdx.x == 32) map_pages(c);
    } else {
        asm volatile("setmaxnreg.inc.sync.aligned.u32 232;");
        const int cw = wg - 1, lane = threadIdx.x & 31, t = lane & 3;
        const int row = m0 + cw * 64 + ((threadIdx.x >> 5) & 3) * 16 + (lane >> 2);
        bf16* dst = g_kv + (size_t)row * 8192 + nb0 * 256 + t * 8;
        float acc[128];
        uint32_t pk[64];
#pragma unroll 1
        for (int tile = 0; tile < 4; tile++) {
#pragma unroll
            for (int kb = 0; kb < 16; kb++) {
                mbar_wait_u(g.full + 8 * (kb & 3), (kb >> 2) & 1);
                gemm_stage<128, 256, 1>(acc, g.st + (kb & 3) * STAGE_BYTES, cw, kb == 0);
                if (tile > 0) kv_store_unit(pk, kb, dst + (size_t)tile_m(tile - 1) * 8192 + tile_n(tile - 1) * 256, t);
                if (kb > 0) {
                    wg_wait<1>();
                    mbar_arrive_one(g.empty + 8 * ((kb - 1) & 3), threadIdx.x & 127);
                }
            }
            wg_wait<0>();
            mbar_arrive_one(g.empty + 8 * 3, threadIdx.x & 127);
#pragma unroll
            for (int i = 0; i < 64; i++) pk[i] = pack2(acc[2 * i], acc[2 * i + 1]);
        }
        if (threadIdx.x == 128) TLK(2);
#pragma unroll
        for (int u = 0; u < 16; u++) kv_store_unit(pk, u, dst + (size_t)tile_m(3) * 8192 + tile_n(3) * 256, t);
        if (threadIdx.x == 128) TLK(1);
        asm volatile("griddepcontrol.wait;" ::: "memory");
    }
}

constexpr int NS1 = 31;
#define RB1 4
#define PFC 4
constexpr int C_W1 = 0;
constexpr int C_W2 = C_W1 + 8 * NS1 * 512;
constexpr int C_KV = C_W2 + 14 * 8 * 512;
constexpr int C_RED = C_KV + 16384;
constexpr int C_QKV = C_RED + 64 * 272;
constexpr int C_SC = C_RED;
constexpr int C_OB = C_SC + 2 * 8 * 52 * 4;
constexpr int C_BAR = C_QKV + 3 * 8 * 272;
__host__ __device__ constexpr int smem_idx(int ks, int j) {
    return ks == 0 ? j : ks < 3 ? (j < 4 ? 4 + 4 * ks + j : -1) : (j < 3 ? 7 + 3 * ks + j : -1);
}
constexpr int CHAIN_SMEM = C_BAR + 64;
#define TS(i)

#define DLY3 8
#define DLY1 2
#define DLY0 2
#define DLY1A 10
#define DLY0A DLY0
#define DLYW 3
template <int N> __device__ __forceinline__ uint32_t delayed(uint32_t x, int lane) {
#pragma unroll
    for (int i = 0; i < N; i++) asm volatile("shfl.sync.idx.b32 %0, %0, %1, 31, -1;" : "+r"(x) : "r"(lane) : "memory");
    return x;
}
__device__ __forceinline__ void lds128v(uint32_t (&r)[4], uint32_t a) {
    asm volatile("ld.volatile.shared.v4.u32 {%0,%1,%2,%3}, [%4];" : "=r"(r[0]), "=r"(r[1]), "=r"(r[2]), "=r"(r[3]) : "r"(a) : "memory");
}
__device__ __forceinline__ uint2 lds64(uint32_t a) {
    uint2 v;
    asm volatile("ld.shared.v2.u32 {%0,%1}, [%2];" : "=r"(v.x), "=r"(v.y) : "r"(a) : "memory");
    return v;
}
#define LDQ ".L1::no_allocate"
__device__ __forceinline__ uint4 ldw128(const void* p) {
    uint4 v;
    asm volatile("ld.global.nc" LDQ ".v4.u32 {%0,%1,%2,%3}, [%4];" : "=r"(v.x), "=r"(v.y), "=r"(v.z), "=r"(v.w) : "l"(p));
    return v;
}
#define P8_LD(i) "ld.relaxed.gpu.global.b64 d" #i ", [src + " #i " * 256];\n"
#define P8_X(i) "mov.b64 {x" #i ", y" #i "}, d" #i ";\n"
#define P8_HEAD(SRC) "{\n.reg .pred p, q;\n.reg .b64 src, d<8>;\n.reg .b32 n, x<8>, y<8>, m0, m1;\nmov.b64 src, " SRC ";\n"         \
                P8_LD(0) P8_LD(1) P8_LD(2) P8_LD(3) P8_LD(4) P8_LD(5) P8_LD(6) P8_LD(7) "mov.u32 n, 0;\nCHECK:\n" \
                P8_X(0) P8_X(1) P8_X(2) P8_X(3) P8_X(4) P8_X(5) P8_X(6) P8_X(7)
#define P8_VOTE "vote.sync.all.pred p, p, -1;\n@p bra.uni DONE;\n"
#define P8_TAIL "add.u32 n, n, 1;\nsetp.lt.u32 p, n, 0x100000;\n@p bra.uni CHECK;\ntrap;\nDONE:\n"
__device__ __forceinline__ void poll_state(uint2 (&v)[8], const void* src) {
#define P8_RS(i) "setp.eq.u32 q, x" #i ", 0xffffffff;\n@q " P8_LD(i)
#define P8_O(i) "mov.b64 %" #i ", d" #i ";\n"
    uint64_t d[8];
    asm volatile(P8_HEAD("%8") "max.u32 m0, x0, x1;\nmax.u32 m0, m0, x2;\nmax.u32 m1, x3, x4;\nmax.u32 m1, m1, x5;\nmax.u32 m0, m0, x6;\n"
                 "max.u32 m0, m0, x7;\nmax.u32 m0, m0, m1;\nsetp.ne.u32 p, m0, 0xffffffff;\n" P8_VOTE
                 P8_RS(0) P8_RS(1) P8_RS(2) P8_RS(3) P8_RS(4) P8_RS(5) P8_RS(6) P8_RS(7) P8_TAIL
                 P8_O(0) P8_O(1) P8_O(2) P8_O(3) P8_O(4) P8_O(5) P8_O(6) P8_O(7) "}"
                 : "=l"(d[0]), "=l"(d[1]), "=l"(d[2]), "=l"(d[3]), "=l"(d[4]), "=l"(d[5]), "=l"(d[6]), "=l"(d[7]) : "l"(src) : "memory");
#pragma unroll
    for (int i = 0; i < 8; i++) { v[i].x = (uint32_t)d[i]; v[i].y = (uint32_t)(d[i] >> 32); }
}
__device__ __forceinline__ uint64_t poll_sum(const void* src, uint32_t tag, uint32_t sel) {
#define P8_RT(i) "lop3.b32 m0, x" #i ", %2, 1, 0x28;\nsetp.ne.u32 q, m0, 0;\n@q " P8_LD(i)
#define P8_MMA(c, i, z) "mma.sync.aligned.m16n8k8.row.col.f32.bf16.bf16.f32 {" #c "0," #c "1," #c "2," #c "3}, {x" #i ", y" #i "}, {%3}, {" #z "0," #z "1," #z "2," #z "3};\n"
    uint64_t r;
    asm volatile(P8_HEAD("%1") "{\n.reg .f32 a<4>, b<4>, z<4>;\nmov.f32 z0, 0f00000000;\nmov.f32 z1, z0;\nmov.f32 z2, z0;\nmov.f32 z3, z0;\n"
                 P8_MMA(a, 0, z) P8_MMA(b, 1, z) P8_MMA(a, 2, a) P8_MMA(b, 3, b) P8_MMA(a, 4, a) P8_MMA(b, 5, b) P8_MMA(a, 6, a) P8_MMA(b, 7, b)
                 "add.f32 a0, a0, b0;\nadd.f32 a1, a1, b1;\nadd.f32 a2, a2, b2;\nadd.f32 a3, a3, b3;\n"
                 "cvt.rn.bf16x2.f32 m0, a1, a0;\ncvt.rn.bf16x2.f32 m1, a3, a2;\nmov.b64 %0, {m0, m1};\n}\n"
                 "lop3.b32 m0, x0, x1, %2, 0x7e;\nlop3.b32 m1, x2, x3, %2, 0x7e;\nlop3.b32 m0, m0, x4, %2, 0xf6;\n"
                 "lop3.b32 m1, m1, x5, %2, 0xf6;\nlop3.b32 m0, m0, x6, %2, 0xf6;\nlop3.b32 m1, m1, x7, %2, 0xf6;\n"
                 "lop3.b32 m0, m0, m1, 1, 0xa8;\nsetp.eq.u32 p, m0, 0;\n" P8_VOTE
                 P8_RT(0) P8_RT(1) P8_RT(2) P8_RT(3) P8_RT(4) P8_RT(5) P8_RT(6) P8_RT(7) P8_TAIL "}"
                 : "=&l"(r) : "l"(src), "r"(tag), "r"(sel) : "memory");
    return r;
}
__device__ __forceinline__ void sum8(float (&c)[4], const uint2 (&v)[8], uint32_t idn) {
    float d[4] = {0.f, 0.f, 0.f, 0.f};
    c[0] = c[1] = c[2] = c[3] = 0.f;
    mma16816(c, v[0].x, v[0].y, v[1].x, v[1].y, idn, idn);
    mma16816(d, v[2].x, v[2].y, v[3].x, v[3].y, idn, idn);
    mma16816(c, v[4].x, v[4].y, v[5].x, v[5].y, idn, idn);
    mma16816(d, v[6].x, v[6].y, v[7].x, v[7].y, idn, idn);
    c[0] += d[0]; c[1] += d[1]; c[2] += d[2]; c[3] += d[3];
}

#define CLS 6
__global__ void __cluster_dims__(CLS, 1, 1) __launch_bounds__(256, 1)
k_chain(const bf16* __restrict__ mem0, const bf16* __restrict__ Wq, const bf16* __restrict__ Wk, const bf16* __restrict__ Wv,
        const bf16* __restrict__ Wo, const __grid_constant__ CUtensorMap mkv) {
    extern __shared__ __align__(1024) uint8_t smem_chain[];
    const uint32_t sb = smem_u32(smem_chain);
    if (sb & 1023) __trap();
    const int w = __shfl_sync(~0u, threadIdx.x >> 5, 0), lane = __shfl_sync(~0u, threadIdx.x & 31, threadIdx.x & 31);
    const int tid = w * 32 + lane, g = lane >> 2, t = lane & 3;
    auto pin = [&](uint32_t x) { return delayed<1>(x, lane); };
    const int h = blockIdx.x / 3, r = blockIdx.x - 3 * h;
    const uint32_t bar_x = sb + C_BAR, bar_kv = sb + C_BAR + 8, bar_go = sb + C_BAR + 16, bar_w = sb + C_BAR + 24;
    asm volatile("griddepcontrol.launch_dependents;");
    const int tbase = r == 0 ? 0 : 1 + 21 * r, ntile = r == 0 ? 22 : 21;
    uint32_t side;
    if (tid == 0) {
        mbar_init(bar_x, 8); mbar_init(bar_kv, 1); mbar_init(bar_go, 1); mbar_init(bar_w, 1);
        asm volatile("fence.mbarrier_init.release.cluster;" ::: "memory");
        asm volatile("fence.proxy.async.shared::cta;" ::: "memory");
        mbar_expect_tx(bar_w, 128 * 32 * ntile);
    }
    __syncthreads();
    asm volatile("barrier.cluster.arrive.relaxed.aligned;" ::: "memory");
    if (tid < 128)
        asm volatile("cp.async.bulk.shared::cluster.global.mbarrier::complete_tx::bytes [%0], [%1], %2, [%3];"
                     ::"r"(sb + C_W1 + tid * 720), "l"(Wo + (size_t)(h * 128 + tid) * DM + tbase * 16), "r"(32 * ntile), "r"(bar_w) : "memory");
    const int tile0 = tbase + 7 - w;
    const bool three = w >= (r == 0 ? 2 : 3);
    const uint32_t wa = pin(sb + tid * 16);
#define W1A(i) (wa + C_W1 + (i) * 4096)
#define W2A(x) (wa + C_W2 + ((x) < 8 ? (x) * 4096 : 32768 - 1024 + ((x) - 8) * 3072))
    uint32_t wo0[8][4], wr[64][4];
    {
        const bf16* W = (r == 0 ? Wq : r == 1 ? Wk : Wv) + (size_t)(128 * w + (lane >> 4)) * HD + h * 128 + 8 * (lane & 15);
        uint4 raw[8][8];
        auto fetch = [&](int ks) {
#pragma unroll
            for (int i = 0; i < 8; i++) raw[ks][i] = ldw128(W + (size_t)(16 * ks + 2 * i) * HD);
        };
        fetch(0); fetch(1); fetch(2); fetch(3);
    asm("mov.u32 %0, %%smid;" : "=r"(side));
    side = ld_acq32(g_side + (side & 255)) & 1;
    if (tid == 0 && r > 0) asm volatile("st.relaxed.gpu.global.u32 [%0], %1;" ::"l"(g_flag + 128 + 2 * h + r - 1), "r"(2 | side) : "memory");
        if (tid == 0) TL(5, 0);
        mbar_wait_u(bar_w, 0);
        if (tid == 0) TL(5, 1);
        const uint32_t p = sb + C_W1 + ((lane & 7) + (lane >> 4) * 8) * 720 + (7 - w) * 32 + ((lane >> 3) & 1) * 16;
#pragma unroll
        for (int ks = 0; ks < 8; ks++) {
            uint32_t a[4];
            ldsm4t(wo0[ks], p + ks * 16 * 720);
            ldsm4t(a, p + ks * 16 * 720 + 256);
            sts128(W2A(ks), a[0], a[1], a[2], a[3]);
            if (three) { ldsm4t(a, p + ks * 16 * 720 + 512); sts128(W2A(8 + ks), a[0], a[1], a[2], a[3]); }
        }
        __syncthreads();
        if (tid == 0) TL(5, 2);
        const uint32_t stg = sb + C_KV + w * 4096;
        const uint32_t rd = stg + ((lane & 7) + 8 * (lane >> 4)) * 256 + ((((lane >> 3) & 1) ^ (lane & 7)) << 4);
#pragma unroll
        for (int ks = 0; ks < 8; ks++) {
#pragma unroll
            for (int i = 0; i < 8; i++)
                sts128(stg + (2 * i + (lane >> 4)) * 256 + (((lane & 15) ^ (((2 * i) & 6) | (lane >> 4))) << 4),
                       raw[ks][i].x, raw[ks][i].y, raw[ks][i].z, raw[ks][i].w);
            if (ks < 2) fetch(ks + 4);
            if (ks == 3 || ks == 5) fetch(ks / 2 + 5);
            __syncwarp();
#pragma unroll
            for (int j = 0; j < 8; j++) {
                if (smem_idx(ks, j) >= 0) {
                    uint32_t a[4];
                    ldsm4t(a, rd ^ (j << 5));
                    sts128(W1A(smem_idx(ks, j)), a[0], a[1], a[2], a[3]);
                } else ldsm4t(wr[8 * ks + j], rd ^ (j << 5));
            }
            __syncwarp();
        }
    }
    if (tid == 0) TL(5, 3);
    asm volatile("griddepcontrol.wait;\nfence.proxy.async.shared::cta;" ::: "memory");
    __syncthreads();
    if (tid == 0) {
        mbar_expect_tx(bar_kv, 16384);
        tma3d(sb + C_KV, &mkv, 0, 0, 2 * h, bar_kv);
        tma3d(sb + C_KV + 8192, &mkv, 0, 0, 64 + 2 * h, bar_kv);
    }
    asm volatile("barrier.cluster.wait.aligned;" ::: "memory");

    auto publish_kvm = [&](int s) {
        uint32_t v[4];
        lds128(v, sb + C_QKV + (8 + (tid >> 4)) * 272 + (tid & 15) * 16);
        asm volatile("st.global.v4.u32 [%0], {%1,%2,%3,%4};"
                     ::"l"(g_kvm + (size_t)(s * 8 + ((tid >> 4) & 7)) * 8192 + (tid >> 7) * HD + h * 128 + (tid & 15) * 8),
                       "r"(v[0]), "r"(v[1]), "r"(v[2]), "r"(v[3]) : "memory");
        if (h == 0 && w == 6) asm volatile("st.relaxed.gpu.global.u32 [%0], %1;" ::"l"(g_flag + 98), "r"(s + 1) : "memory");
        if ((s & 3) == 3) {
            __syncthreads();
            if (w == 7) asm volatile("{\n.reg .pred p;\nsetp.eq.u32 p, %2, 0;\nfence.acq_rel.gpu;\n@p st.relaxed.gpu.global.u32 [%0], %1;\n}"
                                     ::"l"(g_flag + h), "r"(s + 1), "r"(lane) : "memory");
        }
    };
    const float sl2e = 0.08838834764831845f * 1.4426950408889634f;
    const uint32_t idn = pin(g == 2 * t ? 0x00003f80u : g == 2 * t + 1 ? 0x3f800000u : 0u);
    const uint32_t lm = pin(sb + (lane & 7) * 272 + (lane >> 3) * 16);
    const uint32_t sa = pin(sb + C_SC + (w & 1) * (8 * 52 * 4) + (2 * t * 52 + (w < 4 ? 32 : (w & 2) * 8) + g) * 4);
    const uint32_t sr = pin(sb + C_SC + (g * 52 + 8 * t) * 4), sr2 = pin(sb + C_SC + (g * 52 + 32 + 2 * t) * 4);
    uint32_t kva;
    {
        const int pos = (w & 2) * 8 + (lane & 15), row = (pos & 24) + ((pos + (pos >> 2 & 6)) & 7);
        const int key = 4 * (lane & 6) + (((lane & 7) + 2 * (lane >> 4)) & 7);
        kva = pin(w >= 4 ? sb + C_KV + (w & 1) * 4096 + row * 128 + (((lane >> 4) ^ (row & 7)) << 4)
                         : sb + C_KV + 8192 + (w >> 1) * 4096 + key * 128 + ((((w & 1) * 4 + ((lane >> 3) & 1)) ^ (key & 7)) << 4));
    }
    uint32_t buf0[8][4], ring[RB1][4];
    auto stage_w1 = [&]() {
#pragma unroll
        for (int i = 0; i < 8; i++) lds128v(buf0[i], W1A(i));
#pragma unroll
        for (int i = 0; i < RB1; i++) lds128v(ring[i], W1A(8 + i));
    };
    stage_w1();
    uint32_t psel, msel0, msel1;
    {
        const int j = r > 0 ? 2 * h + r - 1 : 0, tl = min(tile0 + 8 * (lane >> 1), 63);
        uint32_t b;
        asm volatile("{\n.reg .pred p;\n.reg .u32 n;\nmov.u32 n, 0;\nAGAIN:\nld.relaxed.gpu.global.u32 %0, [%1];\nsetp.ne.u32 p, %0, 0;\n"
                     "vote.sync.all.pred p, p, -1;\n@p bra.uni DONE;\nadd.u32 n, n, 1;\nsetp.lt.u32 p, n, 0x100000;\n@p bra.uni AGAIN;\ntrap;\nDONE:\n}"
                     : "=&r"(b) : "l"(g_flag + 128 + tl) : "memory");
        psel = __ballot_sync(~0u, (g_home[lane == 6 ? j * 2 + ((w >> 1) & 1) : tl * 2 + (lane & 1)] ^ (lane == 6 ? side : b)) & 1);
        msel0 = __ballot_sync(~0u, (g_home[128 + lane * 4 + (w >> 1)] ^ side) & 1);
        msel1 = __ballot_sync(~0u, (g_home[256 + lane * 4 + (w >> 1)] ^ side) & 1);
        if (r > 0) {
            if (w < 4) asm volatile("prefetch.global.L2 [%0];" ::"l"(g_x + (128 + (1 + (w >> 1)) * 4 + (j >> 4)) * 1024 + (w & 1) * 512 + (j & 15) * 32 + lane) : "memory");
            if (w < 4) asm volatile("prefetch.global.L2 [%0];" ::"l"(g_x + j * 2048 + tid * 16) : "memory");
        }
    }
    uint2 bm[8];
#pragma unroll
    for (int ks = 0; ks < 8; ks++) {
        const uint32_t* p = (const uint32_t*)(mem0 + g * DM + (8 * w + ks) * 16) + t;
        bm[ks] = make_uint2(__ldg(p), __ldg(p + 4));
    }
    mbar_wait_u(bar_kv, 0);
    if (tid == 0) TL(1, 2);
#pragma unroll 1
    for (int s = 0;; s++) {
        TS(1);
        {
            float acc[8][4];
#pragma unroll
            for (int ks = 0; ks < 8; ks++) {
#pragma unroll
                for (int j = 0; j < 8; j++) {
                    const int i = smem_idx(ks, j) - 8;
                    if (ks == 0) {
                        acc[j][0] = acc[j][1] = acc[j][2] = acc[j][3] = 0.f;
                        mma16816(acc[j], buf0[j][0], buf0[j][1], buf0[j][2], buf0[j][3], bm[ks].x, bm[ks].y);
                    } else if (i >= 0) {
                        uint32_t(&a)[4] = ring[i % RB1];
                        mma16816(acc[j], a[0], a[1], a[2], a[3], bm[ks].x, bm[ks].y);
                        if (8 + i + RB1 < NS1) lds128v(a, W1A(8 + i + RB1));
                    } else {
                        const uint32_t(&a)[4] = wr[8 * ks + j];
                        mma16816(acc[j], a[0], a[1], a[2], a[3], bm[ks].x, bm[ks].y);
                    }
                }
            }
#pragma unroll
            for (int c = 0; c < 4; c++)
                stsm4t(lm + C_RED + w * 2176 + c * 64, pack2(acc[2 * c][0], acc[2 * c][1]), pack2(acc[2 * c][2], acc[2 * c][3]),
                       pack2(acc[2 * c + 1][0], acc[2 * c + 1][1]), pack2(acc[2 * c + 1][2], acc[2 * c + 1][3]));
        }
        {
            const uint32_t a = sb + C_RED + w * 272 + lane * 8;
            TS(2);
            __syncthreads();
            TS(3);
            uint2 v[8];
#pragma unroll
            for (int i = 0; i < 8; i++) v[i] = lds64(a + i * 2176);
            float c[4];
            sum8(c, v, idn);
            const uint32_t p0 = pack2(c[0], c[1]), p1 = pack2(c[2], c[3]);
            const uint32_t dst = sb + C_QKV + (r * 8 + w) * 272 + lane * 8;
#pragma unroll
            for (int i = 1; i < 3; i++) {
                const uint32_t peer = (h % (CLS / 3)) * 3 + (r + i >= 3 ? r + i - 3 : r + i);
                uint32_t rd, rb;
                asm("mapa.shared::cluster.u32 %0, %1, %2;" : "=r"(rd) : "r"(dst), "r"(peer));
                asm("mapa.shared::cluster.u32 %0, %1, %2;" : "=r"(rb) : "r"(bar_x), "r"(peer));
                asm volatile("st.async.weak.shared::cluster.mbarrier::complete_tx::bytes.v2.b32 [%0], {%1,%2}, [%3];"
                             ::"r"(rd), "r"(p0), "r"(p1), "r"(rb) : "memory");
            }
            sts64(dst, p0, p1);
            __syncwarp();
            asm volatile("{\n.reg .pred p;\nsetp.eq.u32 p, %1, 0;\n@p mbarrier.arrive.expect_tx.shared::cta.b64 _, [%0], 512;\n}"
                         ::"r"(bar_x), "r"(lane) : "memory");
        }
        TS(4);
        if (s == NSEG - 1) break;
        uint32_t wb[8][4], wc[8][4];
        const uint32_t po = (tile0 * 2 + (lane >> 4)) * 8192 + ((lane >> 3) & 1) * 2048 + h * 64 + (lane & 7) * 8;
        const uint32_t tag = s & 1;
        auto project = [&](const uint32_t(&wt)[8][4], const uint32_t(&ob)[4][4], int i) {
            float c0[4] = {0.f, 0.f, 0.f, 0.f}, c1[4] = {0.f, 0.f, 0.f, 0.f};
#pragma unroll
            for (int ks = 0; ks < 8; ks++)
                mma16816((ks & 1) ? c1 : c0, wt[ks][0], wt[ks][1], wt[ks][2], wt[ks][3], ob[ks >> 1][(ks & 1) * 2], ob[ks >> 1][(ks & 1) * 2 + 1]);
            uint32_t p0 = pack2(c0[0] + c1[0], c0[1] + c1[1]), p1 = pack2(c0[2] + c1[2], c0[3] + c1[3]);
            asm volatile("movmatrix.sync.aligned.m8n8.trans.b16 %0, %0;\nmovmatrix.sync.aligned.m8n8.trans.b16 %1, %1;" : "+r"(p0), "+r"(p1));
            st_rlx64((uint2*)((char*)g_x + po + i * 131072 + ((psel >> (2 * i + (lane >> 4))) & 1) * 4096), (p0 & ~1u) | tag, p1);
        };
        if (w >= 4) {
            uint32_t ka[4][4];
#pragma unroll
            for (int ks = 0; ks < 4; ks++) ldsm4(ka[ks], kva ^ (ks << 5));
            const uint32_t qa = lm + C_QKV + (w & 1) * 128;
            TS(5);
            mbar_wait_u(bar_x, s & 1);
            TS(6);
            {
                uint32_t qb[2][4];
                ldsm4(qb[0], qa);
                ldsm4(qb[1], qa + 64);
                float c0[4] = {0.f, 0.f, 0.f, 0.f}, c1[4] = {0.f, 0.f, 0.f, 0.f};
                mma16816(c0, ka[0][0], ka[0][1], ka[0][2], ka[0][3], qb[0][0], qb[0][1]);
                mma16816(c1, ka[1][0], ka[1][1], ka[1][2], ka[1][3], qb[0][2], qb[0][3]);
                mma16816(c0, ka[2][0], ka[2][1], ka[2][2], ka[2][3], qb[1][0], qb[1][1]);
                mma16816(c1, ka[3][0], ka[3][1], ka[3][2], ka[3][3], qb[1][2], qb[1][3]);
                sts32f(sa, c0[0] + c1[0]);
                sts32f(sa + 208, c0[1] + c1[1]);
                sts32f(sa + 32, c0[2] + c1[2]);
                sts32f(sa + 240, c0[3] + c1[3]);
            }
            __syncthreads();
            TS(7);
            if (w == 7 && s + 1 < NSEG - 1) {
                if (lane == 0) {
                    mbar_expect_tx(bar_kv, 16384);
                    tma3d(sb + C_KV, &mkv, 0, (s + 1) * 32, 2 * h, bar_kv);
                    tma3d(sb + C_KV + 8192, &mkv, 0, (s + 1) * 32, 64 + 2 * h, bar_kv);
                }
                __syncwarp();
            }
            const uint32_t wd = delayed<DLYW>(wa, lane);
#pragma unroll
            for (int i = 0; i < 8; i++) lds128(wb[i], wd + C_W2 + i * 4096);
#pragma unroll
            for (int i = 0; i < PFC; i++) lds128(wc[i], wd + C_W2 + 32768 - 1024 + i * 3072);
            TS(8);
            __syncthreads();
            TS(9);
            uint32_t ob[4][4];
#pragma unroll
            for (int i = 0; i < 4; i++) ldsm4(ob[i], lm + C_OB + i * 64);
#pragma unroll
            for (int i = PFC; i < 8; i++) lds128(wc[i], W2A(8 + i));
            project(wb, ob, 1);
            project(wo0, ob, 0);
            project(wc, ob, 2);
        } else {
            uint32_t va[4][4];
#pragma unroll
            for (int i = 0; i < 4; i++) ldsm4t(va[i], kva ^ (((i >> 1) << 5) | ((i & 1) * 0x240)));
#pragma unroll
            for (int i = 0; i < 8; i++) lds128(wb[i], W2A(i));
            const uint32_t qa = lm + C_QKV + (w & 1) * 128, oa = lm + w * 64;
            TS(5);
            mbar_wait_u(bar_x, s & 1);
            TS(6);
            if (w < 2) {
                uint32_t qb[2][4], km[2][4];
                ldsm4(qb[0], qa);
                ldsm4(km[0], qa + 8 * 272);
                ldsm4(qb[1], qa + 64);
                ldsm4(km[1], qa + 8 * 272 + 64);
                float c0[4] = {0.f, 0.f, 0.f, 0.f}, c1[4] = {0.f, 0.f, 0.f, 0.f};
                mma16816(c0, km[0][0], km[0][1], km[0][2], km[0][3], qb[0][0], qb[0][2]);
                mma16816(c1, km[0][0], km[0][1], km[0][2], km[0][3], qb[0][1], qb[0][3]);
                mma16816(c0, km[1][0], km[1][1], km[1][2], km[1][3], qb[1][0], qb[1][2]);
                mma16816(c1, km[1][0], km[1][1], km[1][2], km[1][3], qb[1][1], qb[1][3]);
                sts32f(sa, c0[0] + c1[2]);
                sts32f(sa + 208, c0[1] + c1[3]);
            }
            __syncthreads();
            TS(7);
            {
                float4 x0 = lds128f(sr), y0 = lds128f(sr + 1664), x1 = lds128f(sr + 16), y1 = lds128f(sr + 1680);
                float2 x2 = lds64f(sr2), y2 = lds64f(sr2 + 1664);
                float p[10] = {x0.x + y0.x, x0.y + y0.y, x0.z + y0.z, x0.w + y0.w, x1.x + y1.x,
                               x1.y + y1.y, x1.z + y1.z, x1.w + y1.w, x2.x + y2.x, x2.y + y2.y};
                float m = fmaxf(fmaxf(fmaxf(p[0], p[1]), fmaxf(p[2], p[3])), fmaxf(fmaxf(fmaxf(p[4], p[5]), fmaxf(p[6], p[7])), fmaxf(p[8], p[9])));
                const float m1 = __shfl_xor_sync(~0u, m, 1), m2 = __shfl_xor_sync(~0u, m, 2), m3 = __shfl_xor_sync(~0u, m, 3);
                uint32_t vm[4];
                ldsm4t(vm, oa + C_QKV + 16 * 272);
                m = fmaxf(fmaxf(m, m1), fmaxf(m2, m3));
                const float ms = m * sl2e;
#pragma unroll
                for (int i = 0; i < 10; i++) p[i] = ex2(fmaf(p[i], sl2e, -ms));
                const uint32_t b0 = pack2(p[0], p[1]), b1 = pack2(p[2], p[3]), b2 = pack2(p[4], p[5]), b3 = pack2(p[6], p[7]), b4 = pack2(p[8], p[9]);
                const uint32_t one = 0x3f803f80u;
                float o0[4] = {0.f, 0.f, 0.f, 0.f}, o1[4] = {0.f, 0.f, 0.f, 0.f}, sm[4] = {0.f, 0.f, 0.f, 0.f};
                mma16816(sm, one, one, one, one, b0, b1);
                mma16816(o0, va[0][0], va[0][1], va[0][2], va[0][3], b0, b1);
                mma16816(o1, va[2][0], va[2][1], va[2][2], va[2][3], b0, b1);
                mma16816(sm, one, one, one, one, b2, b3);
                mma16816(o0, va[1][0], va[1][1], va[1][2], va[1][3], b2, b3);
                mma16816(o1, va[3][0], va[3][1], va[3][2], va[3][3], b2, b3);
                mma1688(sm, one, one, b4);
                mma1688(o0, vm[0], vm[1], b4);
                mma1688(o1, vm[2], vm[3], b4);
                float i0, i1;
                asm("rcp.approx.ftz.f32 %0, %1;" : "=f"(i0) : "f"(sm[0]));
                asm("rcp.approx.ftz.f32 %0, %1;" : "=f"(i1) : "f"(sm[1]));
                stsm4t(oa + C_OB, pack2(o0[0] * i0, o0[1] * i1), pack2(o0[2] * i0, o0[3] * i1),
                       pack2(o1[0] * i0, o1[1] * i1), pack2(o1[2] * i0, o1[3] * i1));
            }
            TS(8);
            __syncthreads();
            TS(9);
            uint32_t ob[4][4];
#pragma unroll
            for (int i = 0; i < 4; i++) ldsm4(ob[i], lm + C_OB + i * 64);
            if (three) {
#pragma unroll
                for (int i = 0; i < 8; i++) lds128(wc[i], W2A(8 + i));
                project(wb, ob, 1);
                project(wo0, ob, 0);
                project(wc, ob, 2);
            } else {
                project(wb, ob, 1);
                project(wo0, ob, 0);
            }
        }
        TS(10);
        __syncthreads();
        uint32_t eo = (128 + (s + 1) * 4 + (w >> 1)) * 8192 + (((s < 31 ? msel0 : msel1) >> ((s + 1) & 31)) & 1) * 4096 + (w & 1) * 2048 + lane * 8;
        if (r == 0) {
            TS(11); TS(12);
            stage_w1();
            if (w < 4 && s + 3 < NSEG - 1)
                asm volatile("prefetch.global.L2 [%0];" ::"l"(g_kv + (size_t)((s + 3) * 32 + lane) * 8192 + (w >> 1) * HD + h * 128 + (w & 1) * 64) : "memory");
            publish_kvm(s);
            if (s < NSEG - 2) mbar_wait_u(bar_kv, (s + 1) & 1);
            mbar_wait_u(bar_go, s & 1);
            if (w < 4) eo = delayed<DLY0>(eo, lane); else eo = delayed<DLY0A>(eo, lane);
        } else {
            const int j = 2 * h + r - 1;
            if (w < 4) {
                const char* src = (const char*)g_x + delayed<DLY3>((j * 2 + (w >> 1)) * 8192 + (psel & 64) * 64 + (w & 1) * 2048 + t * 64 + g * 8, lane);
                const char* dst = (const char*)g_x + pin((128 + (s + 1) * 4 + (j >> 4)) * 8192 + (j & 15) * 256 + w * 64 + (t & 1) * 4096 + g * 8);
                const uint64_t v = poll_sum(src, tag, (lane & 4) ? 0x3f800000u : 0x00003f80u);
                TS(11);
                asm volatile("st.relaxed.gpu.global.b64 [%0], %1;" ::"l"(dst), "l"(v) : "memory");
                asm volatile("bar.arrive 1, 256;" ::: "memory");
                TS(12);
                stage_w1();
                if (s < NSEG - 2) mbar_wait_u(bar_kv, (s + 1) & 1);
                eo = delayed<DLY1>(eo, lane);
            } else {
                if (w >= 6 && s + 3 < NSEG)
                    asm volatile("prefetch.global.L2 [%0];" ::"l"(g_x + (128 + (s + 3) * 4 + (j >> 4)) * 1024 + (w & 1) * 512 + (j & 15) * 32 + lane) : "memory");
                stage_w1();
                if (s < NSEG - 2) mbar_wait_u(bar_kv, (s + 1) & 1);
                TS(11);
                bar_sync(1, 256);
                TS(12);
                if (w == 4 && r == 1)
                    asm volatile("{\n.reg .pred p;\n.reg .u32 a;\nelect.sync _|p, -1;\nmapa.shared::cluster.u32 a, %0, %1;\n"
                                 "@p mbarrier.arrive.relaxed.cluster.shared::cluster.b64 _, [a];\n}" ::"r"(bar_go), "r"((h % (CLS / 3)) * 3) : "memory");
                eo = delayed<DLY1A>(eo, lane);
            }
        }
        { const int s_ = s; { const int s = s_ + 1; TS(0); } }
        poll_state(bm, (const char*)g_x + eo);
    }
    mbar_wait_u(bar_x, (NSEG - 1) & 1);
    if (r == 0) publish_kvm(NSEG - 1);
    asm volatile("barrier.cluster.arrive.relaxed.aligned;\nbarrier.cluster.wait.aligned;" ::: "memory");
}

constexpr int S4_US = 4368;
constexpr int S4_RS = 8848;
constexpr int S4_KS = 1296;
constexpr int S4_U = 0, S4_R = 16 * S4_US, S4_K = S4_R + 16 * S4_RS;
constexpr int S4_SMEM = S4_K + 16 * S4_KS;
constexpr int S4_SIG = 3104, S4_PK = 2 * S4_SIG;

struct cf { float r, i; };
__device__ __forceinline__ cf cmul(cf a, cf b) { return {fmaf(a.r, b.r, -a.i * b.i), fmaf(a.r, b.i, a.i * b.r)}; }
__device__ __forceinline__ cf cmulc(cf a, cf b) { return {fmaf(a.r, b.r, a.i * b.i), fmaf(a.i, b.r, -a.r * b.i)}; }
__device__ __forceinline__ cf csq(cf a) { const float t = a.r * a.i; return {fmaf(a.r, a.r, -a.i * a.i), t + t}; }
__device__ __forceinline__ cf cexp(float l2, float turns) {
    const float mag = ex2(l2), fr = (turns - rintf(turns)) * 6.283185307179586f;
    return {mag * __cosf(fr), mag * __sinf(fr)};
}
__device__ __forceinline__ void sts32(uint32_t a, uint32_t v) { asm volatile("st.shared.u32 [%0], %1;" ::"r"(a), "r"(v) : "memory"); }
__device__ __forceinline__ uint32_t lds16(uint32_t a) {
    uint32_t v;
    asm volatile("ld.shared.u16 %0, [%1];" : "=r"(v) : "r"(a) : "memory");
    return v;
}

template <int M0, int NQ>
__device__ __forceinline__ void s4_class(float (&acc)[16][4], uint32_t sig, uint32_t taps, int x0) {
    constexpr int D0 = M0 / 8, D1 = M0 == 32 ? 9 : 15;
    uint32_t R[D1 - D0 + 2];
#pragma unroll
    for (int D = D0 - 1; D <= D1; D++) {
        if (D < D0 || 8 * D - 7 >= 2 * M0) { R[D - D0 + 1] = 0; continue; }
        const int m = 8 * D + x0;
        uint32_t lo = lds16(taps + m * (2 * NQ)), hi = lds16(taps + (m - 1) * (2 * NQ));
        if (D == D0) { lo = m >= M0 ? lo : 0; hi = m > M0 ? hi : 0; }
        if (D == 2 * D0) { lo = m < 2 * M0 ? lo : 0; hi = m <= 2 * M0 ? hi : 0; }
        R[D - D0 + 1] = lo | (hi << 16);
    }
#pragma unroll
    for (int J = 0; 2 * J + D0 < 16; J++) {
        uint32_t a[4];
        ldsm4t(a, sig + J * 512);
#pragma unroll
        for (int D = D0; D <= D1; D++)
            if (2 * J + D < 16) mma16816(acc[2 * J + D], a[0], a[1], a[2], a[3], R[D - D0 + 1], R[D - D0]);
    }
}

__global__ void __launch_bounds__(512, 1)
k_s4(const bf16* __restrict__ u, const bf16* __restrict__ Are, const bf16* __restrict__ Aim, const bf16* __restrict__ Bre,
     const bf16* __restrict__ Bim, const bf16* __restrict__ Cre, const bf16* __restrict__ Cim, const bf16* __restrict__ logdt,
     const bf16* __restrict__ Dsk, bf16* __restrict__ out) {
    extern __shared__ __align__(16) uint8_t smem_s4[];
    const uint32_t sb = smem_u32(smem_s4);
    asm volatile("griddepcontrol.launch_dependents;");
    const int tid = threadIdx.x, w = __shfl_sync(~0u, tid >> 5, 0), lane = tid & 31, g = lane >> 2, t = lane & 3;
#pragma unroll 1
    for (int item = blockIdx.x; item < 64; item += gridDim.x) {
#define TLS(slot)
    if (tid == 0) TLS(0);
    const int d0 = item * 16;
    const int d = d0 + (w & 1) + ((w >> 1) & 3) * 4 + (w >> 3) * 2;
    const uint32_t tr_off = (lane & 15), tr_l = (lane >> 4) * 16;
    const uint32_t ur = sb + S4_U + w * S4_US, rs = sb + S4_R + w * S4_RS, kd = sb + S4_K + w * S4_KS;
    if (lane < 16) sts128(ur + lane * 16, 0, 0, 0, 0);
    {
        const int o = d * 128 + lane * 4;
        const uint2 ar = __ldg((const uint2*)(Are + o)), ai = __ldg((const uint2*)(Aim + o)), br = __ldg((const uint2*)(Bre + o));
        const uint2 bi = __ldg((const uint2*)(Bim + o)), cr = __ldg((const uint2*)(Cre + o)), ci = __ldg((const uint2*)(Cim + o));
        const float dt = bf_round(expf(__bfloat162float(logdt[d])));
        const bf16* src = u + (size_t)(w * 128 + g) * DM + d0 + 4 * t;
        float T[5][4];
#pragma unroll
        for (int i = 0; i < 5; i++) T[i][0] = T[i][1] = T[i][2] = T[i][3] = 0.f;
        float klast = 0.f;
        const uint32_t wr_ = rs + lane * 272, rd_ = rs + t * 544 + g * 16;
#pragma unroll 1
        for (int c = 0; c < 4; c++) {
            uint2 v[4];
#pragma unroll
            for (int i = 0; i < 4; i++) v[i] = __ldg((const uint2*)(src + (size_t)(c * 32 + i * 8) * DM));
            auto pick = [&](const uint2& x) { const uint32_t y = c < 2 ? x.x : x.y; return (c & 1) ? bf_hi(y) : bf_lo(y); };
            auto pk2 = [](cf x) { return pack2(x.r, x.i); };
            const float l2 = dt * pick(ar) * 1.4426950408889634f, tu = dt * pick(ai) * 0.15915494309189535f;
            const cf z1 = cexp(l2, tu), z2 = csq(z1), z4 = csq(z2), z8 = csq(z4);
            const cf z64 = cexp(l2 * 64.f, tu * 64.f), z128 = csq(z64), z256 = csq(z128), z512 = csq(z256);
            cf a0 = {1.f, 0.f}, a1 = z64;
            cf b0 = cmul({pick(cr), pick(ci)}, {dt * pick(br), dt * pick(bi)});
            b0.i = -b0.i;
            cf b1 = cmulc(b0, z128), b2 = cmulc(b0, z256), y3 = cmulc(b0, z512), b4 = cmulc(y3, z512), b3 = y3;
            const cf y2 = cmulc(b2, z128);
#pragma unroll
            for (int i = 0; i < 8; i++) {
                sts128(wr_ + i * 16, pk2(a0), pk2(a1), pk2(b0), pk2(b1));
                sts128(wr_ + i * 16 + 128, pk2(b2), pk2(b3), pk2(b4), 0);
                b4 = cmulc(b4, z128);
                if (i < 7) {
                    a0 = i == 0 ? z8 : cmul(a0, z8); a1 = cmul(a1, z8);
                    b0 = cmulc(b0, z1); b1 = cmulc(b1, z1);
                    b2 = i == 3 ? y2 : cmulc(b2, z2);
                    if (i & 1) { y3 = cmulc(y3, z128); b3 = y3; } else b3 = cmulc(y3, z4);
                }
            }
            klast += b4.r;
            __syncwarp();
#pragma unroll
            for (int k = 0; k < 8; k++) {
                uint32_t x[4], y[4];
                lds128(x, rd_ + (8 * (k >> 1) + (k & 1)) * 272);
                lds128(y, rd_ + (8 * (k >> 1) + (k & 1)) * 272 + 128);
                mma1688(T[0], x[0], x[1], x[2]);
                mma1688(T[1], x[0], x[1], x[3]);
                mma1688(T[2], x[0], x[1], y[0]);
                mma1688(T[3], x[0], x[1], y[1]);
                mma1688(T[4], x[0], x[1], y[2]);
            }
#pragma unroll
            for (int i = 0; i < 2; i++)
                stsm4t(sb + S4_U + tr_off * S4_US + 256 + (w * 128 + c * 32 + i * 16) * 2 + tr_l, v[2 * i].x, v[2 * i].y, v[2 * i + 1].x, v[2 * i + 1].y);
            __syncwarp();
        }
#pragma unroll
        for (int o2 = 16; o2; o2 >>= 1) klast += __shfl_xor_sync(~0u, klast, o2);
#pragma unroll
        for (int hh = 0; hh < 2; hh++) {
            const int i = g + 8 * hh;
            sts32(kd + (8 * i + 2 * t) * 2, pack2(T[0][2 * hh], T[0][2 * hh + 1]));
            sts32(kd + (128 + 8 * i + 2 * t) * 2, pack2(T[1][2 * hh], T[1][2 * hh + 1]));
            sts32(kd + (256 + 4 * i + 2 * (t & 1) + 64 * (t >> 1)) * 2, pack2(T[2][2 * hh], T[2][2 * hh + 1]));
            sts32(kd + (384 + 2 * i + 32 * t) * 2, pack2(T[3][2 * hh], T[3][2 * hh + 1]));
        }
        asm volatile("stmatrix.sync.aligned.m8n8.x2.trans.shared.b16 [%0], {%1,%2};"
                     ::"r"(kd + 1024 + (lane & 7) * 32 + ((lane >> 3) & 1) * 16), "r"(pack2(T[4][0], T[4][1])), "r"(pack2(T[4][2], T[4][3])) : "memory");
        if (lane == 0) sts32(kd + 1280, pack2(klast, 0.f));
    }
    __syncwarp();
    const uint32_t pk = rs + S4_PK + 64;
    {
#pragma unroll
        for (int i = 0; i < 2; i++) {
            const int x = i * 128 + lane * 4;
            const uint2 c = lds64(kd + x * 2);
            uint32_t p = lds16(kd + x * 2 - 2);
            if (x == 0) p = 0;
            sts128(pk + x * 4, __byte_perm(c.x, p, 0x5410), __byte_perm(c.x, 0, 0x1032), __byte_perm(c.y, c.x, 0x7610), __byte_perm(c.y, 0, 0x1032));
        }
#pragma unroll
        for (int i = 2; i < 4; i++) {
            const int x = i * 128 + lane * 4;
            const uint32_t ab = lds32(kd + 256 + x), c = lds16(kd + 256 + x + 4);
            const uint32_t p = x == 256 ? lds16(kd + 510) : ab;
            sts128(pk + x * 4, __byte_perm(ab, p, 0x5410), __byte_perm(ab, 0, 0x1010), __byte_perm(ab, 0, 0x1032), __byte_perm(c, ab, 0x7610));
        }
        const uint32_t v = lds16(kd + 768), v2 = lds16(kd + 1024);
        if (lane < 24) {
            uint32_t x0 = 0, x1 = 0, x2 = 0, x3 = 0;
            if (lane == 0) { x0 = x1 = x2 = v | (v << 16); x3 = v << 16; }
            if (lane == 12) x3 = v2;
            if (lane == 13) { x0 = v2 | (v2 << 16); x1 = v2 << 16; }
            sts128(lane < 20 ? pk + 2048 + lane * 16 : pk - 64 + (lane - 20) * 16, x0, x1, x2, x3);
        }
        if (lane < 4) sts128(rs + (lane >> 1) * S4_SIG + (lane & 1) * 16, 0, 0, 0, 0);
    }
    __syncthreads();
    float acc[16][4];
#pragma unroll
    for (int i = 0; i < 16; i++) acc[i][0] = acc[i][1] = acc[i][2] = acc[i][3] = 0.f;
    const uint32_t lf = (lane & 7) * 32 + ((lane >> 3) & 1) * 16 + (lane >> 4) * 256;
#pragma unroll 1
    for (int ph = 0; ph < 2; ph++) {
    if (((w >> 2) ^ ph) & 1) {
#pragma unroll
    for (int rg = 3; rg >= 2; rg--) {
#pragma unroll 1
        for (int it = 0; it < (rg == 3 ? 4 : 6); it++) {
            const int n = it * 32 + lane;
            uint32_t x[2][4];
            lds128(x[0], ur + 256 + n * 16 - 16);
            lds128(x[1], ur + 256 + n * 16);
            float e[16], p[15], s[11];
#pragma unroll
            for (int i = 0; i < 8; i++) { e[2 * i] = bf_lo(x[i >> 2][i & 3]); e[2 * i + 1] = bf_hi(x[i >> 2][i & 3]); }
#pragma unroll
            for (int i = 0; i < 15; i++) p[i] = e[i] + e[i + 1];
#pragma unroll
            for (int i = 0; i < 11; i++) s[i] = p[i + 3] + e[i + 5];
            const uint32_t o = rs + 16 + n * 16;
            if (rg == 2) sts128(o, pack2(s[0], s[1]), pack2(s[2], s[3]), pack2(s[4], s[5]), pack2(s[6], s[7]));
#pragma unroll
            for (int i = 0; i < 10; i++) s[i] = p[i + 2] + s[i + 1];
            if (rg == 2) {
                sts64(o + S4_SIG + 8, pack2(s[0], s[1]), pack2(s[2], s[3]));
                sts64(o + S4_SIG + 16, pack2(s[4], s[5]), pack2(s[6], s[7]));
            } else {
#pragma unroll
                for (int i = 0; i < 9; i++) s[i] = p[i + 1] + s[i + 1];
                sts64(o + 8, pack2(s[0], s[1]), pack2(s[2], s[3]));
                sts64(o + 16, pack2(s[4], s[5]), pack2(s[6], s[7]));
#pragma unroll
                for (int i = 0; i < 8; i++) s[i] = p[i] + s[i + 1];
                sts64(o + S4_SIG + 8, pack2(s[0], s[1]), pack2(s[2], s[3]));
                sts64(o + S4_SIG + 16, pack2(s[4], s[5]), pack2(s[6], s[7]));
            }
        }
        __syncwarp();
        if (rg == 3) {
#pragma unroll 1
            for (int q = 1; q <= 2; q++) s4_class<64, 2>(acc, rs + lf + (q == 1 ? 16 : S4_SIG), kd + (384 + q) * 2, g - 2 * t);
        } else {
#pragma unroll 1
            for (int q = 1; q <= 4; q++) s4_class<32, 4>(acc, rs + lf + ((q & 1) ? 0 : S4_SIG) + (q < 3 ? 16 : 0), kd + (256 + q) * 2, g - 2 * t);
        }
        __syncwarp();
    }
    } else
    {
        const uint32_t ub = ur + 256 + lf, kb = pk + (g - 2 * t) * 4;
#pragma unroll 1
        for (int j0 = 0; j0 < 8; j0++) {
            uint32_t B[8][4];
#pragma unroll
            for (int i = 0; i < 8; i++) ldsm4(B[i], ub + i * 512 - j0 * 32);
            auto block = [&](int J, uint32_t a) {
                const uint32_t r0 = lds32(a), rp = lds32(a + 32), rm = lds32(a - 32);
                uint32_t r3;
                asm volatile("ld.volatile.shared.u32 %0, [%1];" : "=r"(r3) : "r"(a) : "memory");
#pragma unroll
                for (int I = J; I < 16; I++)
                    mma16816(acc[I], r0, rp, rm, r3, B[(I - J) >> 1][((I - J) & 1) * 2], B[(I - J) >> 1][((I - J) & 1) * 2 + 1]);
            };
#pragma unroll
            for (int J = 0; J < 4; J++) block(J, kb + j0 * 64 + J * 512);
            if (j0 < 2) { block(4, kb + j0 * 64 + 2048); block(8, kb + j0 * 64 + (544 + 16) * 4); }
        }
    }
    }
    {
        __syncwarp();
#pragma unroll
        for (int i = 0; i < 8; i++)
            stsm4t(rs + lf + i * 512, pack2(acc[2 * i][0], acc[2 * i][1]), pack2(acc[2 * i][2], acc[2 * i][3]),
                   pack2(acc[2 * i + 1][0], acc[2 * i + 1][1]), pack2(acc[2 * i + 1][2], acc[2 * i + 1][3]));
    }
    __syncthreads();
    {
        const uint2 dv = __ldg((const uint2*)(Dsk + d0 + 4 * t));
        bf16* dst = out + (size_t)(w * 128 + g) * 2048 + 1024 + d0 + 4 * t;
#pragma unroll
        for (int i = 0; i < 8; i++) {
            uint32_t y[4], x[4], o[4];
            ldsm4t(y, sb + S4_R + tr_off * S4_RS + (w * 128 + i * 16) * 2 + tr_l);
            ldsm4t(x, sb + S4_U + tr_off * S4_US + 256 + (w * 128 + i * 16) * 2 + tr_l);
#pragma unroll
            for (int j = 0; j < 4; j++)
                asm("{\n.reg .b32 s;\nmul.rn.bf16x2 s, %2, %3;\nadd.rn.bf16x2 %0, %1, s;\n}" : "=r"(o[j]) : "r"(y[j]), "r"(x[j]), "r"((j & 1) ? dv.y : dv.x));
            *reinterpret_cast<uint2*>(dst + (size_t)(i * 16) * 2048) = make_uint2(o[0], o[1]);
            *reinterpret_cast<uint2*>(dst + (size_t)(i * 16 + 8) * 2048) = make_uint2(o[2], o[3]);
        }
    }
    if (tid == 0) TLS(1);
    __syncthreads();
    }
}

enum { IT_QA = 0, IT_W256 = 1, IT_W128 = 2, IT_W64 = 3, IT_W64S = 4, IT_END = 7 };
struct BgParams { CUtensorMap mx, mwq, mkv, mkvm, mo, mo2, mo2s, mwo4, mwo2, mwo1; };
#define LOOK 8
#define NW0 4
#define NW1 16
#define PW1 20
#define P256 54
#define P128 56
__device__ __forceinline__ uint32_t ld_rlx32(const uint32_t* p) {
    uint32_t v;
    asm volatile("ld.relaxed.gpu.global.u32 %0, [%1];" : "=r"(v) : "l"(p) : "memory");
    return v;
}
#define NBT 9
#define NBL 9
constexpr uint32_t W_LONG = NBL * 16, W_LAST = NBT * 16, W_END = W_LAST + 32;
__device__ __forceinline__ bool block_done(uint32_t strip) { return ld_rlx32(g_flag + 64 + (strip < W_LAST ? strip >> 4 : 15)) >= 16; }
struct Sched { uint32_t qb = 0, w0 = 0, w1 = 0; };
__device__ __forceinline__ int next_item(Sched& z) {
    for (int n = 0; n < SPIN_LIMIT; n++) {
        if (z.w0 < z.w1 && (z.qb >= 16 || block_done(z.w0))) {
            const uint32_t i = z.w0, k = i >= W_LAST ? 1 : z.w1 - i >= 4 && !(i & 3) ? 4 : z.w1 - i >= 2 && !(i & 1) ? 2 : 1;
            z.w0 += k;
            if (i >= W_LAST) return IT_W64S | 15 << 3 | (i - W_LAST) << 7;
            return (k == 4 ? IT_W256 : k == 2 ? IT_W128 : IT_W64) | (i >> 4) << 3 | ((i & 15) / k) << 7;
        }
        uint32_t qa, wo, prog, wl;
        asm volatile("ld.relaxed.gpu.global.v4.u32 {%0,%1,%2,%3}, [%4];" : "=r"(qa), "=r"(wo), "=r"(prog), "=r"(wl) : "l"(g_flag + 96) : "memory");
        if (wo >= W_LAST) wo = W_LAST + wl;
        z.qb = qa >> 4;
        const bool wo_ready = z.w0 >= z.w1 && wo < W_END &&
                              (z.qb >= 16 || (wo < W_LONG && blockIdx.x < (prog < PW1 ? NW0 : NW1) && block_done(wo)));
        if (z.qb < 16 && prog + LOOK >= 4 * z.qb + 4 && !wo_ready) {
            const uint32_t i = atomicAdd(g_flag + 96, 1);
            if (i < 256) return IT_QA | (i >> 4) << 3 | (i & 15) << 7;
            continue;
        }
        if (z.w0 < z.w1) {
            if (z.qb >= 16) continue;
        } else if (wo >= W_END) {
            if (z.qb >= 16) return IT_END;
        } else if (wo_ready) {
            if (wo < W_LAST) {
                const uint32_t k = prog <= P256 ? 4 : prog <= P128 ? 2 : 1;
                z.w0 = atomicAdd(g_flag + 97, k);
                z.w1 = min(z.w0 + k, W_LAST);
            } else {
                z.w0 = W_LAST + atomicAdd(g_flag + 99, 1);
                z.w1 = min(z.w0 + 1, W_END);
            }
            continue;
        }
        __nanosleep(300);
    }
    __trap();
    return IT_END;
}
constexpr int B_OST = NSTAGE * STAGE_BYTES + 1024;
constexpr int BG_SMEM = B_OST + 32768;

template <int BM, int BN, int KPS, typename ACC>
__device__ __forceinline__ void gemm_mainloop(ACC& acc, const GemmSmem& g, int cw, int rounds, uint32_t& round) {
#pragma unroll
    for (int i = 0; i < BN / 2; i++) acc[i] = 0.f;
#pragma unroll 1
    for (int k0 = 0; k0 < rounds; k0++, round++) {
#pragma unroll
        for (int s = 0; s < 4; s++) {
            mbar_wait_u(g.full + 8 * s, round & 1);
            gemm_stage<BM, BN, KPS>(acc, g.st + s * STAGE_BYTES, cw, false);
            wg_wait<1>();
            if (s > 0 || k0 > 0) mbar_arrive_one(g.empty + 8 * ((s + 3) & 3), threadIdx.x & 31);
        }
    }
    wg_wait<0>();
    mbar_arrive_one(g.empty + 8 * 3, threadIdx.x & 31);
}

template <int BN>
__device__ __forceinline__ void store_tile(const float (&acc)[BN / 2], bf16* dst, int t) {
#pragma unroll
    for (int G = 0; G < BN / 32; G++)
#pragma unroll
        for (int rr = 0; rr < 2; rr++) {
            uint32_t r0 = pack2(acc[16 * G + 2 * rr], acc[16 * G + 2 * rr + 1]), r1 = pack2(acc[16 * G + 4 + 2 * rr], acc[16 * G + 5 + 2 * rr]);
            uint32_t r2 = pack2(acc[16 * G + 8 + 2 * rr], acc[16 * G + 9 + 2 * rr]), r3 = pack2(acc[16 * G + 12 + 2 * rr], acc[16 * G + 13 + 2 * rr]);
            quad_transpose(r0, r1, r2, r3, t);
            *reinterpret_cast<uint4*>(dst + (size_t)rr * 8 * 2048 + G * 32) = make_uint4(r0, r1, r2, r3);
        }
}

template <int BM, int BN, int KPS>
__device__ __forceinline__ void wo_item(const GemmSmem& g, int cw, uint32_t& round, bf16* dst, int t) {
    if (BM == 64 && cw == 1) {
#pragma unroll 1
        for (int k0 = 0; k0 < 16 / KPS; k0++, round++)
#pragma unroll
            for (int s = 0; s < 4; s++) { mbar_wait_u(g.full + 8 * s, round & 1); mbar_arrive_one(g.empty + 8 * s, threadIdx.x & 31); }
        return;
    }
    float acc[BN / 2];
    gemm_mainloop<BM, BN, KPS>(acc, g, cw, 16 / KPS, round);
    store_tile<BN>(acc, dst, t);
}

template <int HF>
__device__ __forceinline__ void attend(const uint32_t* q, uint32_t st, uint32_t sm, uint32_t ost, uint32_t bar_free, uint32_t parity, int lane) {
    constexpr int NT = HF ? 5 : 3;
    const int r8 = lane & 7, m4 = lane >> 3, gq = lane >> 2, t = lane & 3;
    const float sl2e = 0.08838834764831845f * 1.4426950408889634f;
    const uint32_t la = r8 * 128 + ((m4 ^ r8) << 4);
    float sc[NT][4];
#pragma unroll
    for (int nt = 0; nt < NT; nt++) sc[nt][0] = sc[nt][1] = sc[nt][2] = sc[nt][3] = 0.f;
#pragma unroll
    for (int kp = 0; kp < 4; kp++)
#pragma unroll
        for (int nt = 0; nt < NT; nt++) {
            uint32_t b[4];
            ldsm4(b, (nt == 0 ? sm + (kp >> 1) * 2048 : st + (kp >> 1) * 8192 + (nt - 1) * 1024) + (la ^ ((kp & 1) << 6)));
            mma16816(sc[nt], q[kp * 8], q[kp * 8 + 1], q[kp * 8 + 2], q[kp * 8 + 3], b[0], b[1]);
            mma16816(sc[nt], q[kp * 8 + 4], q[kp * 8 + 5], q[kp * 8 + 6], q[kp * 8 + 7], b[2], b[3]);
        }
    const float ninf = -3.0e38f;
    if (2 * t > gq) sc[NT - 2][0] = sc[NT - 1][2] = ninf;
    if (2 * t + 1 > gq) sc[NT - 2][1] = sc[NT - 1][3] = ninf;
    sc[NT - 1][0] = sc[NT - 1][1] = ninf;
    uint32_t p[NT][2];
#pragma unroll
    for (int i = 0; i < 2; i++) {
        float m = fmaxf(sc[0][2 * i], sc[0][2 * i + 1]);
#pragma unroll
        for (int nt = 1; nt < NT - 1 + i; nt++) m = fmaxf(m, fmaxf(sc[nt][2 * i], sc[nt][2 * i + 1]));
        m = fmaxf(m, __shfl_xor_sync(~0u, m, 1));
        m = fmaxf(m, __shfl_xor_sync(~0u, m, 2));
        const float ms = m * sl2e;
        float sum = 0.f;
#pragma unroll
        for (int nt = 0; nt < NT - 1 + i; nt++) {
            sc[nt][2 * i] = ex2(fmaf(sc[nt][2 * i], sl2e, -ms));
            sc[nt][2 * i + 1] = ex2(fmaf(sc[nt][2 * i + 1], sl2e, -ms));
            sum += sc[nt][2 * i] + sc[nt][2 * i + 1];
        }
        sum += __shfl_xor_sync(~0u, sum, 1);
        sum += __shfl_xor_sync(~0u, sum, 2);
        float inv;
        asm("rcp.approx.ftz.f32 %0, %1;" : "=f"(inv) : "f"(sum));
#pragma unroll
        for (int nt = 0; nt < NT - 1 + i; nt++) p[nt][i] = pack2(sc[nt][2 * i] * inv, sc[nt][2 * i + 1] * inv);
    }
    p[NT - 1][0] = 0;
    const uint32_t lv = ((m4 & 1) * 8 + r8) * 128 + (((m4 >> 1) ^ r8) << 4);
    mbar_wait_u(bar_free, parity);
#pragma unroll
    for (int G = 0; G < 4; G++) {
        float o[4][4];
#pragma unroll
        for (int i = 0; i < 4; i++) o[i][0] = o[i][1] = o[i][2] = o[i][3] = 0.f;
        uint32_t b[4];
        ldsm4t(b, sm + 4096 + (G >> 1) * 2048 + (la ^ ((G & 1) << 6)));
#pragma unroll
        for (int i = 0; i < 4; i++) mma1688(o[i], p[0][0], p[0][1], b[i]);
#pragma unroll
        for (int kk = 0; kk <= HF; kk++)
#pragma unroll
            for (int i = 0; i < 2; i++) {
                ldsm4t(b, st + 16384 + (G >> 1) * 8192 + kk * 2048 + (lv ^ (((G & 1) * 2 + i) << 5)));
                mma16816(o[2 * i], p[1 + 2 * kk][0], p[1 + 2 * kk][1], p[2 + 2 * kk][0], p[2 + 2 * kk][1], b[0], b[1]);
                mma16816(o[2 * i + 1], p[1 + 2 * kk][0], p[1 + 2 * kk][1], p[2 + 2 * kk][0], p[2 + 2 * kk][1], b[2], b[3]);
            }
#pragma unroll
        for (int i = 0; i < 2; i++)
            asm volatile("stmatrix.sync.aligned.m8n8.x4.shared.b16 [%0], {%1,%2,%3,%4};"
                         ::"r"(ost + (G >> 1) * 16384 + (lv ^ (((G & 1) * 2 + i) << 5))),
                           "r"(pack2(o[2 * i][0], o[2 * i][1])), "r"(pack2(o[2 * i][2], o[2 * i][3])),
                           "r"(pack2(o[2 * i + 1][0], o[2 * i + 1][1])), "r"(pack2(o[2 * i + 1][2], o[2 * i + 1][3])) : "memory");
    }
    asm volatile("fence.proxy.async.shared::cta;" ::: "memory");
    __syncwarp();
}

__device__ __forceinline__ void tma_prefetch3d(const CUtensorMap* m, int c0, int c1, int c2) {
    asm volatile("cp.async.bulk.prefetch.tensor.3d.L2.global [%0, {%1, %2, %3}];" ::"l"(m), "r"(c0), "r"(c1), "r"(c2) : "memory");
}

__global__ void __launch_bounds__(384, 1) k_bg(const __grid_constant__ BgParams P, bf16* __restrict__ out) {
    extern __shared__ __align__(1024) uint8_t smem_gemm[];
    asm volatile("griddepcontrol.launch_dependents;");
    const uint32_t xb = smem_u32(smem_gemm) + NSTAGE * STAGE_BYTES + 128;
    const uint32_t bar_item = xb, bar_o = xb + 16, bar_f = xb + 24, slot = xb + 32, slot_o = xb + 40;
    if (threadIdx.x == 0) { mbar_init(bar_item, 1); mbar_init(bar_item + 8, 1); mbar_init(bar_o, 8); mbar_init(bar_f, 1); }
    GemmSmem g = gemm_setup(smem_gemm, 8);
    const int wg = __shfl_sync(~0u, threadIdx.x >> 7, 0);
    if (wg == 0) {
        asm volatile("setmaxnreg.dec.sync.aligned.u32 40;");
        if (threadIdx.x == 0) {
            uint32_t it = 0;
            Sched z;
            wait_flag(g_flag + 98, 1);
            asm volatile("fence.proxy.async.global;" ::: "memory");
            auto acquire = [&](uint32_t bytes) {
                const int s = it & 3;
                mbar_wait(g.empty + 8 * s, ((it >> 2) & 1) ^ 1);
                mbar_expect_tx(g.full + 8 * s, bytes);
                it++;
                return s;
            };
            for (int n = 0;; n++) {
                const int code = next_item(z);
                sts32(slot + (n & 1) * 4, code);
                mbar_arrive(bar_item + (n & 1) * 8);
                const int type = code & 7, blk = (code >> 3) & 15, idx = code >> 7, m0 = blk * 128;
                if (type == IT_END) break;
                if (type == IT_QA) {
                    for (int k = 0; k < 16; k++) {
                        const int s = acquire(STAGE_BYTES);
                        const uint32_t st = g.st + s * STAGE_BYTES, fb = g.full + 8 * s;
                        tma2d(st, &P.mx, k * 64, m0, fb);
                        tma3d(st + 16384, &P.mwq, 0, k * 64, idx * 4, fb);
                        if (k >= 4 && k < 12) tma_prefetch3d(&P.mkv, 0, m0 + (k & 1) * 64, (k & 8) * 8 + idx * 4 + (k & 2));
                    }
                    bool ready = ld_acq32(g_flag + 2 * idx) >= 4 * blk + 4 && ld_acq32(g_flag + 2 * idx + 1) >= 4 * blk + 4;
                    if (ready) asm volatile("fence.proxy.async.global;" ::: "memory");
                    for (int pass = 0; pass < 2; pass++) {
                        for (int s = 0; s < 4; s++) {
                            const uint32_t st = g.st + s * STAGE_BYTES, fb = g.full + 8 * s;
                            if (pass == 0) {
                                acquire(40960);
                                tma3d(st, &P.mkv, 0, m0 + (s & 1) * 64, idx * 4 + (s & 2), fb);
                                tma3d(st + 16384, &P.mkv, 0, m0 + (s & 1) * 64, 64 + idx * 4 + (s & 2), fb);
                            }
                            if (ready) {
                                tma3d(st + 32768, &P.mkvm, 0, blk * 32 + (s & 1) * 16, idx * 4 + (s & 2), fb);
                                tma3d(st + 36864, &P.mkvm, 0, blk * 32 + (s & 1) * 16, 64 + idx * 4 + (s & 2), fb);
                            }
                        }
                        if (ready) break;
                        wait_flag(g_flag + 2 * idx, 4 * blk + 4);
                        wait_flag(g_flag + 2 * idx + 1, 4 * blk + 4);
                        asm volatile("fence.proxy.async.global;" ::: "memory");
                        ready = true;
                    }
                } else {
                    wait_flag(g_flag + 64 + blk, 16);
                    asm volatile("fence.proxy.async.global;" ::: "memory");
                    if (type <= IT_W128) {
                        const int nb = type == IT_W256 ? 4 : 2;
                        for (int k = 0; k < 64; k++) {
                            const int s = acquire(16384 + nb * 8192);
                            const uint32_t st = g.st + s * STAGE_BYTES, fb = g.full + 8 * s;
                            tma2d(st, &P.mo, k * 64, m0, fb);
                            tma3d(st + 16384, nb == 4 ? &P.mwo4 : &P.mwo2, 0, k * 64, idx * nb, fb);
                        }
                    } else {
                        const uint32_t ab = type == IT_W64 ? 32768 : 16384;
                        for (int k = 0; k < 32; k++) {
                            const int s = acquire(ab + 16384);
                            const uint32_t st = g.st + s * STAGE_BYTES, fb = g.full + 8 * s;
                            tma3d(st, type == IT_W64 ? &P.mo2 : &P.mo2s, 0, m0 + (idx >> 4) * 64, k * 2, fb);
                            tma3d(st + ab, &P.mwo1, 0, k * 128, idx & 15, fb);
                        }
                    }
                }
            }
        } else if (threadIdx.x == 32) {
            for (;;) {
                mbar_wait(bar_o, 0);
                const int code = lds32(slot_o), blk = (code >> 3) & 15, idx = (code >> 7) & 31;
                if ((code & 7) == IT_END) break;
                for (int hh = 0; hh < 2; hh++) {
                    if (hh) mbar_wait(bar_o, 1);
                    asm volatile("cp.async.bulk.tensor.3d.global.shared::cta.bulk_group [%0, {%2, %3, %4}], [%1];\n"
                                 "cp.async.bulk.commit_group;\ncp.async.bulk.wait_group.read 0;"
                                 ::"l"(&P.mo2), "r"(g.st + B_OST), "r"(0), "r"(blk * 128), "r"(idx * 4 + hh * 2) : "memory");
                    mbar_arrive(bar_f);
                }
                asm volatile("cp.async.bulk.wait_group 0;\nfence.acq_rel.gpu;\nred.relaxed.gpu.global.add.u32 [%0], 1;"
                             ::"l"(g_flag + 64 + blk) : "memory");
            }
        }
    } else {
        asm volatile("setmaxnreg.inc.sync.aligned.u32 232;");
        const int cw = wg - 1, ww = __shfl_sync(~0u, (threadIdx.x >> 5) & 3, 0), lane = threadIdx.x & 31;
        uint32_t round = 0;
#pragma unroll 1
        for (int n = 0;; n++) {
            mbar_wait_u(bar_item + (n & 1) * 8, (n >> 1) & 1);
            const int code = __shfl_sync(~0u, lds32(slot + (n & 1) * 4), 0);
            const int type = code & 7, blk = (code >> 3) & 15, idx = (code >> 7) & 31;
#define TLB(slot_)
            if (type == IT_END) {
                mbar_wait_u(bar_f, 1);
                if (threadIdx.x == 128) sts32(slot_o, IT_END);
                __syncwarp();
                mbar_arrive_one(bar_o, lane);
                break;
            }
            TLB(0);
            if (type == IT_QA) {
                uint32_t q[64];
                {
                    float acc[128];
                    gemm_mainloop<128, 256, 1>(acc, g, cw, 4, round);
#pragma unroll
                    for (int i = 0; i < 64; i++) q[i] = pack2(acc[2 * i], acc[2 * i + 1]);
                }
                if (threadIdx.x == 128) sts32(slot_o, code);
                TLB(2);
#pragma unroll
                for (int hh = 0; hh < 2; hh++) {
                    const uint32_t st = g.st + (2 * hh + cw) * STAGE_BYTES, ost = g.st + B_OST + (cw * 4 + ww) * 2048;
                    mbar_wait_u(g.full + 16 * hh, round & 1);
                    mbar_wait_u(g.full + 16 * hh + 8, round & 1);
                    if (hh == 0) { TLB(3); }
                    if (ww & 1) attend<1>(q + 32 * hh, st + (ww >> 1) * 4096, st + 32768 + (ww >> 1) * 1024, ost, bar_f, hh ^ 1, lane);
                    else attend<0>(q + 32 * hh, st + (ww >> 1) * 4096, st + 32768 + (ww >> 1) * 1024, ost, bar_f, hh ^ 1, lane);
                    mbar_arrive_one(bar_o, lane);
                    mbar_arrive_one(g.empty + 16 * hh, lane);
                    mbar_arrive_one(g.empty + 16 * hh + 8, lane);
                }
                round++;
            } else {
                bf16* dst = out + (size_t)(blk * 128 + cw * 64 + ww * 16 + (lane >> 2)) * 2048 + (lane & 3) * 8;
                if (type == IT_W256) wo_item<128, 256, 1>(g, cw, round, dst + idx * 256, lane & 3);
                else if (type == IT_W128) wo_item<128, 128, 1>(g, cw, round, dst + idx * 128, lane & 3);
                else if (type == IT_W64) wo_item<128, 64, 2>(g, cw, round, dst + idx * 64, lane & 3);
                else wo_item<64, 64, 2>(g, cw, round, dst + (size_t)(idx >> 4) * 64 * 2048 + (idx & 15) * 64, lane & 3);
            }
            TLB(1);
        }
    }
}

#define TCL 6
__global__ void __cluster_dims__(TCL, 1, 1) __launch_bounds__(384, 1)
k_tail(const __grid_constant__ CUtensorMap mo, const __grid_constant__ CUtensorMap mwo2, bf16* __restrict__ out) {
    extern __shared__ __align__(1024) uint8_t smem_gemm[];
    const uint32_t bar_s = smem_u32(smem_gemm) + NSTAGE * STAGE_BYTES + 128;
    if (threadIdx.x == 0) { TL(4, 0); mbar_init(bar_s, 1); mbar_expect_tx(bar_s, 32768); }
    GemmSmem g = gemm_setup(smem_gemm, 8);
    asm volatile("barrier.cluster.arrive.relaxed.aligned;" ::: "memory");
    const int half = blockIdx.x & 1, cl = blockIdx.x / 6, peer = TCL == 6 ? (blockIdx.x - 6 * cl) ^ 1 : half ^ 1;
    const int blk = TCL == 6 ? NBT + (cl >> 3) * 3 + (peer >> 1) : NBT + (blockIdx.x >> 4), idx = TCL == 6 ? cl & 7 : (blockIdx.x >> 1) & 7;
    const int wg = __shfl_sync(~0u, threadIdx.x >> 7, 0);
    if (wg == 0) {
        if (threadIdx.x == 0) {
            wait_flag(g_flag + 64 + blk, 16);
            asm volatile("fence.proxy.async.global;" ::: "memory");
            for (int k = 0; k < 32; k++) {
                const int s = k & 3;
                const uint32_t st = g.st + s * STAGE_BYTES, fb = g.full + 8 * s;
                mbar_wait(g.empty + 8 * s, ((k >> 2) & 1) ^ 1);
                mbar_expect_tx(fb, 32768);
                tma2d(st, &mo, (half * 32 + k) * 64, blk * 128, fb);
                tma3d(st + 16384, &mwo2, 0, (half * 32 + k) * 64, idx * 2, fb);
            }
        }
        __syncwarp();
        asm volatile("barrier.cluster.wait.aligned;" ::: "memory");
    } else {
        const int cw = wg - 1, lane = threadIdx.x & 31, t = lane & 3;
        float acc[64];
        uint32_t round = 0;
        gemm_mainloop<128, 128, 1>(acc, g, cw, 8, round);
        asm volatile("barrier.cluster.wait.aligned;" ::: "memory");
        const uint32_t xa = g.st + B_OST + (threadIdx.x & 127) * 16;
        if (cw != half) {
            uint32_t ra, rb;
            asm("mapa.shared::cluster.u32 %0, %1, %2;" : "=r"(ra) : "r"(xa), "r"(peer));
            asm("mapa.shared::cluster.u32 %0, %1, %2;" : "=r"(rb) : "r"(bar_s), "r"(peer));
#pragma unroll
            for (int i = 0; i < 16; i++)
                asm volatile("st.async.weak.shared::cluster.mbarrier::complete_tx::bytes.v4.f32 [%0], {%1,%2,%3,%4}, [%5];"
                             ::"r"(ra + i * 2048), "f"(acc[4 * i]), "f"(acc[4 * i + 1]), "f"(acc[4 * i + 2]), "f"(acc[4 * i + 3]), "r"(rb) : "memory");
        } else {
            mbar_wait_u(bar_s, 0);
#pragma unroll
            for (int i = 0; i < 16; i++) {
                const float4 v = lds128f(xa + i * 2048);
                acc[4 * i] += v.x; acc[4 * i + 1] += v.y; acc[4 * i + 2] += v.z; acc[4 * i + 3] += v.w;
            }
            store_tile<128>(acc, out + (size_t)(blk * 128 + cw * 64 + ((threadIdx.x >> 5) & 3) * 16 + (lane >> 2)) * 2048 + idx * 128 + t * 8, t);
            if ((threadIdx.x & 127) == 0) TL(4, 1);
        }
    }
    asm volatile("barrier.cluster.arrive.relaxed.aligned;\nbarrier.cluster.wait.aligned;" ::: "memory");
}

typedef CUresult (*EncodeFn)(CUtensorMap*, CUtensorMapDataType, cuuint32_t, void*, const cuuint64_t*, const cuuint64_t*,
                             const cuuint32_t*, const cuuint32_t*, CUtensorMapInterleave, CUtensorMapSwizzle,
                             CUtensorMapL2promotion, CUtensorMapFloatOOBfill);

static void map2d(EncodeFn enc, CUtensorMap* m, const void* p, int rows, int cols, int box_rows) {
    cuuint64_t dim[2] = {(cuuint64_t)cols, (cuuint64_t)rows}, str[1] = {(cuuint64_t)cols * 2};
    cuuint32_t box[2] = {64, (cuuint32_t)box_rows}, es[2] = {1, 1};
    enc(m, CU_TENSOR_MAP_DATA_TYPE_BFLOAT16, 2, (void*)p, dim, str, box, es, CU_TENSOR_MAP_INTERLEAVE_NONE,
        CU_TENSOR_MAP_SWIZZLE_128B, CU_TENSOR_MAP_L2_PROMOTION_L2_256B, CU_TENSOR_MAP_FLOAT_OOB_FILL_NONE);
}
static void map3d(EncodeFn enc, CUtensorMap* m, const void* p, int rows, int cols, int box_rows, int nblk) {
    cuuint64_t dim[3] = {64, (cuuint64_t)rows, (cuuint64_t)cols / 64}, str[2] = {(cuuint64_t)cols * 2, 128};
    cuuint32_t box[3] = {64, (cuuint32_t)box_rows, (cuuint32_t)nblk}, es[3] = {1, 1, 1};
    enc(m, CU_TENSOR_MAP_DATA_TYPE_BFLOAT16, 3, (void*)p, dim, str, box, es, CU_TENSOR_MAP_INTERLEAVE_NONE,
        CU_TENSOR_MAP_SWIZZLE_128B, CU_TENSOR_MAP_L2_PROMOTION_L2_256B, CU_TENSOR_MAP_FLOAT_OOB_FILL_NONE);
}

#define USE_PDL 1

extern "C" void kernel_launch(void* const* d_in, const int* in_sizes, int n_in, void* d_out, int out_size) {
    const bf16 *x = (const bf16*)d_in[0], *mem0 = (const bf16*)d_in[1], *Wq = (const bf16*)d_in[2], *Wk = (const bf16*)d_in[3];
    const bf16 *Wv = (const bf16*)d_in[4], *Wo = (const bf16*)d_in[5];
    const bf16 *u = (const bf16*)d_in[7], *Are = (const bf16*)d_in[8], *Aim = (const bf16*)d_in[9], *Bre = (const bf16*)d_in[10];
    const bf16 *Bim = (const bf16*)d_in[11], *Cre = (const bf16*)d_in[12], *Cim = (const bf16*)d_in[13];
    const bf16 *logdt = (const bf16*)d_in[14], *Dsk = (const bf16*)d_in[15];
    bf16* out = (bf16*)d_out;

    void* fn = nullptr;
    cudaDriverEntryPointQueryResult qr;
    cudaGetDriverEntryPoint("cuTensorMapEncodeTiled", &fn, cudaEnableDefault, &qr);
    EncodeFn enc = (EncodeFn)fn;
    void *kv, *kvm, *o;
    cudaGetSymbolAddress(&kv, g_kv);
    cudaGetSymbolAddress(&kvm, g_kvm);
    cudaGetSymbolAddress(&o, g_o);
    CUtensorMap mwk, mwv, mkv2;
    BgParams P;
    map2d(enc, &P.mx, x, SEQ, DM, 128);
    map2d(enc, &P.mo, o, SEQ, HD, 128);
    map3d(enc, &P.mo2, o, SEQ, HD, 128, 2);
    map3d(enc, &P.mo2s, o, SEQ, HD, 64, 2);
    map3d(enc, &P.mwq, Wq, DM, HD, 64, 4);
    map3d(enc, &mwk, Wk, DM, HD, 64, 4);
    map3d(enc, &mwv, Wv, DM, HD, 64, 4);
    map3d(enc, &P.mwo4, Wo, HD, DM, 64, 4);
    map3d(enc, &P.mwo2, Wo, HD, DM, 64, 2);
    map3d(enc, &P.mwo1, Wo, HD, DM, 128, 1);
    map3d(enc, &mkv2, kv, SEQ, 8192, 32, 2);
    map3d(enc, &P.mkv, kv, SEQ, 8192, 64, 2);
    map3d(enc, &P.mkvm, kvm, NSEG * 8, 8192, 16, 2);
    cudaFuncSetAttribute(k_kv, cudaFuncAttributeMaxDynamicSharedMemorySize, GEMM_SMEM);
    cudaFuncSetAttribute(k_bg, cudaFuncAttributeMaxDynamicSharedMemorySize, BG_SMEM);
    cudaFuncSetAttribute(k_tail, cudaFuncAttributeMaxDynamicSharedMemorySize, BG_SMEM);
    cudaFuncSetAttribute(k_chain, cudaFuncAttributeMaxDynamicSharedMemorySize, CHAIN_SMEM);
    cudaFuncSetAttribute(k_s4, cudaFuncAttributeMaxDynamicSharedMemorySize, S4_SMEM);

    cudaStream_t st = cudaStreamPerThread;
    cudaLaunchAttribute pdl[1], cls[1];
    pdl[0].id = cudaLaunchAttributeProgrammaticStreamSerialization;
    pdl[0].val.programmaticStreamSerializationAllowed = 1;
    cls[0].id = cudaLaunchAttributeClusterDimension;
    cls[0].val.clusterDim.x = CLS; cls[0].val.clusterDim.y = 1; cls[0].val.clusterDim.z = 1;
    cudaLaunchConfig_t cfg = {};
    cfg.stream = st; cfg.attrs = cls; cfg.numAttrs = 1;
    cfg.gridDim = dim3(96); cfg.blockDim = dim3(384); cfg.dynamicSmemBytes = GEMM_SMEM;
    cudaLaunchKernelEx(&cfg, k_kv, P.mx, mwk, mwv, Wq, Wk, Wo, 0);
    cfg.attrs = pdl; cfg.numAttrs = 1;
    cfg.gridDim = dim3(36);
    cudaLaunchKernelEx(&cfg, k_kv, P.mx, mwk, mwv, Wq, Wk, Wo, 96);
    cfg.gridDim = dim3(96); cfg.blockDim = dim3(256); cfg.dynamicSmemBytes = CHAIN_SMEM;
    cudaLaunchKernelEx(&cfg, k_chain, mem0, Wq, Wk, Wv, Wo, mkv2);
    cfg.numAttrs = USE_PDL;
    cfg.gridDim = dim3(36); cfg.blockDim = dim3(512); cfg.dynamicSmemBytes = S4_SMEM;
    cudaLaunchKernelEx(&cfg, k_s4, u, Are, Aim, Bre, Bim, Cre, Cim, logdt, Dsk, out);
    cfg.gridDim = dim3(36); cfg.blockDim = dim3(384); cfg.dynamicSmemBytes = BG_SMEM;
    cudaLaunchKernelEx(&cfg, k_bg, P, out);
    cfg.gridDim = dim3((15 - NBT) * 16);
    cudaLaunchKernelEx(&cfg, k_tail, P.mo, P.mwo2, out);
}
```

```cpp
#include <cuda_runtime.h>
#include <cuda_bf16.h>
#include <cuda.h>
#include <stdint.h>

typedef __nv_bfloat16 bf16;

constexpr int SEQ = 2048, DM = 1024, HD = 4096, NSEG = 64;

__device__ __align__(1024) bf16 g_kv[(size_t)SEQ * 8192];
__device__ __align__(1024) bf16 g_kvm[(size_t)NSEG * 8 * 8192];
__device__ __align__(1024) bf16 g_o[(size_t)SEQ * HD];
constexpr int XPAIRS = 128 + NSEG * 4;
__device__ __align__(8192) uint2 g_x[XPAIRS * 1024];
__device__ uint32_t g_home[XPAIRS];
__device__ uint32_t g_side[256];
__device__ __align__(1024) uint32_t g_flag[256];

#define TL(kern, slot)

__device__ __forceinline__ uint32_t smem_u32(const void* p) { return (uint32_t)__cvta_generic_to_shared(p); }
__device__ __forceinline__ void mbar_init(uint32_t bar, uint32_t cnt) {
    asm volatile("mbarrier.init.shared::cta.b64 [%0], %1;" ::"r"(bar), "r"(cnt) : "memory");
}
__device__ __forceinline__ void mbar_expect_tx(uint32_t bar, uint32_t bytes) {
    asm volatile("mbarrier.arrive.expect_tx.shared::cta.b64 _, [%0], %1;" ::"r"(bar), "r"(bytes) : "memory");
}
__device__ __forceinline__ void mbar_arrive(uint32_t bar) {
    asm volatile("mbarrier.arrive.shared::cta.b64 _, [%0];" ::"r"(bar) : "memory");
}
__device__ __forceinline__ bool mbar_try(uint32_t bar, uint32_t parity) {
    uint32_t ok;
    asm volatile("{\n.reg .pred p;\nmbarrier.try_wait.parity.shared::cta.b64 p, [%1], %2;\nselp.u32 %0, 1, 0, p;\n}"
                 : "=r"(ok) : "r"(bar), "r"(parity) : "memory");
    return ok;
}
constexpr int SPIN_LIMIT = 1 << 20;
__device__ __forceinline__ void mbar_wait(uint32_t bar, uint32_t parity) {
    int n = 0;
    while (!mbar_try(bar, parity)) { if (++n > SPIN_LIMIT) __trap(); }
}
__device__ __forceinline__ void mbar_wait_u(uint32_t bar, uint32_t parity) {
    asm volatile("{\n.reg .pred p;\n.reg .u32 n;\n"
                 "mbarrier.try_wait.parity.shared::cta.b64 p, [%0], %1;\n@p bra.uni DONE;\nmov.u32 n, 0;\n"
                 "AGAIN:\nmbarrier.try_wait.parity.shared::cta.b64 p, [%0], %1;\n@p bra.uni DONE;\n"
                 "add.u32 n, n, 1;\nsetp.lt.u32 p, n, 0x100000;\n@p bra.uni AGAIN;\ntrap;\nDONE:\n}"
                 ::"r"(bar), "r"(parity) : "memory");
}
__device__ __forceinline__ void tma2d(uint32_t dst, const CUtensorMap* m, int c0, int c1, uint32_t bar) {
    asm volatile("cp.async.bulk.tensor.2d.shared::cluster.global.mbarrier::complete_tx::bytes [%0], [%1, {%3, %4}], [%2];"
                 ::"r"(dst), "l"(m), "r"(bar), "r"(c0), "r"(c1) : "memory");
}
__device__ __forceinline__ void tma3d(uint32_t dst, const CUtensorMap* m, int c0, int c1, int c2, uint32_t bar) {
    asm volatile("cp.async.bulk.tensor.3d.shared::cluster.global.mbarrier::complete_tx::bytes [%0], [%1, {%3, %4, %5}], [%2];"
                 ::"r"(dst), "l"(m), "r"(bar), "r"(c0), "r"(c1), "r"(c2) : "memory");
}
__device__ __forceinline__ uint32_t pack2(float lo, float hi) {
    uint32_t r;
    asm("cvt.rn.bf16x2.f32 %0, %1, %2;" : "=r"(r) : "f"(hi), "f"(lo));
    return r;
}
__device__ __forceinline__ float bf_lo(uint32_t v) { return __uint_as_float(v << 16); }
__device__ __forceinline__ float bf_hi(uint32_t v) { return __uint_as_float(v & 0xffff0000u); }
__device__ __forceinline__ float bf_round(float x) { return bf_lo(pack2(x, 0.f)); }
__device__ __forceinline__ float ex2(float x) { float y; asm("ex2.approx.ftz.f32 %0, %1;" : "=f"(y) : "f"(x)); return y; }
__device__ __forceinline__ void mma16816(float (&c)[4], uint32_t a0, uint32_t a1, uint32_t a2, uint32_t a3, uint32_t b0, uint32_t b1) {
    asm volatile("mma.sync.aligned.m16n8k16.row.col.f32.bf16.bf16.f32 {%0,%1,%2,%3}, {%4,%5,%6,%7}, {%8,%9}, {%0,%1,%2,%3};"
                 : "+f"(c[0]), "+f"(c[1]), "+f"(c[2]), "+f"(c[3]) : "r"(a0), "r"(a1), "r"(a2), "r"(a3), "r"(b0), "r"(b1));
}
__device__ __forceinline__ void mma1688(float (&c)[4], uint32_t a0, uint32_t a1, uint32_t b0) {
    asm volatile("mma.sync.aligned.m16n8k8.row.col.f32.bf16.bf16.f32 {%0,%1,%2,%3}, {%4,%5}, {%6}, {%0,%1,%2,%3};"
                 : "+f"(c[0]), "+f"(c[1]), "+f"(c[2]), "+f"(c[3]) : "r"(a0), "r"(a1), "r"(b0));
}
__device__ __forceinline__ void ldsm4(uint32_t (&r)[4], uint32_t a) {
    asm volatile("ldmatrix.sync.aligned.m8n8.x4.shared.b16 {%0,%1,%2,%3}, [%4];"
                 : "=r"(r[0]), "=r"(r[1]), "=r"(r[2]), "=r"(r[3]) : "r"(a) : "memory");
}
__device__ __forceinline__ void ldsm4t(uint32_t (&r)[4], uint32_t a) {
    asm volatile("ldmatrix.sync.aligned.m8n8.x4.trans.shared.b16 {%0,%1,%2,%3}, [%4];"
                 : "=r"(r[0]), "=r"(r[1]), "=r"(r[2]), "=r"(r[3]) : "r"(a) : "memory");
}
__device__ __forceinline__ void ldsm2t(uint32_t& r0, uint32_t& r1, uint32_t a) {
    asm volatile("ldmatrix.sync.aligned.m8n8.x2.trans.shared.b16 {%0,%1}, [%2];" : "=r"(r0), "=r"(r1) : "r"(a) : "memory");
}
__device__ __forceinline__ void stsm4t(uint32_t a, uint32_t r0, uint32_t r1, uint32_t r2, uint32_t r3) {
    asm volatile("stmatrix.sync.aligned.m8n8.x4.trans.shared.b16 [%0], {%1,%2,%3,%4};"
                 ::"r"(a), "r"(r0), "r"(r1), "r"(r2), "r"(r3) : "memory");
}
__device__ __forceinline__ void lds128(uint32_t (&r)[4], uint32_t a) {
    asm volatile("ld.shared.v4.u32 {%0,%1,%2,%3}, [%4];" : "=r"(r[0]), "=r"(r[1]), "=r"(r[2]), "=r"(r[3]) : "r"(a) : "memory");
}
__device__ __forceinline__ float4 lds128f(uint32_t a) {
    float4 v;
    asm volatile("ld.shared.v4.f32 {%0,%1,%2,%3}, [%4];" : "=f"(v.x), "=f"(v.y), "=f"(v.z), "=f"(v.w) : "r"(a) : "memory");
    return v;
}
__device__ __forceinline__ float2 lds64f(uint32_t a) {
    float2 v;
    asm volatile("ld.shared.v2.f32 {%0,%1}, [%2];" : "=f"(v.x), "=f"(v.y) : "r"(a) : "memory");
    return v;
}
__device__ __forceinline__ uint32_t lds32(uint32_t a) {
    uint32_t v;
    asm volatile("ld.shared.u32 %0, [%1];" : "=r"(v) : "r"(a) : "memory");
    return v;
}
__device__ __forceinline__ void sts128(uint32_t a, uint32_t r0, uint32_t r1, uint32_t r2, uint32_t r3) {
    asm volatile("st.shared.v4.u32 [%0], {%1,%2,%3,%4};" ::"r"(a), "r"(r0), "r"(r1), "r"(r2), "r"(r3) : "memory");
}
__device__ __forceinline__ void sts128f(uint32_t a, float r0, float r1, float r2, float r3) {
    asm volatile("st.shared.v4.f32 [%0], {%1,%2,%3,%4};" ::"r"(a), "f"(r0), "f"(r1), "f"(r2), "f"(r3) : "memory");
}
__device__ __forceinline__ void sts64(uint32_t a, uint32_t r0, uint32_t r1) {
    asm volatile("st.shared.v2.u32 [%0], {%1,%2};" ::"r"(a), "r"(r0), "r"(r1) : "memory");
}
__device__ __forceinline__ void sts64f(uint32_t a, float r0, float r1) {
    asm volatile("st.shared.v2.f32 [%0], {%1,%2};" ::"r"(a), "f"(r0), "f"(r1) : "memory");
}
__device__ __forceinline__ void sts32f(uint32_t a, float r0) {
    asm volatile("st.shared.f32 [%0], %1;" ::"r"(a), "f"(r0) : "memory");
}
__device__ __forceinline__ uint2 ld_rlx64(const uint2* p) {
    uint2 v;
    asm volatile("{\n.reg .b64 t;\nld.relaxed.gpu.global.b64 t, [%2];\nmov.b64 {%0,%1}, t;\n}" : "=r"(v.x), "=r"(v.y) : "l"(p) : "memory");
    return v;
}
__device__ __forceinline__ void st_rlx64(uint2* p, uint32_t x, uint32_t y) {
    asm volatile("{\n.reg .b64 t;\nmov.b64 t, {%1,%2};\nst.relaxed.gpu.global.b64 [%0], t;\n}" ::"l"(p), "r"(x), "r"(y) : "memory");
}
__device__ __forceinline__ uint32_t ld_acq32(const uint32_t* p) {
    uint32_t v;
    asm volatile("ld.acquire.gpu.global.u32 %0, [%1];" : "=r"(v) : "l"(p) : "memory");
    return v;
}
__device__ __forceinline__ void wait_flag(const uint32_t* p, uint32_t need) {
    int n = 0;
    while (ld_acq32(p) < need) { __nanosleep(200); if (++n > SPIN_LIMIT) __trap(); }
}
__device__ __forceinline__ void bar_sync(int id, int n) { asm volatile("bar.sync %0, %1;" ::"r"(id), "r"(n) : "memory"); }
__device__ __forceinline__ void wg_fence() { asm volatile("wgmma.fence.sync.aligned;" ::: "memory"); }
__device__ __forceinline__ void wg_commit() { asm volatile("wgmma.commit_group.sync.aligned;" ::: "memory"); }
template <int N> __device__ __forceinline__ void wg_wait() { asm volatile("wgmma.wait_group.sync.aligned %0;" ::"n"(N) : "memory"); }
__device__ __forceinline__ uint64_t desc_sw128(uint32_t addr, uint32_t lbo, uint32_t sbo) {
    return (uint64_t)((addr & 0x3FFFF) >> 4) | ((uint64_t)(lbo >> 4) << 16) | ((uint64_t)(sbo >> 4) << 32) | (1ull << 62);
}
__device__ __forceinline__ void quad_transpose(uint32_t& r0, uint32_t& r1, uint32_t& r2, uint32_t& r3, int t) {
    const bool o = t & 1, h = t & 2;
    uint32_t s0 = __shfl_xor_sync(~0u, o ? r0 : r1, 1), s1 = __shfl_xor_sync(~0u, o ? r2 : r3, 1);
    uint32_t a0 = o ? s0 : r0, a1 = o ? r1 : s0, a2 = o ? s1 : r2, a3 = o ? r3 : s1;
    s0 = __shfl_xor_sync(~0u, h ? a0 : a2, 2); s1 = __shfl_xor_sync(~0u, h ? a1 : a3, 2);
    r0 = h ? s0 : a0; r1 = h ? s1 : a1; r2 = h ? a2 : s0; r3 = h ? a3 : s1;
}

__device__ __forceinline__ void wgmma_n256(float (&d)[128], uint64_t da, uint64_t db, int sd) {
    asm volatile("{\n.reg .pred p;\nsetp.ne.b32 p, %130, 0;\n"
        "wgmma.mma_async.sync.aligned.m64n256k16.f32.bf16.bf16 "
        "{%0,%1,%2,%3,%4,%5,%6,%7,%8,%9,%10,%11,%12,%13,%14,%15,"
        "%16,%17,%18,%19,%20,%21,%22,%23,%24,%25,%26,%27,%28,%29,%30,%31,"
        "%32,%33,%34,%35,%36,%37,%38,%39,%40,%41,%42,%43,%44,%45,%46,%47,"
        "%48,%49,%50,%51,%52,%53,%54,%55,%56,%57,%58,%59,%60,%61,%62,%63,"
        "%64,%65,%66,%67,%68,%69,%70,%71,%72,%73,%74,%75,%76,%77,%78,%79,"
        "%80,%81,%82,%83,%84,%85,%86,%87,%88,%89,%90,%91,%92,%93,%94,%95,"
        "%96,%97,%98,%99,%100,%101,%102,%103,%104,%105,%106,%107,%108,%109,%110,%111,"
        "%112,%113,%114,%115,%116,%117,%118,%119,%120,%121,%122,%123,%124,%125,%126,%127}, %128, %129, p, 1, 1, 0, 1;\n}\n"
        : "+f"(d[0]), "+f"(d[1]), "+f"(d[2]), "+f"(d[3]), "+f"(d[4]), "+f"(d[5]), "+f"(d[6]), "+f"(d[7]),
          "+f"(d[8]), "+f"(d[9]), "+f"(d[10]), "+f"(d[11]), "+f"(d[12]), "+f"(d[13]), "+f"(d[14]), "+f"(d[15]),
          "+f"(d[16]), "+f"(d[17]), "+f"(d[18]), "+f"(d[19]), "+f"(d[20]), "+f"(d[21]), "+f"(d[22]), "+f"(d[23]),
          "+f"(d[24]), "+f"(d[25]), "+f"(d[26]), "+f"(d[27]), "+f"(d[28]), "+f"(d[29]), "+f"(d[30]), "+f"(d[31]),
          "+f"(d[32]), "+f"(d[33]), "+f"(d[34]), "+f"(d[35]), "+f"(d[36]), "+f"(d[37]), "+f"(d[38]), "+f"(d[39]),
          "+f"(d[40]), "+f"(d[41]), "+f"(d[42]), "+f"(d[43]), "+f"(d[44]), "+f"(d[45]), "+f"(d[46]), "+f"(d[47]),
          "+f"(d[48]), "+f"(d[49]), "+f"(d[50]), "+f"(d[51]), "+f"(d[52]), "+f"(d[53]), "+f"(d[54]), "+f"(d[55]),
          "+f"(d[56]), "+f"(d[57]), "+f"(d[58]), "+f"(d[59]), "+f"(d[60]), "+f"(d[61]), "+f"(d[62]), "+f"(d[63]),
          "+f"(d[64]), "+f"(d[65]), "+f"(d[66]), "+f"(d[67]), "+f"(d[68]), "+f"(d[69]), "+f"(d[70]), "+f"(d[71]),
          "+f"(d[72]), "+f"(d[73]), "+f"(d[74]), "+f"(d[75]), "+f"(d[76]), "+f"(d[77]), "+f"(d[78]), "+f"(d[79]),
          "+f"(d[80]), "+f"(d[81]), "+f"(d[82]), "+f"(d[83]), "+f"(d[84]), "+f"(d[85]), "+f"(d[86]), "+f"(d[87]),
          "+f"(d[88]), "+f"(d[89]), "+f"(d[90]), "+f"(d[91]), "+f"(d[92]), "+f"(d[93]), "+f"(d[94]), "+f"(d[95]),
          "+f"(d[96]), "+f"(d[97]), "+f"(d[98]), "+f"(d[99]), "+f"(d[100]), "+f"(d[101]), "+f"(d[102]), "+f"(d[103]),
          "+f"(d[104]), "+f"(d[105]), "+f"(d[106]), "+f"(d[107]), "+f"(d[108]), "+f"(d[109]), "+f"(d[110]), "+f"(d[111]),
          "+f"(d[112]), "+f"(d[113]), "+f"(d[114]), "+f"(d[115]), "+f"(d[116]), "+f"(d[117]), "+f"(d[118]), "+f"(d[119]),
          "+f"(d[120]), "+f"(d[121]), "+f"(d[122]), "+f"(d[123]), "+f"(d[124]), "+f"(d[125]), "+f"(d[126]), "+f"(d[127])
        : "l"(da), "l"(db), "r"(sd));
}

__device__ __forceinline__ void wgmma_n128(float (&d)[64], uint64_t da, uint64_t db, int sd) {
    asm volatile("{\n.reg .pred p;\nsetp.ne.b32 p, %66, 0;\n"
        "wgmma.mma_async.sync.aligned.m64n128k16.f32.bf16.bf16 "
        "{%0,%1,%2,%3,%4,%5,%6,%7,%8,%9,%10,%11,%12,%13,%14,%15,"
        "%16,%17,%18,%19,%20,%21,%22,%23,%24,%25,%26,%27,%28,%29,%30,%31,"
        "%32,%33,%34,%35,%36,%37,%38,%39,%40,%41,%42,%43,%44,%45,%46,%47,"
        "%48,%49,%50,%51,%52,%53,%54,%55,%56,%57,%58,%59,%60,%61,%62,%63}, %64, %65, p, 1, 1, 0, 1;\n}\n"
        : "+f"(d[0]), "+f"(d[1]), "+f"(d[2]), "+f"(d[3]), "+f"(d[4]), "+f"(d[5]), "+f"(d[6]), "+f"(d[7]),
          "+f"(d[8]), "+f"(d[9]), "+f"(d[10]), "+f"(d[11]), "+f"(d[12]), "+f"(d[13]), "+f"(d[14]), "+f"(d[15]),
          "+f"(d[16]), "+f"(d[17]), "+f"(d[18]), "+f"(d[19]), "+f"(d[20]), "+f"(d[21]), "+f"(d[22]), "+f"(d[23]),
          "+f"(d[24]), "+f"(d[25]), "+f"(d[26]), "+f"(d[27]), "+f"(d[28]), "+f"(d[29]), "+f"(d[30]), "+f"(d[31]),
          "+f"(d[32]), "+f"(d[33]), "+f"(d[34]), "+f"(d[35]), "+f"(d[36]), "+f"(d[37]), "+f"(d[38]), "+f"(d[39]),
          "+f"(d[40]), "+f"(d[41]), "+f"(d[42]), "+f"(d[43]), "+f"(d[44]), "+f"(d[45]), "+f"(d[46]), "+f"(d[47]),
          "+f"(d[48]), "+f"(d[49]), "+f"(d[50]), "+f"(d[51]), "+f"(d[52]), "+f"(d[53]), "+f"(d[54]), "+f"(d[55]),
          "+f"(d[56]), "+f"(d[57]), "+f"(d[58]), "+f"(d[59]), "+f"(d[60]), "+f"(d[61]), "+f"(d[62]), "+f"(d[63])
        : "l"(da), "l"(db), "r"(sd));
}

__device__ __forceinline__ void wgmma_n64(float (&d)[32], uint64_t da, uint64_t db, int sd) {
    asm volatile("{\n.reg .pred p;\nsetp.ne.b32 p, %34, 0;\n"
        "wgmma.mma_async.sync.aligned.m64n64k16.f32.bf16.bf16 "
        "{%0,%1,%2,%3,%4,%5,%6,%7,%8,%9,%10,%11,%12,%13,%14,%15,"
        "%16,%17,%18,%19,%20,%21,%22,%23,%24,%25,%26,%27,%28,%29,%30,%31}, %32, %33, p, 1, 1, 0, 1;\n}\n"
        : "+f"(d[0]), "+f"(d[1]), "+f"(d[2]), "+f"(d[3]), "+f"(d[4]), "+f"(d[5]), "+f"(d[6]), "+f"(d[7]),
          "+f"(d[8]), "+f"(d[9]), "+f"(d[10]), "+f"(d[11]), "+f"(d[12]), "+f"(d[13]), "+f"(d[14]), "+f"(d[15]),
          "+f"(d[16]), "+f"(d[17]), "+f"(d[18]), "+f"(d[19]), "+f"(d[20]), "+f"(d[21]), "+f"(d[22]), "+f"(d[23]),
          "+f"(d[24]), "+f"(d[25]), "+f"(d[26]), "+f"(d[27]), "+f"(d[28]), "+f"(d[29]), "+f"(d[30]), "+f"(d[31])
        : "l"(da), "l"(db), "r"(sd));
}

constexpr int STAGE_BYTES = 49152, NSTAGE = 4;
constexpr int GEMM_SMEM = NSTAGE * STAGE_BYTES + 128;

struct GemmSmem { uint32_t st, full, empty; };
__device__ __forceinline__ GemmSmem gemm_setup(uint8_t* raw, int releases) {
    GemmSmem g;
    g.st = smem_u32(raw);
    if (g.st & 1023) __trap();
    g.full = g.st + NSTAGE * STAGE_BYTES; g.empty = g.full + 64;
    if (threadIdx.x == 0) {
        for (int s = 0; s < NSTAGE; s++) { mbar_init(g.full + 8 * s, 1); mbar_init(g.empty + 8 * s, releases); }
        asm volatile("fence.mbarrier_init.release.cluster;" ::: "memory");
        asm volatile("fence.proxy.async.shared::cta;" ::: "memory");
    }
    __syncthreads();
    return g;
}
__device__ __forceinline__ void mbar_arrive_one(uint32_t bar, uint32_t who) {
    asm volatile("{\n.reg .pred p;\nsetp.eq.u32 p, %1, 0;\n@p mbarrier.arrive.shared::cta.b64 _, [%0];\n}" ::"r"(bar), "r"(who) : "memory");
}
template <int BM, int BN, int KPS, typename ACC>
__device__ __forceinline__ void gemm_stage(ACC& acc, uint32_t stage, int wg, bool first) {
    const uint64_t da = desc_sw128(stage + wg * 8192, 16, 1024);
    const uint64_t db = desc_sw128(stage + KPS * BM * 128, 8192, 1024);
    wg_fence();
#pragma unroll
    for (int k = 0; k < 4 * KPS; k++) {
        const uint64_t a = da + (k >> 2) * (BM * 8) + (k & 3) * 2, b = db + k * 128;
        if constexpr (BN == 256) wgmma_n256(acc, a, b, first && k == 0 ? 0 : 1);
        else if constexpr (BN == 128) wgmma_n128(acc, a, b, first && k == 0 ? 0 : 1);
        else wgmma_n64(acc, a, b, first && k == 0 ? 0 : 1);
    }
    wg_commit();
}

__device__ __forceinline__ void kv_store_unit(const uint32_t (&pk)[64], int u, bf16* dst, int t) {
    const int G = (u >> 2) * 2 + (u & 1), hh = (u >> 1) & 1;
    uint32_t r0 = pk[(4 * G + 0) * 2 + hh], r1 = pk[(4 * G + 1) * 2 + hh], r2 = pk[(4 * G + 2) * 2 + hh], r3 = pk[(4 * G + 3) * 2 + hh];
    quad_transpose(r0, r1, r2, r3, t);
#define KVST ".cs"
    asm volatile("st.global" KVST ".v4.u32 [%0], {%1,%2,%3,%4};" ::"l"(dst + (size_t)hh * 8 * 8192 + G * 32), "r"(r0), "r"(r1), "r"(r2), "r"(r3) : "memory");
}

#define TLK(slot)
#define TLK2(slot)
__device__ __forceinline__ uint32_t near_page(int pair, int line) {
    uint32_t best[2] = {~0u, ~0u};
#pragma unroll 1
    for (int i = 0; i < 16; i++) {
        uint32_t t0, t1, v;
        asm volatile("mov.u32 %0, %%clock;" : "=r"(t0)::"memory");
        asm volatile("atom.relaxed.gpu.global.or.b32 %0, [%1], -1;" : "=r"(v) : "l"(g_x + pair * 1024 + (i & 1) * 512 + line * 16) : "memory");
        asm volatile("{\n.reg .pred p;\nsetp.ne.u32 p, %1, 0x12345;\nmov.u32 %0, -1;\n@p mov.u32 %0, %%clock;\n}" : "=r"(t1) : "r"(v) : "memory");
        if (i & 1) best[1] = min(best[1], t1 - t0); else best[0] = min(best[0], t1 - t0);
    }
    return best[1] < best[0];
}
__device__ __forceinline__ void map_pages(int c) {
    uint32_t smid;
    asm("mov.u32 %0, %%smid;" : "=r"(smid));
    const uint32_t side = near_page(0, c & 31);
    g_side[smid & 255] = side;
    for (int p = c; p < XPAIRS; p += 132) g_home[p] = near_page(p, 0) ^ side;
}

__global__ void __launch_bounds__(384, 1)
k_kv(const __grid_constant__ CUtensorMap mx, const __grid_constant__ CUtensorMap mwk, const __grid_constant__ CUtensorMap mwv,
     const bf16* __restrict__ Wq, const bf16* __restrict__ Wk, const bf16* __restrict__ Wo, int c0) {
    extern __shared__ __align__(1024) uint8_t smem_gemm[];
    const int c = c0 + blockIdx.x;
    if (c == 128) {
        if (threadIdx.x < 256) g_flag[threadIdx.x] = 0;
        __threadfence();
        __syncthreads();
    }
    asm volatile("griddepcontrol.launch_dependents;");
    if (threadIdx.x == 0) TLK(0);
    if (c >= 128) {
        const int i0 = (c - 128) * 384 + threadIdx.x;
        const uint4 ones = make_uint4(~0u, ~0u, ~0u, ~0u);
        if (threadIdx.x == 32) map_pages(c);
        for (int i = i0; i < XPAIRS * 512; i += 4 * 384) reinterpret_cast<uint4*>(g_x)[i] = ones;
        if (threadIdx.x == 0) TLK(1);
        asm volatile("griddepcontrol.wait;" ::: "memory");
        return;
    }
    GemmSmem g = gemm_setup(smem_gemm, 4);
    uint32_t rank, peer_empty;
    asm("mov.u32 %0, %%cluster_ctarank;" : "=r"(rank));
    asm("mapa.shared::cluster.u32 %0, %1, %2;" : "=r"(peer_empty) : "r"(g.empty), "r"(rank ^ 1));
    asm volatile("barrier.cluster.arrive.relaxed.aligned;\nbarrier.cluster.wait.aligned;" ::: "memory");
    auto release = [&](int s) {
        asm volatile("{\n.reg .pred p;\nsetp.eq.u32 p, %2, 0;\n@p mbarrier.arrive.relaxed.cta.shared::cta.b64 _, [%0];\n"
                     "@p mbarrier.arrive.relaxed.cluster.shared::cluster.b64 _, [%1];\n}"
                     ::"r"(g.empty + 8 * s), "r"(peer_empty + 8 * s), "r"(threadIdx.x & 127) : "memory");
    };
#define MW 4
    const int m0 = (c % MW) * 128, nb0 = c / MW;
    auto tile_m = [](int tile) { return (tile % (16 / MW)) * MW * 128; };
    auto tile_n = [](int tile) { return (tile / (16 / MW)) * (128 / MW); };
    const int wg = __shfl_sync(~0u, threadIdx.x >> 7, 0);
    if (wg == 0) {
        asm volatile("setmaxnreg.dec.sync.aligned.u32 40;");
        if (threadIdx.x == 0) {
            for (int it = 0; it < 64; it++) {
                const int s = it & 3, tile = it >> 4, kb = it & 15;
                mbar_wait(g.empty + 8 * s, ((it >> 2) & 1) ^ 1);
                mbar_expect_tx(g.full + 8 * s, STAGE_BYTES);
                const int nb = nb0 + tile_n(tile);
                tma2d(g.st + s * STAGE_BYTES, &mx, kb * 64, m0 + tile_m(tile), g.full + 8 * s);
                asm volatile("cp.async.bulk.tensor.3d.shared::cluster.global.mbarrier::complete_tx::bytes.multicast::cluster "
                             "[%0], [%1, {%3, %4, %5}], [%2], %6;"
                             ::"r"(g.st + s * STAGE_BYTES + 16384 + (c & 1) * 16384), "l"(nb < 16 ? &mwk : &mwv), "r"(g.full + 8 * s),
                               "r"(0), "r"(kb * 64), "r"((nb & 15) * 4 + (c & 1) * 2), "h"((uint16_t)(3u << (rank & ~1u))) : "memory");
#define PF0 32
#define PFN 32
#define PFB 4096
                const int pi = it - PF0;
                if (pi >= 0 && pi < PFN) {
                    const uint32_t o = (pi * 128 + c) * PFB;
                    const char* p = (const char*)(o < (8 << 20) ? Wo : o < (16 << 20) ? Wq : Wk) + (o & ((8 << 20) - 1));
                    asm volatile("cp.async.bulk.prefetch.L2.global [%0], %1;" ::"l"(p), "n"(PFB) : "memory");
                }
            }
        } else if (threadIdx.x == 32) map_pages(c);
    } else {
        asm volatile("setmaxnreg.inc.sync.aligned.u32 232;");
        const int cw = wg - 1, lane = threadIdx.x & 31, t = lane & 3;
        const int row = m0 + cw * 64 + ((threadIdx.x >> 5) & 3) * 16 + (lane >> 2);
        bf16* dst = g_kv + (size_t)row * 8192 + nb0 * 256 + t * 8;
        float acc[128];
        uint32_t pk[64];
#pragma unroll 1
        for (int tile = 0; tile < 4; tile++) {
#pragma unroll
            for (int kb = 0; kb < 16; kb++) {
                mbar_wait_u(g.full + 8 * (kb & 3), (kb >> 2) & 1);
                if (kb == 0 && tile == 0 && threadIdx.x == 128) TLK2(0);
                gemm_stage<128, 256, 1>(acc, g.st + (kb & 3) * STAGE_BYTES, cw, kb == 0);
                if (tile > 0) kv_store_unit(pk, kb, dst + (size_t)tile_m(tile - 1) * 8192 + tile_n(tile - 1) * 256, t);
                if (kb > 0) {
                    wg_wait<1>();
                    if (kb <= 12 || tile < 3) release((kb - 1) & 3);
                }
            }
            wg_wait<0>();
            if (threadIdx.x == 128) TLK2(tile + 1);
            if (tile < 3) release(3);
#pragma unroll
            for (int i = 0; i < 64; i++) pk[i] = pack2(acc[2 * i], acc[2 * i + 1]);
        }
        if (threadIdx.x == 128) TLK(2);
#pragma unroll
        for (int u = 0; u < 16; u++) kv_store_unit(pk, u, dst + (size_t)tile_m(3) * 8192 + tile_n(3) * 256, t);
        if (threadIdx.x == 128) TLK(1);
        asm volatile("griddepcontrol.wait;" ::: "memory");
    }
}

constexpr int NS1 = 31;
#define RB1 4
#define PFC 4
constexpr int C_W1 = 0;
constexpr int C_W2 = C_W1 + 8 * NS1 * 512;
constexpr int C_KV = C_W2 + 14 * 8 * 512;
constexpr int C_RED = C_KV + 16384;
constexpr int C_QKV = C_RED + 64 * 272;
constexpr int C_SC = C_RED;
constexpr int C_OB = C_SC + 2 * 8 * 52 * 4;
constexpr int C_BAR = C_QKV + 3 * 8 * 272;
__host__ __device__ constexpr int smem_idx(int ks, int j) {
    return ks == 0 ? j : ks < 3 ? (j < 4 ? 4 + 4 * ks + j : -1) : (j < 3 ? 7 + 3 * ks + j : -1);
}
constexpr int CHAIN_SMEM = C_BAR + 64;
#define TS(i)
#define TG(i)

#define DLY3 8
#define DLY1 2
#define DLY0 2
#define DLY1A 10
#define DLY0A DLY0
#define DLYW 3
template <int N> __device__ __forceinline__ uint32_t delayed(uint32_t x, int lane) {
#pragma unroll
    for (int i = 0; i < N; i++) asm volatile("shfl.sync.idx.b32 %0, %0, %1, 31, -1;" : "+r"(x) : "r"(lane) : "memory");
    return x;
}
__device__ __forceinline__ void lds128v(uint32_t (&r)[4], uint32_t a) {
    asm volatile("ld.volatile.shared.v4.u32 {%0,%1,%2,%3}, [%4];" : "=r"(r[0]), "=r"(r[1]), "=r"(r[2]), "=r"(r[3]) : "r"(a) : "memory");
}
__device__ __forceinline__ uint2 lds64(uint32_t a) {
    uint2 v;
    asm volatile("ld.shared.v2.u32 {%0,%1}, [%2];" : "=r"(v.x), "=r"(v.y) : "r"(a) : "memory");
    return v;
}
#define LDQ ".L1::no_allocate"
__device__ __forceinline__ uint4 ldw128(const void* p) {
    uint4 v;
    asm volatile("ld.global.nc" LDQ ".v4.u32 {%0,%1,%2,%3}, [%4];" : "=r"(v.x), "=r"(v.y), "=r"(v.z), "=r"(v.w) : "l"(p));
    return v;
}
#define P8_LD(i) "ld.relaxed.gpu.global.b64 d" #i ", [src + " #i " * 256];\n"
#define P8_X(i) "mov.b64 {x" #i ", y" #i "}, d" #i ";\n"
#define P8_HEAD(SRC) "{\n.reg .pred p, q;\n.reg .b64 src, d<8>;\n.reg .b32 n, x<8>, y<8>, m0, m1;\nmov.b64 src, " SRC ";\n"         \
                P8_LD(0) P8_LD(1) P8_LD(2) P8_LD(3) P8_LD(4) P8_LD(5) P8_LD(6) P8_LD(7) "mov.u32 n, 0;\nCHECK:\n" \
                P8_X(0) P8_X(1) P8_X(2) P8_X(3) P8_X(4) P8_X(5) P8_X(6) P8_X(7)
#define P8_VOTE "vote.sync.all.pred p, p, -1;\n@p bra.uni DONE;\n"
#define P8_TAIL "add.u32 n, n, 1;\nsetp.lt.u32 p, n, 0x100000;\n@p bra.uni CHECK;\ntrap;\nDONE:\n"
__device__ __forceinline__ void poll_state(uint2 (&v)[8], const void* src) {
#define P8_RS(i) "setp.eq.u32 q, x" #i ", 0xffffffff;\n@q " P8_LD(i)
#define P8_O(i) "mov.b64 %" #i ", d" #i ";\n"
    uint64_t d[8];
    asm volatile(P8_HEAD("%8") "max.u32 m0, x0, x1;\nmax.u32 m0, m0, x2;\nmax.u32 m1, x3, x4;\nmax.u32 m1, m1, x5;\nmax.u32 m0, m0, x6;\n"
                 "max.u32 m0, m0, x7;\nmax.u32 m0, m0, m1;\nsetp.ne.u32 p, m0, 0xffffffff;\n" P8_VOTE
                 P8_RS(0) P8_RS(1) P8_RS(2) P8_RS(3) P8_RS(4) P8_RS(5) P8_RS(6) P8_RS(7) P8_TAIL
                 P8_O(0) P8_O(1) P8_O(2) P8_O(3) P8_O(4) P8_O(5) P8_O(6) P8_O(7) "}"
                 : "=l"(d[0]), "=l"(d[1]), "=l"(d[2]), "=l"(d[3]), "=l"(d[4]), "=l"(d[5]), "=l"(d[6]), "=l"(d[7]) : "l"(src) : "memory");
#pragma unroll
    for (int i = 0; i < 8; i++) { v[i].x = (uint32_t)d[i]; v[i].y = (uint32_t)(d[i] >> 32); }
}
__device__ __forceinline__ uint64_t poll_sum(const void* src, uint32_t tag, uint32_t sel) {
#define P8_RT(i) "lop3.b32 m0, x" #i ", %2, 1, 0x28;\nsetp.ne.u32 q, m0, 0;\n@q " P8_LD(i)
#define P8_MMA(c, i, z) "mma.sync.aligned.m16n8k8.row.col.f32.bf16.bf16.f32 {" #c "0," #c "1," #c "2," #c "3}, {x" #i ", y" #i "}, {%3}, {" #z "0," #z "1," #z "2," #z "3};\n"
    uint64_t r;
    asm volatile(P8_HEAD("%1") "{\n.reg .f32 a<4>, b<4>, z<4>;\nmov.f32 z0, 0f00000000;\nmov.f32 z1, z0;\nmov.f32 z2, z0;\nmov.f32 z3, z0;\n"
                 P8_MMA(a, 0, z) P8_MMA(b, 1, z) P8_MMA(a, 2, a) P8_MMA(b, 3, b) P8_MMA(a, 4, a) P8_MMA(b, 5, b) P8_MMA(a, 6, a) P8_MMA(b, 7, b)
                 "add.f32 a0, a0, b0;\nadd.f32 a1, a1, b1;\nadd.f32 a2, a2, b2;\nadd.f32 a3, a3, b3;\n"
                 "cvt.rn.bf16x2.f32 m0, a1, a0;\ncvt.rn.bf16x2.f32 m1, a3, a2;\nmov.b64 %0, {m0, m1};\n}\n"
                 "lop3.b32 m0, x0, x1, %2, 0x7e;\nlop3.b32 m1, x2, x3, %2, 0x7e;\nlop3.b32 m0, m0, x4, %2, 0xf6;\n"
                 "lop3.b32 m1, m1, x5, %2, 0xf6;\nlop3.b32 m0, m0, x6, %2, 0xf6;\nlop3.b32 m1, m1, x7, %2, 0xf6;\n"
                 "lop3.b32 m0, m0, m1, 1, 0xa8;\nsetp.eq.u32 p, m0, 0;\n" P8_VOTE
                 P8_RT(0) P8_RT(1) P8_RT(2) P8_RT(3) P8_RT(4) P8_RT(5) P8_RT(6) P8_RT(7) P8_TAIL "}"
                 : "=&l"(r) : "l"(src), "r"(tag), "r"(sel) : "memory");
    return r;
}
__device__ __forceinline__ void sum8(float (&c)[4], const uint2 (&v)[8], uint32_t idn) {
    float d[4] = {0.f, 0.f, 0.f, 0.f};
    c[0] = c[1] = c[2] = c[3] = 0.f;
    mma16816(c, v[0].x, v[0].y, v[1].x, v[1].y, idn, idn);
    mma16816(d, v[2].x, v[2].y, v[3].x, v[3].y, idn, idn);
    mma16816(c, v[4].x, v[4].y, v[5].x, v[5].y, idn, idn);
    mma16816(d, v[6].x, v[6].y, v[7].x, v[7].y, idn, idn);
    c[0] += d[0]; c[1] += d[1]; c[2] += d[2]; c[3] += d[3];
}

#define CLS 6
__global__ void __cluster_dims__(CLS, 1, 1) __launch_bounds__(256, 1)
k_chain(const bf16* __restrict__ mem0, const bf16* __restrict__ Wq, const bf16* __restrict__ Wk, const bf16* __restrict__ Wv,
        const bf16* __restrict__ Wo, const __grid_constant__ CUtensorMap mkv) {
    extern __shared__ __align__(1024) uint8_t smem_chain[];
    const uint32_t sb = smem_u32(smem_chain);
    if (sb & 1023) __trap();
    const int w = __shfl_sync(~0u, threadIdx.x >> 5, 0), lane = __shfl_sync(~0u, threadIdx.x & 31, threadIdx.x & 31);
    const int tid = w * 32 + lane, g = lane >> 2, t = lane & 3;
    auto pin = [&](uint32_t x) { return delayed<1>(x, lane); };
    const int h = blockIdx.x / 3, r = blockIdx.x - 3 * h;
    const uint32_t bar_x = sb + C_BAR, bar_kv = sb + C_BAR + 8, bar_go = sb + C_BAR + 16, bar_w = sb + C_BAR + 24;
    asm volatile("griddepcontrol.launch_dependents;");
    const int tbase = r == 0 ? 0 : 1 + 21 * r, ntile = r == 0 ? 22 : 21;
    uint32_t side;
    if (tid == 0) {
        mbar_init(bar_x, 8); mbar_init(bar_kv, 1); mbar_init(bar_go, 1); mbar_init(bar_w, 1);
        asm volatile("fence.mbarrier_init.release.cluster;" ::: "memory");
        asm volatile("fence.proxy.async.shared::cta;" ::: "memory");
        mbar_expect_tx(bar_w, 128 * 32 * ntile);
    }
    __syncthreads();
    asm volatile("barrier.cluster.arrive.relaxed.aligned;" ::: "memory");
    if (tid < 128)
        asm volatile("cp.async.bulk.shared::cluster.global.mbarrier::complete_tx::bytes [%0], [%1], %2, [%3];"
                     ::"r"(sb + C_W1 + tid * 720), "l"(Wo + (size_t)(h * 128 + tid) * DM + tbase * 16), "r"(32 * ntile), "r"(bar_w) : "memory");
    const int tile0 = tbase + 7 - w;
    const bool three = w >= (r == 0 ? 2 : 3);
    const uint32_t wa = pin(sb + tid * 16);
#define W1A(i) (wa + C_W1 + (i) * 4096)
#define W2A(x) (wa + C_W2 + ((x) < 8 ? (x) * 4096 : 32768 - 1024 + ((x) - 8) * 3072))
    uint32_t wo0[8][4], wr[64][4];
    {
        const bf16* W = (r == 0 ? Wq : r == 1 ? Wk : Wv) + (size_t)(128 * w + (lane >> 4)) * HD + h * 128 + 8 * (lane & 15);
        uint4 raw[8][8];
        auto fetch = [&](int ks) {
#pragma unroll
            for (int i = 0; i < 8; i++) raw[ks][i] = ldw128(W + (size_t)(16 * ks + 2 * i) * HD);
        };
        fetch(0); fetch(1); fetch(2); fetch(3);
    asm("mov.u32 %0, %%smid;" : "=r"(side));
    side = __ldcg(g_side + (side & 255)) & 1;
    if (tid == 0 && r > 0) asm volatile("st.relaxed.gpu.global.u32 [%0], %1;" ::"l"(g_flag + 128 + 2 * h + r - 1), "r"(2 | side) : "memory");
        if (w == 0) TG(0);
        mbar_wait_u(bar_w, 0);
        if (w == 0) TG(1);
        const uint32_t p = sb + C_W1 + ((lane & 7) + (lane >> 4) * 8) * 720 + (7 - w) * 32 + ((lane >> 3) & 1) * 16;
#pragma unroll
        for (int ks = 0; ks < 8; ks++) {
            uint32_t a[4];
            ldsm4t(wo0[ks], p + ks * 16 * 720);
            ldsm4t(a, p + ks * 16 * 720 + 256);
            sts128(W2A(ks), a[0], a[1], a[2], a[3]);
            if (three) { ldsm4t(a, p + ks * 16 * 720 + 512); sts128(W2A(8 + ks), a[0], a[1], a[2], a[3]); }
        }
        __syncthreads();
        if (w == 0) TG(2);
        const uint32_t stg = sb + C_KV + w * 4096;
        const uint32_t rd = stg + ((lane & 7) + 8 * (lane >> 4)) * 256 + ((((lane >> 3) & 1) ^ (lane & 7)) << 4);
#pragma unroll
        for (int ks = 0; ks < 8; ks++) {
#pragma unroll
            for (int i = 0; i < 8; i++)
                sts128(stg + (2 * i + (lane >> 4)) * 256 + (((lane & 15) ^ (((2 * i) & 6) | (lane >> 4))) << 4),
                       raw[ks][i].x, raw[ks][i].y, raw[ks][i].z, raw[ks][i].w);
            if (ks < 2) fetch(ks + 4);
            if (ks == 3 || ks == 5) fetch(ks / 2 + 5);
            __syncwarp();
#pragma unroll
            for (int j = 0; j < 8; j++) {
                if (smem_idx(ks, j) >= 0) {
                    uint32_t a[4];
                    ldsm4t(a, rd ^ (j << 5));
                    sts128(W1A(smem_idx(ks, j)), a[0], a[1], a[2], a[3]);
                } else ldsm4t(wr[8 * ks + j], rd ^ (j << 5));
            }
            __syncwarp();
        }
    }
    if (w == 0) TG(3);
    asm volatile("griddepcontrol.wait;\nfence.proxy.async.shared::cta;" ::: "memory");
    __syncthreads();
    if (tid == 0) {
        mbar_expect_tx(bar_kv, 16384);
        tma3d(sb + C_KV, &mkv, 0, 0, 2 * h, bar_kv);
        tma3d(sb + C_KV + 8192, &mkv, 0, 0, 64 + 2 * h, bar_kv);
    }
    asm volatile("barrier.cluster.wait.aligned;" ::: "memory");

    auto publish_kvm = [&](int s) {
        uint32_t v[4];
        lds128(v, sb + C_QKV + (8 + (tid >> 4)) * 272 + (tid & 15) * 16);
        asm volatile("st.global.v4.u32 [%0], {%1,%2,%3,%4};"
                     ::"l"(g_kvm + (size_t)(s * 8 + ((tid >> 4) & 7)) * 8192 + (tid >> 7) * HD + h * 128 + (tid & 15) * 8),
                       "r"(v[0]), "r"(v[1]), "r"(v[2]), "r"(v[3]) : "memory");
        if (h == 0 && w == 6) asm volatile("st.relaxed.gpu.global.u32 [%0], %1;" ::"l"(g_flag + 98), "r"(s + 1) : "memory");
        if ((s & 3) == 3) {
            __syncthreads();
            if (w == 7) asm volatile("{\n.reg .pred p;\nsetp.eq.u32 p, %2, 0;\nfence.acq_rel.gpu;\n@p st.relaxed.gpu.global.u32 [%0], %1;\n}"
                                     ::"l"(g_flag + h), "r"(s + 1), "r"(lane) : "memory");
        }
    };
    const float sl2e = 0.08838834764831845f * 1.4426950408889634f;
    const uint32_t idn = pin(g == 2 * t ? 0x00003f80u : g == 2 * t + 1 ? 0x3f800000u : 0u);
    const uint32_t lm = pin(sb + (lane & 7) * 272 + (lane >> 3) * 16);
    const uint32_t sa = pin(sb + C_SC + (w & 1) * (8 * 52 * 4) + (2 * t * 52 + (w < 4 ? 32 : (w & 2) * 8) + g) * 4);
    const uint32_t sr = pin(sb + C_SC + (g * 52 + 8 * t) * 4), sr2 = pin(sb + C_SC + (g * 52 + 32 + 2 * t) * 4);
    uint32_t kva;
    {
        const int pos = (w & 2) * 8 + (lane & 15), row = (pos & 24) + ((pos + (pos >> 2 & 6)) & 7);
        const int key = 4 * (lane & 6) + (((lane & 7) + 2 * (lane >> 4)) & 7);
        kva = pin(w >= 4 ? sb + C_KV + (w & 1) * 4096 + row * 128 + (((lane >> 4) ^ (row & 7)) << 4)
                         : sb + C_KV + 8192 + (w >> 1) * 4096 + key * 128 + ((((w & 1) * 4 + ((lane >> 3) & 1)) ^ (key & 7)) << 4));
    }
    uint32_t buf0[8][4], ring[RB1][4];
    auto stage_w1 = [&]() {
#pragma unroll
        for (int i = 0; i < 8; i++) lds128v(buf0[i], W1A(i));
#pragma unroll
        for (int i = 0; i < RB1; i++) lds128v(ring[i], W1A(8 + i));
    };
    stage_w1();
    uint32_t psel, msel0, msel1;
    {
        const int j = r > 0 ? 2 * h + r - 1 : 0, tl = min(tile0 + 8 * (lane >> 1), 63);
        uint32_t b;
        asm volatile("{\n.reg .pred p;\n.reg .u32 n;\nmov.u32 n, 0;\nAGAIN:\nld.relaxed.gpu.global.u32 %0, [%1];\nsetp.ne.u32 p, %0, 0;\n"
                     "vote.sync.all.pred p, p, -1;\n@p bra.uni DONE;\nadd.u32 n, n, 1;\nsetp.lt.u32 p, n, 0x100000;\n@p bra.uni AGAIN;\ntrap;\nDONE:\n}"
                     : "=&r"(b) : "l"(g_flag + 128 + tl) : "memory");
        psel = __ballot_sync(~0u, (g_home[lane == 6 ? j * 2 + ((w >> 1) & 1) : tl * 2 + (lane & 1)] ^ (lane == 6 ? side : b)) & 1);
        msel0 = __ballot_sync(~0u, (g_home[128 + lane * 4 + (w >> 1)] ^ side) & 1);
        msel1 = __ballot_sync(~0u, (g_home[256 + lane * 4 + (w >> 1)] ^ side) & 1);
        if (r > 0) {
            if (w < 4) asm volatile("prefetch.global.L2 [%0];" ::"l"(g_x + (128 + (1 + (w >> 1)) * 4 + (j >> 4)) * 1024 + (w & 1) * 512 + (j & 15) * 32 + lane) : "memory");
            if (w < 4) asm volatile("prefetch.global.L2 [%0];" ::"l"(g_x + j * 2048 + tid * 16) : "memory");
        }
    }
    uint2 bm[8];
#pragma unroll
    for (int ks = 0; ks < 8; ks++) {
        const uint32_t* p = (const uint32_t*)(mem0 + g * DM + (8 * w + ks) * 16) + t;
        bm[ks] = make_uint2(__ldg(p), __ldg(p + 4));
    }
    if (w == 0) TG(5);
#pragma unroll 1
    for (int s = 0;; s++) {
        TS(1);
        {
            float acc[8][4];
#pragma unroll
            for (int ks = 0; ks < 8; ks++) {
#pragma unroll
                for (int j = 0; j < 8; j++) {
                    const int i = smem_idx(ks, j) - 8;
                    if (ks == 0) {
                        acc[j][0] = acc[j][1] = acc[j][2] = acc[j][3] = 0.f;
                        mma16816(acc[j], buf0[j][0], buf0[j][1], buf0[j][2], buf0[j][3], bm[ks].x, bm[ks].y);
                    } else if (i >= 0) {
                        uint32_t(&a)[4] = ring[i % RB1];
                        mma16816(acc[j], a[0], a[1], a[2], a[3], bm[ks].x, bm[ks].y);
                        if (8 + i + RB1 < NS1) lds128v(a, W1A(8 + i + RB1));
                    } else {
                        const uint32_t(&a)[4] = wr[8 * ks + j];
                        mma16816(acc[j], a[0], a[1], a[2], a[3], bm[ks].x, bm[ks].y);
                    }
                }
            }
#pragma unroll
            for (int c = 0; c < 4; c++)
                stsm4t(lm + C_RED + w * 2176 + c * 64, pack2(acc[2 * c][0], acc[2 * c][1]), pack2(acc[2 * c][2], acc[2 * c][3]),
                       pack2(acc[2 * c + 1][0], acc[2 * c + 1][1]), pack2(acc[2 * c + 1][2], acc[2 * c + 1][3]));
        }
        {
            const uint32_t a = sb + C_RED + w * 272 + lane * 8;
            TS(2);
            __syncthreads();
            TS(3);
            uint2 v[8];
#pragma unroll
            for (int i = 0; i < 8; i++) v[i] = lds64(a + i * 2176);
            float c[4];
            sum8(c, v, idn);
            const uint32_t p0 = pack2(c[0], c[1]), p1 = pack2(c[2], c[3]);
            const uint32_t dst = sb + C_QKV + (r * 8 + w) * 272 + lane * 8;
#pragma unroll
            for (int i = 1; i < 3; i++) {
                const uint32_t peer = (h % (CLS / 3)) * 3 + (r + i >= 3 ? r + i - 3 : r + i);
                uint32_t rd, rb;
                asm("mapa.shared::cluster.u32 %0, %1, %2;" : "=r"(rd) : "r"(dst), "r"(peer));
                asm("mapa.shared::cluster.u32 %0, %1, %2;" : "=r"(rb) : "r"(bar_x), "r"(peer));
                asm volatile("st.async.weak.shared::cluster.mbarrier::complete_tx::bytes.v2.b32 [%0], {%1,%2}, [%3];"
                             ::"r"(rd), "r"(p0), "r"(p1), "r"(rb) : "memory");
            }
            sts64(dst, p0, p1);
            __syncwarp();
            asm volatile("{\n.reg .pred p;\nsetp.eq.u32 p, %1, 0;\n@p mbarrier.arrive.expect_tx.shared::cta.b64 _, [%0], 512;\n}"
                         ::"r"(bar_x), "r"(lane) : "memory");
        }
        TS(4);
        if (s == NSEG - 1) break;
        if (s == 0) mbar_wait_u(bar_kv, 0);
        uint32_t wb[8][4], wc[8][4];
        const uint32_t po = (tile0 * 2 + (lane >> 4)) * 8192 + ((lane >> 3) & 1) * 2048 + h * 64 + (lane & 7) * 8;
        const uint32_t tag = s & 1;
        auto project = [&](const uint32_t(&wt)[8][4], const uint32_t(&ob)[4][4], int i) {
            float c0[4] = {0.f, 0.f, 0.f, 0.f}, c1[4] = {0.f, 0.f, 0.f, 0.f};
#pragma unroll
            for (int ks = 0; ks < 8; ks++)
                mma16816((ks & 1) ? c1 : c0, wt[ks][0], wt[ks][1], wt[ks][2], wt[ks][3], ob[ks >> 1][(ks & 1) * 2], ob[ks >> 1][(ks & 1) * 2 + 1]);
            uint32_t p0 = pack2(c0[0] + c1[0], c0[1] + c1[1]), p1 = pack2(c0[2] + c1[2], c0[3] + c1[3]);
            asm volatile("movmatrix.sync.aligned.m8n8.trans.b16 %0, %0;\nmovmatrix.sync.aligned.m8n8.trans.b16 %1, %1;" : "+r"(p0), "+r"(p1));
            st_rlx64((uint2*)((char*)g_x + po + i * 131072 + ((psel >> (2 * i + (lane >> 4))) & 1) * 4096), (p0 & ~1u) | tag, p1);
        };
        if (w >= 4) {
            uint32_t ka[4][4];
#pragma unroll
            for (int ks = 0; ks < 4; ks++) ldsm4(ka[ks], kva ^ (ks << 5));
            const uint32_t qa = lm + C_QKV + (w & 1) * 128;
            TS(5);
            mbar_wait_u(bar_x, s & 1);
            TS(6);
            {
                uint32_t qb[2][4];
                ldsm4(qb[0], qa);
                ldsm4(qb[1], qa + 64);
                float c0[4] = {0.f, 0.f, 0.f, 0.f}, c1[4] = {0.f, 0.f, 0.f, 0.f};
                mma16816(c0, ka[0][0], ka[0][1], ka[0][2], ka[0][3], qb[0][0], qb[0][1]);
                mma16816(c1, ka[1][0], ka[1][1], ka[1][2], ka[1][3], qb[0][2], qb[0][3]);
                mma16816(c0, ka[2][0], ka[2][1], ka[2][2], ka[2][3], qb[1][0], qb[1][1]);
                mma16816(c1, ka[3][0], ka[3][1], ka[3][2], ka[3][3], qb[1][2], qb[1][3]);
                sts32f(sa, c0[0] + c1[0]);
                sts32f(sa + 208, c0[1] + c1[1]);
                sts32f(sa + 32, c0[2] + c1[2]);
                sts32f(sa + 240, c0[3] + c1[3]);
            }
            __syncthreads();
            TS(7);
            if (w == 7 && s + 1 < NSEG - 1) {
                if (lane == 0) {
                    mbar_expect_tx(bar_kv, 16384);
                    tma3d(sb + C_KV, &mkv, 0, (s + 1) * 32, 2 * h, bar_kv);
                    tma3d(sb + C_KV + 8192, &mkv, 0, (s + 1) * 32, 64 + 2 * h, bar_kv);
                }
                __syncwarp();
            }
            const uint32_t wd = delayed<DLYW>(wa, lane);
#pragma unroll
            for (int i = 0; i < 8; i++) lds128(wb[i], wd + C_W2 + i * 4096);
#pragma unroll
            for (int i = 0; i < PFC; i++) lds128(wc[i], wd + C_W2 + 32768 - 1024 + i * 3072);
            TS(8);
            __syncthreads();
            TS(9);
            uint32_t ob[4][4];
#pragma unroll
            for (int i = 0; i < 4; i++) ldsm4(ob[i], lm + C_OB + i * 64);
#pragma unroll
            for (int i = PFC; i < 8; i++) lds128(wc[i], W2A(8 + i));
            project(wb, ob, 1);
            project(wo0, ob, 0);
            project(wc, ob, 2);
        } else {
            uint32_t va[4][4];
#pragma unroll
            for (int i = 0; i < 4; i++) ldsm4t(va[i], kva ^ (((i >> 1) << 5) | ((i & 1) * 0x240)));
#pragma unroll
            for (int i = 0; i < 8; i++) lds128(wb[i], W2A(i));
            const uint32_t qa = lm + C_QKV + (w & 1) * 128, oa = lm + w * 64;
            TS(5);
            mbar_wait_u(bar_x, s & 1);
            TS(6);
            if (w < 2) {
                uint32_t qb[2][4], km[2][4];
                ldsm4(qb[0], qa);
                ldsm4(km[0], qa + 8 * 272);
                ldsm4(qb[1], qa + 64);
                ldsm4(km[1], qa + 8 * 272 + 64);
                float c0[4] = {0.f, 0.f, 0.f, 0.f}, c1[4] = {0.f, 0.f, 0.f, 0.f};
                mma16816(c0, km[0][0], km[0][1], km[0][2], km[0][3], qb[0][0], qb[0][2]);
                mma16816(c1, km[0][0], km[0][1], km[0][2], km[0][3], qb[0][1], qb[0][3]);
                mma16816(c0, km[1][0], km[1][1], km[1][2], km[1][3], qb[1][0], qb[1][2]);
                mma16816(c1, km[1][0], km[1][1], km[1][2], km[1][3], qb[1][1], qb[1][3]);
                sts32f(sa, c0[0] + c1[2]);
                sts32f(sa + 208, c0[1] + c1[3]);
            }
            __syncthreads();
            TS(7);
            {
                float4 x0 = lds128f(sr), y0 = lds128f(sr + 1664), x1 = lds128f(sr + 16), y1 = lds128f(sr + 1680);
                float2 x2 = lds64f(sr2), y2 = lds64f(sr2 + 1664);
                float p[10] = {x0.x + y0.x, x0.y + y0.y, x0.z + y0.z, x0.w + y0.w, x1.x + y1.x,
                               x1.y + y1.y, x1.z + y1.z, x1.w + y1.w, x2.x + y2.x, x2.y + y2.y};
                float m = fmaxf(fmaxf(fmaxf(p[0], p[1]), fmaxf(p[2], p[3])), fmaxf(fmaxf(fmaxf(p[4], p[5]), fmaxf(p[6], p[7])), fmaxf(p[8], p[9])));
                const float m1 = __shfl_xor_sync(~0u, m, 1), m2 = __shfl_xor_sync(~0u, m, 2), m3 = __shfl_xor_sync(~0u, m, 3);
                uint32_t vm[4];
                ldsm4t(vm, oa + C_QKV + 16 * 272);
                m = fmaxf(fmaxf(m, m1), fmaxf(m2, m3));
                const float ms = m * sl2e;
#pragma unroll
                for (int i = 0; i < 10; i++) p[i] = ex2(fmaf(p[i], sl2e, -ms));
                const uint32_t b0 = pack2(p[0], p[1]), b1 = pack2(p[2], p[3]), b2 = pack2(p[4], p[5]), b3 = pack2(p[6], p[7]), b4 = pack2(p[8], p[9]);
                const uint32_t one = 0x3f803f80u;
                float o0[4] = {0.f, 0.f, 0.f, 0.f}, o1[4] = {0.f, 0.f, 0.f, 0.f}, sm[4] = {0.f, 0.f, 0.f, 0.f};
                mma16816(sm, one, one, one, one, b0, b1);
                mma16816(o0, va[0][0], va[0][1], va[0][2], va[0][3], b0, b1);
                mma16816(o1, va[2][0], va[2][1], va[2][2], va[2][3], b0, b1);
                mma16816(sm, one, one, one, one, b2, b3);
                mma16816(o0, va[1][0], va[1][1], va[1][2], va[1][3], b2, b3);
                mma16816(o1, va[3][0], va[3][1], va[3][2], va[3][3], b2, b3);
                mma1688(sm, one, one, b4);
                mma1688(o0, vm[0], vm[1], b4);
                mma1688(o1, vm[2], vm[3], b4);
                float i0, i1;
                asm("rcp.approx.ftz.f32 %0, %1;" : "=f"(i0) : "f"(sm[0]));
                asm("rcp.approx.ftz.f32 %0, %1;" : "=f"(i1) : "f"(sm[1]));
                stsm4t(oa + C_OB, pack2(o0[0] * i0, o0[1] * i1), pack2(o0[2] * i0, o0[3] * i1),
                       pack2(o1[0] * i0, o1[1] * i1), pack2(o1[2] * i0, o1[3] * i1));
            }
            TS(8);
            __syncthreads();
            TS(9);
            uint32_t ob[4][4];
#pragma unroll
            for (int i = 0; i < 4; i++) ldsm4(ob[i], lm + C_OB + i * 64);
            if (three) {
#pragma unroll
                for (int i = 0; i < 8; i++) lds128(wc[i], W2A(8 + i));
                project(wb, ob, 1);
                project(wo0, ob, 0);
                project(wc, ob, 2);
            } else {
                project(wb, ob, 1);
                project(wo0, ob, 0);
            }
        }
        TS(10);
        __syncthreads();
        uint32_t eo = (128 + (s + 1) * 4 + (w >> 1)) * 8192 + (((s < 31 ? msel0 : msel1) >> ((s + 1) & 31)) & 1) * 4096 + (w & 1) * 2048 + lane * 8;
        if (r == 0) {
            TS(11); TS(12);
            stage_w1();
            if (w < 4 && s + 3 < NSEG - 1)
                asm volatile("prefetch.global.L2 [%0];" ::"l"(g_kv + (size_t)((s + 3) * 32 + lane) * 8192 + (w >> 1) * HD + h * 128 + (w & 1) * 64) : "memory");
            publish_kvm(s);
            if (s < NSEG - 2) mbar_wait_u(bar_kv, (s + 1) & 1);
            mbar_wait_u(bar_go, s & 1);
            if (w < 4) eo = delayed<DLY0>(eo, lane); else eo = delayed<DLY0A>(eo, lane);
        } else {
            const int j = 2 * h + r - 1;
            if (w < 4) {
                const char* src = (const char*)g_x + delayed<DLY3>((j * 2 + (w >> 1)) * 8192 + (psel & 64) * 64 + (w & 1) * 2048 + t * 64 + g * 8, lane);
                const char* dst = (const char*)g_x + pin((128 + (s + 1) * 4 + (j >> 4)) * 8192 + (j & 15) * 256 + w * 64 + (t & 1) * 4096 + g * 8);
                const uint64_t v = poll_sum(src, tag, (lane & 4) ? 0x3f800000u : 0x00003f80u);
                TS(11);
                asm volatile("st.relaxed.gpu.global.b64 [%0], %1;" ::"l"(dst), "l"(v) : "memory");
                asm volatile("bar.arrive 1, 256;" ::: "memory");
                TS(12);
                stage_w1();
                if (s < NSEG - 2) mbar_wait_u(bar_kv, (s + 1) & 1);
                eo = delayed<DLY1>(eo, lane);
            } else {
                if (w >= 6 && s + 3 < NSEG)
                    asm volatile("prefetch.global.L2 [%0];" ::"l"(g_x + (128 + (s + 3) * 4 + (j >> 4)) * 1024 + (w & 1) * 512 + (j & 15) * 32 + lane) : "memory");
                stage_w1();
                if (s < NSEG - 2) mbar_wait_u(bar_kv, (s + 1) & 1);
                TS(11);
                bar_sync(1, 256);
                TS(12);
                if (w == 4 && r == 1)
                    asm volatile("{\n.reg .pred p;\n.reg .u32 a;\nelect.sync _|p, -1;\nmapa.shared::cluster.u32 a, %0, %1;\n"
                                 "@p mbarrier.arrive.relaxed.cluster.shared::cluster.b64 _, [a];\n}" ::"r"(bar_go), "r"((h % (CLS / 3)) * 3) : "memory");
                eo = delayed<DLY1A>(eo, lane);
            }
        }
        { const int s_ = s; { const int s = s_ + 1; TS(0); } }
        poll_state(bm, (const char*)g_x + eo);
    }
    mbar_wait_u(bar_x, (NSEG - 1) & 1);
    if (r == 0) publish_kvm(NSEG - 1);
    asm volatile("barrier.cluster.arrive.relaxed.aligned;\nbarrier.cluster.wait.aligned;" ::: "memory");
}

constexpr int S4_US = 4368;
constexpr int S4_RS = 8848;
constexpr int S4_KS = 1296;
constexpr int S4_U = 0, S4_R = 16 * S4_US, S4_K = S4_R + 16 * S4_RS;
constexpr int S4_SMEM = S4_K + 16 * S4_KS;
constexpr int S4_SIG = 3104, S4_PK = 2 * S4_SIG;

struct cf { float r, i; };
__device__ __forceinline__ cf cmul(cf a, cf b) { return {fmaf(a.r, b.r, -a.i * b.i), fmaf(a.r, b.i, a.i * b.r)}; }
__device__ __forceinline__ cf cmulc(cf a, cf b) { return {fmaf(a.r, b.r, a.i * b.i), fmaf(a.i, b.r, -a.r * b.i)}; }
__device__ __forceinline__ cf csq(cf a) { const float t = a.r * a.i; return {fmaf(a.r, a.r, -a.i * a.i), t + t}; }
__device__ __forceinline__ cf cexp(float l2, float turns) {
    const float mag = ex2(l2), fr = (turns - rintf(turns)) * 6.283185307179586f;
    return {mag * __cosf(fr), mag * __sinf(fr)};
}
__device__ __forceinline__ void sts32(uint32_t a, uint32_t v) { asm volatile("st.shared.u32 [%0], %1;" ::"r"(a), "r"(v) : "memory"); }
__device__ __forceinline__ uint32_t lds16(uint32_t a) {
    uint32_t v;
    asm volatile("ld.shared.u16 %0, [%1];" : "=r"(v) : "r"(a) : "memory");
    return v;
}

template <int M0, int NQ>
__device__ __forceinline__ void s4_class(float (&acc)[16][4], uint32_t sig, uint32_t taps, int x0) {
    constexpr int D0 = M0 / 8, D1 = M0 == 32 ? 9 : 15;
    uint32_t R[D1 - D0 + 2];
#pragma unroll
    for (int D = D0 - 1; D <= D1; D++) {
        if (D < D0 || 8 * D - 7 >= 2 * M0) { R[D - D0 + 1] = 0; continue; }
        const int m = 8 * D + x0;
        uint32_t lo = lds16(taps + m * (2 * NQ)), hi = lds16(taps + (m - 1) * (2 * NQ));
        if (D == D0) { lo = m >= M0 ? lo : 0; hi = m > M0 ? hi : 0; }
        if (D == 2 * D0) { lo = m < 2 * M0 ? lo : 0; hi = m <= 2 * M0 ? hi : 0; }
        R[D - D0 + 1] = lo | (hi << 16);
    }
#pragma unroll
    for (int J = 0; 2 * J + D0 < 16; J++) {
        uint32_t a[4];
        ldsm4t(a, sig + J * 512);
#pragma unroll
        for (int D = D0; D <= D1; D++)
            if (2 * J + D < 16) mma16816(acc[2 * J + D], a[0], a[1], a[2], a[3], R[D - D0 + 1], R[D - D0]);
    }
}

__global__ void __launch_bounds__(512, 1)
k_s4(const bf16* __restrict__ u, const bf16* __restrict__ Are, const bf16* __restrict__ Aim, const bf16* __restrict__ Bre,
     const bf16* __restrict__ Bim, const bf16* __restrict__ Cre, const bf16* __restrict__ Cim, const bf16* __restrict__ logdt,
     const bf16* __restrict__ Dsk, bf16* __restrict__ out) {
    extern __shared__ __align__(16) uint8_t smem_s4[];
    const uint32_t sb = smem_u32(smem_s4);
    asm volatile("griddepcontrol.launch_dependents;");
    const int tid = threadIdx.x, w = __shfl_sync(~0u, tid >> 5, 0), lane = tid & 31, g = lane >> 2, t = lane & 3;
#pragma unroll 1
    for (int item = blockIdx.x; item < 64; item += gridDim.x) {
#define TLS(slot)
    if (tid == 0) TLS(0);
    const int d0 = item * 16;
    const int d = d0 + (w & 1) + ((w >> 1) & 3) * 4 + (w >> 3) * 2;
    const uint32_t tr_off = (lane & 15), tr_l = (lane >> 4) * 16;
    const uint32_t ur = sb + S4_U + w * S4_US, rs = sb + S4_R + w * S4_RS, kd = sb + S4_K + w * S4_KS;
    if (lane < 16) sts128(ur + lane * 16, 0, 0, 0, 0);
    {
        const int o = d * 128 + lane * 4;
        const uint2 ar = __ldg((const uint2*)(Are + o)), ai = __ldg((const uint2*)(Aim + o)), br = __ldg((const uint2*)(Bre + o));
        const uint2 bi = __ldg((const uint2*)(Bim + o)), cr = __ldg((const uint2*)(Cre + o)), ci = __ldg((const uint2*)(Cim + o));
        const float dt = bf_round(expf(__bfloat162float(logdt[d])));
        const bf16* src = u + (size_t)(w * 128 + g) * DM + d0 + 4 * t;
        float T[5][4];
#pragma unroll
        for (int i = 0; i < 5; i++) T[i][0] = T[i][1] = T[i][2] = T[i][3] = 0.f;
        float klast = 0.f;
        const uint32_t wr_ = rs + lane * 272, rd_ = rs + t * 544 + g * 16;
#pragma unroll 1
        for (int c = 0; c < 4; c++) {
            uint2 v[4];
#pragma unroll
            for (int i = 0; i < 4; i++) v[i] = __ldg((const uint2*)(src + (size_t)(c * 32 + i * 8) * DM));
            auto pick = [&](const uint2& x) { const uint32_t y = c < 2 ? x.x : x.y; return (c & 1) ? bf_hi(y) : bf_lo(y); };
            auto pk2 = [](cf x) { return pack2(x.r, x.i); };
            const float l2 = dt * pick(ar) * 1.4426950408889634f, tu = dt * pick(ai) * 0.15915494309189535f;
            const cf z1 = cexp(l2, tu), z2 = csq(z1), z4 = csq(z2), z8 = csq(z4);
            const cf z64 = cexp(l2 * 64.f, tu * 64.f), z128 = csq(z64), z256 = csq(z128), z512 = csq(z256);
            cf a0 = {1.f, 0.f}, a1 = z64;
            cf b0 = cmul({pick(cr), pick(ci)}, {dt * pick(br), dt * pick(bi)});
            b0.i = -b0.i;
            cf b1 = cmulc(b0, z128), b2 = cmulc(b0, z256), y3 = cmulc(b0, z512), b4 = cmulc(y3, z512), b3 = y3;
            const cf y2 = cmulc(b2, z128);
#pragma unroll
            for (int i = 0; i < 8; i++) {
                sts128(wr_ + i * 16, pk2(a0), pk2(a1), pk2(b0), pk2(b1));
                sts128(wr_ + i * 16 + 128, pk2(b2), pk2(b3), pk2(b4), 0);
                b4 = cmulc(b4, z128);
                if (i < 7) {
                    a0 = i == 0 ? z8 : cmul(a0, z8); a1 = cmul(a1, z8);
                    b0 = cmulc(b0, z1); b1 = cmulc(b1, z1);
                    b2 = i == 3 ? y2 : cmulc(b2, z2);
                    if (i & 1) { y3 = cmulc(y3, z128); b3 = y3; } else b3 = cmulc(y3, z4);
                }
            }
            klast += b4.r;
            __syncwarp();
#pragma unroll
            for (int k = 0; k < 8; k++) {
                uint32_t x[4], y[4];
                lds128(x, rd_ + (8 * (k >> 1) + (k & 1)) * 272);
                lds128(y, rd_ + (8 * (k >> 1) + (k & 1)) * 272 + 128);
                mma1688(T[0], x[0], x[1], x[2]);
                mma1688(T[1], x[0], x[1], x[3]);
                mma1688(T[2], x[0], x[1], y[0]);
                mma1688(T[3], x[0], x[1], y[1]);
                mma1688(T[4], x[0], x[1], y[2]);
            }
#pragma unroll
            for (int i = 0; i < 2; i++)
                stsm4t(sb + S4_U + tr_off * S4_US + 256 + (w * 128 + c * 32 + i * 16) * 2 + tr_l, v[2 * i].x, v[2 * i].y, v[2 * i + 1].x, v[2 * i + 1].y);
            __syncwarp();
        }
#pragma unroll
        for (int o2 = 16; o2; o2 >>= 1) klast += __shfl_xor_sync(~0u, klast, o2);
#pragma unroll
        for (int hh = 0; hh < 2; hh++) {
            const int i = g + 8 * hh;
            sts32(kd + (8 * i + 2 * t) * 2, pack2(T[0][2 * hh], T[0][2 * hh + 1]));
            sts32(kd + (128 + 8 * i + 2 * t) * 2, pack2(T[1][2 * hh], T[1][2 * hh + 1]));
            sts32(kd + (256 + 4 * i + 2 * (t & 1) + 64 * (t >> 1)) * 2, pack2(T[2][2 * hh], T[2][2 * hh + 1]));
            sts32(kd + (384 + 2 * i + 32 * t) * 2, pack2(T[3][2 * hh], T[3][2 * hh + 1]));
        }
        asm volatile("stmatrix.sync.aligned.m8n8.x2.trans.shared.b16 [%0], {%1,%2};"
                     ::"r"(kd + 1024 + (lane & 7) * 32 + ((lane >> 3) & 1) * 16), "r"(pack2(T[4][0], T[4][1])), "r"(pack2(T[4][2], T[4][3])) : "memory");
        if (lane == 0) sts32(kd + 1280, pack2(klast, 0.f));
    }
    __syncwarp();
    const uint32_t pk = rs + S4_PK + 64;
    {
#pragma unroll
        for (int i = 0; i < 2; i++) {
            const int x = i * 128 + lane * 4;
            const uint2 c = lds64(kd + x * 2);
            uint32_t p = lds16(kd + x * 2 - 2);
            if (x == 0) p = 0;
            sts128(pk + x * 4, __byte_perm(c.x, p, 0x5410), __byte_perm(c.x, 0, 0x1032), __byte_perm(c.y, c.x, 0x7610), __byte_perm(c.y, 0, 0x1032));
        }
#pragma unroll
        for (int i = 2; i < 4; i++) {
            const int x = i * 128 + lane * 4;
            const uint32_t ab = lds32(kd + 256 + x), c = lds16(kd + 256 + x + 4);
            const uint32_t p = x == 256 ? lds16(kd + 510) : ab;
            sts128(pk + x * 4, __byte_perm(ab, p, 0x5410), __byte_perm(ab, 0, 0x1010), __byte_perm(ab, 0, 0x1032), __byte_perm(c, ab, 0x7610));
        }
        const uint32_t v = lds16(kd + 768), v2 = lds16(kd + 1024);
        if (lane < 24) {
            uint32_t x0 = 0, x1 = 0, x2 = 0, x3 = 0;
            if (lane == 0) { x0 = x1 = x2 = v | (v << 16); x3 = v << 16; }
            if (lane == 12) x3 = v2;
            if (lane == 13) { x0 = v2 | (v2 << 16); x1 = v2 << 16; }
            sts128(lane < 20 ? pk + 2048 + lane * 16 : pk - 64 + (lane - 20) * 16, x0, x1, x2, x3);
        }
        if (lane < 4) sts128(rs + (lane >> 1) * S4_SIG + (lane & 1) * 16, 0, 0, 0, 0);
    }
    __syncthreads();
    float acc[16][4];
#pragma unroll
    for (int i = 0; i < 16; i++) acc[i][0] = acc[i][1] = acc[i][2] = acc[i][3] = 0.f;
    const uint32_t lf = (lane & 7) * 32 + ((lane >> 3) & 1) * 16 + (lane >> 4) * 256;
#pragma unroll 1
    for (int ph = 0; ph < 2; ph++) {
    if (((w >> 2) ^ ph) & 1) {
#pragma unroll
    for (int rg = 3; rg >= 2; rg--) {
#pragma unroll 1
        for (int it = 0; it < (rg == 3 ? 4 : 6); it++) {
            const int n = it * 32 + lane;
            uint32_t x[2][4];
            lds128(x[0], ur + 256 + n * 16 - 16);
            lds128(x[1], ur + 256 + n * 16);
            float e[16], p[15], s[11];
#pragma unroll
            for (int i = 0; i < 8; i++) { e[2 * i] = bf_lo(x[i >> 2][i & 3]); e[2 * i + 1] = bf_hi(x[i >> 2][i & 3]); }
#pragma unroll
            for (int i = 0; i < 15; i++) p[i] = e[i] + e[i + 1];
#pragma unroll
            for (int i = 0; i < 11; i++) s[i] = p[i + 3] + e[i + 5];
            const uint32_t o = rs + 16 + n * 16;
            if (rg == 2) sts128(o, pack2(s[0], s[1]), pack2(s[2], s[3]), pack2(s[4], s[5]), pack2(s[6], s[7]));
#pragma unroll
            for (int i = 0; i < 10; i++) s[i] = p[i + 2] + s[i + 1];
            if (rg == 2) {
                sts64(o + S4_SIG + 8, pack2(s[0], s[1]), pack2(s[2], s[3]));
                sts64(o + S4_SIG + 16, pack2(s[4], s[5]), pack2(s[6], s[7]));
            } else {
#pragma unroll
                for (int i = 0; i < 9; i++) s[i] = p[i + 1] + s[i + 1];
                sts64(o + 8, pack2(s[0], s[1]), pack2(s[2], s[3]));
                sts64(o + 16, pack2(s[4], s[5]), pack2(s[6], s[7]));
#pragma unroll
                for (int i = 0; i < 8; i++) s[i] = p[i] + s[i + 1];
                sts64(o + S4_SIG + 8, pack2(s[0], s[1]), pack2(s[2], s[3]));
                sts64(o + S4_SIG + 16, pack2(s[4], s[5]), pack2(s[6], s[7]));
            }
        }
        __syncwarp();
        if (rg == 3) {
#pragma unroll 1
            for (int q = 1; q <= 2; q++) s4_class<64, 2>(acc, rs + lf + (q == 1 ? 16 : S4_SIG), kd + (384 + q) * 2, g - 2 * t);
        } else {
#pragma unroll 1
            for (int q = 1; q <= 4; q++) s4_class<32, 4>(acc, rs + lf + ((q & 1) ? 0 : S4_SIG) + (q < 3 ? 16 : 0), kd + (256 + q) * 2, g - 2 * t);
        }
        __syncwarp();
    }
    } else
    {
        const uint32_t ub = ur + 256 + lf, kb = pk + (g - 2 * t) * 4;
#pragma unroll 1
        for (int j0 = 0; j0 < 8; j0++) {
            uint32_t B[8][4];
#pragma unroll
            for (int i = 0; i < 8; i++) ldsm4(B[i], ub + i * 512 - j0 * 32);
            auto block = [&](int J, uint32_t a) {
                const uint32_t r0 = lds32(a), rp = lds32(a + 32), rm = lds32(a - 32);
                uint32_t r3;
                asm volatile("ld.volatile.shared.u32 %0, [%1];" : "=r"(r3) : "r"(a) : "memory");
#pragma unroll
                for (int I = J; I < 16; I++)
                    mma16816(acc[I], r0, rp, rm, r3, B[(I - J) >> 1][((I - J) & 1) * 2], B[(I - J) >> 1][((I - J) & 1) * 2 + 1]);
            };
#pragma unroll
            for (int J = 0; J < 4; J++) block(J, kb + j0 * 64 + J * 512);
            if (j0 < 2) { block(4, kb + j0 * 64 + 2048); block(8, kb + j0 * 64 + (544 + 16) * 4); }
        }
    }
    }
    {
        __syncwarp();
#pragma unroll
        for (int i = 0; i < 8; i++)
            stsm4t(rs + lf + i * 512, pack2(acc[2 * i][0], acc[2 * i][1]), pack2(acc[2 * i][2], acc[2 * i][3]),
                   pack2(acc[2 * i + 1][0], acc[2 * i + 1][1]), pack2(acc[2 * i + 1][2], acc[2 * i + 1][3]));
    }
    __syncthreads();
    {
        const uint2 dv = __ldg((const uint2*)(Dsk + d0 + 4 * t));
        bf16* dst = out + (size_t)(w * 128 + g) * 2048 + 1024 + d0 + 4 * t;
#pragma unroll
        for (int i = 0; i < 8; i++) {
            uint32_t y[4], x[4], o[4];
            ldsm4t(y, sb + S4_R + tr_off * S4_RS + (w * 128 + i * 16) * 2 + tr_l);
            ldsm4t(x, sb + S4_U + tr_off * S4_US + 256 + (w * 128 + i * 16) * 2 + tr_l);
#pragma unroll
            for (int j = 0; j < 4; j++)
                asm("{\n.reg .b32 s;\nmul.rn.bf16x2 s, %2, %3;\nadd.rn.bf16x2 %0, %1, s;\n}" : "=r"(o[j]) : "r"(y[j]), "r"(x[j]), "r"((j & 1) ? dv.y : dv.x));
            *reinterpret_cast<uint2*>(dst + (size_t)(i * 16) * 2048) = make_uint2(o[0], o[1]);
            *reinterpret_cast<uint2*>(dst + (size_t)(i * 16 + 8) * 2048) = make_uint2(o[2], o[3]);
        }
    }
    if (tid == 0) TLS(1);
    __syncthreads();
    }
}

enum { IT_QA = 0, IT_W256 = 1, IT_W128 = 2, IT_W64 = 3, IT_W64S = 4, IT_END = 7 };
struct BgParams { CUtensorMap mx, mwq, mkv, mkvm, mo, mo2, mo2s, mwo4, mwo2, mwo1; };
#define LOOK 8
#define NW0 4
#define NW1 16
#define PW1 20
#define P256 54
#define P128 56
__device__ __forceinline__ uint32_t ld_rlx32(const uint32_t* p) {
    uint32_t v;
    asm volatile("ld.relaxed.gpu.global.u32 %0, [%1];" : "=r"(v) : "l"(p) : "memory");
    return v;
}
#define NBT 9
#define NBL 9
constexpr uint32_t W_LONG = NBL * 16, W_LAST = NBT * 16, W_END = W_LAST + 32;
__device__ __forceinline__ bool block_done(uint32_t strip) { return ld_rlx32(g_flag + 64 + (strip < W_LAST ? strip >> 4 : 15)) >= 16; }
struct Sched { uint32_t qb = 0, w0 = 0, w1 = 0; };
__device__ __forceinline__ int next_item(Sched& z) {
    for (int n = 0; n < SPIN_LIMIT; n++) {
        if (z.w0 < z.w1 && (z.qb >= 16 || block_done(z.w0))) {
            const uint32_t i = z.w0, k = i >= W_LAST ? 1 : z.w1 - i >= 4 && !(i & 3) ? 4 : z.w1 - i >= 2 && !(i & 1) ? 2 : 1;
            z.w0 += k;
            if (i >= W_LAST) return IT_W64S | 15 << 3 | (i - W_LAST) << 7;
            return (k == 4 ? IT_W256 : k == 2 ? IT_W128 : IT_W64) | (i >> 4) << 3 | ((i & 15) / k) << 7;
        }
        uint32_t qa, wo, prog, wl;
        asm volatile("ld.relaxed.gpu.global.v4.u32 {%0,%1,%2,%3}, [%4];" : "=r"(qa), "=r"(wo), "=r"(prog), "=r"(wl) : "l"(g_flag + 96) : "memory");
        if (wo >= W_LAST) wo = W_LAST + wl;
        z.qb = qa >> 4;
        const bool wo_ready = z.w0 >= z.w1 && wo < W_END &&
                              (z.qb >= 16 || (wo < W_LONG && blockIdx.x < (prog < PW1 ? NW0 : NW1) && block_done(wo)));
        if (z.qb < 16 && prog + LOOK >= 4 * z.qb + 4 && !wo_ready) {
            const uint32_t i = atomicAdd(g_flag + 96, 1);
            if (i < 256) return IT_QA | (i >> 4) << 3 | (i & 15) << 7;
            continue;
        }
        if (z.w0 < z.w1) {
            if (z.qb >= 16) continue;
        } else if (wo >= W_END) {
            if (z.qb >= 16) return IT_END;
        } else if (wo_ready) {
            if (wo < W_LAST) {
                const uint32_t k = prog <= P256 ? 4 : prog <= P128 ? 2 : 1;
                z.w0 = atomicAdd(g_flag + 97, k);
                z.w1 = min(z.w0 + k, W_LAST);
            } else {
                z.w0 = W_LAST + atomicAdd(g_flag + 99, 1);
                z.w1 = min(z.w0 + 1, W_END);
            }
            continue;
        }
        __nanosleep(300);
    }
    __trap();
    return IT_END;
}
constexpr int B_OST = NSTAGE * STAGE_BYTES + 1024;
constexpr int BG_SMEM = B_OST + 32768;

template <int BM, int BN, int KPS, typename ACC>
__device__ __forceinline__ void gemm_mainloop(ACC& acc, const GemmSmem& g, int cw, int rounds, uint32_t& round) {
#pragma unroll
    for (int i = 0; i < BN / 2; i++) acc[i] = 0.f;
#pragma unroll 1
    for (int k0 = 0; k0 < rounds; k0++, round++) {
#pragma unroll
        for (int s = 0; s < 4; s++) {
            mbar_wait_u(g.full + 8 * s, round & 1);
            gemm_stage<BM, BN, KPS>(acc, g.st + s * STAGE_BYTES, cw, false);
            wg_wait<1>();
            if (s > 0 || k0 > 0) mbar_arrive_one(g.empty + 8 * ((s + 3) & 3), threadIdx.x & 31);
        }
    }
    wg_wait<0>();
    mbar_arrive_one(g.empty + 8 * 3, threadIdx.x & 31);
}

template <int BN>
__device__ __forceinline__ void store_tile(const float (&acc)[BN / 2], bf16* dst, int t) {
#pragma unroll
    for (int G = 0; G < BN / 32; G++)
#pragma unroll
        for (int rr = 0; rr < 2; rr++) {
            uint32_t r0 = pack2(acc[16 * G + 2 * rr], acc[16 * G + 2 * rr + 1]), r1 = pack2(acc[16 * G + 4 + 2 * rr], acc[16 * G + 5 + 2 * rr]);
            uint32_t r2 = pack2(acc[16 * G + 8 + 2 * rr], acc[16 * G + 9 + 2 * rr]), r3 = pack2(acc[16 * G + 12 + 2 * rr], acc[16 * G + 13 + 2 * rr]);
            quad_transpose(r0, r1, r2, r3, t);
            *reinterpret_cast<uint4*>(dst + (size_t)rr * 8 * 2048 + G * 32) = make_uint4(r0, r1, r2, r3);
        }
}

template <int BM, int BN, int KPS>
__device__ __forceinline__ void wo_item(const GemmSmem& g, int cw, uint32_t& round, bf16* dst, int t) {
    if (BM == 64 && cw == 1) {
#pragma unroll 1
        for (int k0 = 0; k0 < 16 / KPS; k0++, round++)
#pragma unroll
            for (int s = 0; s < 4; s++) { mbar_wait_u(g.full + 8 * s, round & 1); mbar_arrive_one(g.empty + 8 * s, threadIdx.x & 31); }
        return;
    }
    float acc[BN / 2];
    gemm_mainloop<BM, BN, KPS>(acc, g, cw, 16 / KPS, round);
    store_tile<BN>(acc, dst, t);
}

template <int HF>
__device__ __forceinline__ void attend(const uint32_t* q, uint32_t st, uint32_t sm, uint32_t ost, uint32_t bar_free, uint32_t parity, int lane) {
    constexpr int NT = HF ? 5 : 3;
    const int r8 = lane & 7, m4 = lane >> 3, gq = lane >> 2, t = lane & 3;
    const float sl2e = 0.08838834764831845f * 1.4426950408889634f;
    const uint32_t la = r8 * 128 + ((m4 ^ r8) << 4);
    float sc[NT][4];
#pragma unroll
    for (int nt = 0; nt < NT; nt++) sc[nt][0] = sc[nt][1] = sc[nt][2] = sc[nt][3] = 0.f;
#pragma unroll
    for (int kp = 0; kp < 4; kp++)
#pragma unroll
        for (int nt = 0; nt < NT; nt++) {
            uint32_t b[4];
            ldsm4(b, (nt == 0 ? sm + (kp >> 1) * 2048 : st + (kp >> 1) * 8192 + (nt - 1) * 1024) + (la ^ ((kp & 1) << 6)));
            mma16816(sc[nt], q[kp * 8], q[kp * 8 + 1], q[kp * 8 + 2], q[kp * 8 + 3], b[0], b[1]);
            mma16816(sc[nt], q[kp * 8 + 4], q[kp * 8 + 5], q[kp * 8 + 6], q[kp * 8 + 7], b[2], b[3]);
        }
    const float ninf = -3.0e38f;
    if (2 * t > gq) sc[NT - 2][0] = sc[NT - 1][2] = ninf;
    if (2 * t + 1 > gq) sc[NT - 2][1] = sc[NT - 1][3] = ninf;
    sc[NT - 1][0] = sc[NT - 1][1] = ninf;
    uint32_t p[NT][2];
#pragma unroll
    for (int i = 0; i < 2; i++) {
        float m = fmaxf(sc[0][2 * i], sc[0][2 * i + 1]);
#pragma unroll
        for (int nt = 1; nt < NT - 1 + i; nt++) m = fmaxf(m, fmaxf(sc[nt][2 * i], sc[nt][2 * i + 1]));
        m = fmaxf(m, __shfl_xor_sync(~0u, m, 1));
        m = fmaxf(m, __shfl_xor_sync(~0u, m, 2));
        const float ms = m * sl2e;
        float sum = 0.f;
#pragma unroll
        for (int nt = 0; nt < NT - 1 + i; nt++) {
            sc[nt][2 * i] = ex2(fmaf(sc[nt][2 * i], sl2e, -ms));
            sc[nt][2 * i + 1] = ex2(fmaf(sc[nt][2 * i + 1], sl2e, -ms));
            sum += sc[nt][2 * i] + sc[nt][2 * i + 1];
        }
        sum += __shfl_xor_sync(~0u, sum, 1);
        sum += __shfl_xor_sync(~0u, sum, 2);
        float inv;
        asm("rcp.approx.ftz.f32 %0, %1;" : "=f"(inv) : "f"(sum));
#pragma unroll
        for (int nt = 0; nt < NT - 1 + i; nt++) p[nt][i] = pack2(sc[nt][2 * i] * inv, sc[nt][2 * i + 1] * inv);
    }
    p[NT - 1][0] = 0;
    const uint32_t lv = ((m4 & 1) * 8 + r8) * 128 + (((m4 >> 1) ^ r8) << 4);
    mbar_wait_u(bar_free, parity);
#pragma unroll
    for (int G = 0; G < 4; G++) {
        float o[4][4];
#pragma unroll
        for (int i = 0; i < 4; i++) o[i][0] = o[i][1] = o[i][2] = o[i][3] = 0.f;
        uint32_t b[4];
        ldsm4t(b, sm + 4096 + (G >> 1) * 2048 + (la ^ ((G & 1) << 6)));
#pragma unroll
        for (int i = 0; i < 4; i++) mma1688(o[i], p[0][0], p[0][1], b[i]);
#pragma unroll
        for (int kk = 0; kk <= HF; kk++)
#pragma unroll
            for (int i = 0; i < 2; i++) {
                ldsm4t(b, st + 16384 + (G >> 1) * 8192 + kk * 2048 + (lv ^ (((G & 1) * 2 + i) << 5)));
                mma16816(o[2 * i], p[1 + 2 * kk][0], p[1 + 2 * kk][1], p[2 + 2 * kk][0], p[2 + 2 * kk][1], b[0], b[1]);
                mma16816(o[2 * i + 1], p[1 + 2 * kk][0], p[1 + 2 * kk][1], p[2 + 2 * kk][0], p[2 + 2 * kk][1], b[2], b[3]);
            }
#pragma unroll
        for (int i = 0; i < 2; i++)
            asm volatile("stmatrix.sync.aligned.m8n8.x4.shared.b16 [%0], {%1,%2,%3,%4};"
                         ::"r"(ost + (G >> 1) * 16384 + (lv ^ (((G & 1) * 2 + i) << 5))),
                           "r"(pack2(o[2 * i][0], o[2 * i][1])), "r"(pack2(o[2 * i][2], o[2 * i][3])),
                           "r"(pack2(o[2 * i + 1][0], o[2 * i + 1][1])), "r"(pack2(o[2 * i + 1][2], o[2 * i + 1][3])) : "memory");
    }
    asm volatile("fence.proxy.async.shared::cta;" ::: "memory");
    __syncwarp();
}

__device__ __forceinline__ void tma_prefetch3d(const CUtensorMap* m, int c0, int c1, int c2) {
    asm volatile("cp.async.bulk.prefetch.tensor.3d.L2.global [%0, {%1, %2, %3}];" ::"l"(m), "r"(c0), "r"(c1), "r"(c2) : "memory");
}

__global__ void __launch_bounds__(384, 1) k_bg(const __grid_constant__ BgParams P, bf16* __restrict__ out) {
    extern __shared__ __align__(1024) uint8_t smem_gemm[];
    asm volatile("griddepcontrol.launch_dependents;");
    const uint32_t xb = smem_u32(smem_gemm) + NSTAGE * STAGE_BYTES + 128;
    const uint32_t bar_item = xb, bar_o = xb + 16, bar_f = xb + 24, slot = xb + 32, slot_o = xb + 40;
    if (threadIdx.x == 0) { mbar_init(bar_item, 1); mbar_init(bar_item + 8, 1); mbar_init(bar_o, 8); mbar_init(bar_f, 1); }
    GemmSmem g = gemm_setup(smem_gemm, 8);
    const int wg = __shfl_sync(~0u, threadIdx.x >> 7, 0);
    if (wg == 0) {
        asm volatile("setmaxnreg.dec.sync.aligned.u32 40;");
        if (threadIdx.x == 0) {
            uint32_t it = 0;
            Sched z;
            wait_flag(g_flag + 98, 1);
            asm volatile("fence.proxy.async.global;" ::: "memory");
            auto acquire = [&](uint32_t bytes) {
                const int s = it & 3;
                mbar_wait(g.empty + 8 * s, ((it >> 2) & 1) ^ 1);
                mbar_expect_tx(g.full + 8 * s, bytes);
                it++;
                return s;
            };
            for (int n = 0;; n++) {
                const int code = next_item(z);
                sts32(slot + (n & 1) * 4, code);
                mbar_arrive(bar_item + (n & 1) * 8);
                const int type = code & 7, blk = (code >> 3) & 15, idx = code >> 7, m0 = blk * 128;
                if (type == IT_END) break;
                if (type == IT_QA) {
                    for (int k = 0; k < 16; k++) {
                        const int s = acquire(STAGE_BYTES);
                        const uint32_t st = g.st + s * STAGE_BYTES, fb = g.full + 8 * s;
                        tma2d(st, &P.mx, k * 64, m0, fb);
                        tma3d(st + 16384, &P.mwq, 0, k * 64, idx * 4, fb);
                        if (k >= 4 && k < 12) tma_prefetch3d(&P.mkv, 0, m0 + (k & 1) * 64, (k & 8) * 8 + idx * 4 + (k & 2));
                    }
                    bool ready = ld_acq32(g_flag + 2 * idx) >= 4 * blk + 4 && ld_acq32(g_flag + 2 * idx + 1) >= 4 * blk + 4;
                    if (ready) asm volatile("fence.proxy.async.global;" ::: "memory");
                    for (int pass = 0; pass < 2; pass++) {
                        for (int s = 0; s < 4; s++) {
                            const uint32_t st = g.st + s * STAGE_BYTES, fb = g.full + 8 * s;
                            if (pass == 0) {
                                acquire(40960);
                                tma3d(st, &P.mkv, 0, m0 + (s & 1) * 64, idx * 4 + (s & 2), fb);
                                tma3d(st + 16384, &P.mkv, 0, m0 + (s & 1) * 64, 64 + idx * 4 + (s & 2), fb);
                            }
                            if (ready) {
                                tma3d(st + 32768, &P.mkvm, 0, blk * 32 + (s & 1) * 16, idx * 4 + (s & 2), fb);
                                tma3d(st + 36864, &P.mkvm, 0, blk * 32 + (s & 1) * 16, 64 + idx * 4 + (s & 2), fb);
                            }
                        }
                        if (ready) break;
                        wait_flag(g_flag + 2 * idx, 4 * blk + 4);
                        wait_flag(g_flag + 2 * idx + 1, 4 * blk + 4);
                        asm volatile("fence.proxy.async.global;" ::: "memory");
                        ready = true;
                    }
                } else {
                    wait_flag(g_flag + 64 + blk, 16);
                    asm volatile("fence.proxy.async.global;" ::: "memory");
                    if (type <= IT_W128) {
                        const int nb = type == IT_W256 ? 4 : 2;
                        for (int k = 0; k < 64; k++) {
                            const int s = acquire(16384 + nb * 8192);
                            const uint32_t st = g.st + s * STAGE_BYTES, fb = g.full + 8 * s;
                            tma2d(st, &P.mo, k * 64, m0, fb);
                            tma3d(st + 16384, nb == 4 ? &P.mwo4 : &P.mwo2, 0, k * 64, idx * nb, fb);
                        }
                    } else {
                        const uint32_t ab = type == IT_W64 ? 32768 : 16384;
                        for (int k = 0; k < 32; k++) {
                            const int s = acquire(ab + 16384);
                            const uint32_t st = g.st + s * STAGE_BYTES, fb = g.full + 8 * s;
                            tma3d(st, type == IT_W64 ? &P.mo2 : &P.mo2s, 0, m0 + (idx >> 4) * 64, k * 2, fb);
                            tma3d(st + ab, &P.mwo1, 0, k * 128, idx & 15, fb);
                        }
                    }
                }
            }
        } else if (threadIdx.x == 32) {
            for (;;) {
                mbar_wait(bar_o, 0);
                const int code = lds32(slot_o), blk = (code >> 3) & 15, idx = (code >> 7) & 31;
                if ((code & 7) == IT_END) break;
                for (int hh = 0; hh < 2; hh++) {
                    if (hh) mbar_wait(bar_o, 1);
                    asm volatile("cp.async.bulk.tensor.3d.global.shared::cta.bulk_group [%0, {%2, %3, %4}], [%1];\n"
                                 "cp.async.bulk.commit_group;\ncp.async.bulk.wait_group.read 0;"
                                 ::"l"(&P.mo2), "r"(g.st + B_OST), "r"(0), "r"(blk * 128), "r"(idx * 4 + hh * 2) : "memory");
                    mbar_arrive(bar_f);
                }
                asm volatile("cp.async.bulk.wait_group 0;\nfence.acq_rel.gpu;\nred.relaxed.gpu.global.add.u32 [%0], 1;"
                             ::"l"(g_flag + 64 + blk) : "memory");
            }
        }
    } else {
        asm volatile("setmaxnreg.inc.sync.aligned.u32 232;");
        const int cw = wg - 1, ww = __shfl_sync(~0u, (threadIdx.x >> 5) & 3, 0), lane = threadIdx.x & 31;
        uint32_t round = 0;
#pragma unroll 1
        for (int n = 0;; n++) {
            mbar_wait_u(bar_item + (n & 1) * 8, (n >> 1) & 1);
            const int code = __shfl_sync(~0u, lds32(slot + (n & 1) * 4), 0);
            const int type = code & 7, blk = (code >> 3) & 15, idx = (code >> 7) & 31;
#define TLB(slot_)
            if (type == IT_END) {
                mbar_wait_u(bar_f, 1);
                if (threadIdx.x == 128) sts32(slot_o, IT_END);
                __syncwarp();
                mbar_arrive_one(bar_o, lane);
                break;
            }
            TLB(0);
            if (type == IT_QA) {
                uint32_t q[64];
                {
                    float acc[128];
                    gemm_mainloop<128, 256, 1>(acc, g, cw, 4, round);
#pragma unroll
                    for (int i = 0; i < 64; i++) q[i] = pack2(acc[2 * i], acc[2 * i + 1]);
                }
                if (threadIdx.x == 128) sts32(slot_o, code);
                TLB(2);
#pragma unroll
                for (int hh = 0; hh < 2; hh++) {
                    const uint32_t st = g.st + (2 * hh + cw) * STAGE_BYTES, ost = g.st + B_OST + (cw * 4 + ww) * 2048;
                    mbar_wait_u(g.full + 16 * hh, round & 1);
                    mbar_wait_u(g.full + 16 * hh + 8, round & 1);
                    if (hh == 0) { TLB(3); }
                    if (ww & 1) attend<1>(q + 32 * hh, st + (ww >> 1) * 4096, st + 32768 + (ww >> 1) * 1024, ost, bar_f, hh ^ 1, lane);
                    else attend<0>(q + 32 * hh, st + (ww >> 1) * 4096, st + 32768 + (ww >> 1) * 1024, ost, bar_f, hh ^ 1, lane);
                    mbar_arrive_one(bar_o, lane);
                    mbar_arrive_one(g.empty + 16 * hh, lane);
                    mbar_arrive_one(g.empty + 16 * hh + 8, lane);
                }
                round++;
            } else {
                bf16* dst = out + (size_t)(blk * 128 + cw * 64 + ww * 16 + (lane >> 2)) * 2048 + (lane & 3) * 8;
                if (type == IT_W256) wo_item<128, 256, 1>(g, cw, round, dst + idx * 256, lane & 3);
                else if (type == IT_W128) wo_item<128, 128, 1>(g, cw, round, dst + idx * 128, lane & 3);
                else if (type == IT_W64) wo_item<128, 64, 2>(g, cw, round, dst + idx * 64, lane & 3);
                else wo_item<64, 64, 2>(g, cw, round, dst + (size_t)(idx >> 4) * 64 * 2048 + (idx & 15) * 64, lane & 3);
            }
            TLB(1);
        }
    }
}

#define TCL 6
__global__ void __cluster_dims__(TCL, 1, 1) __launch_bounds__(384, 1)
k_tail(const __grid_constant__ CUtensorMap mo, const __grid_constant__ CUtensorMap mwo2, bf16* __restrict__ out) {
    extern __shared__ __align__(1024) uint8_t smem_gemm[];
    const uint32_t bar_s = smem_u32(smem_gemm) + NSTAGE * STAGE_BYTES + 128;
    if (threadIdx.x == 0) { TL(4, 0); mbar_init(bar_s, 1); mbar_expect_tx(bar_s, 32768); }
    GemmSmem g = gemm_setup(smem_gemm, 8);
    asm volatile("barrier.cluster.arrive.relaxed.aligned;" ::: "memory");
    const int half = blockIdx.x & 1, cl = blockIdx.x / 6, peer = TCL == 6 ? (blockIdx.x - 6 * cl) ^ 1 : half ^ 1;
    const int blk = TCL == 6 ? NBT + (cl >> 3) * 3 + (peer >> 1) : NBT + (blockIdx.x >> 4), idx = TCL == 6 ? cl & 7 : (blockIdx.x >> 1) & 7;
    const int wg = __shfl_sync(~0u, threadIdx.x >> 7, 0);
    if (wg == 0) {
        if (threadIdx.x == 0) {
            wait_flag(g_flag + 64 + blk, 16);
            asm volatile("fence.proxy.async.global;" ::: "memory");
            for (int k = 0; k < 32; k++) {
                const int s = k & 3;
                const uint32_t st = g.st + s * STAGE_BYTES, fb = g.full + 8 * s;
                mbar_wait(g.empty + 8 * s, ((k >> 2) & 1) ^ 1);
                mbar_expect_tx(fb, 32768);
                tma2d(st, &mo, (half * 32 + k) * 64, blk * 128, fb);
                tma3d(st + 16384, &mwo2, 0, (half * 32 + k) * 64, idx * 2, fb);
            }
        }
        __syncwarp();
        asm volatile("barrier.cluster.wait.aligned;" ::: "memory");
    } else {
        const int cw = wg - 1, lane = threadIdx.x & 31, t = lane & 3;
        float acc[64];
        uint32_t round = 0;
        gemm_mainloop<128, 128, 1>(acc, g, cw, 8, round);
        asm volatile("barrier.cluster.wait.aligned;" ::: "memory");
        const uint32_t xa = g.st + B_OST + (threadIdx.x & 127) * 16;
        if (cw != half) {
            uint32_t ra, rb;
            asm("mapa.shared::cluster.u32 %0, %1, %2;" : "=r"(ra) : "r"(xa), "r"(peer));
            asm("mapa.shared::cluster.u32 %0, %1, %2;" : "=r"(rb) : "r"(bar_s), "r"(peer));
#pragma unroll
            for (int i = 0; i < 16; i++)
                asm volatile("st.async.weak.shared::cluster.mbarrier::complete_tx::bytes.v4.f32 [%0], {%1,%2,%3,%4}, [%5];"
                             ::"r"(ra + i * 2048), "f"(acc[4 * i]), "f"(acc[4 * i + 1]), "f"(acc[4 * i + 2]), "f"(acc[4 * i + 3]), "r"(rb) : "memory");
        } else {
            mbar_wait_u(bar_s, 0);
#pragma unroll
            for (int i = 0; i < 16; i++) {
                const float4 v = lds128f(xa + i * 2048);
                acc[4 * i] += v.x; acc[4 * i + 1] += v.y; acc[4 * i + 2] += v.z; acc[4 * i + 3] += v.w;
            }
            store_tile<128>(acc, out + (size_t)(blk * 128 + cw * 64 + ((threadIdx.x >> 5) & 3) * 16 + (lane >> 2)) * 2048 + idx * 128 + t * 8, t);
            if ((threadIdx.x & 127) == 0) TL(4, 1);
        }
    }
    asm volatile("barrier.cluster.arrive.relaxed.aligned;\nbarrier.cluster.wait.aligned;" ::: "memory");
}

typedef CUresult (*EncodeFn)(CUtensorMap*, CUtensorMapDataType, cuuint32_t, void*, const cuuint64_t*, const cuuint64_t*,
                             const cuuint32_t*, const cuuint32_t*, CUtensorMapInterleave, CUtensorMapSwizzle,
                             CUtensorMapL2promotion, CUtensorMapFloatOOBfill);

static void map2d(EncodeFn enc, CUtensorMap* m, const void* p, int rows, int cols, int box_rows) {
    cuuint64_t dim[2] = {(cuuint64_t)cols, (cuuint64_t)rows}, str[1] = {(cuuint64_t)cols * 2};
    cuuint32_t box[2] = {64, (cuuint32_t)box_rows}, es[2] = {1, 1};
    enc(m, CU_TENSOR_MAP_DATA_TYPE_BFLOAT16, 2, (void*)p, dim, str, box, es, CU_TENSOR_MAP_INTERLEAVE_NONE,
        CU_TENSOR_MAP_SWIZZLE_128B, CU_TENSOR_MAP_L2_PROMOTION_L2_256B, CU_TENSOR_MAP_FLOAT_OOB_FILL_NONE);
}
static void map3d(EncodeFn enc, CUtensorMap* m, const void* p, int rows, int cols, int box_rows, int nblk) {
    cuuint64_t dim[3] = {64, (cuuint64_t)rows, (cuuint64_t)cols / 64}, str[2] = {(cuuint64_t)cols * 2, 128};
    cuuint32_t box[3] = {64, (cuuint32_t)box_rows, (cuuint32_t)nblk}, es[3] = {1, 1, 1};
    enc(m, CU_TENSOR_MAP_DATA_TYPE_BFLOAT16, 3, (void*)p, dim, str, box, es, CU_TENSOR_MAP_INTERLEAVE_NONE,
        CU_TENSOR_MAP_SWIZZLE_128B, CU_TENSOR_MAP_L2_PROMOTION_L2_256B, CU_TENSOR_MAP_FLOAT_OOB_FILL_NONE);
}

#define USE_PDL 1

extern "C" void kernel_launch(void* const* d_in, const int* in_sizes, int n_in, void* d_out, int out_size) {
    const bf16 *x = (const bf16*)d_in[0], *mem0 = (const bf16*)d_in[1], *Wq = (const bf16*)d_in[2], *Wk = (const bf16*)d_in[3];
    const bf16 *Wv = (const bf16*)d_in[4], *Wo = (const bf16*)d_in[5];
    const bf16 *u = (const bf16*)d_in[7], *Are = (const bf16*)d_in[8], *Aim = (const bf16*)d_in[9], *Bre = (const bf16*)d_in[10];
    const bf16 *Bim = (const bf16*)d_in[11], *Cre = (const bf16*)d_in[12], *Cim = (const bf16*)d_in[13];
    const bf16 *logdt = (const bf16*)d_in[14], *Dsk = (const bf16*)d_in[15];
    bf16* out = (bf16*)d_out;

    void* fn = nullptr;
    cudaDriverEntryPointQueryResult qr;
    cudaGetDriverEntryPoint("cuTensorMapEncodeTiled", &fn, cudaEnableDefault, &qr);
    EncodeFn enc = (EncodeFn)fn;
    void *kv, *kvm, *o;
    cudaGetSymbolAddress(&kv, g_kv);
    cudaGetSymbolAddress(&kvm, g_kvm);
    cudaGetSymbolAddress(&o, g_o);
    CUtensorMap mwk, mwv, mkv2;
    BgParams P;
    map2d(enc, &P.mx, x, SEQ, DM, 128);
    map2d(enc, &P.mo, o, SEQ, HD, 128);
    map3d(enc, &P.mo2, o, SEQ, HD, 128, 2);
    map3d(enc, &P.mo2s, o, SEQ, HD, 64, 2);
    map3d(enc, &P.mwq, Wq, DM, HD, 64, 4);
    map3d(enc, &mwk, Wk, DM, HD, 64, 2);
    map3d(enc, &mwv, Wv, DM, HD, 64, 2);
    map3d(enc, &P.mwo4, Wo, HD, DM, 64, 4);
    map3d(enc, &P.mwo2, Wo, HD, DM, 64, 2);
    map3d(enc, &P.mwo1, Wo, HD, DM, 128, 1);
    map3d(enc, &mkv2, kv, SEQ, 8192, 32, 2);
    map3d(enc, &P.mkv, kv, SEQ, 8192, 64, 2);
    map3d(enc, &P.mkvm, kvm, NSEG * 8, 8192, 16, 2);
    cudaFuncSetAttribute(k_kv, cudaFuncAttributeMaxDynamicSharedMemorySize, GEMM_SMEM);
    cudaFuncSetAttribute(k_bg, cudaFuncAttributeMaxDynamicSharedMemorySize, BG_SMEM);
    cudaFuncSetAttribute(k_tail, cudaFuncAttributeMaxDynamicSharedMemorySize, BG_SMEM);
    cudaFuncSetAttribute(k_chain, cudaFuncAttributeMaxDynamicSharedMemorySize, CHAIN_SMEM);
    cudaFuncSetAttribute(k_s4, cudaFuncAttributeMaxDynamicSharedMemorySize, S4_SMEM);

    cudaStream_t st = cudaStreamPerThread;
    cudaLaunchAttribute pdl[2], cls[1];
    pdl[0].id = cudaLaunchAttributeProgrammaticStreamSerialization;
    pdl[0].val.programmaticStreamSerializationAllowed = 1;
    cls[0].id = cudaLaunchAttributeClusterDimension;
    cls[0].val.clusterDim.x = CLS; cls[0].val.clusterDim.y = 1; cls[0].val.clusterDim.z = 1;
    cudaLaunchConfig_t cfg = {};
    cfg.stream = st; cfg.attrs = cls; cfg.numAttrs = 1;
    cfg.gridDim = dim3(96); cfg.blockDim = dim3(384); cfg.dynamicSmemBytes = GEMM_SMEM;
    cudaLaunchKernelEx(&cfg, k_kv, P.mx, mwk, mwv, Wq, Wk, Wo, 0);
    pdl[1] = cls[0]; pdl[1].val.clusterDim.x = 2;
    cfg.attrs = pdl; cfg.numAttrs = 2;
    cfg.gridDim = dim3(36);
    cudaLaunchKernelEx(&cfg, k_kv, P.mx, mwk, mwv, Wq, Wk, Wo, 96);
    cfg.numAttrs = 1;
    cfg.gridDim = dim3(96); cfg.blockDim = dim3(256); cfg.dynamicSmemBytes = CHAIN_SMEM;
    cudaLaunchKernelEx(&cfg, k_chain, mem0, Wq, Wk, Wv, Wo, mkv2);
    cfg.numAttrs = USE_PDL;
    cfg.gridDim = dim3(36); cfg.blockDim = dim3(512); cfg.dynamicSmemBytes = S4_SMEM;
    cudaLaunchKernelEx(&cfg, k_s4, u, Are, Aim, Bre, Bim, Cre, Cim, logdt, Dsk, out);
    cfg.gridDim = dim3(36); cfg.blockDim = dim3(384); cfg.dynamicSmemBytes = BG_SMEM;
    cudaLaunchKernelEx(&cfg, k_bg, P, out);
    cfg.gridDim = dim3((15 - NBT) * 16);
    cudaLaunchKernelEx(&cfg, k_tail, P.mo, P.mwo2, out);
}
```

```cpp
#include <cuda_runtime.h>
#include <cuda_bf16.h>
#include <cuda.h>
#include <stdint.h>

typedef __nv_bfloat16 bf16;

constexpr int SEQ = 2048, DM = 1024, HD = 4096, NSEG = 64;

__device__ __align__(1024) bf16 g_kv[(size_t)SEQ * 8192];
__device__ __align__(1024) bf16 g_kvm[(size_t)NSEG * 8 * 8192];
__device__ __align__(1024) bf16 g_o[(size_t)SEQ * HD];
constexpr int XPAIRS = 128 + NSEG * 4;
__device__ __align__(8192) uint2 g_x[XPAIRS * 1024];
__device__ uint32_t g_home[XPAIRS];
__device__ uint32_t g_side[256];
__device__ __align__(1024) uint32_t g_flag[256];

#define TL(kern, slot)

__device__ __forceinline__ uint32_t smem_u32(const void* p) { return (uint32_t)__cvta_generic_to_shared(p); }
__device__ __forceinline__ void mbar_init(uint32_t bar, uint32_t cnt) {
    asm volatile("mbarrier.init.shared::cta.b64 [%0], %1;" ::"r"(bar), "r"(cnt) : "memory");
}
__device__ __forceinline__ void mbar_expect_tx(uint32_t bar, uint32_t bytes) {
    asm volatile("mbarrier.arrive.expect_tx.shared::cta.b64 _, [%0], %1;" ::"r"(bar), "r"(bytes) : "memory");
}
__device__ __forceinline__ void mbar_arrive(uint32_t bar) {
    asm volatile("mbarrier.arrive.shared::cta.b64 _, [%0];" ::"r"(bar) : "memory");
}
__device__ __forceinline__ bool mbar_try(uint32_t bar, uint32_t parity) {
    uint32_t ok;
    asm volatile("{\n.reg .pred p;\nmbarrier.try_wait.parity.shared::cta.b64 p, [%1], %2;\nselp.u32 %0, 1, 0, p;\n}"
                 : "=r"(ok) : "r"(bar), "r"(parity) : "memory");
    return ok;
}
constexpr int SPIN_LIMIT = 1 << 20;
__device__ __forceinline__ void mbar_wait(uint32_t bar, uint32_t parity) {
    int n = 0;
    while (!mbar_try(bar, parity)) { if (++n > SPIN_LIMIT) __trap(); }
}
__device__ __forceinline__ void mbar_wait_u(uint32_t bar, uint32_t parity) {
    asm volatile("{\n.reg .pred p;\n.reg .u32 n;\n"
                 "mbarrier.try_wait.parity.shared::cta.b64 p, [%0], %1;\n@p bra.uni DONE;\nmov.u32 n, 0;\n"
                 "AGAIN:\nmbarrier.try_wait.parity.shared::cta.b64 p, [%0], %1;\n@p bra.uni DONE;\n"
                 "add.u32 n, n, 1;\nsetp.lt.u32 p, n, 0x100000;\n@p bra.uni AGAIN;\ntrap;\nDONE:\n}"
                 ::"r"(bar), "r"(parity) : "memory");
}
__device__ __forceinline__ void tma2d(uint32_t dst, const CUtensorMap* m, int c0, int c1, uint32_t bar) {
    asm volatile("cp.async.bulk.tensor.2d.shared::cluster.global.mbarrier::complete_tx::bytes [%0], [%1, {%3, %4}], [%2];"
                 ::"r"(dst), "l"(m), "r"(bar), "r"(c0), "r"(c1) : "memory");
}
__device__ __forceinline__ void tma3d(uint32_t dst, const CUtensorMap* m, int c0, int c1, int c2, uint32_t bar) {
    asm volatile("cp.async.bulk.tensor.3d.shared::cluster.global.mbarrier::complete_tx::bytes [%0], [%1, {%3, %4, %5}], [%2];"
                 ::"r"(dst), "l"(m), "r"(bar), "r"(c0), "r"(c1), "r"(c2) : "memory");
}
__device__ __forceinline__ uint32_t pack2(float lo, float hi) {
    uint32_t r;
    asm("cvt.rn.bf16x2.f32 %0, %1, %2;" : "=r"(r) : "f"(hi), "f"(lo));
    return r;
}
__device__ __forceinline__ float bf_lo(uint32_t v) { return __uint_as_float(v << 16); }
__device__ __forceinline__ float bf_hi(uint32_t v) { return __uint_as_float(v & 0xffff0000u); }
__device__ __forceinline__ float bf_round(float x) { return bf_lo(pack2(x, 0.f)); }
__device__ __forceinline__ float ex2(float x) { float y; asm("ex2.approx.ftz.f32 %0, %1;" : "=f"(y) : "f"(x)); return y; }
__device__ __forceinline__ void mma16816(float (&c)[4], uint32_t a0, uint32_t a1, uint32_t a2, uint32_t a3, uint32_t b0, uint32_t b1) {
    asm volatile("mma.sync.aligned.m16n8k16.row.col.f32.bf16.bf16.f32 {%0,%1,%2,%3}, {%4,%5,%6,%7}, {%8,%9}, {%0,%1,%2,%3};"
                 : "+f"(c[0]), "+f"(c[1]), "+f"(c[2]), "+f"(c[3]) : "r"(a0), "r"(a1), "r"(a2), "r"(a3), "r"(b0), "r"(b1));
}
__device__ __forceinline__ void mma1688(float (&c)[4], uint32_t a0, uint32_t a1, uint32_t b0) {
    asm volatile("mma.sync.aligned.m16n8k8.row.col.f32.bf16.bf16.f32 {%0,%1,%2,%3}, {%4,%5}, {%6}, {%0,%1,%2,%3};"
                 : "+f"(c[0]), "+f"(c[1]), "+f"(c[2]), "+f"(c[3]) : "r"(a0), "r"(a1), "r"(b0));
}
__device__ __forceinline__ void ldsm4(uint32_t (&r)[4], uint32_t a) {
    asm volatile("ldmatrix.sync.aligned.m8n8.x4.shared.b16 {%0,%1,%2,%3}, [%4];"
                 : "=r"(r[0]), "=r"(r[1]), "=r"(r[2]), "=r"(r[3]) : "r"(a) : "memory");
}
__device__ __forceinline__ void ldsm4t(uint32_t (&r)[4], uint32_t a) {
    asm volatile("ldmatrix.sync.aligned.m8n8.x4.trans.shared.b16 {%0,%1,%2,%3}, [%4];"
                 : "=r"(r[0]), "=r"(r[1]), "=r"(r[2]), "=r"(r[3]) : "r"(a) : "memory");
}
__device__ __forceinline__ void ldsm2t(uint32_t& r0, uint32_t& r1, uint32_t a) {
    asm volatile("ldmatrix.sync.aligned.m8n8.x2.trans.shared.b16 {%0,%1}, [%2];" : "=r"(r0), "=r"(r1) : "r"(a) : "memory");
}
__device__ __forceinline__ void stsm4t(uint32_t a, uint32_t r0, uint32_t r1, uint32_t r2, uint32_t r3) {
    asm volatile("stmatrix.sync.aligned.m8n8.x4.trans.shared.b16 [%0], {%1,%2,%3,%4};"
                 ::"r"(a), "r"(r0), "r"(r1), "r"(r2), "r"(r3) : "memory");
}
__device__ __forceinline__ void lds128(uint32_t (&r)[4], uint32_t a) {
    asm volatile("ld.shared.v4.u32 {%0,%1,%2,%3}, [%4];" : "=r"(r[0]), "=r"(r[1]), "=r"(r[2]), "=r"(r[3]) : "r"(a) : "memory");
}
__device__ __forceinline__ float4 lds128f(uint32_t a) {
    float4 v;
    asm volatile("ld.shared.v4.f32 {%0,%1,%2,%3}, [%4];" : "=f"(v.x), "=f"(v.y), "=f"(v.z), "=f"(v.w) : "r"(a) : "memory");
    return v;
}
__device__ __forceinline__ float2 lds64f(uint32_t a) {
    float2 v;
    asm volatile("ld.shared.v2.f32 {%0,%1}, [%2];" : "=f"(v.x), "=f"(v.y) : "r"(a) : "memory");
    return v;
}
__device__ __forceinline__ uint32_t lds32(uint32_t a) {
    uint32_t v;
    asm volatile("ld.shared.u32 %0, [%1];" : "=r"(v) : "r"(a) : "memory");
    return v;
}
__device__ __forceinline__ void sts128(uint32_t a, uint32_t r0, uint32_t r1, uint32_t r2, uint32_t r3) {
    asm volatile("st.shared.v4.u32 [%0], {%1,%2,%3,%4};" ::"r"(a), "r"(r0), "r"(r1), "r"(r2), "r"(r3) : "memory");
}
__device__ __forceinline__ void sts128f(uint32_t a, float r0, float r1, float r2, float r3) {
    asm volatile("st.shared.v4.f32 [%0], {%1,%2,%3,%4};" ::"r"(a), "f"(r0), "f"(r1), "f"(r2), "f"(r3) : "memory");
}
__device__ __forceinline__ void sts64(uint32_t a, uint32_t r0, uint32_t r1) {
    asm volatile("st.shared.v2.u32 [%0], {%1,%2};" ::"r"(a), "r"(r0), "r"(r1) : "memory");
}
__device__ __forceinline__ void sts64f(uint32_t a, float r0, float r1) {
    asm volatile("st.shared.v2.f32 [%0], {%1,%2};" ::"r"(a), "f"(r0), "f"(r1) : "memory");
}
__device__ __forceinline__ void sts32f(uint32_t a, float r0) {
    asm volatile("st.shared.f32 [%0], %1;" ::"r"(a), "f"(r0) : "memory");
}
__device__ __forceinline__ uint2 ld_rlx64(const uint2* p) {
    uint2 v;
    asm volatile("{\n.reg .b64 t;\nld.relaxed.gpu.global.b64 t, [%2];\nmov.b64 {%0,%1}, t;\n}" : "=r"(v.x), "=r"(v.y) : "l"(p) : "memory");
    return v;
}
__device__ __forceinline__ void st_rlx64(uint2* p, uint32_t x, uint32_t y) {
    asm volatile("{\n.reg .b64 t;\nmov.b64 t, {%1,%2};\nst.relaxed.gpu.global.b64 [%0], t;\n}" ::"l"(p), "r"(x), "r"(y) : "memory");
}
__device__ __forceinline__ uint32_t ld_acq32(const uint32_t* p) {
    uint32_t v;
    asm volatile("ld.acquire.gpu.global.u32 %0, [%1];" : "=r"(v) : "l"(p) : "memory");
    return v;
}
__device__ __forceinline__ void wait_flag(const uint32_t* p, uint32_t need) {
    int n = 0;
    while (ld_acq32(p) < need) { __nanosleep(200); if (++n > SPIN_LIMIT) __trap(); }
}
__device__ __forceinline__ void bar_sync(int id, int n) { asm volatile("bar.sync %0, %1;" ::"r"(id), "r"(n) : "memory"); }
__device__ __forceinline__ void wg_fence() { asm volatile("wgmma.fence.sync.aligned;" ::: "memory"); }
__device__ __forceinline__ void wg_commit() { asm volatile("wgmma.commit_group.sync.aligned;" ::: "memory"); }
template <int N> __device__ __forceinline__ void wg_wait() { asm volatile("wgmma.wait_group.sync.aligned %0;" ::"n"(N) : "memory"); }
__device__ __forceinline__ uint64_t desc_sw128(uint32_t addr, uint32_t lbo, uint32_t sbo) {
    return (uint64_t)((addr & 0x3FFFF) >> 4) | ((uint64_t)(lbo >> 4) << 16) | ((uint64_t)(sbo >> 4) << 32) | (1ull << 62);
}
__device__ __forceinline__ void quad_transpose(uint32_t& r0, uint32_t& r1, uint32_t& r2, uint32_t& r3, int t) {
    const bool o = t & 1, h = t & 2;
    uint32_t s0 = __shfl_xor_sync(~0u, o ? r0 : r1, 1), s1 = __shfl_xor_sync(~0u, o ? r2 : r3, 1);
    uint32_t a0 = o ? s0 : r0, a1 = o ? r1 : s0, a2 = o ? s1 : r2, a3 = o ? r3 : s1;
    s0 = __shfl_xor_sync(~0u, h ? a0 : a2, 2); s1 = __shfl_xor_sync(~0u, h ? a1 : a3, 2);
    r0 = h ? s0 : a0; r1 = h ? s1 : a1; r2 = h ? a2 : s0; r3 = h ? a3 : s1;
}

__device__ __forceinline__ void wgmma_n256(float (&d)[128], uint64_t da, uint64_t db, int sd) {
    asm volatile("{\n.reg .pred p;\nsetp.ne.b32 p, %130, 0;\n"
        "wgmma.mma_async.sync.aligned.m64n256k16.f32.bf16.bf16 "
        "{%0,%1,%2,%3,%4,%5,%6,%7,%8,%9,%10,%11,%12,%13,%14,%15,"
        "%16,%17,%18,%19,%20,%21,%22,%23,%24,%25,%26,%27,%28,%29,%30,%31,"
        "%32,%33,%34,%35,%36,%37,%38,%39,%40,%41,%42,%43,%44,%45,%46,%47,"
        "%48,%49,%50,%51,%52,%53,%54,%55,%56,%57,%58,%59,%60,%61,%62,%63,"
        "%64,%65,%66,%67,%68,%69,%70,%71,%72,%73,%74,%75,%76,%77,%78,%79,"
        "%80,%81,%82,%83,%84,%85,%86,%87,%88,%89,%90,%91,%92,%93,%94,%95,"
        "%96,%97,%98,%99,%100,%101,%102,%103,%104,%105,%106,%107,%108,%109,%110,%111,"
        "%112,%113,%114,%115,%116,%117,%118,%119,%120,%121,%122,%123,%124,%125,%126,%127}, %128, %129, p, 1, 1, 0, 1;\n}\n"
        : "+f"(d[0]), "+f"(d[1]), "+f"(d[2]), "+f"(d[3]), "+f"(d[4]), "+f"(d[5]), "+f"(d[6]), "+f"(d[7]),
          "+f"(d[8]), "+f"(d[9]), "+f"(d[10]), "+f"(d[11]), "+f"(d[12]), "+f"(d[13]), "+f"(d[14]), "+f"(d[15]),
          "+f"(d[16]), "+f"(d[17]), "+f"(d[18]), "+f"(d[19]), "+f"(d[20]), "+f"(d[21]), "+f"(d[22]), "+f"(d[23]),
          "+f"(d[24]), "+f"(d[25]), "+f"(d[26]), "+f"(d[27]), "+f"(d[28]), "+f"(d[29]), "+f"(d[30]), "+f"(d[31]),
          "+f"(d[32]), "+f"(d[33]), "+f"(d[34]), "+f"(d[35]), "+f"(d[36]), "+f"(d[37]), "+f"(d[38]), "+f"(d[39]),
          "+f"(d[40]), "+f"(d[41]), "+f"(d[42]), "+f"(d[43]), "+f"(d[44]), "+f"(d[45]), "+f"(d[46]), "+f"(d[47]),
          "+f"(d[48]), "+f"(d[49]), "+f"(d[50]), "+f"(d[51]), "+f"(d[52]), "+f"(d[53]), "+f"(d[54]), "+f"(d[55]),
          "+f"(d[56]), "+f"(d[57]), "+f"(d[58]), "+f"(d[59]), "+f"(d[60]), "+f"(d[61]), "+f"(d[62]), "+f"(d[63]),
          "+f"(d[64]), "+f"(d[65]), "+f"(d[66]), "+f"(d[67]), "+f"(d[68]), "+f"(d[69]), "+f"(d[70]), "+f"(d[71]),
          "+f"(d[72]), "+f"(d[73]), "+f"(d[74]), "+f"(d[75]), "+f"(d[76]), "+f"(d[77]), "+f"(d[78]), "+f"(d[79]),
          "+f"(d[80]), "+f"(d[81]), "+f"(d[82]), "+f"(d[83]), "+f"(d[84]), "+f"(d[85]), "+f"(d[86]), "+f"(d[87]),
          "+f"(d[88]), "+f"(d[89]), "+f"(d[90]), "+f"(d[91]), "+f"(d[92]), "+f"(d[93]), "+f"(d[94]), "+f"(d[95]),
          "+f"(d[96]), "+f"(d[97]), "+f"(d[98]), "+f"(d[99]), "+f"(d[100]), "+f"(d[101]), "+f"(d[102]), "+f"(d[103]),
          "+f"(d[104]), "+f"(d[105]), "+f"(d[106]), "+f"(d[107]), "+f"(d[108]), "+f"(d[109]), "+f"(d[110]), "+f"(d[111]),
          "+f"(d[112]), "+f"(d[113]), "+f"(d[114]), "+f"(d[115]), "+f"(d[116]), "+f"(d[117]), "+f"(d[118]), "+f"(d[119]),
          "+f"(d[120]), "+f"(d[121]), "+f"(d[122]), "+f"(d[123]), "+f"(d[124]), "+f"(d[125]), "+f"(d[126]), "+f"(d[127])
        : "l"(da), "l"(db), "r"(sd));
}

__device__ __forceinline__ void wgmma_n128(float (&d)[64], uint64_t da, uint64_t db, int sd) {
    asm volatile("{\n.reg .pred p;\nsetp.ne.b32 p, %66, 0;\n"
        "wgmma.mma_async.sync.aligned.m64n128k16.f32.bf16.bf16 "
        "{%0,%1,%2,%3,%4,%5,%6,%7,%8,%9,%10,%11,%12,%13,%14,%15,"
        "%16,%17,%18,%19,%20,%21,%22,%23,%24,%25,%26,%27,%28,%29,%30,%31,"
        "%32,%33,%34,%35,%36,%37,%38,%39,%40,%41,%42,%43,%44,%45,%46,%47,"
        "%48,%49,%50,%51,%52,%53,%54,%55,%56,%57,%58,%59,%60,%61,%62,%63}, %64, %65, p, 1, 1, 0, 1;\n}\n"
        : "+f"(d[0]), "+f"(d[1]), "+f"(d[2]), "+f"(d[3]), "+f"(d[4]), "+f"(d[5]), "+f"(d[6]), "+f"(d[7]),
          "+f"(d[8]), "+f"(d[9]), "+f"(d[10]), "+f"(d[11]), "+f"(d[12]), "+f"(d[13]), "+f"(d[14]), "+f"(d[15]),
          "+f"(d[16]), "+f"(d[17]), "+f"(d[18]), "+f"(d[19]), "+f"(d[20]), "+f"(d[21]), "+f"(d[22]), "+f"(d[23]),
          "+f"(d[24]), "+f"(d[25]), "+f"(d[26]), "+f"(d[27]), "+f"(d[28]), "+f"(d[29]), "+f"(d[30]), "+f"(d[31]),
          "+f"(d[32]), "+f"(d[33]), "+f"(d[34]), "+f"(d[35]), "+f"(d[36]), "+f"(d[37]), "+f"(d[38]), "+f"(d[39]),
          "+f"(d[40]), "+f"(d[41]), "+f"(d[42]), "+f"(d[43]), "+f"(d[44]), "+f"(d[45]), "+f"(d[46]), "+f"(d[47]),
          "+f"(d[48]), "+f"(d[49]), "+f"(d[50]), "+f"(d[51]), "+f"(d[52]), "+f"(d[53]), "+f"(d[54]), "+f"(d[55]),
          "+f"(d[56]), "+f"(d[57]), "+f"(d[58]), "+f"(d[59]), "+f"(d[60]), "+f"(d[61]), "+f"(d[62]), "+f"(d[63])
        : "l"(da), "l"(db), "r"(sd));
}

__device__ __forceinline__ void wgmma_n64(float (&d)[32], uint64_t da, uint64_t db, int sd) {
    asm volatile("{\n.reg .pred p;\nsetp.ne.b32 p, %34, 0;\n"
        "wgmma.mma_async.sync.aligned.m64n64k16.f32.bf16.bf16 "
        "{%0,%1,%2,%3,%4,%5,%6,%7,%8,%9,%10,%11,%12,%13,%14,%15,"
        "%16,%17,%18,%19,%20,%21,%22,%23,%24,%25,%26,%27,%28,%29,%30,%31}, %32, %33, p, 1, 1, 0, 1;\n}\n"
        : "+f"(d[0]), "+f"(d[1]), "+f"(d[2]), "+f"(d[3]), "+f"(d[4]), "+f"(d[5]), "+f"(d[6]), "+f"(d[7]),
          "+f"(d[8]), "+f"(d[9]), "+f"(d[10]), "+f"(d[11]), "+f"(d[12]), "+f"(d[13]), "+f"(d[14]), "+f"(d[15]),
          "+f"(d[16]), "+f"(d[17]), "+f"(d[18]), "+f"(d[19]), "+f"(d[20]), "+f"(d[21]), "+f"(d[22]), "+f"(d[23]),
          "+f"(d[24]), "+f"(d[25]), "+f"(d[26]), "+f"(d[27]), "+f"(d[28]), "+f"(d[29]), "+f"(d[30]), "+f"(d[31])
        : "l"(da), "l"(db), "r"(sd));
}

constexpr int STAGE_BYTES = 49152, NSTAGE = 4;
constexpr int GEMM_SMEM = NSTAGE * STAGE_BYTES + 128;

struct GemmSmem { uint32_t st, full, empty; };
__device__ __forceinline__ GemmSmem gemm_setup(uint8_t* raw, int releases) {
    GemmSmem g;
    g.st = smem_u32(raw);
    if (g.st & 1023) __trap();
    g.full = g.st + NSTAGE * STAGE_BYTES; g.empty = g.full + 64;
    if (threadIdx.x == 0) {
        for (int s = 0; s < NSTAGE; s++) { mbar_init(g.full + 8 * s, 1); mbar_init(g.empty + 8 * s, releases); }
        asm volatile("fence.mbarrier_init.release.cluster;" ::: "memory");
        asm volatile("fence.proxy.async.shared::cta;" ::: "memory");
    }
    __syncthreads();
    return g;
}
__device__ __forceinline__ void mbar_arrive_one(uint32_t bar, uint32_t who) {
    asm volatile("{\n.reg .pred p;\nsetp.eq.u32 p, %1, 0;\n@p mbarrier.arrive.shared::cta.b64 _, [%0];\n}" ::"r"(bar), "r"(who) : "memory");
}
template <int BM, int BN, int KPS, typename ACC>
__device__ __forceinline__ void gemm_stage(ACC& acc, uint32_t stage, int wg, bool first) {
    const uint64_t da = desc_sw128(stage + wg * 8192, 16, 1024);
    const uint64_t db = desc_sw128(stage + KPS * BM * 128, 8192, 1024);
    wg_fence();
#pragma unroll
    for (int k = 0; k < 4 * KPS; k++) {
        const uint64_t a = da + (k >> 2) * (BM * 8) + (k & 3) * 2, b = db + k * 128;
        if constexpr (BN == 256) wgmma_n256(acc, a, b, first && k == 0 ? 0 : 1);
        else if constexpr (BN == 128) wgmma_n128(acc, a, b, first && k == 0 ? 0 : 1);
        else wgmma_n64(acc, a, b, first && k == 0 ? 0 : 1);
    }
    wg_commit();
}

__device__ __forceinline__ void kv_store_unit(const uint32_t (&pk)[64], int u, bf16* dst, int t) {
    const int G = (u >> 2) * 2 + (u & 1), hh = (u >> 1) & 1;
    uint32_t r0 = pk[(4 * G + 0) * 2 + hh], r1 = pk[(4 * G + 1) * 2 + hh], r2 = pk[(4 * G + 2) * 2 + hh], r3 = pk[(4 * G + 3) * 2 + hh];
    quad_transpose(r0, r1, r2, r3, t);
#define KVST ".cs"
    asm volatile("st.global" KVST ".v4.u32 [%0], {%1,%2,%3,%4};" ::"l"(dst + (size_t)hh * 8 * 8192 + G * 32), "r"(r0), "r"(r1), "r"(r2), "r"(r3) : "memory");
}

#define TLK(slot)
#define TLK2(slot)
__device__ __forceinline__ uint32_t near_page(int pair, int line) {
    uint32_t best[2] = {~0u, ~0u};
#pragma unroll 1
    for (int i = 0; i < 16; i++) {
        uint32_t t0, t1, v;
        asm volatile("mov.u32 %0, %%clock;" : "=r"(t0)::"memory");
        asm volatile("atom.relaxed.gpu.global.or.b32 %0, [%1], -1;" : "=r"(v) : "l"(g_x + pair * 1024 + (i & 1) * 512 + line * 16) : "memory");
        asm volatile("{\n.reg .pred p;\nsetp.ne.u32 p, %1, 0x12345;\nmov.u32 %0, -1;\n@p mov.u32 %0, %%clock;\n}" : "=r"(t1) : "r"(v) : "memory");
        if (i & 1) best[1] = min(best[1], t1 - t0); else best[0] = min(best[0], t1 - t0);
    }
    return best[1] < best[0];
}
__device__ __forceinline__ void map_pages(int c) {
    uint32_t smid;
    asm("mov.u32 %0, %%smid;" : "=r"(smid));
    const uint32_t side = near_page(0, c & 31);
    g_side[smid & 255] = side;
    for (int p = c; p < XPAIRS; p += 132) g_home[p] = near_page(p, 0) ^ side;
}

__global__ void __launch_bounds__(384, 1)
k_kv(const __grid_constant__ CUtensorMap mx, const __grid_constant__ CUtensorMap mwk, const __grid_constant__ CUtensorMap mwv,
     const bf16* __restrict__ Wq, const bf16* __restrict__ Wk, const bf16* __restrict__ Wo, int c0) {
    extern __shared__ __align__(1024) uint8_t smem_gemm[];
    const int c = c0 + blockIdx.x;
    if (c == 128) {
        if (threadIdx.x < 256) g_flag[threadIdx.x] = 0;
        __threadfence();
        __syncthreads();
    }
    asm volatile("griddepcontrol.launch_dependents;");
    if (threadIdx.x == 0) TLK(0);
    if (c >= 128) {
        const int i0 = (c - 128) * 384 + threadIdx.x;
        const uint4 ones = make_uint4(~0u, ~0u, ~0u, ~0u);
        if (threadIdx.x == 32) map_pages(c);
        for (int i = i0; i < XPAIRS * 512; i += 4 * 384) reinterpret_cast<uint4*>(g_x)[i] = ones;
        if (threadIdx.x == 0) TLK(1);
        asm volatile("griddepcontrol.wait;" ::: "memory");
        return;
    }
    GemmSmem g = gemm_setup(smem_gemm, 4);
    uint32_t rank, peer_empty;
    asm("mov.u32 %0, %%cluster_ctarank;" : "=r"(rank));
    asm("mapa.shared::cluster.u32 %0, %1, %2;" : "=r"(peer_empty) : "r"(g.empty), "r"(rank ^ 1));
    asm volatile("barrier.cluster.arrive.relaxed.aligned;\nbarrier.cluster.wait.aligned;" ::: "memory");
    auto release = [&](int s) {
        asm volatile("{\n.reg .pred p;\nsetp.eq.u32 p, %2, 0;\n@p mbarrier.arrive.relaxed.cta.shared::cta.b64 _, [%0];\n"
                     "@p mbarrier.arrive.relaxed.cluster.shared::cluster.b64 _, [%1];\n}"
                     ::"r"(g.empty + 8 * s), "r"(peer_empty + 8 * s), "r"(threadIdx.x & 127) : "memory");
    };
#define MW 4
    const int m0 = (c % MW) * 128, nb0 = c / MW;
    auto tile_m = [](int tile) { return (tile % (16 / MW)) * MW * 128; };
    auto tile_n = [](int tile) { return (tile / (16 / MW)) * (128 / MW); };
    const int wg = __shfl_sync(~0u, threadIdx.x >> 7, 0);
    if (wg == 0) {
        asm volatile("setmaxnreg.dec.sync.aligned.u32 40;");
        if (threadIdx.x == 0) {
            for (int it = 0; it < 64; it++) {
                const int s = it & 3, tile = it >> 4, kb = it & 15;
                mbar_wait(g.empty + 8 * s, ((it >> 2) & 1) ^ 1);
                mbar_expect_tx(g.full + 8 * s, STAGE_BYTES);
                const int nb = nb0 + tile_n(tile);
                tma2d(g.st + s * STAGE_BYTES, &mx, kb * 64, m0 + tile_m(tile), g.full + 8 * s);
                asm volatile("cp.async.bulk.tensor.3d.shared::cluster.global.mbarrier::complete_tx::bytes.multicast::cluster "
                             "[%0], [%1, {%3, %4, %5}], [%2], %6;"
                             ::"r"(g.st + s * STAGE_BYTES + 16384 + (c & 1) * 16384), "l"(nb < 16 ? &mwk : &mwv), "r"(g.full + 8 * s),
                               "r"(0), "r"(kb * 64), "r"((nb & 15) * 4 + (c & 1) * 2), "h"((uint16_t)(3u << (rank & ~1u))) : "memory");
#define PF0 32
#define PFN 32
#define PFB 4096
                const int pi = it - PF0;
                if (pi >= 0 && pi < PFN) {
                    const uint32_t o = (pi * 128 + c) * PFB;
                    const char* p = (const char*)(o < (8 << 20) ? Wo : o < (16 << 20) ? Wq : Wk) + (o & ((8 << 20) - 1));
                    asm volatile("cp.async.bulk.prefetch.L2.global [%0], %1;" ::"l"(p), "n"(PFB) : "memory");
                }
            }
        } else if (threadIdx.x == 32) map_pages(c);
    } else {
        asm volatile("setmaxnreg.inc.sync.aligned.u32 232;");
        const int cw = wg - 1, lane = threadIdx.x & 31, t = lane & 3;
        const int row = m0 + cw * 64 + ((threadIdx.x >> 5) & 3) * 16 + (lane >> 2);
        bf16* dst = g_kv + (size_t)row * 8192 + nb0 * 256 + t * 8;
        float acc[128];
        uint32_t pk[64];
#pragma unroll 1
        for (int tile = 0; tile < 4; tile++) {
#pragma unroll
            for (int kb = 0; kb < 16; kb++) {
                mbar_wait_u(g.full + 8 * (kb & 3), (kb >> 2) & 1);
                if (kb == 0 && tile == 0 && threadIdx.x == 128) TLK2(0);
                gemm_stage<128, 256, 1>(acc, g.st + (kb & 3) * STAGE_BYTES, cw, kb == 0);
                if (tile > 0) kv_store_unit(pk, kb, dst + (size_t)tile_m(tile - 1) * 8192 + tile_n(tile - 1) * 256, t);
                if (kb > 0) {
                    wg_wait<1>();
                    if (kb <= 12 || tile < 3) release((kb - 1) & 3);
                }
            }
            wg_wait<0>();
            if (threadIdx.x == 128) TLK2(tile + 1);
            if (tile < 3) release(3);
#pragma unroll
            for (int i = 0; i < 64; i++) pk[i] = pack2(acc[2 * i], acc[2 * i + 1]);
        }
        if (threadIdx.x == 128) TLK(2);
#pragma unroll
        for (int u = 0; u < 16; u++) kv_store_unit(pk, u, dst + (size_t)tile_m(3) * 8192 + tile_n(3) * 256, t);
        if (threadIdx.x == 128) TLK(1);
        asm volatile("griddepcontrol.wait;" ::: "memory");
    }
}

constexpr int NS1 = 31;
#define RB1 4
#define PFC 4
constexpr int C_W1 = 0;
constexpr int C_W2 = C_W1 + 8 * NS1 * 512;
constexpr int C_KV = C_W2 + 14 * 8 * 512;
constexpr int C_RED = C_KV + 16384;
constexpr int C_QKV = C_RED + 64 * 272;
constexpr int C_SC = C_RED;
constexpr int C_OB = C_SC + 2 * 8 * 52 * 4;
constexpr int C_BAR = C_QKV + 3 * 8 * 272;
__host__ __device__ constexpr int smem_idx(int ks, int j) {
    return ks == 0 ? j : ks < 3 ? (j < 4 ? 4 + 4 * ks + j : -1) : (j < 3 ? 7 + 3 * ks + j : -1);
}
constexpr int CHAIN_SMEM = C_BAR + 64;
#define TS(i)
#define TG(i)

#define DLY3 8
#define DLY1 2
#define DLY0 2
#define DLY1A 10
#define DLY0A DLY0
#define DLYW 3
template <int N> __device__ __forceinline__ uint32_t delayed(uint32_t x, int lane) {
#pragma unroll
    for (int i = 0; i < N; i++) asm volatile("shfl.sync.idx.b32 %0, %0, %1, 31, -1;" : "+r"(x) : "r"(lane) : "memory");
    return x;
}
__device__ __forceinline__ void lds128v(uint32_t (&r)[4], uint32_t a) {
    asm volatile("ld.volatile.shared.v4.u32 {%0,%1,%2,%3}, [%4];" : "=r"(r[0]), "=r"(r[1]), "=r"(r[2]), "=r"(r[3]) : "r"(a) : "memory");
}
__device__ __forceinline__ uint2 lds64(uint32_t a) {
    uint2 v;
    asm volatile("ld.shared.v2.u32 {%0,%1}, [%2];" : "=r"(v.x), "=r"(v.y) : "r"(a) : "memory");
    return v;
}
#define LDQ ".L1::no_allocate"
__device__ __forceinline__ uint4 ldw128(const void* p) {
    uint4 v;
    asm volatile("ld.global.nc" LDQ ".v4.u32 {%0,%1,%2,%3}, [%4];" : "=r"(v.x), "=r"(v.y), "=r"(v.z), "=r"(v.w) : "l"(p));
    return v;
}
#define P8_LD(i) "ld.relaxed.gpu.global.b64 d" #i ", [src + " #i " * 256];\n"
#define P8_X(i) "mov.b64 {x" #i ", y" #i "}, d" #i ";\n"
#define P8_HEAD(SRC) "{\n.reg .pred p, q;\n.reg .b64 src, d<8>;\n.reg .b32 n, x<8>, y<8>, m0, m1;\nmov.b64 src, " SRC ";\n"         \
                P8_LD(0) P8_LD(1) P8_LD(2) P8_LD(3) P8_LD(4) P8_LD(5) P8_LD(6) P8_LD(7) "mov.u32 n, 0;\nCHECK:\n" \
                P8_X(0) P8_X(1) P8_X(2) P8_X(3) P8_X(4) P8_X(5) P8_X(6) P8_X(7)
#define P8_VOTE "vote.sync.all.pred p, p, -1;\n@p bra.uni DONE;\n"
#define P8_TAIL "add.u32 n, n, 1;\nsetp.lt.u32 p, n, 0x100000;\n@p bra.uni CHECK;\ntrap;\nDONE:\n"
__device__ __forceinline__ void poll_state(uint2 (&v)[8], const void* src) {
#define P8_RS(i) "setp.eq.u32 q, x" #i ", 0xffffffff;\n@q " P8_LD(i)
#define P8_O(i) "mov.b64 %" #i ", d" #i ";\n"
    uint64_t d[8];
    asm volatile(P8_HEAD("%8") "max.u32 m0, x0, x1;\nmax.u32 m0, m0, x2;\nmax.u32 m1, x3, x4;\nmax.u32 m1, m1, x5;\nmax.u32 m0, m0, x6;\n"
                 "max.u32 m0, m0, x7;\nmax.u32 m0, m0, m1;\nsetp.ne.u32 p, m0, 0xffffffff;\n" P8_VOTE
                 P8_RS(0) P8_RS(1) P8_RS(2) P8_RS(3) P8_RS(4) P8_RS(5) P8_RS(6) P8_RS(7) P8_TAIL
                 P8_O(0) P8_O(1) P8_O(2) P8_O(3) P8_O(4) P8_O(5) P8_O(6) P8_O(7) "}"
                 : "=l"(d[0]), "=l"(d[1]), "=l"(d[2]), "=l"(d[3]), "=l"(d[4]), "=l"(d[5]), "=l"(d[6]), "=l"(d[7]) : "l"(src) : "memory");
#pragma unroll
    for (int i = 0; i < 8; i++) { v[i].x = (uint32_t)d[i]; v[i].y = (uint32_t)(d[i] >> 32); }
}
__device__ __forceinline__ uint64_t poll_sum(const void* src, uint32_t tag, uint32_t sel) {
#define P8_RT(i) "lop3.b32 m0, x" #i ", %2, 1, 0x28;\nsetp.ne.u32 q, m0, 0;\n@q " P8_LD(i)
#define P8_MMA(c, i, z) "mma.sync.aligned.m16n8k8.row.col.f32.bf16.bf16.f32 {" #c "0," #c "1," #c "2," #c "3}, {x" #i ", y" #i "}, {%3}, {" #z "0," #z "1," #z "2," #z "3};\n"
    uint64_t r;
    asm volatile(P8_HEAD("%1") "{\n.reg .f32 a<4>, b<4>, z<4>;\nmov.f32 z0, 0f00000000;\nmov.f32 z1, z0;\nmov.f32 z2, z0;\nmov.f32 z3, z0;\n"
                 P8_MMA(a, 0, z) P8_MMA(b, 1, z) P8_MMA(a, 2, a) P8_MMA(b, 3, b) P8_MMA(a, 4, a) P8_MMA(b, 5, b) P8_MMA(a, 6, a) P8_MMA(b, 7, b)
                 "add.f32 a0, a0, b0;\nadd.f32 a1, a1, b1;\nadd.f32 a2, a2, b2;\nadd.f32 a3, a3, b3;\n"
                 "cvt.rn.bf16x2.f32 m0, a1, a0;\ncvt.rn.bf16x2.f32 m1, a3, a2;\nmov.b64 %0, {m0, m1};\n}\n"
                 "lop3.b32 m0, x0, x1, %2, 0x7e;\nlop3.b32 m1, x2, x3, %2, 0x7e;\nlop3.b32 m0, m0, x4, %2, 0xf6;\n"
                 "lop3.b32 m1, m1, x5, %2, 0xf6;\nlop3.b32 m0, m0, x6, %2, 0xf6;\nlop3.b32 m1, m1, x7, %2, 0xf6;\n"
                 "lop3.b32 m0, m0, m1, 1, 0xa8;\nsetp.eq.u32 p, m0, 0;\n" P8_VOTE
                 P8_RT(0) P8_RT(1) P8_RT(2) P8_RT(3) P8_RT(4) P8_RT(5) P8_RT(6) P8_RT(7) P8_TAIL "}"
                 : "=&l"(r) : "l"(src), "r"(tag), "r"(sel) : "memory");
    return r;
}
__device__ __forceinline__ void sum8(float (&c)[4], const uint2 (&v)[8], uint32_t idn) {
    float d[4] = {0.f, 0.f, 0.f, 0.f};
    c[0] = c[1] = c[2] = c[3] = 0.f;
    mma16816(c, v[0].x, v[0].y, v[1].x, v[1].y, idn, idn);
    mma16816(d, v[2].x, v[2].y, v[3].x, v[3].y, idn, idn);
    mma16816(c, v[4].x, v[4].y, v[5].x, v[5].y, idn, idn);
    mma16816(d, v[6].x, v[6].y, v[7].x, v[7].y, idn, idn);
    c[0] += d[0]; c[1] += d[1]; c[2] += d[2]; c[3] += d[3];
}

#define CLS 6
__global__ void __cluster_dims__(CLS, 1, 1) __launch_bounds__(256, 1)
k_chain(const bf16* __restrict__ mem0, const bf16* __restrict__ Wq, const bf16* __restrict__ Wk, const bf16* __restrict__ Wv,
        const bf16* __restrict__ Wo, const __grid_constant__ CUtensorMap mkv) {
    extern __shared__ __align__(1024) uint8_t smem_chain[];
    const uint32_t sb = smem_u32(smem_chain);
    if (sb & 1023) __trap();
    const int w = __shfl_sync(~0u, threadIdx.x >> 5, 0), lane = __shfl_sync(~0u, threadIdx.x & 31, threadIdx.x & 31);
    const int tid = w * 32 + lane, g = lane >> 2, t = lane & 3;
    auto pin = [&](uint32_t x) { return delayed<1>(x, lane); };
    const int h = blockIdx.x / 3, r = blockIdx.x - 3 * h;
    const uint32_t bar_x = sb + C_BAR, bar_kv = sb + C_BAR + 8, bar_go = sb + C_BAR + 16, bar_w = sb + C_BAR + 24;
    asm volatile("griddepcontrol.launch_dependents;");
    const int tbase = r == 0 ? 0 : 1 + 21 * r, ntile = r == 0 ? 22 : 21;
    uint32_t side;
    if (tid == 0) {
        mbar_init(bar_x, 8); mbar_init(bar_kv, 1); mbar_init(bar_go, 1); mbar_init(bar_w, 1);
        asm volatile("fence.mbarrier_init.release.cluster;" ::: "memory");
        asm volatile("fence.proxy.async.shared::cta;" ::: "memory");
        mbar_expect_tx(bar_w, 128 * 32 * ntile);
    }
    __syncthreads();
    asm volatile("barrier.cluster.arrive.relaxed.aligned;" ::: "memory");
    if (tid < 128)
        asm volatile("cp.async.bulk.shared::cluster.global.mbarrier::complete_tx::bytes [%0], [%1], %2, [%3];"
                     ::"r"(sb + C_W1 + tid * 720), "l"(Wo + (size_t)(h * 128 + tid) * DM + tbase * 16), "r"(32 * ntile), "r"(bar_w) : "memory");
    const int tile0 = tbase + 7 - w;
    const bool three = w >= (r == 0 ? 2 : 3);
    const uint32_t wa = pin(sb + tid * 16);
#define W1A(i) (wa + C_W1 + (i) * 4096)
#define W2A(x) (wa + C_W2 + ((x) < 8 ? (x) * 4096 : 32768 - 1024 + ((x) - 8) * 3072))
    uint32_t wo0[8][4], wr[64][4];
    {
        const bf16* W = (r == 0 ? Wq : r == 1 ? Wk : Wv) + (size_t)(128 * w + (lane >> 4)) * HD + h * 128 + 8 * (lane & 15);
        uint4 raw[8][8];
        auto fetch = [&](int ks) {
#pragma unroll
            for (int i = 0; i < 8; i++) raw[ks][i] = ldw128(W + (size_t)(16 * ks + 2 * i) * HD);
        };
        fetch(0); fetch(1); fetch(2); fetch(3);
    asm("mov.u32 %0, %%smid;" : "=r"(side));
    side = __ldcg(g_side + (side & 255)) & 1;
    if (tid == 0 && r > 0) asm volatile("st.relaxed.gpu.global.u32 [%0], %1;" ::"l"(g_flag + 128 + 2 * h + r - 1), "r"(2 | side) : "memory");
        if (w == 0) TG(0);
        mbar_wait_u(bar_w, 0);
        if (w == 0) TG(1);
        const uint32_t p = sb + C_W1 + ((lane & 7) + (lane >> 4) * 8) * 720 + (7 - w) * 32 + ((lane >> 3) & 1) * 16;
#pragma unroll
        for (int ks = 0; ks < 8; ks++) {
            uint32_t a[4];
            ldsm4t(wo0[ks], p + ks * 16 * 720);
            ldsm4t(a, p + ks * 16 * 720 + 256);
            sts128(W2A(ks), a[0], a[1], a[2], a[3]);
            if (three) { ldsm4t(a, p + ks * 16 * 720 + 512); sts128(W2A(8 + ks), a[0], a[1], a[2], a[3]); }
        }
        __syncthreads();
        if (w == 0) TG(2);
        const uint32_t stg = sb + C_KV + w * 4096;
        const uint32_t rd = stg + ((lane & 7) + 8 * (lane >> 4)) * 256 + ((((lane >> 3) & 1) ^ (lane & 7)) << 4);
#pragma unroll
        for (int ks = 0; ks < 8; ks++) {
#pragma unroll
            for (int i = 0; i < 8; i++)
                sts128(stg + (2 * i + (lane >> 4)) * 256 + (((lane & 15) ^ (((2 * i) & 6) | (lane >> 4))) << 4),
                       raw[ks][i].x, raw[ks][i].y, raw[ks][i].z, raw[ks][i].w);
            if (ks < 2) fetch(ks + 4);
            if (ks == 3 || ks == 5) fetch(ks / 2 + 5);
            __syncwarp();
#pragma unroll
            for (int j = 0; j < 8; j++) {
                if (smem_idx(ks, j) >= 0) {
                    uint32_t a[4];
                    ldsm4t(a, rd ^ (j << 5));
                    sts128(W1A(smem_idx(ks, j)), a[0], a[1], a[2], a[3]);
                } else ldsm4t(wr[8 * ks + j], rd ^ (j << 5));
            }
            __syncwarp();
        }
    }
    if (w == 0) TG(3);
    asm volatile("griddepcontrol.wait;\nfence.proxy.async.shared::cta;" ::: "memory");
    __syncthreads();
    if (tid == 0) {
        mbar_expect_tx(bar_kv, 16384);
        tma3d(sb + C_KV, &mkv, 0, 0, 2 * h, bar_kv);
        tma3d(sb + C_KV + 8192, &mkv, 0, 0, 64 + 2 * h, bar_kv);
    }
    asm volatile("barrier.cluster.wait.aligned;" ::: "memory");

    auto publish_kvm = [&](int s) {
        uint32_t v[4];
        lds128(v, sb + C_QKV + (8 + (tid >> 4)) * 272 + (tid & 15) * 16);
        asm volatile("st.global.v4.u32 [%0], {%1,%2,%3,%4};"
                     ::"l"(g_kvm + (size_t)(s * 8 + ((tid >> 4) & 7)) * 8192 + (tid >> 7) * HD + h * 128 + (tid & 15) * 8),
                       "r"(v[0]), "r"(v[1]), "r"(v[2]), "r"(v[3]) : "memory");
        if (h == 0 && w == 6) asm volatile("st.relaxed.gpu.global.u32 [%0], %1;" ::"l"(g_flag + 98), "r"(s + 1) : "memory");
        if ((s & 3) == 3) {
            __syncthreads();
            if (w == 7) asm volatile("{\n.reg .pred p;\nsetp.eq.u32 p, %2, 0;\nfence.acq_rel.gpu;\n@p st.relaxed.gpu.global.u32 [%0], %1;\n}"
                                     ::"l"(g_flag + h), "r"(s + 1), "r"(lane) : "memory");
        }
    };
    const float sl2e = 0.08838834764831845f * 1.4426950408889634f;
    const uint32_t idn = pin(g == 2 * t ? 0x00003f80u : g == 2 * t + 1 ? 0x3f800000u : 0u);
    const uint32_t lm = pin(sb + (lane & 7) * 272 + (lane >> 3) * 16);
    const uint32_t sa = pin(sb + C_SC + (w & 1) * (8 * 52 * 4) + (2 * t * 52 + (w < 4 ? 32 : (w & 2) * 8) + g) * 4);
    const uint32_t sr = pin(sb + C_SC + (g * 52 + 8 * t) * 4), sr2 = pin(sb + C_SC + (g * 52 + 32 + 2 * t) * 4);
    uint32_t kva;
    {
        const int pos = (w & 2) * 8 + (lane & 15), row = (pos & 24) + ((pos + (pos >> 2 & 6)) & 7);
        const int key = 4 * (lane & 6) + (((lane & 7) + 2 * (lane >> 4)) & 7);
        kva = pin(w >= 4 ? sb + C_KV + (w & 1) * 4096 + row * 128 + (((lane >> 4) ^ (row & 7)) << 4)
                         : sb + C_KV + 8192 + (w >> 1) * 4096 + key * 128 + ((((w & 1) * 4 + ((lane >> 3) & 1)) ^ (key & 7)) << 4));
    }
    uint32_t buf0[8][4], ring[RB1][4];
    auto stage_w1 = [&]() {
#pragma unroll
        for (int i = 0; i < 8; i++) lds128v(buf0[i], W1A(i));
#pragma unroll
        for (int i = 0; i < RB1; i++) lds128v(ring[i], W1A(8 + i));
    };
    stage_w1();
    uint32_t psel, msel0, msel1;
    {
        const int j = r > 0 ? 2 * h + r - 1 : 0, tl = min(tile0 + 8 * (lane >> 1), 63);
        uint32_t b;
        asm volatile("{\n.reg .pred p;\n.reg .u32 n;\nmov.u32 n, 0;\nAGAIN:\nld.relaxed.gpu.global.u32 %0, [%1];\nsetp.ne.u32 p, %0, 0;\n"
                     "vote.sync.all.pred p, p, -1;\n@p bra.uni DONE;\nadd.u32 n, n, 1;\nsetp.lt.u32 p, n, 0x100000;\n@p bra.uni AGAIN;\ntrap;\nDONE:\n}"
                     : "=&r"(b) : "l"(g_flag + 128 + tl) : "memory");
        psel = __ballot_sync(~0u, (g_home[lane == 6 ? j * 2 + ((w >> 1) & 1) : tl * 2 + (lane & 1)] ^ (lane == 6 ? side : b)) & 1);
        msel0 = __ballot_sync(~0u, (g_home[128 + lane * 4 + (w >> 1)] ^ side) & 1);
        msel1 = __ballot_sync(~0u, (g_home[256 + lane * 4 + (w >> 1)] ^ side) & 1);
        if (r > 0) {
            if (w < 4) asm volatile("prefetch.global.L2 [%0];" ::"l"(g_x + (128 + (1 + (w >> 1)) * 4 + (j >> 4)) * 1024 + (w & 1) * 512 + (j & 15) * 32 + lane) : "memory");
            if (w < 4) asm volatile("prefetch.global.L2 [%0];" ::"l"(g_x + j * 2048 + tid * 16) : "memory");
        }
    }
    uint2 bm[8];
#pragma unroll
    for (int ks = 0; ks < 8; ks++) {
        const uint32_t* p = (const uint32_t*)(mem0 + g * DM + (8 * w + ks) * 16) + t;
        bm[ks] = make_uint2(__ldg(p), __ldg(p + 4));
    }
    if (w == 0) TG(5);
#pragma unroll 1
    for (int s = 0;; s++) {
        TS(1);
        {
            float acc[8][4];
#pragma unroll
            for (int ks = 0; ks < 8; ks++) {
#pragma unroll
                for (int j = 0; j < 8; j++) {
                    const int i = smem_idx(ks, j) - 8;
                    if (ks == 0) {
                        acc[j][0] = acc[j][1] = acc[j][2] = acc[j][3] = 0.f;
                        mma16816(acc[j], buf0[j][0], buf0[j][1], buf0[j][2], buf0[j][3], bm[ks].x, bm[ks].y);
                    } else if (i >= 0) {
                        uint32_t(&a)[4] = ring[i % RB1];
                        mma16816(acc[j], a[0], a[1], a[2], a[3], bm[ks].x, bm[ks].y);
                        if (8 + i + RB1 < NS1) lds128v(a, W1A(8 + i + RB1));
                    } else {
                        const uint32_t(&a)[4] = wr[8 * ks + j];
                        mma16816(acc[j], a[0], a[1], a[2], a[3], bm[ks].x, bm[ks].y);
                    }
                }
            }
#pragma unroll
            for (int c = 0; c < 4; c++)
                stsm4t(lm + C_RED + w * 2176 + c * 64, pack2(acc[2 * c][0], acc[2 * c][1]), pack2(acc[2 * c][2], acc[2 * c][3]),
                       pack2(acc[2 * c + 1][0], acc[2 * c + 1][1]), pack2(acc[2 * c + 1][2], acc[2 * c + 1][3]));
        }
        {
            const uint32_t a = sb + C_RED + w * 272 + lane * 8;
            TS(2);
            __syncthreads();
            TS(3);
            uint2 v[8];
#pragma unroll
            for (int i = 0; i < 8; i++) v[i] = lds64(a + i * 2176);
            float c[4];
            sum8(c, v, idn);
            const uint32_t p0 = pack2(c[0], c[1]), p1 = pack2(c[2], c[3]);
            const uint32_t dst = sb + C_QKV + (r * 8 + w) * 272 + lane * 8;
#pragma unroll
            for (int i = 1; i < 3; i++) {
                const uint32_t peer = (h % (CLS / 3)) * 3 + (r + i >= 3 ? r + i - 3 : r + i);
                uint32_t rd, rb;
                asm("mapa.shared::cluster.u32 %0, %1, %2;" : "=r"(rd) : "r"(dst), "r"(peer));
                asm("mapa.shared::cluster.u32 %0, %1, %2;" : "=r"(rb) : "r"(bar_x), "r"(peer));
                asm volatile("st.async.weak.shared::cluster.mbarrier::complete_tx::bytes.v2.b32 [%0], {%1,%2}, [%3];"
                             ::"r"(rd), "r"(p0), "r"(p1), "r"(rb) : "memory");
            }
            sts64(dst, p0, p1);
            __syncwarp();
            asm volatile("{\n.reg .pred p;\nsetp.eq.u32 p, %1, 0;\n@p mbarrier.arrive.expect_tx.shared::cta.b64 _, [%0], 512;\n}"
                         ::"r"(bar_x), "r"(lane) : "memory");
        }
        TS(4);
        if (s == NSEG - 1) break;
        if (s == 0) mbar_wait_u(bar_kv, 0);
        uint32_t wb[8][4], wc[8][4];
        const uint32_t po = (tile0 * 2 + (lane >> 4)) * 8192 + ((lane >> 3) & 1) * 2048 + h * 64 + (lane & 7) * 8;
        const uint32_t tag = s & 1;
        auto project = [&](const uint32_t(&wt)[8][4], const uint32_t(&ob)[4][4], int i) {
            float c0[4] = {0.f, 0.f, 0.f, 0.f}, c1[4] = {0.f, 0.f, 0.f, 0.f};
#pragma unroll
            for (int ks = 0; ks < 8; ks++)
                mma16816((ks & 1) ? c1 : c0, wt[ks][0], wt[ks][1], wt[ks][2], wt[ks][3], ob[ks >> 1][(ks & 1) * 2], ob[ks >> 1][(ks & 1) * 2 + 1]);
            uint32_t p0 = pack2(c0[0] + c1[0], c0[1] + c1[1]), p1 = pack2(c0[2] + c1[2], c0[3] + c1[3]);
            asm volatile("movmatrix.sync.aligned.m8n8.trans.b16 %0, %0;\nmovmatrix.sync.aligned.m8n8.trans.b16 %1, %1;" : "+r"(p0), "+r"(p1));
            st_rlx64((uint2*)((char*)g_x + po + i * 131072 + ((psel >> (2 * i + (lane >> 4))) & 1) * 4096), (p0 & ~1u) | tag, p1);
        };
        if (w >= 4) {
            uint32_t ka[4][4];
#pragma unroll
            for (int ks = 0; ks < 4; ks++) ldsm4(ka[ks], kva ^ (ks << 5));
            const uint32_t qa = lm + C_QKV + (w & 1) * 128;
            TS(5);
            mbar_wait_u(bar_x, s & 1);
            TS(6);
            {
                uint32_t qb[2][4];
                ldsm4(qb[0], qa);
                ldsm4(qb[1], qa + 64);
                float c0[4] = {0.f, 0.f, 0.f, 0.f}, c1[4] = {0.f, 0.f, 0.f, 0.f};
                mma16816(c0, ka[0][0], ka[0][1], ka[0][2], ka[0][3], qb[0][0], qb[0][1]);
                mma16816(c1, ka[1][0], ka[1][1], ka[1][2], ka[1][3], qb[0][2], qb[0][3]);
                mma16816(c0, ka[2][0], ka[2][1], ka[2][2], ka[2][3], qb[1][0], qb[1][1]);
                mma16816(c1, ka[3][0], ka[3][1], ka[3][2], ka[3][3], qb[1][2], qb[1][3]);
                sts32f(sa, c0[0] + c1[0]);
                sts32f(sa + 208, c0[1] + c1[1]);
                sts32f(sa + 32, c0[2] + c1[2]);
                sts32f(sa + 240, c0[3] + c1[3]);
            }
            __syncthreads();
            TS(7);
            if (w == 7 && s + 1 < NSEG - 1) {
                if (lane == 0) {
                    mbar_expect_tx(bar_kv, 16384);
                    tma3d(sb + C_KV, &mkv, 0, (s + 1) * 32, 2 * h, bar_kv);
                    tma3d(sb + C_KV + 8192, &mkv, 0, (s + 1) * 32, 64 + 2 * h, bar_kv);
                }
                __syncwarp();
            }
            const uint32_t wd = delayed<DLYW>(wa, lane);
#pragma unroll
            for (int i = 0; i < 8; i++) lds128(wb[i], wd + C_W2 + i * 4096);
#pragma unroll
            for (int i = 0; i < PFC; i++) lds128(wc[i], wd + C_W2 + 32768 - 1024 + i * 3072);
            TS(8);
            __syncthreads();
            TS(9);
            uint32_t ob[4][4];
#pragma unroll
            for (int i = 0; i < 4; i++) ldsm4(ob[i], lm + C_OB + i * 64);
#pragma unroll
            for (int i = PFC; i < 8; i++) lds128(wc[i], W2A(8 + i));
            project(wb, ob, 1);
            project(wo0, ob, 0);
            project(wc, ob, 2);
        } else {
            uint32_t va[4][4];
#pragma unroll
            for (int i = 0; i < 4; i++) ldsm4t(va[i], kva ^ (((i >> 1) << 5) | ((i & 1) * 0x240)));
#pragma unroll
            for (int i = 0; i < 8; i++) lds128(wb[i], W2A(i));
            const uint32_t qa = lm + C_QKV + (w & 1) * 128, oa = lm + w * 64;
            TS(5);
            mbar_wait_u(bar_x, s & 1);
            TS(6);
            if (w < 2) {
                uint32_t qb[2][4], km[2][4];
                ldsm4(qb[0], qa);
                ldsm4(km[0], qa + 8 * 272);
                ldsm4(qb[1], qa + 64);
                ldsm4(km[1], qa + 8 * 272 + 64);
                float c0[4] = {0.f, 0.f, 0.f, 0.f}, c1[4] = {0.f, 0.f, 0.f, 0.f};
                mma16816(c0, km[0][0], km[0][1], km[0][2], km[0][3], qb[0][0], qb[0][2]);
                mma16816(c1, km[0][0], km[0][1], km[0][2], km[0][3], qb[0][1], qb[0][3]);
                mma16816(c0, km[1][0], km[1][1], km[1][2], km[1][3], qb[1][0], qb[1][2]);
                mma16816(c1, km[1][0], km[1][1], km[1][2], km[1][3], qb[1][1], qb[1][3]);
                sts32f(sa, c0[0] + c1[2]);
                sts32f(sa + 208, c0[1] + c1[3]);
            }
            __syncthreads();
            TS(7);
            {
                float4 x0 = lds128f(sr), y0 = lds128f(sr + 1664), x1 = lds128f(sr + 16), y1 = lds128f(sr + 1680);
                float2 x2 = lds64f(sr2), y2 = lds64f(sr2 + 1664);
                float p[10] = {x0.x + y0.x, x0.y + y0.y, x0.z + y0.z, x0.w + y0.w, x1.x + y1.x,
                               x1.y + y1.y, x1.z + y1.z, x1.w + y1.w, x2.x + y2.x, x2.y + y2.y};
                float m = fmaxf(fmaxf(fmaxf(p[0], p[1]), fmaxf(p[2], p[3])), fmaxf(fmaxf(fmaxf(p[4], p[5]), fmaxf(p[6], p[7])), fmaxf(p[8], p[9])));
                const float m1 = __shfl_xor_sync(~0u, m, 1), m2 = __shfl_xor_sync(~0u, m, 2), m3 = __shfl_xor_sync(~0u, m, 3);
                uint32_t vm[4];
                ldsm4t(vm, oa + C_QKV + 16 * 272);
                m = fmaxf(fmaxf(m, m1), fmaxf(m2, m3));
                const float ms = m * sl2e;
#pragma unroll
                for (int i = 0; i < 10; i++) p[i] = ex2(fmaf(p[i], sl2e, -ms));
                const uint32_t b0 = pack2(p[0], p[1]), b1 = pack2(p[2], p[3]), b2 = pack2(p[4], p[5]), b3 = pack2(p[6], p[7]), b4 = pack2(p[8], p[9]);
                const uint32_t one = 0x3f803f80u;
                float o0[4] = {0.f, 0.f, 0.f, 0.f}, o1[4] = {0.f, 0.f, 0.f, 0.f}, sm[4] = {0.f, 0.f, 0.f, 0.f};
                mma16816(sm, one, one, one, one, b0, b1);
                mma16816(o0, va[0][0], va[0][1], va[0][2], va[0][3], b0, b1);
                mma16816(o1, va[2][0], va[2][1], va[2][2], va[2][3], b0, b1);
                mma16816(sm, one, one, one, one, b2, b3);
                mma16816(o0, va[1][0], va[1][1], va[1][2], va[1][3], b2, b3);
                mma16816(o1, va[3][0], va[3][1], va[3][2], va[3][3], b2, b3);
                mma1688(sm, one, one, b4);
                mma1688(o0, vm[0], vm[1], b4);
                mma1688(o1, vm[2], vm[3], b4);
                float i0, i1;
                asm("rcp.approx.ftz.f32 %0, %1;" : "=f"(i0) : "f"(sm[0]));
                asm("rcp.approx.ftz.f32 %0, %1;" : "=f"(i1) : "f"(sm[1]));
                stsm4t(oa + C_OB, pack2(o0[0] * i0, o0[1] * i1), pack2(o0[2] * i0, o0[3] * i1),
                       pack2(o1[0] * i0, o1[1] * i1), pack2(o1[2] * i0, o1[3] * i1));
            }
            TS(8);
            __syncthreads();
            TS(9);
            uint32_t ob[4][4];
#pragma unroll
            for (int i = 0; i < 4; i++) ldsm4(ob[i], lm + C_OB + i * 64);
            if (three) {
#pragma unroll
                for (int i = 0; i < 8; i++) lds128(wc[i], W2A(8 + i));
                project(wb, ob, 1);
                project(wo0, ob, 0);
                project(wc, ob, 2);
            } else {
                project(wb, ob, 1);
                project(wo0, ob, 0);
            }
        }
        TS(10);
        __syncthreads();
        uint32_t eo = (128 + (s + 1) * 4 + (w >> 1)) * 8192 + (((s < 31 ? msel0 : msel1) >> ((s + 1) & 31)) & 1) * 4096 + (w & 1) * 2048 + lane * 8;
        if (r == 0) {
            TS(11); TS(12);
            stage_w1();
            if (w < 4 && s + 3 < NSEG - 1)
                asm volatile("prefetch.global.L2 [%0];" ::"l"(g_kv + (size_t)((s + 3) * 32 + lane) * 8192 + (w >> 1) * HD + h * 128 + (w & 1) * 64) : "memory");
            publish_kvm(s);
            if (s < NSEG - 2) mbar_wait_u(bar_kv, (s + 1) & 1);
            mbar_wait_u(bar_go, s & 1);
            if (w < 4) eo = delayed<DLY0>(eo, lane); else eo = delayed<DLY0A>(eo, lane);
        } else {
            const int j = 2 * h + r - 1;
            if (w < 4) {
                const char* src = (const char*)g_x + delayed<DLY3>((j * 2 + (w >> 1)) * 8192 + (psel & 64) * 64 + (w & 1) * 2048 + t * 64 + g * 8, lane);
                const char* dst = (const char*)g_x + pin((128 + (s + 1) * 4 + (j >> 4)) * 8192 + (j & 15) * 256 + w * 64 + (t & 1) * 4096 + g * 8);
                const uint64_t v = poll_sum(src, tag, (lane & 4) ? 0x3f800000u : 0x00003f80u);
                TS(11);
                asm volatile("st.relaxed.gpu.global.b64 [%0], %1;" ::"l"(dst), "l"(v) : "memory");
                asm volatile("bar.arrive 1, 256;" ::: "memory");
                TS(12);
                stage_w1();
                if (s < NSEG - 2) mbar_wait_u(bar_kv, (s + 1) & 1);
                eo = delayed<DLY1>(eo, lane);
            } else {
                if (w >= 6 && s + 3 < NSEG)
                    asm volatile("prefetch.global.L2 [%0];" ::"l"(g_x + (128 + (s + 3) * 4 + (j >> 4)) * 1024 + (w & 1) * 512 + (j & 15) * 32 + lane) : "memory");
                stage_w1();
                if (s < NSEG - 2) mbar_wait_u(bar_kv, (s + 1) & 1);
                TS(11);
                bar_sync(1, 256);
                TS(12);
                if (w == 4 && r == 1)
                    asm volatile("{\n.reg .pred p;\n.reg .u32 a;\nelect.sync _|p, -1;\nmapa.shared::cluster.u32 a, %0, %1;\n"
                                 "@p mbarrier.arrive.relaxed.cluster.shared::cluster.b64 _, [a];\n}" ::"r"(bar_go), "r"((h % (CLS / 3)) * 3) : "memory");
                eo = delayed<DLY1A>(eo, lane);
            }
        }
        { const int s_ = s; { const int s = s_ + 1; TS(0); } }
        poll_state(bm, (const char*)g_x + eo);
    }
    mbar_wait_u(bar_x, (NSEG - 1) & 1);
    if (r == 0) publish_kvm(NSEG - 1);
    asm volatile("barrier.cluster.arrive.relaxed.aligned;\nbarrier.cluster.wait.aligned;" ::: "memory");
}

constexpr int S4_US = 4368;
constexpr int S4_RS = 8848;
constexpr int S4_KS = 1296;
constexpr int S4_U = 0, S4_R = 16 * S4_US, S4_K = S4_R + 16 * S4_RS;
constexpr int S4_SMEM = S4_K + 16 * S4_KS;
constexpr int S4_SIG = 3104, S4_PK = 2 * S4_SIG;

struct cf { float r, i; };
__device__ __forceinline__ cf cmul(cf a, cf b) { return {fmaf(a.r, b.r, -a.i * b.i), fmaf(a.r, b.i, a.i * b.r)}; }
__device__ __forceinline__ cf cmulc(cf a, cf b) { return {fmaf(a.r, b.r, a.i * b.i), fmaf(a.i, b.r, -a.r * b.i)}; }
__device__ __forceinline__ cf csq(cf a) { const float t = a.r * a.i; return {fmaf(a.r, a.r, -a.i * a.i), t + t}; }
__device__ __forceinline__ cf cexp(float l2, float turns) {
    const float mag = ex2(l2), fr = (turns - rintf(turns)) * 6.283185307179586f;
    return {mag * __cosf(fr), mag * __sinf(fr)};
}
__device__ __forceinline__ void sts32(uint32_t a, uint32_t v) { asm volatile("st.shared.u32 [%0], %1;" ::"r"(a), "r"(v) : "memory"); }
__device__ __forceinline__ uint32_t lds16(uint32_t a) {
    uint32_t v;
    asm volatile("ld.shared.u16 %0, [%1];" : "=r"(v) : "r"(a) : "memory");
    return v;
}

template <int M0, int NQ>
__device__ __forceinline__ void s4_class(float (&acc)[16][4], uint32_t sig, uint32_t taps, int x0) {
    constexpr int D0 = M0 / 8, D1 = M0 == 32 ? 9 : 15;
    uint32_t R[D1 - D0 + 2];
#pragma unroll
    for (int D = D0 - 1; D <= D1; D++) {
        if (D < D0 || 8 * D - 7 >= 2 * M0) { R[D - D0 + 1] = 0; continue; }
        const int m = 8 * D + x0;
        uint32_t lo = lds16(taps + m * (2 * NQ)), hi = lds16(taps + (m - 1) * (2 * NQ));
        if (D == D0) { lo = m >= M0 ? lo : 0; hi = m > M0 ? hi : 0; }
        if (D == 2 * D0) { lo = m < 2 * M0 ? lo : 0; hi = m <= 2 * M0 ? hi : 0; }
        R[D - D0 + 1] = lo | (hi << 16);
    }
#pragma unroll
    for (int J = 0; 2 * J + D0 < 16; J++) {
        uint32_t a[4];
        ldsm4t(a, sig + J * 512);
#pragma unroll
        for (int D = D0; D <= D1; D++)
            if (2 * J + D < 16) mma16816(acc[2 * J + D], a[0], a[1], a[2], a[3], R[D - D0 + 1], R[D - D0]);
    }
}

__global__ void __launch_bounds__(512, 1)
k_s4(const bf16* __restrict__ u, const bf16* __restrict__ Are, const bf16* __restrict__ Aim, const bf16* __restrict__ Bre,
     const bf16* __restrict__ Bim, const bf16* __restrict__ Cre, const bf16* __restrict__ Cim, const bf16* __restrict__ logdt,
     const bf16* __restrict__ Dsk, bf16* __restrict__ out) {
    extern __shared__ __align__(16) uint8_t smem_s4[];
    const uint32_t sb = smem_u32(smem_s4);
    asm volatile("griddepcontrol.launch_dependents;");
    const int tid = threadIdx.x, w = __shfl_sync(~0u, tid >> 5, 0), lane = tid & 31, g = lane >> 2, t = lane & 3;
#pragma unroll 1
    for (int item = blockIdx.x; item < 64; item += gridDim.x) {
#define TLS(slot)
    if (tid == 0) TLS(0);
    const int d0 = item * 16;
    const int d = d0 + (w & 1) + ((w >> 1) & 3) * 4 + (w >> 3) * 2;
    const uint32_t tr_off = (lane & 15), tr_l = (lane >> 4) * 16;
    const uint32_t ur = sb + S4_U + w * S4_US, rs = sb + S4_R + w * S4_RS, kd = sb + S4_K + w * S4_KS;
    if (lane < 16) sts128(ur + lane * 16, 0, 0, 0, 0);
    {
        const int o = d * 128 + lane * 4;
        const uint2 ar = __ldg((const uint2*)(Are + o)), ai = __ldg((const uint2*)(Aim + o)), br = __ldg((const uint2*)(Bre + o));
        const uint2 bi = __ldg((const uint2*)(Bim + o)), cr = __ldg((const uint2*)(Cre + o)), ci = __ldg((const uint2*)(Cim + o));
        const float dt = bf_round(expf(__bfloat162float(logdt[d])));
        const bf16* src = u + (size_t)(w * 128 + g) * DM + d0 + 4 * t;
        float T[5][4];
#pragma unroll
        for (int i = 0; i < 5; i++) T[i][0] = T[i][1] = T[i][2] = T[i][3] = 0.f;
        float klast = 0.f;
        const uint32_t wr_ = rs + lane * 272, rd_ = rs + t * 544 + g * 16;
#pragma unroll 1
        for (int c = 0; c < 4; c++) {
            uint2 v[4];
#pragma unroll
            for (int i = 0; i < 4; i++) v[i] = __ldg((const uint2*)(src + (size_t)(c * 32 + i * 8) * DM));
            auto pick = [&](const uint2& x) { const uint32_t y = c < 2 ? x.x : x.y; return (c & 1) ? bf_hi(y) : bf_lo(y); };
            auto pk2 = [](cf x) { return pack2(x.r, x.i); };
            const float l2 = dt * pick(ar) * 1.4426950408889634f, tu = dt * pick(ai) * 0.15915494309189535f;
            const cf z1 = cexp(l2, tu), z2 = csq(z1), z4 = csq(z2), z8 = csq(z4);
            const cf z64 = cexp(l2 * 64.f, tu * 64.f), z128 = csq(z64), z256 = csq(z128), z512 = csq(z256);
            cf a0 = {1.f, 0.f}, a1 = z64;
            cf b0 = cmul({pick(cr), pick(ci)}, {dt * pick(br), dt * pick(bi)});
            b0.i = -b0.i;
            cf b1 = cmulc(b0, z128), b2 = cmulc(b0, z256), y3 = cmulc(b0, z512), b4 = cmulc(y3, z512), b3 = y3;
            const cf y2 = cmulc(b2, z128);
#pragma unroll
            for (int i = 0; i < 8; i++) {
                sts128(wr_ + i * 16, pk2(a0), pk2(a1), pk2(b0), pk2(b1));
                sts128(wr_ + i * 16 + 128, pk2(b2), pk2(b3), pk2(b4), 0);
                b4 = cmulc(b4, z128);
                if (i < 7) {
                    a0 = i == 0 ? z8 : cmul(a0, z8); a1 = cmul(a1, z8);
                    b0 = cmulc(b0, z1); b1 = cmulc(b1, z1);
                    b2 = i == 3 ? y2 : cmulc(b2, z2);
                    if (i & 1) { y3 = cmulc(y3, z128); b3 = y3; } else b3 = cmulc(y3, z4);
                }
            }
            klast += b4.r;
            __syncwarp();
#pragma unroll
            for (int k = 0; k < 8; k++) {
                uint32_t x[4], y[4];
                lds128(x, rd_ + (8 * (k >> 1) + (k & 1)) * 272);
                lds128(y, rd_ + (8 * (k >> 1) + (k & 1)) * 272 + 128);
                mma1688(T[0], x[0], x[1], x[2]);
                mma1688(T[1], x[0], x[1], x[3]);
                mma1688(T[2], x[0], x[1], y[0]);
                mma1688(T[3], x[0], x[1], y[1]);
                mma1688(T[4], x[0], x[1], y[2]);
            }
#pragma unroll
            for (int i = 0; i < 2; i++)
                stsm4t(sb + S4_U + tr_off * S4_US + 256 + (w * 128 + c * 32 + i * 16) * 2 + tr_l, v[2 * i].x, v[2 * i].y, v[2 * i + 1].x, v[2 * i + 1].y);
            __syncwarp();
        }
#pragma unroll
        for (int o2 = 16; o2; o2 >>= 1) klast += __shfl_xor_sync(~0u, klast, o2);
#pragma unroll
        for (int hh = 0; hh < 2; hh++) {
            const int i = g + 8 * hh;
            sts32(kd + (8 * i + 2 * t) * 2, pack2(T[0][2 * hh], T[0][2 * hh + 1]));
            sts32(kd + (128 + 8 * i + 2 * t) * 2, pack2(T[1][2 * hh], T[1][2 * hh + 1]));
            sts32(kd + (256 + 4 * i + 2 * (t & 1) + 64 * (t >> 1)) * 2, pack2(T[2][2 * hh], T[2][2 * hh + 1]));
            sts32(kd + (384 + 2 * i + 32 * t) * 2, pack2(T[3][2 * hh], T[3][2 * hh + 1]));
        }
        asm volatile("stmatrix.sync.aligned.m8n8.x2.trans.shared.b16 [%0], {%1,%2};"
                     ::"r"(kd + 1024 + (lane & 7) * 32 + ((lane >> 3) & 1) * 16), "r"(pack2(T[4][0], T[4][1])), "r"(pack2(T[4][2], T[4][3])) : "memory");
        if (lane == 0) sts32(kd + 1280, pack2(klast, 0.f));
    }
    __syncwarp();
    const uint32_t pk = rs + S4_PK + 64;
    {
#pragma unroll
        for (int i = 0; i < 2; i++) {
            const int x = i * 128 + lane * 4;
            const uint2 c = lds64(kd + x * 2);
            uint32_t p = lds16(kd + x * 2 - 2);
            if (x == 0) p = 0;
            sts128(pk + x * 4, __byte_perm(c.x, p, 0x5410), __byte_perm(c.x, 0, 0x1032), __byte_perm(c.y, c.x, 0x7610), __byte_perm(c.y, 0, 0x1032));
        }
#pragma unroll
        for (int i = 2; i < 4; i++) {
            const int x = i * 128 + lane * 4;
            const uint32_t ab = lds32(kd + 256 + x), c = lds16(kd + 256 + x + 4);
            const uint32_t p = x == 256 ? lds16(kd + 510) : ab;
            sts128(pk + x * 4, __byte_perm(ab, p, 0x5410), __byte_perm(ab, 0, 0x1010), __byte_perm(ab, 0, 0x1032), __byte_perm(c, ab, 0x7610));
        }
        const uint32_t v = lds16(kd + 768), v2 = lds16(kd + 1024);
        if (lane < 24) {
            uint32_t x0 = 0, x1 = 0, x2 = 0, x3 = 0;
            if (lane == 0) { x0 = x1 = x2 = v | (v << 16); x3 = v << 16; }
            if (lane == 12) x3 = v2;
            if (lane == 13) { x0 = v2 | (v2 << 16); x1 = v2 << 16; }
            sts128(lane < 20 ? pk + 2048 + lane * 16 : pk - 64 + (lane - 20) * 16, x0, x1, x2, x3);
        }
        if (lane < 4) sts128(rs + (lane >> 1) * S4_SIG + (lane & 1) * 16, 0, 0, 0, 0);
    }
    __syncthreads();
    float acc[16][4];
#pragma unroll
    for (int i = 0; i < 16; i++) acc[i][0] = acc[i][1] = acc[i][2] = acc[i][3] = 0.f;
    const uint32_t lf = (lane & 7) * 32 + ((lane >> 3) & 1) * 16 + (lane >> 4) * 256;
#pragma unroll 1
    for (int ph = 0; ph < 2; ph++) {
    if (((w >> 2) ^ ph) & 1) {
#pragma unroll
    for (int rg = 3; rg >= 2; rg--) {
#pragma unroll 1
        for (int it = 0; it < (rg == 3 ? 4 : 6); it++) {
            const int n = it * 32 + lane;
            uint32_t x[2][4];
            lds128(x[0], ur + 256 + n * 16 - 16);
            lds128(x[1], ur + 256 + n * 16);
            float e[16], p[15], s[11];
#pragma unroll
            for (int i = 0; i < 8; i++) { e[2 * i] = bf_lo(x[i >> 2][i & 3]); e[2 * i + 1] = bf_hi(x[i >> 2][i & 3]); }
#pragma unroll
            for (int i = 0; i < 15; i++) p[i] = e[i] + e[i + 1];
#pragma unroll
            for (int i = 0; i < 11; i++) s[i] = p[i + 3] + e[i + 5];
            const uint32_t o = rs + 16 + n * 16;
            if (rg == 2) sts128(o, pack2(s[0], s[1]), pack2(s[2], s[3]), pack2(s[4], s[5]), pack2(s[6], s[7]));
#pragma unroll
            for (int i = 0; i < 10; i++) s[i] = p[i + 2] + s[i + 1];
            if (rg == 2) {
                sts64(o + S4_SIG + 8, pack2(s[0], s[1]), pack2(s[2], s[3]));
                sts64(o + S4_SIG + 16, pack2(s[4], s[5]), pack2(s[6], s[7]));
            } else {
#pragma unroll
                for (int i = 0; i < 9; i++) s[i] = p[i + 1] + s[i + 1];
                sts64(o + 8, pack2(s[0], s[1]), pack2(s[2], s[3]));
                sts64(o + 16, pack2(s[4], s[5]), pack2(s[6], s[7]));
#pragma unroll
                for (int i = 0; i < 8; i++) s[i] = p[i] + s[i + 1];
                sts64(o + S4_SIG + 8, pack2(s[0], s[1]), pack2(s[2], s[3]));
                sts64(o + S4_SIG + 16, pack2(s[4], s[5]), pack2(s[6], s[7]));
            }
        }
        __syncwarp();
        if (rg == 3) {
#pragma unroll 1
            for (int q = 1; q <= 2; q++) s4_class<64, 2>(acc, rs + lf + (q == 1 ? 16 : S4_SIG), kd + (384 + q) * 2, g - 2 * t);
        } else {
#pragma unroll 1
            for (int q = 1; q <= 4; q++) s4_class<32, 4>(acc, rs + lf + ((q & 1) ? 0 : S4_SIG) + (q < 3 ? 16 : 0), kd + (256 + q) * 2, g - 2 * t);
        }
        __syncwarp();
    }
    } else
    {
        const uint32_t ub = ur + 256 + lf, kb = pk + (g - 2 * t) * 4;
#pragma unroll 1
        for (int j0 = 0; j0 < 8; j0++) {
            uint32_t B[8][4];
#pragma unroll
            for (int i = 0; i < 8; i++) ldsm4(B[i], ub + i * 512 - j0 * 32);
            auto block = [&](int J, uint32_t a) {
                const uint32_t r0 = lds32(a), rp = lds32(a + 32), rm = lds32(a - 32);
                uint32_t r3;
                asm volatile("ld.volatile.shared.u32 %0, [%1];" : "=r"(r3) : "r"(a) : "memory");
#pragma unroll
                for (int I = J; I < 16; I++)
                    mma16816(acc[I], r0, rp, rm, r3, B[(I - J) >> 1][((I - J) & 1) * 2], B[(I - J) >> 1][((I - J) & 1) * 2 + 1]);
            };
#pragma unroll
            for (int J = 0; J < 4; J++) block(J, kb + j0 * 64 + J * 512);
            if (j0 < 2) { block(4, kb + j0 * 64 + 2048); block(8, kb + j0 * 64 + (544 + 16) * 4); }
        }
    }
    }
    {
        __syncwarp();
#pragma unroll
        for (int i = 0; i < 8; i++)
            stsm4t(rs + lf + i * 512, pack2(acc[2 * i][0], acc[2 * i][1]), pack2(acc[2 * i][2], acc[2 * i][3]),
                   pack2(acc[2 * i + 1][0], acc[2 * i + 1][1]), pack2(acc[2 * i + 1][2], acc[2 * i + 1][3]));
    }
    __syncthreads();
    {
        const uint2 dv = __ldg((const uint2*)(Dsk + d0 + 4 * t));
        bf16* dst = out + (size_t)(w * 128 + g) * 2048 + 1024 + d0 + 4 * t;
#pragma unroll
        for (int i = 0; i < 8; i++) {
            uint32_t y[4], x[4], o[4];
            ldsm4t(y, sb + S4_R + tr_off * S4_RS + (w * 128 + i * 16) * 2 + tr_l);
            ldsm4t(x, sb + S4_U + tr_off * S4_US + 256 + (w * 128 + i * 16) * 2 + tr_l);
#pragma unroll
            for (int j = 0; j < 4; j++)
                asm("{\n.reg .b32 s;\nmul.rn.bf16x2 s, %2, %3;\nadd.rn.bf16x2 %0, %1, s;\n}" : "=r"(o[j]) : "r"(y[j]), "r"(x[j]), "r"((j & 1) ? dv.y : dv.x));
            *reinterpret_cast<uint2*>(dst + (size_t)(i * 16) * 2048) = make_uint2(o[0], o[1]);
            *reinterpret_cast<uint2*>(dst + (size_t)(i * 16 + 8) * 2048) = make_uint2(o[2], o[3]);
        }
    }
    if (tid == 0) TLS(1);
    __syncthreads();
    }
}

enum { IT_QA = 0, IT_W256 = 1, IT_W128 = 2, IT_W64 = 3, IT_W64S = 4, IT_END = 7 };
struct BgParams { CUtensorMap mx, mwq, mkv, mkvm, mo, mo2, mo2s, mwo4, mwo2, mwo1; };
#define LOOK 8
#define NW0 4
#define NW1 16
#define PW1 20
#define P256 54
#define P128 56
__device__ __forceinline__ uint32_t ld_rlx32(const uint32_t* p) {
    uint32_t v;
    asm volatile("ld.relaxed.gpu.global.u32 %0, [%1];" : "=r"(v) : "l"(p) : "memory");
    return v;
}
#define NBT 9
#define NBL 9
constexpr uint32_t W_LONG = NBL * 16, W_LAST = NBT * 16, W_END = W_LAST + 32;
__device__ __forceinline__ bool block_done(uint32_t strip) { return ld_rlx32(g_flag + 64 + (strip < W_LAST ? strip >> 4 : 15)) >= 16; }
struct Sched { uint32_t qb = 0, w0 = 0, w1 = 0; };
__device__ __forceinline__ int next_item(Sched& z) {
    for (int n = 0; n < SPIN_LIMIT; n++) {
        if (z.w0 < z.w1 && (z.qb >= 16 || block_done(z.w0))) {
            const uint32_t i = z.w0, k = i >= W_LAST ? 1 : z.w1 - i >= 4 && !(i & 3) ? 4 : z.w1 - i >= 2 && !(i & 1) ? 2 : 1;
            z.w0 += k;
            if (i >= W_LAST) return IT_W64S | 15 << 3 | (i - W_LAST) << 7;
            return (k == 4 ? IT_W256 : k == 2 ? IT_W128 : IT_W64) | (i >> 4) << 3 | ((i & 15) / k) << 7;
        }
        uint32_t qa, wo, prog, wl;
        asm volatile("ld.relaxed.gpu.global.v4.u32 {%0,%1,%2,%3}, [%4];" : "=r"(qa), "=r"(wo), "=r"(prog), "=r"(wl) : "l"(g_flag + 96) : "memory");
        if (wo >= W_LAST) wo = W_LAST + wl;
        z.qb = qa >> 4;
        const bool wo_ready = z.w0 >= z.w1 && wo < W_END &&
                              (z.qb >= 16 || (wo < W_LONG && blockIdx.x < (prog < PW1 ? NW0 : NW1) && block_done(wo)));
        if (z.qb < 16 && prog + LOOK >= 4 * z.qb + 4 && !wo_ready) {
            const uint32_t i = atomicAdd(g_flag + 96, 1);
            if (i < 256) return IT_QA | (i >> 4) << 3 | (i & 15) << 7;
            continue;
        }
        if (z.w0 < z.w1) {
            if (z.qb >= 16) continue;
        } else if (wo >= W_END) {
            if (z.qb >= 16) return IT_END;
        } else if (wo_ready) {
            if (wo < W_LAST) {
                const uint32_t k = prog <= P256 ? 4 : prog <= P128 ? 2 : 1;
                z.w0 = atomicAdd(g_flag + 97, k);
                z.w1 = min(z.w0 + k, W_LAST);
            } else {
                z.w0 = W_LAST + atomicAdd(g_flag + 99, 1);
                z.w1 = min(z.w0 + 1, W_END);
            }
            continue;
        }
        __nanosleep(300);
    }
    __trap();
    return IT_END;
}
constexpr int B_OST = NSTAGE * STAGE_BYTES + 1024;
constexpr int BG_SMEM = B_OST + 32768;

template <int BM, int BN, int KPS, typename ACC>
__device__ __forceinline__ void gemm_mainloop(ACC& acc, const GemmSmem& g, int cw, int rounds, uint32_t& round) {
#pragma unroll
    for (int i = 0; i < BN / 2; i++) acc[i] = 0.f;
#pragma unroll 1
    for (int k0 = 0; k0 < rounds; k0++, round++) {
#pragma unroll
        for (int s = 0; s < 4; s++) {
            mbar_wait_u(g.full + 8 * s, round & 1);
            gemm_stage<BM, BN, KPS>(acc, g.st + s * STAGE_BYTES, cw, false);
            wg_wait<1>();
            if (s > 0 || k0 > 0) mbar_arrive_one(g.empty + 8 * ((s + 3) & 3), threadIdx.x & 31);
        }
    }
    wg_wait<0>();
    mbar_arrive_one(g.empty + 8 * 3, threadIdx.x & 31);
}

template <int BN>
__device__ __forceinline__ void store_tile(const float (&acc)[BN / 2], bf16* dst, int t) {
#pragma unroll
    for (int G = 0; G < BN / 32; G++)
#pragma unroll
        for (int rr = 0; rr < 2; rr++) {
            uint32_t r0 = pack2(acc[16 * G + 2 * rr], acc[16 * G + 2 * rr + 1]), r1 = pack2(acc[16 * G + 4 + 2 * rr], acc[16 * G + 5 + 2 * rr]);
            uint32_t r2 = pack2(acc[16 * G + 8 + 2 * rr], acc[16 * G + 9 + 2 * rr]), r3 = pack2(acc[16 * G + 12 + 2 * rr], acc[16 * G + 13 + 2 * rr]);
            quad_transpose(r0, r1, r2, r3, t);
            *reinterpret_cast<uint4*>(dst + (size_t)rr * 8 * 2048 + G * 32) = make_uint4(r0, r1, r2, r3);
        }
}

template <int BM, int BN, int KPS>
__device__ __forceinline__ void wo_item(const GemmSmem& g, int cw, uint32_t& round, bf16* dst, int t) {
    if (BM == 64 && cw == 1) {
#pragma unroll 1
        for (int k0 = 0; k0 < 16 / KPS; k0++, round++)
#pragma unroll
            for (int s = 0; s < 4; s++) { mbar_wait_u(g.full + 8 * s, round & 1); mbar_arrive_one(g.empty + 8 * s, threadIdx.x & 31); }
        return;
    }
    float acc[BN / 2];
    gemm_mainloop<BM, BN, KPS>(acc, g, cw, 16 / KPS, round);
    store_tile<BN>(acc, dst, t);
}

template <int HF>
__device__ __forceinline__ void attend(const uint32_t (&q)[64], uint32_t st, uint32_t sm, uint32_t ost, uint32_t bar_f, uint32_t bar_o,
                                       uint32_t full, uint32_t parity, uint32_t empty, int lane) {
    constexpr int NT = HF ? 5 : 3;
    const int r8 = lane & 7, m4 = lane >> 3, gq = lane >> 2, t = lane & 3;
    const float sl2e = 0.08838834764831845f * 1.4426950408889634f;
    const uint32_t la = r8 * 128 + ((m4 ^ r8) << 4), lv = ((m4 & 1) * 8 + r8) * 128 + (((m4 >> 1) ^ r8) << 4);
#pragma unroll
    for (int hh = 0; hh < 2; hh++) {
        mbar_wait_u(full + 16 * hh, parity);
        mbar_wait_u(full + 16 * hh + 8, parity);
        float x[NT][4];
#pragma unroll
        for (int nt = 0; nt < NT; nt++) x[nt][0] = x[nt][1] = x[nt][2] = x[nt][3] = 0.f;
#pragma unroll
        for (int kp = 0; kp < 4; kp++)
#pragma unroll
            for (int nt = 0; nt < NT; nt++) {
                uint32_t b[4];
                ldsm4(b, (nt == 0 ? sm + (kp >> 1) * 2048 : st + (kp >> 1) * 8192 + (nt - 1) * 1024) + hh * 2 * STAGE_BYTES + (la ^ ((kp & 1) << 6)));
                const uint32_t* a = q + hh * 32 + kp * 8;
                mma16816(x[nt], a[0], a[1], a[2], a[3], b[0], b[1]);
                mma16816(x[nt], a[4], a[5], a[6], a[7], b[2], b[3]);
            }
        const float ninf = -3.0e38f;
        if (2 * t > gq) x[NT - 2][0] = x[NT - 1][2] = ninf;
        if (2 * t + 1 > gq) x[NT - 2][1] = x[NT - 1][3] = ninf;
        uint32_t p[NT][2];
#pragma unroll
        for (int i = 0; i < 2; i++) {
            float m = fmaxf(x[0][2 * i], x[0][2 * i + 1]);
#pragma unroll
            for (int nt = 1; nt < NT - 1 + i; nt++) m = fmaxf(m, fmaxf(x[nt][2 * i], x[nt][2 * i + 1]));
            m = fmaxf(m, __shfl_xor_sync(~0u, m, 1));
            m = fmaxf(m, __shfl_xor_sync(~0u, m, 2));
            const float ms = m * sl2e;
            float sum = 0.f;
#pragma unroll
            for (int nt = 0; nt < NT - 1 + i; nt++) {
                x[nt][2 * i] = ex2(fmaf(x[nt][2 * i], sl2e, -ms));
                x[nt][2 * i + 1] = ex2(fmaf(x[nt][2 * i + 1], sl2e, -ms));
                sum += x[nt][2 * i] + x[nt][2 * i + 1];
            }
            sum += __shfl_xor_sync(~0u, sum, 1);
            sum += __shfl_xor_sync(~0u, sum, 2);
            float inv;
            asm("rcp.approx.ftz.f32 %0, %1;" : "=f"(inv) : "f"(sum));
#pragma unroll
            for (int nt = 0; nt < NT - 1 + i; nt++) p[nt][i] = pack2(x[nt][2 * i] * inv, x[nt][2 * i + 1] * inv);
        }
        p[NT - 1][0] = 0;
        uint32_t o[8][4];
#pragma unroll
        for (int G = 0; G < 4; G++) {
            float c[4][4];
#pragma unroll
            for (int i = 0; i < 4; i++) c[i][0] = c[i][1] = c[i][2] = c[i][3] = 0.f;
            uint32_t b[4];
            ldsm4t(b, sm + 4096 + (G >> 1) * 2048 + hh * 2 * STAGE_BYTES + (la ^ ((G & 1) << 6)));
#pragma unroll
            for (int i = 0; i < 4; i++) mma1688(c[i], p[0][0], p[0][1], b[i]);
#pragma unroll
            for (int kk = 0; kk <= HF; kk++)
#pragma unroll
                for (int i = 0; i < 2; i++) {
                    ldsm4t(b, st + 16384 + (G >> 1) * 8192 + kk * 2048 + hh * 2 * STAGE_BYTES + (lv ^ (((G & 1) * 2 + i) << 5)));
                    mma16816(c[2 * i], p[1 + 2 * kk][0], p[1 + 2 * kk][1], p[2 + 2 * kk][0], p[2 + 2 * kk][1], b[0], b[1]);
                    mma16816(c[2 * i + 1], p[1 + 2 * kk][0], p[1 + 2 * kk][1], p[2 + 2 * kk][0], p[2 + 2 * kk][1], b[2], b[3]);
                }
#pragma unroll
            for (int i = 0; i < 4; i++) {
                o[2 * G + (i >> 1)][(i & 1) * 2] = pack2(c[i][0], c[i][1]);
                o[2 * G + (i >> 1)][(i & 1) * 2 + 1] = pack2(c[i][2], c[i][3]);
            }
        }
        mbar_arrive_one(empty + 16 * hh, lane);
        mbar_arrive_one(empty + 16 * hh + 8, lane);
        mbar_wait_u(bar_f, hh ^ 1);
#pragma unroll
        for (int i = 0; i < 8; i++)
            asm volatile("stmatrix.sync.aligned.m8n8.x4.shared.b16 [%0], {%1,%2,%3,%4};"
                         ::"r"(ost + (i >> 2) * 16384 + (lv ^ ((i & 3) << 5))), "r"(o[i][0]), "r"(o[i][1]), "r"(o[i][2]), "r"(o[i][3]) : "memory");
        asm volatile("fence.proxy.async.shared::cta;" ::: "memory");
        __syncwarp();
        mbar_arrive_one(bar_o, lane);
    }
}

__device__ __forceinline__ void tma_prefetch3d(const CUtensorMap* m, int c0, int c1, int c2) {
    asm volatile("cp.async.bulk.prefetch.tensor.3d.L2.global [%0, {%1, %2, %3}];" ::"l"(m), "r"(c0), "r"(c1), "r"(c2) : "memory");
}

__global__ void __launch_bounds__(384, 1) k_bg(const __grid_constant__ BgParams P, bf16* __restrict__ out) {
    extern __shared__ __align__(1024) uint8_t smem_gemm[];
    asm volatile("griddepcontrol.launch_dependents;");
    const uint32_t xb = smem_u32(smem_gemm) + NSTAGE * STAGE_BYTES + 128;
    const uint32_t bar_item = xb, bar_o = xb + 16, bar_f = xb + 24, slot = xb + 32, slot_o = xb + 40;
    if (threadIdx.x == 0) { mbar_init(bar_item, 1); mbar_init(bar_item + 8, 1); mbar_init(bar_o, 8); mbar_init(bar_f, 1); }
    GemmSmem g = gemm_setup(smem_gemm, 8);
    const int wg = __shfl_sync(~0u, threadIdx.x >> 7, 0);
    if (wg == 0) {
        asm volatile("setmaxnreg.dec.sync.aligned.u32 40;");
        if (threadIdx.x == 0) {
            uint32_t it = 0;
            Sched z;
            wait_flag(g_flag + 98, 1);
            asm volatile("fence.proxy.async.global;" ::: "memory");
            auto acquire = [&](uint32_t bytes) {
                const int s = it & 3;
                mbar_wait(g.empty + 8 * s, ((it >> 2) & 1) ^ 1);
                mbar_expect_tx(g.full + 8 * s, bytes);
                it++;
                return s;
            };
            for (int n = 0;; n++) {
                const int code = next_item(z);
                sts32(slot + (n & 1) * 4, code);
                mbar_arrive(bar_item + (n & 1) * 8);
                const int type = code & 7, blk = (code >> 3) & 15, idx = code >> 7, m0 = blk * 128;
                if (type == IT_END) break;
                if (type == IT_QA) {
                    for (int k = 0; k < 16; k++) {
                        const int s = acquire(STAGE_BYTES);
                        const uint32_t st = g.st + s * STAGE_BYTES, fb = g.full + 8 * s;
                        tma2d(st, &P.mx, k * 64, m0, fb);
                        tma3d(st + 16384, &P.mwq, 0, k * 64, idx * 4, fb);
                        if (k >= 4 && k < 12) tma_prefetch3d(&P.mkv, 0, m0 + (k & 1) * 64, (k & 8) * 8 + idx * 4 + (k & 2));
                    }
                    bool ready = ld_acq32(g_flag + 2 * idx) >= 4 * blk + 4 && ld_acq32(g_flag + 2 * idx + 1) >= 4 * blk + 4;
                    if (ready) asm volatile("fence.proxy.async.global;" ::: "memory");
                    for (int pass = 0; pass < 2; pass++) {
                        for (int s = 0; s < 4; s++) {
                            const uint32_t st = g.st + s * STAGE_BYTES, fb = g.full + 8 * s;
                            if (pass == 0) {
                                acquire(40960);
                                tma3d(st, &P.mkv, 0, m0 + (s & 1) * 64, idx * 4 + (s & 2), fb);
                                tma3d(st + 16384, &P.mkv, 0, m0 + (s & 1) * 64, 64 + idx * 4 + (s & 2), fb);
                            }
                            if (ready) {
                                tma3d(st + 32768, &P.mkvm, 0, blk * 32 + (s & 1) * 16, idx * 4 + (s & 2), fb);
                                tma3d(st + 36864, &P.mkvm, 0, blk * 32 + (s & 1) * 16, 64 + idx * 4 + (s & 2), fb);
                            }
                        }
                        if (ready) break;
                        wait_flag(g_flag + 2 * idx, 4 * blk + 4);
                        wait_flag(g_flag + 2 * idx + 1, 4 * blk + 4);
                        asm volatile("fence.proxy.async.global;" ::: "memory");
                        ready = true;
                    }
                } else {
                    wait_flag(g_flag + 64 + blk, 16);
                    asm volatile("fence.proxy.async.global;" ::: "memory");
                    if (type <= IT_W128) {
                        const int nb = type == IT_W256 ? 4 : 2;
                        for (int k = 0; k < 64; k++) {
                            const int s = acquire(16384 + nb * 8192);
                            const uint32_t st = g.st + s * STAGE_BYTES, fb = g.full + 8 * s;
                            tma2d(st, &P.mo, k * 64, m0, fb);
                            tma3d(st + 16384, nb == 4 ? &P.mwo4 : &P.mwo2, 0, k * 64, idx * nb, fb);
                        }
                    } else {
                        const uint32_t ab = type == IT_W64 ? 32768 : 16384;
                        for (int k = 0; k < 32; k++) {
                            const int s = acquire(ab + 16384);
                            const uint32_t st = g.st + s * STAGE_BYTES, fb = g.full + 8 * s;
                            tma3d(st, type == IT_W64 ? &P.mo2 : &P.mo2s, 0, m0 + (idx >> 4) * 64, k * 2, fb);
                            tma3d(st + ab, &P.mwo1, 0, k * 128, idx & 15, fb);
                        }
                    }
                }
            }
        } else if (threadIdx.x == 32) {
            for (;;) {
                mbar_wait(bar_o, 0);
                const int code = lds32(slot_o), blk = (code >> 3) & 15, idx = (code >> 7) & 31;
                if ((code & 7) == IT_END) break;
                for (int hh = 0; hh < 2; hh++) {
                    if (hh) mbar_wait(bar_o, 1);
                    asm volatile("cp.async.bulk.tensor.3d.global.shared::cta.bulk_group [%0, {%2, %3, %4}], [%1];\n"
                                 "cp.async.bulk.commit_group;\ncp.async.bulk.wait_group.read 0;"
                                 ::"l"(&P.mo2), "r"(g.st + B_OST), "r"(0), "r"(blk * 128), "r"(idx * 4 + hh * 2) : "memory");
                    mbar_arrive(bar_f);
                }
                asm volatile("cp.async.bulk.wait_group 0;\nfence.acq_rel.gpu;\nred.relaxed.gpu.global.add.u32 [%0], 1;"
                             ::"l"(g_flag + 64 + blk) : "memory");
            }
        }
    } else {
        asm volatile("setmaxnreg.inc.sync.aligned.u32 232;");
        const int cw = wg - 1, ww = __shfl_sync(~0u, (threadIdx.x >> 5) & 3, 0), lane = threadIdx.x & 31;
        uint32_t round = 0;
#pragma unroll 1
        for (int n = 0;; n++) {
            mbar_wait_u(bar_item + (n & 1) * 8, (n >> 1) & 1);
            const int code = __shfl_sync(~0u, lds32(slot + (n & 1) * 4), 0);
            const int type = code & 7, blk = (code >> 3) & 15, idx = (code >> 7) & 31;
#define TLB(slot_)
            if (type == IT_END) {
                mbar_wait_u(bar_f, 1);
                if (threadIdx.x == 128) sts32(slot_o, IT_END);
                __syncwarp();
                mbar_arrive_one(bar_o, lane);
                break;
            }
            TLB(0);
            if (type == IT_QA) {
                uint32_t q[64];
                {
                    float acc[128];
                    gemm_mainloop<128, 256, 1>(acc, g, cw, 4, round);
#pragma unroll
                    for (int i = 0; i < 64; i++) q[i] = pack2(acc[2 * i], acc[2 * i + 1]);
                }
                if (threadIdx.x == 128) sts32(slot_o, code);
                TLB(2);
                const uint32_t st = g.st + cw * STAGE_BYTES, ost = g.st + B_OST + (cw * 4 + ww) * 2048;
                if (ww & 1) attend<1>(q, st + (ww >> 1) * 4096, st + 32768 + (ww >> 1) * 1024, ost, bar_f, bar_o, g.full, round & 1, g.empty, lane);
                else attend<0>(q, st + (ww >> 1) * 4096, st + 32768 + (ww >> 1) * 1024, ost, bar_f, bar_o, g.full, round & 1, g.empty, lane);
                round++;
            } else {
                bf16* dst = out + (size_t)(blk * 128 + cw * 64 + ww * 16 + (lane >> 2)) * 2048 + (lane & 3) * 8;
                if (type == IT_W256) wo_item<128, 256, 1>(g, cw, round, dst + idx * 256, lane & 3);
                else if (type == IT_W128) wo_item<128, 128, 1>(g, cw, round, dst + idx * 128, lane & 3);
                else if (type == IT_W64) wo_item<128, 64, 2>(g, cw, round, dst + idx * 64, lane & 3);
                else wo_item<64, 64, 2>(g, cw, round, dst + (size_t)(idx >> 4) * 64 * 2048 + (idx & 15) * 64, lane & 3);
            }
            TLB(1);
        }
    }
}

#define TCL 6
__global__ void __cluster_dims__(TCL, 1, 1) __launch_bounds__(384, 1)
k_tail(const __grid_constant__ CUtensorMap mo, const __grid_constant__ CUtensorMap mwo2, bf16* __restrict__ out) {
    extern __shared__ __align__(1024) uint8_t smem_gemm[];
    const uint32_t bar_s = smem_u32(smem_gemm) + NSTAGE * STAGE_BYTES + 128;
    if (threadIdx.x == 0) { TL(4, 0); mbar_init(bar_s, 1); mbar_expect_tx(bar_s, 32768); }
    GemmSmem g = gemm_setup(smem_gemm, 8);
    asm volatile("barrier.cluster.arrive.relaxed.aligned;" ::: "memory");
    const int half = blockIdx.x & 1, cl = blockIdx.x / 6, peer = TCL == 6 ? (blockIdx.x - 6 * cl) ^ 1 : half ^ 1;
    const int blk = TCL == 6 ? NBT + (cl >> 3) * 3 + (peer >> 1) : NBT + (blockIdx.x >> 4), idx = TCL == 6 ? cl & 7 : (blockIdx.x >> 1) & 7;
    const int wg = __shfl_sync(~0u, threadIdx.x >> 7, 0);
    if (wg == 0) {
        if (threadIdx.x == 0) {
            wait_flag(g_flag + 64 + blk, 16);
            asm volatile("fence.proxy.async.global;" ::: "memory");
            for (int k = 0; k < 32; k++) {
                const int s = k & 3;
                const uint32_t st = g.st + s * STAGE_BYTES, fb = g.full + 8 * s;
                mbar_wait(g.empty + 8 * s, ((k >> 2) & 1) ^ 1);
                mbar_expect_tx(fb, 32768);
                tma2d(st, &mo, (half * 32 + k) * 64, blk * 128, fb);
                tma3d(st + 16384, &mwo2, 0, (half * 32 + k) * 64, idx * 2, fb);
            }
        }
        __syncwarp();
        asm volatile("barrier.cluster.wait.aligned;" ::: "memory");
    } else {
        const int cw = wg - 1, lane = threadIdx.x & 31, t = lane & 3;
        float acc[64];
        uint32_t round = 0;
        gemm_mainloop<128, 128, 1>(acc, g, cw, 8, round);
        asm volatile("barrier.cluster.wait.aligned;" ::: "memory");
        const uint32_t xa = g.st + B_OST + (threadIdx.x & 127) * 16;
        if (cw != half) {
            uint32_t ra, rb;
            asm("mapa.shared::cluster.u32 %0, %1, %2;" : "=r"(ra) : "r"(xa), "r"(peer));
            asm("mapa.shared::cluster.u32 %0, %1, %2;" : "=r"(rb) : "r"(bar_s), "r"(peer));
#pragma unroll
            for (int i = 0; i < 16; i++)
                asm volatile("st.async.weak.shared::cluster.mbarrier::complete_tx::bytes.v4.f32 [%0], {%1,%2,%3,%4}, [%5];"
                             ::"r"(ra + i * 2048), "f"(acc[4 * i]), "f"(acc[4 * i + 1]), "f"(acc[4 * i + 2]), "f"(acc[4 * i + 3]), "r"(rb) : "memory");
        } else {
            mbar_wait_u(bar_s, 0);
#pragma unroll
            for (int i = 0; i < 16; i++) {
                const float4 v = lds128f(xa + i * 2048);
                acc[4 * i] += v.x; acc[4 * i + 1] += v.y; acc[4 * i + 2] += v.z; acc[4 * i + 3] += v.w;
            }
            store_tile<128>(acc, out + (size_t)(blk * 128 + cw * 64 + ((threadIdx.x >> 5) & 3) * 16 + (lane >> 2)) * 2048 + idx * 128 + t * 8, t);
            if ((threadIdx.x & 127) == 0) TL(4, 1);
        }
    }
    asm volatile("barrier.cluster.arrive.relaxed.aligned;\nbarrier.cluster.wait.aligned;" ::: "memory");
}

typedef CUresult (*EncodeFn)(CUtensorMap*, CUtensorMapDataType, cuuint32_t, void*, const cuuint64_t*, const cuuint64_t*,
                             const cuuint32_t*, const cuuint32_t*, CUtensorMapInterleave, CUtensorMapSwizzle,
                             CUtensorMapL2promotion, CUtensorMapFloatOOBfill);

static void map2d(EncodeFn enc, CUtensorMap* m, const void* p, int rows, int cols, int box_rows) {
    cuuint64_t dim[2] = {(cuuint64_t)cols, (cuuint64_t)rows}, str[1] = {(cuuint64_t)cols * 2};
    cuuint32_t box[2] = {64, (cuuint32_t)box_rows}, es[2] = {1, 1};
    enc(m, CU_TENSOR_MAP_DATA_TYPE_BFLOAT16, 2, (void*)p, dim, str, box, es, CU_TENSOR_MAP_INTERLEAVE_NONE,
        CU_TENSOR_MAP_SWIZZLE_128B, CU_TENSOR_MAP_L2_PROMOTION_L2_256B, CU_TENSOR_MAP_FLOAT_OOB_FILL_NONE);
}
static void map3d(EncodeFn enc, CUtensorMap* m, const void* p, int rows, int cols, int box_rows, int nblk) {
    cuuint64_t dim[3] = {64, (cuuint64_t)rows, (cuuint64_t)cols / 64}, str[2] = {(cuuint64_t)cols * 2, 128};
    cuuint32_t box[3] = {64, (cuuint32_t)box_rows, (cuuint32_t)nblk}, es[3] = {1, 1, 1};
    enc(m, CU_TENSOR_MAP_DATA_TYPE_BFLOAT16, 3, (void*)p, dim, str, box, es, CU_TENSOR_MAP_INTERLEAVE_NONE,
        CU_TENSOR_MAP_SWIZZLE_128B, CU_TENSOR_MAP_L2_PROMOTION_L2_256B, CU_TENSOR_MAP_FLOAT_OOB_FILL_NONE);
}

#define USE_PDL 1

extern "C" void kernel_launch(void* const* d_in, const int* in_sizes, int n_in, void* d_out, int out_size) {
    const bf16 *x = (const bf16*)d_in[0], *mem0 = (const bf16*)d_in[1], *Wq = (const bf16*)d_in[2], *Wk = (const bf16*)d_in[3];
    const bf16 *Wv = (const bf16*)d_in[4], *Wo = (const bf16*)d_in[5];
    const bf16 *u = (const bf16*)d_in[7], *Are = (const bf16*)d_in[8], *Aim = (const bf16*)d_in[9], *Bre = (const bf16*)d_in[10];
    const bf16 *Bim = (const bf16*)d_in[11], *Cre = (const bf16*)d_in[12], *Cim = (const bf16*)d_in[13];
    const bf16 *logdt = (const bf16*)d_in[14], *Dsk = (const bf16*)d_in[15];
    bf16* out = (bf16*)d_out;

    void* fn = nullptr;
    cudaDriverEntryPointQueryResult qr;
    cudaGetDriverEntryPoint("cuTensorMapEncodeTiled", &fn, cudaEnableDefault, &qr);
    EncodeFn enc = (EncodeFn)fn;
    void *kv, *kvm, *o;
    cudaGetSymbolAddress(&kv, g_kv);
    cudaGetSymbolAddress(&kvm, g_kvm);
    cudaGetSymbolAddress(&o, g_o);
    CUtensorMap mwk, mwv, mkv2;
    BgParams P;
    map2d(enc, &P.mx, x, SEQ, DM, 128);
    map2d(enc, &P.mo, o, SEQ, HD, 128);
    map3d(enc, &P.mo2, o, SEQ, HD, 128, 2);
    map3d(enc, &P.mo2s, o, SEQ, HD, 64, 2);
    map3d(enc, &P.mwq, Wq, DM, HD, 64, 4);
    map3d(enc, &mwk, Wk, DM, HD, 64, 2);
    map3d(enc, &mwv, Wv, DM, HD, 64, 2);
    map3d(enc, &P.mwo4, Wo, HD, DM, 64, 4);
    map3d(enc, &P.mwo2, Wo, HD, DM, 64, 2);
    map3d(enc, &P.mwo1, Wo, HD, DM, 128, 1);
    map3d(enc, &mkv2, kv, SEQ, 8192, 32, 2);
    map3d(enc, &P.mkv, kv, SEQ, 8192, 64, 2);
    map3d(enc, &P.mkvm, kvm, NSEG * 8, 8192, 16, 2);
    cudaFuncSetAttribute(k_kv, cudaFuncAttributeMaxDynamicSharedMemorySize, GEMM_SMEM);
    cudaFuncSetAttribute(k_bg, cudaFuncAttributeMaxDynamicSharedMemorySize, BG_SMEM);
    cudaFuncSetAttribute(k_tail, cudaFuncAttributeMaxDynamicSharedMemorySize, BG_SMEM);
    cudaFuncSetAttribute(k_chain, cudaFuncAttributeMaxDynamicSharedMemorySize, CHAIN_SMEM);
    cudaFuncSetAttribute(k_s4, cudaFuncAttributeMaxDynamicSharedMemorySize, S4_SMEM);

    cudaStream_t st = cudaStreamPerThread;
    cudaLaunchAttribute pdl[2], cls[1];
    pdl[0].id = cudaLaunchAttributeProgrammaticStreamSerialization;
    pdl[0].val.programmaticStreamSerializationAllowed = 1;
    cls[0].id = cudaLaunchAttributeClusterDimension;
    cls[0].val.clusterDim.x = CLS; cls[0].val.clusterDim.y = 1; cls[0].val.clusterDim.z = 1;
    cudaLaunchConfig_t cfg = {};
    cfg.stream = st; cfg.attrs = cls; cfg.numAttrs = 1;
    cfg.gridDim = dim3(96); cfg.blockDim = dim3(384); cfg.dynamicSmemBytes = GEMM_SMEM;
    cudaLaunchKernelEx(&cfg, k_kv, P.mx, mwk, mwv, Wq, Wk, Wo, 0);
    pdl[1] = cls[0]; pdl[1].val.clusterDim.x = 2;
    cfg.attrs = pdl; cfg.numAttrs = 2;
    cfg.gridDim = dim3(36);
    cudaLaunchKernelEx(&cfg, k_kv, P.mx, mwk, mwv, Wq, Wk, Wo, 96);
    cfg.numAttrs = 1;
    cfg.gridDim = dim3(96); cfg.blockDim = dim3(256); cfg.dynamicSmemBytes = CHAIN_SMEM;
    cudaLaunchKernelEx(&cfg, k_chain, mem0, Wq, Wk, Wv, Wo, mkv2);
    cfg.numAttrs = USE_PDL;
    cfg.gridDim = dim3(36); cfg.blockDim = dim3(512); cfg.dynamicSmemBytes = S4_SMEM;
    cudaLaunchKernelEx(&cfg, k_s4, u, Are, Aim, Bre, Bim, Cre, Cim, logdt, Dsk, out);
    cfg.gridDim = dim3(36); cfg.blockDim = dim3(384); cfg.dynamicSmemBytes = BG_SMEM;
    cudaLaunchKernelEx(&cfg, k_bg, P, out);
    cfg.gridDim = dim3((15 - NBT) * 16);
    cudaLaunchKernelEx(&cfg, k_tail, P.mo, P.mwo2, out);
}
```

```cpp
#include <cuda_runtime.h>
#include <cuda_bf16.h>
#include <cuda.h>
#include <stdint.h>

typedef __nv_bfloat16 bf16;

constexpr int SEQ = 2048, DM = 1024, HD = 4096, NSEG = 64;

constexpr int PW = 3 * HD;
#define NTA 3
__device__ __align__(1024) bf16 g_kv[(size_t)SEQ * PW];
__device__ __align__(1024) bf16 g_o[(size_t)SEQ * HD];
constexpr int XPAIRS = 128 + NSEG * 4;
__device__ __align__(8192) uint2 g_x[XPAIRS * 1024];
__device__ uint32_t g_home[XPAIRS];
__device__ uint32_t g_side[256];
__device__ __align__(1024) uint32_t g_flag[256];

#define TL(kern, slot)

__device__ __forceinline__ uint32_t smem_u32(const void* p) { return (uint32_t)__cvta_generic_to_shared(p); }
__device__ __forceinline__ void mbar_init(uint32_t bar, uint32_t cnt) {
    asm volatile("mbarrier.init.shared::cta.b64 [%0], %1;" ::"r"(bar), "r"(cnt) : "memory");
}
__device__ __forceinline__ void mbar_expect_tx(uint32_t bar, uint32_t bytes) {
    asm volatile("mbarrier.arrive.expect_tx.shared::cta.b64 _, [%0], %1;" ::"r"(bar), "r"(bytes) : "memory");
}
__device__ __forceinline__ void mbar_arrive(uint32_t bar) {
    asm volatile("mbarrier.arrive.shared::cta.b64 _, [%0];" ::"r"(bar) : "memory");
}
__device__ __forceinline__ bool mbar_try(uint32_t bar, uint32_t parity) {
    uint32_t ok;
    asm volatile("{\n.reg .pred p;\nmbarrier.try_wait.parity.shared::cta.b64 p, [%1], %2;\nselp.u32 %0, 1, 0, p;\n}"
                 : "=r"(ok) : "r"(bar), "r"(parity) : "memory");
    return ok;
}
constexpr int SPIN_LIMIT = 1 << 20;
__device__ __forceinline__ void mbar_wait(uint32_t bar, uint32_t parity) {
    int n = 0;
    while (!mbar_try(bar, parity)) { if (++n > SPIN_LIMIT) __trap(); }
}
__device__ __forceinline__ void mbar_wait_u(uint32_t bar, uint32_t parity) {
    asm volatile("{\n.reg .pred p;\n.reg .u32 n;\n"
                 "mbarrier.try_wait.parity.shared::cta.b64 p, [%0], %1;\n@p bra.uni DONE;\nmov.u32 n, 0;\n"
                 "AGAIN:\nmbarrier.try_wait.parity.shared::cta.b64 p, [%0], %1;\n@p bra.uni DONE;\n"
                 "add.u32 n, n, 1;\nsetp.lt.u32 p, n, 0x100000;\n@p bra.uni AGAIN;\ntrap;\nDONE:\n}"
                 ::"r"(bar), "r"(parity) : "memory");
}
__device__ __forceinline__ void tma2d(uint32_t dst, const CUtensorMap* m, int c0, int c1, uint32_t bar) {
    asm volatile("cp.async.bulk.tensor.2d.shared::cluster.global.mbarrier::complete_tx::bytes [%0], [%1, {%3, %4}], [%2];"
                 ::"r"(dst), "l"(m), "r"(bar), "r"(c0), "r"(c1) : "memory");
}
__device__ __forceinline__ void tma3d(uint32_t dst, const CUtensorMap* m, int c0, int c1, int c2, uint32_t bar) {
    asm volatile("cp.async.bulk.tensor.3d.shared::cluster.global.mbarrier::complete_tx::bytes [%0], [%1, {%3, %4, %5}], [%2];"
                 ::"r"(dst), "l"(m), "r"(bar), "r"(c0), "r"(c1), "r"(c2) : "memory");
}
__device__ __forceinline__ uint32_t pack2(float lo, float hi) {
    uint32_t r;
    asm("cvt.rn.bf16x2.f32 %0, %1, %2;" : "=r"(r) : "f"(hi), "f"(lo));
    return r;
}
__device__ __forceinline__ float bf_lo(uint32_t v) { return __uint_as_float(v << 16); }
__device__ __forceinline__ float bf_hi(uint32_t v) { return __uint_as_float(v & 0xffff0000u); }
__device__ __forceinline__ float bf_round(float x) { return bf_lo(pack2(x, 0.f)); }
__device__ __forceinline__ float ex2(float x) { float y; asm("ex2.approx.ftz.f32 %0, %1;" : "=f"(y) : "f"(x)); return y; }
__device__ __forceinline__ void mma16816(float (&c)[4], uint32_t a0, uint32_t a1, uint32_t a2, uint32_t a3, uint32_t b0, uint32_t b1) {
    asm volatile("mma.sync.aligned.m16n8k16.row.col.f32.bf16.bf16.f32 {%0,%1,%2,%3}, {%4,%5,%6,%7}, {%8,%9}, {%0,%1,%2,%3};"
                 : "+f"(c[0]), "+f"(c[1]), "+f"(c[2]), "+f"(c[3]) : "r"(a0), "r"(a1), "r"(a2), "r"(a3), "r"(b0), "r"(b1));
}
__device__ __forceinline__ void mma1688(float (&c)[4], uint32_t a0, uint32_t a1, uint32_t b0) {
    asm volatile("mma.sync.aligned.m16n8k8.row.col.f32.bf16.bf16.f32 {%0,%1,%2,%3}, {%4,%5}, {%6}, {%0,%1,%2,%3};"
                 : "+f"(c[0]), "+f"(c[1]), "+f"(c[2]), "+f"(c[3]) : "r"(a0), "r"(a1), "r"(b0));
}
__device__ __forceinline__ void ldsm4(uint32_t (&r)[4], uint32_t a) {
    asm volatile("ldmatrix.sync.aligned.m8n8.x4.shared.b16 {%0,%1,%2,%3}, [%4];"
                 : "=r"(r[0]), "=r"(r[1]), "=r"(r[2]), "=r"(r[3]) : "r"(a) : "memory");
}
__device__ __forceinline__ void ldsm4t(uint32_t (&r)[4], uint32_t a) {
    asm volatile("ldmatrix.sync.aligned.m8n8.x4.trans.shared.b16 {%0,%1,%2,%3}, [%4];"
                 : "=r"(r[0]), "=r"(r[1]), "=r"(r[2]), "=r"(r[3]) : "r"(a) : "memory");
}
__device__ __forceinline__ void ldsm2t(uint32_t& r0, uint32_t& r1, uint32_t a) {
    asm volatile("ldmatrix.sync.aligned.m8n8.x2.trans.shared.b16 {%0,%1}, [%2];" : "=r"(r0), "=r"(r1) : "r"(a) : "memory");
}
__device__ __forceinline__ void stsm4t(uint32_t a, uint32_t r0, uint32_t r1, uint32_t r2, uint32_t r3) {
    asm volatile("stmatrix.sync.aligned.m8n8.x4.trans.shared.b16 [%0], {%1,%2,%3,%4};"
                 ::"r"(a), "r"(r0), "r"(r1), "r"(r2), "r"(r3) : "memory");
}
__device__ __forceinline__ void lds128(uint32_t (&r)[4], uint32_t a) {
    asm volatile("ld.shared.v4.u32 {%0,%1,%2,%3}, [%4];" : "=r"(r[0]), "=r"(r[1]), "=r"(r[2]), "=r"(r[3]) : "r"(a) : "memory");
}
__device__ __forceinline__ float4 lds128f(uint32_t a) {
    float4 v;
    asm volatile("ld.shared.v4.f32 {%0,%1,%2,%3}, [%4];" : "=f"(v.x), "=f"(v.y), "=f"(v.z), "=f"(v.w) : "r"(a) : "memory");
    return v;
}
__device__ __forceinline__ float2 lds64f(uint32_t a) {
    float2 v;
    asm volatile("ld.shared.v2.f32 {%0,%1}, [%2];" : "=f"(v.x), "=f"(v.y) : "r"(a) : "memory");
    return v;
}
__device__ __forceinline__ uint32_t lds32(uint32_t a) {
    uint32_t v;
    asm volatile("ld.shared.u32 %0, [%1];" : "=r"(v) : "r"(a) : "memory");
    return v;
}
__device__ __forceinline__ void sts128(uint32_t a, uint32_t r0, uint32_t r1, uint32_t r2, uint32_t r3) {
    asm volatile("st.shared.v4.u32 [%0], {%1,%2,%3,%4};" ::"r"(a), "r"(r0), "r"(r1), "r"(r2), "r"(r3) : "memory");
}
__device__ __forceinline__ void sts128f(uint32_t a, float r0, float r1, float r2, float r3) {
    asm volatile("st.shared.v4.f32 [%0], {%1,%2,%3,%4};" ::"r"(a), "f"(r0), "f"(r1), "f"(r2), "f"(r3) : "memory");
}
__device__ __forceinline__ void sts64(uint32_t a, uint32_t r0, uint32_t r1) {
    asm volatile("st.shared.v2.u32 [%0], {%1,%2};" ::"r"(a), "r"(r0), "r"(r1) : "memory");
}
__device__ __forceinline__ void sts64f(uint32_t a, float r0, float r1) {
    asm volatile("st.shared.v2.f32 [%0], {%1,%2};" ::"r"(a), "f"(r0), "f"(r1) : "memory");
}
__device__ __forceinline__ void sts32f(uint32_t a, float r0) {
    asm volatile("st.shared.f32 [%0], %1;" ::"r"(a), "f"(r0) : "memory");
}
__device__ __forceinline__ uint2 ld_rlx64(const uint2* p) {
    uint2 v;
    asm volatile("{\n.reg .b64 t;\nld.relaxed.gpu.global.b64 t, [%2];\nmov.b64 {%0,%1}, t;\n}" : "=r"(v.x), "=r"(v.y) : "l"(p) : "memory");
    return v;
}
__device__ __forceinline__ void st_rlx64(uint2* p, uint32_t x, uint32_t y) {
    asm volatile("{\n.reg .b64 t;\nmov.b64 t, {%1,%2};\nst.relaxed.gpu.global.b64 [%0], t;\n}" ::"l"(p), "r"(x), "r"(y) : "memory");
}
__device__ __forceinline__ uint32_t ld_acq32(const uint32_t* p) {
    uint32_t v;
    asm volatile("ld.acquire.gpu.global.u32 %0, [%1];" : "=r"(v) : "l"(p) : "memory");
    return v;
}
__device__ __forceinline__ void wait_flag(const uint32_t* p, uint32_t need) {
    int n = 0;
    while (ld_acq32(p) < need) { __nanosleep(200); if (++n > SPIN_LIMIT) __trap(); }
}
__device__ __forceinline__ void bar_sync(int id, int n) { asm volatile("bar.sync %0, %1;" ::"r"(id), "r"(n) : "memory"); }
__device__ __forceinline__ void wg_fence() { asm volatile("wgmma.fence.sync.aligned;" ::: "memory"); }
__device__ __forceinline__ void wg_commit() { asm volatile("wgmma.commit_group.sync.aligned;" ::: "memory"); }
template <int N> __device__ __forceinline__ void wg_wait() { asm volatile("wgmma.wait_group.sync.aligned %0;" ::"n"(N) : "memory"); }
__device__ __forceinline__ uint64_t desc_sw128(uint32_t addr, uint32_t lbo, uint32_t sbo) {
    return (uint64_t)((addr & 0x3FFFF) >> 4) | ((uint64_t)(lbo >> 4) << 16) | ((uint64_t)(sbo >> 4) << 32) | (1ull << 62);
}
__device__ __forceinline__ void quad_transpose(uint32_t& r0, uint32_t& r1, uint32_t& r2, uint32_t& r3, int t) {
    const bool o = t & 1, h = t & 2;
    uint32_t s0 = __shfl_xor_sync(~0u, o ? r0 : r1, 1), s1 = __shfl_xor_sync(~0u, o ? r2 : r3, 1);
    uint32_t a0 = o ? s0 : r0, a1 = o ? r1 : s0, a2 = o ? s1 : r2, a3 = o ? r3 : s1;
    s0 = __shfl_xor_sync(~0u, h ? a0 : a2, 2); s1 = __shfl_xor_sync(~0u, h ? a1 : a3, 2);
    r0 = h ? s0 : a0; r1 = h ? s1 : a1; r2 = h ? a2 : s0; r3 = h ? a3 : s1;
}

__device__ __forceinline__ void wgmma_n256(float (&d)[128], uint64_t da, uint64_t db, int sd) {
    asm volatile("{\n.reg .pred p;\nsetp.ne.b32 p, %130, 0;\n"
        "wgmma.mma_async.sync.aligned.m64n256k16.f32.bf16.bf16 "
        "{%0,%1,%2,%3,%4,%5,%6,%7,%8,%9,%10,%11,%12,%13,%14,%15,"
        "%16,%17,%18,%19,%20,%21,%22,%23,%24,%25,%26,%27,%28,%29,%30,%31,"
        "%32,%33,%34,%35,%36,%37,%38,%39,%40,%41,%42,%43,%44,%45,%46,%47,"
        "%48,%49,%50,%51,%52,%53,%54,%55,%56,%57,%58,%59,%60,%61,%62,%63,"
        "%64,%65,%66,%67,%68,%69,%70,%71,%72,%73,%74,%75,%76,%77,%78,%79,"
        "%80,%81,%82,%83,%84,%85,%86,%87,%88,%89,%90,%91,%92,%93,%94,%95,"
        "%96,%97,%98,%99,%100,%101,%102,%103,%104,%105,%106,%107,%108,%109,%110,%111,"
        "%112,%113,%114,%115,%116,%117,%118,%119,%120,%121,%122,%123,%124,%125,%126,%127}, %128, %129, p, 1, 1, 0, 1;\n}\n"
        : "+f"(d[0]), "+f"(d[1]), "+f"(d[2]), "+f"(d[3]), "+f"(d[4]), "+f"(d[5]), "+f"(d[6]), "+f"(d[7]),
          "+f"(d[8]), "+f"(d[9]), "+f"(d[10]), "+f"(d[11]), "+f"(d[12]), "+f"(d[13]), "+f"(d[14]), "+f"(d[15]),
          "+f"(d[16]), "+f"(d[17]), "+f"(d[18]), "+f"(d[19]), "+f"(d[20]), "+f"(d[21]), "+f"(d[22]), "+f"(d[23]),
          "+f"(d[24]), "+f"(d[25]), "+f"(d[26]), "+f"(d[27]), "+f"(d[28]), "+f"(d[29]), "+f"(d[30]), "+f"(d[31]),
          "+f"(d[32]), "+f"(d[33]), "+f"(d[34]), "+f"(d[35]), "+f"(d[36]), "+f"(d[37]), "+f"(d[38]), "+f"(d[39]),
          "+f"(d[40]), "+f"(d[41]), "+f"(d[42]), "+f"(d[43]), "+f"(d[44]), "+f"(d[45]), "+f"(d[46]), "+f"(d[47]),
          "+f"(d[48]), "+f"(d[49]), "+f"(d[50]), "+f"(d[51]), "+f"(d[52]), "+f"(d[53]), "+f"(d[54]), "+f"(d[55]),
          "+f"(d[56]), "+f"(d[57]), "+f"(d[58]), "+f"(d[59]), "+f"(d[60]), "+f"(d[61]), "+f"(d[62]), "+f"(d[63]),
          "+f"(d[64]), "+f"(d[65]), "+f"(d[66]), "+f"(d[67]), "+f"(d[68]), "+f"(d[69]), "+f"(d[70]), "+f"(d[71]),
          "+f"(d[72]), "+f"(d[73]), "+f"(d[74]), "+f"(d[75]), "+f"(d[76]), "+f"(d[77]), "+f"(d[78]), "+f"(d[79]),
          "+f"(d[80]), "+f"(d[81]), "+f"(d[82]), "+f"(d[83]), "+f"(d[84]), "+f"(d[85]), "+f"(d[86]), "+f"(d[87]),
          "+f"(d[88]), "+f"(d[89]), "+f"(d[90]), "+f"(d[91]), "+f"(d[92]), "+f"(d[93]), "+f"(d[94]), "+f"(d[95]),
          "+f"(d[96]), "+f"(d[97]), "+f"(d[98]), "+f"(d[99]), "+f"(d[100]), "+f"(d[101]), "+f"(d[102]), "+f"(d[103]),
          "+f"(d[104]), "+f"(d[105]), "+f"(d[106]), "+f"(d[107]), "+f"(d[108]), "+f"(d[109]), "+f"(d[110]), "+f"(d[111]),
          "+f"(d[112]), "+f"(d[113]), "+f"(d[114]), "+f"(d[115]), "+f"(d[116]), "+f"(d[117]), "+f"(d[118]), "+f"(d[119]),
          "+f"(d[120]), "+f"(d[121]), "+f"(d[122]), "+f"(d[123]), "+f"(d[124]), "+f"(d[125]), "+f"(d[126]), "+f"(d[127])
        : "l"(da), "l"(db), "r"(sd));
}

__device__ __forceinline__ void wgmma_n128(float (&d)[64], uint64_t da, uint64_t db, int sd) {
    asm volatile("{\n.reg .pred p;\nsetp.ne.b32 p, %66, 0;\n"
        "wgmma.mma_async.sync.aligned.m64n128k16.f32.bf16.bf16 "
        "{%0,%1,%2,%3,%4,%5,%6,%7,%8,%9,%10,%11,%12,%13,%14,%15,"
        "%16,%17,%18,%19,%20,%21,%22,%23,%24,%25,%26,%27,%28,%29,%30,%31,"
        "%32,%33,%34,%35,%36,%37,%38,%39,%40,%41,%42,%43,%44,%45,%46,%47,"
        "%48,%49,%50,%51,%52,%53,%54,%55,%56,%57,%58,%59,%60,%61,%62,%63}, %64, %65, p, 1, 1, 0, 1;\n}\n"
        : "+f"(d[0]), "+f"(d[1]), "+f"(d[2]), "+f"(d[3]), "+f"(d[4]), "+f"(d[5]), "+f"(d[6]), "+f"(d[7]),
          "+f"(d[8]), "+f"(d[9]), "+f"(d[10]), "+f"(d[11]), "+f"(d[12]), "+f"(d[13]), "+f"(d[14]), "+f"(d[15]),
          "+f"(d[16]), "+f"(d[17]), "+f"(d[18]), "+f"(d[19]), "+f"(d[20]), "+f"(d[21]), "+f"(d[22]), "+f"(d[23]),
          "+f"(d[24]), "+f"(d[25]), "+f"(d[26]), "+f"(d[27]), "+f"(d[28]), "+f"(d[29]), "+f"(d[30]), "+f"(d[31]),
          "+f"(d[32]), "+f"(d[33]), "+f"(d[34]), "+f"(d[35]), "+f"(d[36]), "+f"(d[37]), "+f"(d[38]), "+f"(d[39]),
          "+f"(d[40]), "+f"(d[41]), "+f"(d[42]), "+f"(d[43]), "+f"(d[44]), "+f"(d[45]), "+f"(d[46]), "+f"(d[47]),
          "+f"(d[48]), "+f"(d[49]), "+f"(d[50]), "+f"(d[51]), "+f"(d[52]), "+f"(d[53]), "+f"(d[54]), "+f"(d[55]),
          "+f"(d[56]), "+f"(d[57]), "+f"(d[58]), "+f"(d[59]), "+f"(d[60]), "+f"(d[61]), "+f"(d[62]), "+f"(d[63])
        : "l"(da), "l"(db), "r"(sd));
}

__device__ __forceinline__ void wgmma_n64(float (&d)[32], uint64_t da, uint64_t db, int sd) {
    asm volatile("{\n.reg .pred p;\nsetp.ne.b32 p, %34, 0;\n"
        "wgmma.mma_async.sync.aligned.m64n64k16.f32.bf16.bf16 "
        "{%0,%1,%2,%3,%4,%5,%6,%7,%8,%9,%10,%11,%12,%13,%14,%15,"
        "%16,%17,%18,%19,%20,%21,%22,%23,%24,%25,%26,%27,%28,%29,%30,%31}, %32, %33, p, 1, 1, 0, 1;\n}\n"
        : "+f"(d[0]), "+f"(d[1]), "+f"(d[2]), "+f"(d[3]), "+f"(d[4]), "+f"(d[5]), "+f"(d[6]), "+f"(d[7]),
          "+f"(d[8]), "+f"(d[9]), "+f"(d[10]), "+f"(d[11]), "+f"(d[12]), "+f"(d[13]), "+f"(d[14]), "+f"(d[15]),
          "+f"(d[16]), "+f"(d[17]), "+f"(d[18]), "+f"(d[19]), "+f"(d[20]), "+f"(d[21]), "+f"(d[22]), "+f"(d[23]),
          "+f"(d[24]), "+f"(d[25]), "+f"(d[26]), "+f"(d[27]), "+f"(d[28]), "+f"(d[29]), "+f"(d[30]), "+f"(d[31])
        : "l"(da), "l"(db), "r"(sd));
}

constexpr int STAGE_BYTES = 49152, NSTAGE = 4;
constexpr int GEMM_SMEM = NSTAGE * STAGE_BYTES + 128;

struct GemmSmem { uint32_t st, full, empty; };
__device__ __forceinline__ GemmSmem gemm_setup(uint8_t* raw, int releases) {
    GemmSmem g;
    g.st = smem_u32(raw);
    if (g.st & 1023) __trap();
    g.full = g.st + NSTAGE * STAGE_BYTES; g.empty = g.full + 64;
    if (threadIdx.x == 0) {
        for (int s = 0; s < NSTAGE; s++) { mbar_init(g.full + 8 * s, 1); mbar_init(g.empty + 8 * s, releases); }
        asm volatile("fence.mbarrier_init.release.cluster;" ::: "memory");
        asm volatile("fence.proxy.async.shared::cta;" ::: "memory");
    }
    __syncthreads();
    return g;
}
__device__ __forceinline__ void mbar_arrive_one(uint32_t bar, uint32_t who) {
    asm volatile("{\n.reg .pred p;\nsetp.eq.u32 p, %1, 0;\n@p mbarrier.arrive.shared::cta.b64 _, [%0];\n}" ::"r"(bar), "r"(who) : "memory");
}
template <int BM, int BN, int KPS, typename ACC>
__device__ __forceinline__ void gemm_stage(ACC& acc, uint32_t stage, int wg, bool first) {
    const uint64_t da = desc_sw128(stage + wg * 8192, 16, 1024);
    const uint64_t db = desc_sw128(stage + KPS * BM * 128, 8192, 1024);
    wg_fence();
#pragma unroll
    for (int k = 0; k < 4 * KPS; k++) {
        const uint64_t a = da + (k >> 2) * (BM * 8) + (k & 3) * 2, b = db + k * 128;
        if constexpr (BN == 256) wgmma_n256(acc, a, b, first && k == 0 ? 0 : 1);
        else if constexpr (BN == 128) wgmma_n128(acc, a, b, first && k == 0 ? 0 : 1);
        else wgmma_n64(acc, a, b, first && k == 0 ? 0 : 1);
    }
    wg_commit();
}

__device__ __forceinline__ void kv_store_unit(const uint32_t (&pk)[64], int u, bf16* dst, int t) {
    const int G = (u >> 2) * 2 + (u & 1), hh = (u >> 1) & 1;
    uint32_t r0 = pk[(4 * G + 0) * 2 + hh], r1 = pk[(4 * G + 1) * 2 + hh], r2 = pk[(4 * G + 2) * 2 + hh], r3 = pk[(4 * G + 3) * 2 + hh];
    quad_transpose(r0, r1, r2, r3, t);
#define KVST ".cs"
    asm volatile("st.global" KVST ".v4.u32 [%0], {%1,%2,%3,%4};" ::"l"(dst + (size_t)hh * 8 * PW + G * 32), "r"(r0), "r"(r1), "r"(r2), "r"(r3) : "memory");
}

#define TLK(slot)
#define TLK2(slot)
__device__ __forceinline__ uint32_t near_page(int pair, int line) {
    uint32_t best[2] = {~0u, ~0u};
#pragma unroll 1
    for (int i = 0; i < 16; i++) {
        uint32_t t0, t1, v;
        asm volatile("mov.u32 %0, %%clock;" : "=r"(t0)::"memory");
        asm volatile("atom.relaxed.gpu.global.or.b32 %0, [%1], -1;" : "=r"(v) : "l"(g_x + pair * 1024 + (i & 1) * 512 + line * 16) : "memory");
        asm volatile("{\n.reg .pred p;\nsetp.ne.u32 p, %1, 0x12345;\nmov.u32 %0, -1;\n@p mov.u32 %0, %%clock;\n}" : "=r"(t1) : "r"(v) : "memory");
        if (i & 1) best[1] = min(best[1], t1 - t0); else best[0] = min(best[0], t1 - t0);
    }
    return best[1] < best[0];
}
__device__ __forceinline__ void map_pages(int c) {
    uint32_t smid;
    asm("mov.u32 %0, %%smid;" : "=r"(smid));
    const uint32_t side = near_page(0, c & 31);
    g_side[smid & 255] = side;
    for (int p = c; p < XPAIRS; p += 132) g_home[p] = near_page(p, 0) ^ side;
}

__device__ __forceinline__ void kv_tile(int c, int n, int& m, int& nb) {
    if (c < 96) { m = (c & 3) + 4 * n; nb = c >> 2; }
    else {
        const int i = ((c - 96) >> 1) + 18 * n, j = i - 48 * NTA, p = j < 0 ? i / 24 : 2 * NTA + j / 48;
        m = 2 * p + (c & 1); nb = j < 0 ? 24 + i % 24 : j % 48;
    }
}

__global__ void __launch_bounds__(384, 1)
k_kv(const __grid_constant__ CUtensorMap mx, const __grid_constant__ CUtensorMap mwk, const __grid_constant__ CUtensorMap mwv,
     const __grid_constant__ CUtensorMap mwq, const bf16* __restrict__ Wq, const bf16* __restrict__ Wo, int c0) {
    extern __shared__ __align__(1024) uint8_t smem_gemm[];
    const int c = c0 + blockIdx.x, ntile = c < 96 ? NTA : (384 - 48 * NTA + 17 - ((c - 96) >> 1)) / 18;
    if (c != 0) asm volatile("griddepcontrol.launch_dependents;");
    const uint32_t bar_done = smem_u32(smem_gemm) + NSTAGE * STAGE_BYTES + 96;
    if (threadIdx.x == 0) { mbar_init(bar_done, 8); mbar_init(bar_done + 8, 8); }
    GemmSmem g = gemm_setup(smem_gemm, 4);
    if (threadIdx.x == 0) TLK(0);
    uint32_t rank, peer_empty;
    asm("mov.u32 %0, %%cluster_ctarank;" : "=r"(rank));
    asm("mapa.shared::cluster.u32 %0, %1, %2;" : "=r"(peer_empty) : "r"(g.empty), "r"(rank ^ 1));
    asm volatile("barrier.cluster.arrive.relaxed.aligned;\nbarrier.cluster.wait.aligned;" ::: "memory");
    auto release = [&](int s) {
        asm volatile("{\n.reg .pred p;\nsetp.eq.u32 p, %2, 0;\n@p mbarrier.arrive.relaxed.cta.shared::cta.b64 _, [%0];\n"
                     "@p mbarrier.arrive.relaxed.cluster.shared::cluster.b64 _, [%1];\n}"
                     ::"r"(g.empty + 8 * s), "r"(peer_empty + 8 * s), "r"(threadIdx.x & 127) : "memory");
    };
    const int wg = __shfl_sync(~0u, threadIdx.x >> 7, 0);
    if (wg == 0) {
        asm volatile("setmaxnreg.dec.sync.aligned.u32 40;");
        if (threadIdx.x == 0) {
            for (int it = 0; it < ntile * 16; it++) {
                const int s = it & 3, kb = it & 15;
                int m, nb;
                kv_tile(c, it >> 4, m, nb);
                mbar_wait(g.empty + 8 * s, ((it >> 2) & 1) ^ 1);
                mbar_expect_tx(g.full + 8 * s, STAGE_BYTES);
                tma2d(g.st + s * STAGE_BYTES, &mx, kb * 64, m * 128, g.full + 8 * s);
                asm volatile("cp.async.bulk.tensor.3d.shared::cluster.global.mbarrier::complete_tx::bytes.multicast::cluster "
                             "[%0], [%1, {%3, %4, %5}], [%2], %6;"
                             ::"r"(g.st + s * STAGE_BYTES + 16384 + (c & 1) * 16384), "l"(nb < 16 ? &mwk : nb < 32 ? &mwv : &mwq), "r"(g.full + 8 * s),
                               "r"(0), "r"(kb * 64), "r"((nb & 15) * 4 + (c & 1) * 2), "h"((uint16_t)(3u << (rank & ~1u))) : "memory");
#define PF0 (16 * NTA - 22)
                if (c < 96 && it >= PF0 && (it - PF0) * 96 + c < 2048)
                    asm volatile("cp.async.bulk.prefetch.L2.global [%0], 4096;" ::"l"((const char*)Wo + ((it - PF0) * 96 + c) * 4096) : "memory");
            }
        } else if (threadIdx.x == 32) {
            if (c == 0) {
                for (int i = 0; i < 64; i++) reinterpret_cast<uint4*>(g_flag)[i] = make_uint4(0, 0, 0, 0);
                asm volatile("fence.acq_rel.gpu;\ngriddepcontrol.launch_dependents;" ::: "memory");
            }
            if (c == 96)
                asm volatile("griddepcontrol.wait;\nfence.acq_rel.gpu;\nred.relaxed.gpu.global.add.u32 [%0], 1;" ::"l"(g_flag + 8) : "memory");
        } else if (threadIdx.x == 64) {
            for (int n = 0; n < (c < 96 ? 0 : ntile); n++) {
                int m, nb;
                kv_tile(c, n, m, nb);
                mbar_wait(bar_done + (n & 1) * 8, (n >> 1) & 1);
                asm volatile("fence.acq_rel.gpu;\nred.relaxed.gpu.global.add.u32 [%0], 1;" ::"l"(g_flag + (m >> 1)) : "memory");
            }
        } else if (threadIdx.x >= 96) {
            const uint4 ones = make_uint4(~0u, ~0u, ~0u, ~0u);
            for (int i = c * 32 + threadIdx.x - 96; i < XPAIRS * 512; i += 132 * 32) reinterpret_cast<uint4*>(g_x)[i] = ones;
            __syncwarp();
            if (threadIdx.x == 96) {
                map_pages(c);
                asm volatile("fence.acq_rel.gpu;\nred.relaxed.gpu.global.add.u32 [%0], 1;" ::"l"(g_flag + 8) : "memory");
            }
        }
    } else {
        asm volatile("setmaxnreg.inc.sync.aligned.u32 232;");
        const int cw = wg - 1, lane = threadIdx.x & 31, t = lane & 3;
        bf16* const dst0 = g_kv + (size_t)(cw * 64 + ((threadIdx.x >> 5) & 3) * 16 + (lane >> 2)) * PW + t * 8;
        bf16* dst = dst0;
        float acc[128];
        uint32_t pk[64];
#pragma unroll 1
        for (int tile = 0; tile < ntile; tile++) {
#pragma unroll
            for (int kb = 0; kb < 16; kb++) {
                mbar_wait_u(g.full + 8 * (kb & 3), (kb >> 2) & 1);
                if (kb == 0 && tile == 0 && threadIdx.x == 128) TLK2(0);
                gemm_stage<128, 256, 1>(acc, g.st + (kb & 3) * STAGE_BYTES, cw, kb == 0);
                if (tile > 0) {
                    kv_store_unit(pk, kb, dst, t);
                    if (kb == 15) { __syncwarp(); mbar_arrive_one(bar_done + (~tile & 1) * 8, lane); }
                }
                if (kb > 0) {
                    wg_wait<1>();
                    if (kb <= 12 || tile < ntile - 1) release((kb - 1) & 3);
                }
            }
            wg_wait<0>();
            if (tile < 4 && threadIdx.x == 128) TLK2(tile + 1);
            if (tile < ntile - 1) release(3);
#pragma unroll
            for (int i = 0; i < 64; i++) pk[i] = pack2(acc[2 * i], acc[2 * i + 1]);
            int m, nb;
            kv_tile(c, tile, m, nb);
            dst = dst0 + (size_t)m * 128 * PW + nb * 256;
        }
        if (threadIdx.x == 128) TLK(2);
#pragma unroll
        for (int u = 0; u < 16; u++) kv_store_unit(pk, u, dst, t);
        __syncwarp();
        mbar_arrive_one(bar_done + (~ntile & 1) * 8, lane);
        if (threadIdx.x == 128) TLK(1);
    }
}

constexpr int NS1 = 31;
#define RB1 4
#define PFC 4
constexpr int C_W1 = 0;
constexpr int C_W2 = C_W1 + 8 * NS1 * 512;
constexpr int C_KV = C_W2 + 14 * 8 * 512;
constexpr int C_RED = C_KV + 16384;
constexpr int C_QKV = C_RED + 64 * 272;
constexpr int QKV_SZ = 3 * 8 * 272;
constexpr int C_SC = C_RED;
constexpr int C_OB = C_SC + 2 * 8 * 52 * 4;
constexpr int C_BAR = C_QKV + 2 * QKV_SZ;
__host__ __device__ constexpr int smem_idx(int ks, int j) {
    return ks == 0 ? j : ks < 3 ? (j < 4 ? 4 + 4 * ks + j : -1) : (j < 3 ? 7 + 3 * ks + j : -1);
}
constexpr int CHAIN_SMEM = C_BAR + 64;
#define TS(i)
#define TG(i)

#define DLY3 8
#define DLY1 5
#define DLY0 2
#define DLY1A 10
#define DLY0A 0
#define DLY1B 10
#define DLYQ 1
#define PFD 3
#define PFI 0
#define DLYS 0
#define DLYW 3
template <int N> __device__ __forceinline__ uint32_t delayed(uint32_t x, int lane) {
#pragma unroll
    for (int i = 0; i < N; i++) asm volatile("shfl.sync.idx.b32 %0, %0, %1, 31, -1;" : "+r"(x) : "r"(lane) : "memory");
    return x;
}
__device__ __forceinline__ int fresh(int x) { asm volatile("mov.b32 %0, %0;" : "+r"(x)); return x; }
__device__ __forceinline__ void lds128v(uint32_t (&r)[4], uint32_t a) {
    asm volatile("ld.volatile.shared.v4.u32 {%0,%1,%2,%3}, [%4];" : "=r"(r[0]), "=r"(r[1]), "=r"(r[2]), "=r"(r[3]) : "r"(a) : "memory");
}
__device__ __forceinline__ uint2 lds64(uint32_t a) {
    uint2 v;
    asm volatile("ld.shared.v2.u32 {%0,%1}, [%2];" : "=r"(v.x), "=r"(v.y) : "r"(a) : "memory");
    return v;
}
#define LDQ ".L1::no_allocate"
__device__ __forceinline__ uint4 ldw128(const void* p) {
    uint4 v;
    asm volatile("ld.global.nc" LDQ ".v4.u32 {%0,%1,%2,%3}, [%4];" : "=r"(v.x), "=r"(v.y), "=r"(v.z), "=r"(v.w) : "l"(p));
    return v;
}
#define P8_LD(i) "ld.relaxed.gpu.global.b64 d" #i ", [src + " #i " * 256];\n"
#define P8_X(i) "mov.b64 {x" #i ", y" #i "}, d" #i ";\n"
#define P8_HEAD(SRC) "{\n.reg .pred p, q;\n.reg .b64 src, d<8>;\n.reg .b32 n, x<8>, y<8>, m0, m1;\nmov.b64 src, " SRC ";\n"         \
                P8_LD(0) P8_LD(1) P8_LD(2) P8_LD(3) P8_LD(4) P8_LD(5) P8_LD(6) P8_LD(7) "mov.u32 n, 0;\nCHECK:\n" \
                P8_X(0) P8_X(1) P8_X(2) P8_X(3) P8_X(4) P8_X(5) P8_X(6) P8_X(7)
#define P8_VOTE "vote.sync.all.pred p, p, -1;\n@p bra.uni DONE;\n"
#define P8_TAIL "add.u32 n, n, 1;\nsetp.lt.u32 p, n, 0x100000;\n@p bra.uni CHECK;\ntrap;\nDONE:\n"
#define S8_LD(i) "ld.relaxed.gpu.global.b64 %" #i ", [%8 + " #i " * 256];\n"
__device__ __forceinline__ void fetch_state(uint64_t (&d)[8], const void* src) {
    asm volatile(S8_LD(0) S8_LD(1) S8_LD(2) S8_LD(3) S8_LD(4) S8_LD(5) S8_LD(6) S8_LD(7)
                 : "=&l"(d[0]), "=&l"(d[1]), "=&l"(d[2]), "=&l"(d[3]), "=&l"(d[4]), "=&l"(d[5]), "=&l"(d[6]), "=&l"(d[7]) : "l"(src) : "memory");
}
__device__ __forceinline__ void settle_state(uint64_t (&d)[8], const void* src) {
#define S8_X(i) "mov.b64 {x" #i ", _}, %" #i ";\n"
#define S8_R(i) "setp.eq.u32 q, x" #i ", 0xffffffff;\n@q " S8_LD(i)
    asm volatile("{\n.reg .pred p, q;\n.reg .b32 n, x<8>, m0, m1;\nmov.u32 n, 0;\nCHECK:\n"
                 S8_X(0) S8_X(1) S8_X(2) S8_X(3) S8_X(4) S8_X(5) S8_X(6) S8_X(7)
                 "max.u32 m0, x0, x1;\nmax.u32 m0, m0, x2;\nmax.u32 m1, x3, x4;\nmax.u32 m1, m1, x5;\nmax.u32 m0, m0, x6;\n"
                 "max.u32 m0, m0, x7;\nmax.u32 m0, m0, m1;\nsetp.ne.u32 p, m0, 0xffffffff;\n" P8_VOTE
                 S8_R(0) S8_R(1) S8_R(2) S8_R(3) S8_R(4) S8_R(5) S8_R(6) S8_R(7) P8_TAIL "}"
                 : "+l"(d[0]), "+l"(d[1]), "+l"(d[2]), "+l"(d[3]), "+l"(d[4]), "+l"(d[5]), "+l"(d[6]), "+l"(d[7]) : "l"(src) : "memory");
}
__device__ __forceinline__ uint64_t poll_sum(const void* src, uint32_t tag, uint32_t sel) {
#define P8_RT(i) "lop3.b32 m0, x" #i ", %2, 1, 0x28;\nsetp.ne.u32 q, m0, 0;\n@q " P8_LD(i)
#define P8_MMA(c, i, z) "mma.sync.aligned.m16n8k8.row.col.f32.bf16.bf16.f32 {" #c "0," #c "1," #c "2," #c "3}, {x" #i ", y" #i "}, {%3}, {" #z "0," #z "1," #z "2," #z "3};\n"
    uint64_t r;
    asm volatile(P8_HEAD("%1") "{\n.reg .f32 a<4>, b<4>, z<4>;\nmov.f32 z0, 0f00000000;\nmov.f32 z1, z0;\nmov.f32 z2, z0;\nmov.f32 z3, z0;\n"
                 P8_MMA(a, 0, z) P8_MMA(b, 1, z) P8_MMA(a, 2, a) P8_MMA(b, 3, b) P8_MMA(a, 4, a) P8_MMA(b, 5, b) P8_MMA(a, 6, a) P8_MMA(b, 7, b)
                 "add.f32 a0, a0, b0;\nadd.f32 a1, a1, b1;\nadd.f32 a2, a2, b2;\nadd.f32 a3, a3, b3;\n"
                 "cvt.rn.bf16x2.f32 m0, a1, a0;\ncvt.rn.bf16x2.f32 m1, a3, a2;\nmov.b64 %0, {m0, m1};\n}\n"
                 "lop3.b32 m0, x0, x1, %2, 0x7e;\nlop3.b32 m1, x2, x3, %2, 0x7e;\nlop3.b32 m0, m0, x4, %2, 0xf6;\n"
                 "lop3.b32 m1, m1, x5, %2, 0xf6;\nlop3.b32 m0, m0, x6, %2, 0xf6;\nlop3.b32 m1, m1, x7, %2, 0xf6;\n"
                 "lop3.b32 m0, m0, m1, 1, 0xa8;\nsetp.eq.u32 p, m0, 0;\n" P8_VOTE
                 P8_RT(0) P8_RT(1) P8_RT(2) P8_RT(3) P8_RT(4) P8_RT(5) P8_RT(6) P8_RT(7) P8_TAIL "}"
                 : "=&l"(r) : "l"(src), "r"(tag), "r"(sel) : "memory");
    return r;
}
__device__ __forceinline__ void wait_count_u(const uint32_t* p, uint32_t need) {
    asm volatile("{\n.reg .pred p;\n.reg .u32 n, v;\nmov.u32 n, 0;\nAGAIN:\nld.acquire.gpu.global.u32 v, [%0];\nsetp.ge.u32 p, v, %1;\n"
                 "vote.sync.all.pred p, p, -1;\n@p bra.uni DONE;\nadd.u32 n, n, 1;\nsetp.lt.u32 p, n, 0x100000;\n@p bra.uni AGAIN;\ntrap;\n"
                 "DONE:\nfence.proxy.async.global;\n}" ::"l"(p), "r"(need) : "memory");
}
__device__ __forceinline__ uint32_t movm(uint32_t x) { asm volatile("movmatrix.sync.aligned.m8n8.trans.b16 %0, %0;" : "+r"(x)); return x; }
template <int NK, typename F>
__device__ __forceinline__ void attend(uint32_t sb, uint32_t lm, uint32_t qs, uint32_t xq, int i8, int lane, bf16* dst, F mid) {
    const int r8 = lane & 7, m4 = lane >> 3;
    const float sl2e = 0.08838834764831845f * 1.4426950408889634f;
    const uint32_t lk = sb + C_KV + ((m4 & 1) * 8 + r8) * 128 + (((m4 >> 1) ^ r8) << 4);
    const uint32_t lkm = sb + xq + (8 + r8) * 272 + (m4 & 1) * 32 + (m4 >> 1) * 16;
    asm volatile("cp.async.wait_all;" ::: "memory");
    __syncwarp();
    float x[4][4];
#pragma unroll
    for (int i = 0; i < 4; i++) x[i][0] = x[i][1] = x[i][2] = x[i][3] = 0.f;
#pragma unroll
    for (int kp = 0; kp < 4; kp++) {
        uint32_t q[4], a[4];
        ldsm4(q, lm + qs + kp * 64);
        ldsm4(a, lkm + kp * 64);
        mma16816(x[2], a[0], a[1], a[2], a[3], q[0], q[1]);
        mma16816(x[3], a[0], a[1], a[2], a[3], q[2], q[3]);
#pragma unroll
        for (int u = 0; u < 4; u++) {
            if ((u & 1) >= NK) continue;
            ldsm4(a, (lk ^ (((kp & 1) * 2 + (u >> 1)) << 5)) + (kp >> 1) * 4096 + (u & 1) * 2048);
            mma16816(x[u & 1], a[0], a[1], a[2], a[3], q[u & 2], q[(u & 2) + 1]);
        }
    }
    x[2][0] += x[3][2]; x[2][1] += x[3][3];
    const int lim = i8 + 2 * (lane & 3) - (lane >> 2);
    uint32_t p[5];
    {
        float m[2], e[5][2];
#pragma unroll
        for (int b = 0; b < 2; b++) {
            e[4][b] = m[b] = x[2][b];
#pragma unroll
            for (int j = 0; j < 2 * NK; j++) {
                e[j][b] = j < 2 * NK - 2 || 8 * j - b <= lim ? x[j >> 1][(j & 1) * 2 + b] : -3.0e38f;
                m[b] = fmaxf(m[b], e[j][b]);
            }
        }
#pragma unroll
        for (int o = 4; o < 32; o <<= 1) {
            m[0] = fmaxf(m[0], __shfl_xor_sync(~0u, m[0], o));
            m[1] = fmaxf(m[1], __shfl_xor_sync(~0u, m[1], o));
        }
        m[0] *= sl2e; m[1] *= sl2e;
#pragma unroll
        for (int j = 0; j < 5; j++)
            if (j < 2 * NK || j == 4) p[j] = movm(pack2(ex2(fmaf(e[j][0], sl2e, -m[0])), ex2(fmaf(e[j][1], sl2e, -m[1]))));
    }
    const uint32_t lvt = sb + C_KV + 8192 + ((m4 >> 1) * 8 + r8) * 128 + (((m4 & 1) ^ r8) << 4), one = 0x3f803f80u;
    float sm[4] = {0.f, 0.f, 0.f, 0.f}, c[8][4];
    mma16816(sm, one, one, one, one, p[0], p[1]);
    if (NK == 2) mma16816(sm, one, one, one, one, p[2], p[3]);
    mma1688(sm, one, one, p[4]);
#pragma unroll
    for (int j = 0; j < 8; j++) c[j][0] = c[j][1] = c[j][2] = c[j][3] = 0.f;
#pragma unroll
    for (int kk = 0; kk < NK; kk++)
#pragma unroll
        for (int j = 0; j < 8; j++) {
            uint32_t a[4];
            ldsm4t(a, (lvt ^ ((j & 3) << 5)) + (j >> 2) * 4096 + kk * 2048);
            mma16816(c[j], a[0], a[1], a[2], a[3], p[2 * kk], p[2 * kk + 1]);
        }
    float i0, i1;
    asm("rcp.approx.ftz.f32 %0, %1;" : "=f"(i0) : "f"(sm[0]));
    asm("rcp.approx.ftz.f32 %0, %1;" : "=f"(i1) : "f"(sm[1]));
    uint32_t o[4][4];
#pragma unroll
    for (int j = 0; j < 4; j++) {
        uint32_t a[4];
        ldsm4t(a, lm + xq + 16 * 272 + j * 64);
        mma1688(c[2 * j], a[0], a[1], p[4]);
        mma1688(c[2 * j + 1], a[2], a[3], p[4]);
#pragma unroll
        for (int u = 0; u < 4; u++) o[j][u] = pack2(c[2 * j + (u >> 1)][(u & 1) * 2] * i0, c[2 * j + (u >> 1)][(u & 1) * 2 + 1] * i1);
    }
#pragma unroll
    for (int j = 0; j < 4; j++) stsm4t(lm + qs + j * 64, o[j][0], o[j][1], o[j][2], o[j][3]);
    mid();
    __syncwarp();
#pragma unroll
    for (int j = 0; j < 4; j++) lds128(o[j], sb + qs + ((lane >> 4) + 2 * j) * 272 + (lane & 15) * 16);
#pragma unroll
    for (int j = 0; j < 4; j++)
        asm volatile("st.global.v4.u32 [%0], {%1,%2,%3,%4};" ::"l"(dst + (size_t)2 * j * HD), "r"(o[j][0]), "r"(o[j][1]), "r"(o[j][2]), "r"(o[j][3]) : "memory");
}
__device__ __forceinline__ void sum8(float (&c)[4], const uint2 (&v)[8], uint32_t idn) {
    float d[4] = {0.f, 0.f, 0.f, 0.f};
    c[0] = c[1] = c[2] = c[3] = 0.f;
    mma16816(c, v[0].x, v[0].y, v[1].x, v[1].y, idn, idn);
    mma16816(d, v[2].x, v[2].y, v[3].x, v[3].y, idn, idn);
    mma16816(c, v[4].x, v[4].y, v[5].x, v[5].y, idn, idn);
    mma16816(d, v[6].x, v[6].y, v[7].x, v[7].y, idn, idn);
    c[0] += d[0]; c[1] += d[1]; c[2] += d[2]; c[3] += d[3];
}

#define CLS 6
__global__ void __cluster_dims__(CLS, 1, 1) __launch_bounds__(256, 1)
k_chain(const bf16* __restrict__ mem0, const bf16* __restrict__ Wq, const bf16* __restrict__ Wk, const bf16* __restrict__ Wv,
        const bf16* __restrict__ Wo, const __grid_constant__ CUtensorMap mkv) {
    extern __shared__ __align__(1024) uint8_t smem_chain[];
    const uint32_t sb = smem_u32(smem_chain);
    if (sb & 1023) __trap();
    const int w = __shfl_sync(~0u, threadIdx.x >> 5, 0), lane = __shfl_sync(~0u, threadIdx.x & 31, threadIdx.x & 31);
    const int tid = w * 32 + lane, g = lane >> 2, t = lane & 3;
    auto pin = [&](uint32_t x) { return delayed<1>(x, lane); };
    const int h = blockIdx.x / 3, r = blockIdx.x - 3 * h;
    const uint32_t bar_x = sb + C_BAR, bar_kv = sb + C_BAR + 8, bar_go = sb + C_BAR + 16, bar_w = sb + C_BAR + 24;
    asm volatile("griddepcontrol.launch_dependents;");
    const int tbase = r == 0 ? 0 : 1 + 21 * r, ntile = r == 0 ? 22 : 21;
    uint32_t side;
    if (tid == 0) {
        mbar_init(bar_x, 8); mbar_init(bar_kv, 1); mbar_init(bar_go, 1); mbar_init(bar_w, 1);
        asm volatile("fence.mbarrier_init.release.cluster;" ::: "memory");
        asm volatile("fence.proxy.async.shared::cta;" ::: "memory");
        mbar_expect_tx(bar_w, 128 * 32 * ntile);
    }
    __syncthreads();
    asm volatile("barrier.cluster.arrive.relaxed.aligned;" ::: "memory");
    if (tid < 128)
        asm volatile("cp.async.bulk.shared::cluster.global.mbarrier::complete_tx::bytes [%0], [%1], %2, [%3];"
                     ::"r"(sb + C_W1 + tid * 720), "l"(Wo + (size_t)(h * 128 + tid) * DM + tbase * 16), "r"(32 * ntile), "r"(bar_w) : "memory");
    const int tile0 = tbase + 7 - w;
    const bool three = w >= (r == 0 ? 2 : 3);
    const uint32_t wa = pin(sb + tid * 16);
#define W1A(i) (wa + C_W1 + (i) * 4096)
#define W2A(x) (wa + C_W2 + ((x) < 8 ? (x) * 4096 : 32768 - 1024 + ((x) - 8) * 3072))
    uint32_t wo0[8][4], wr[64][4];
    {
        const bf16* W = (r == 0 ? Wq : r == 1 ? Wk : Wv) + (size_t)(128 * w + (lane >> 4)) * HD + h * 128 + 8 * (lane & 15);
        uint4 raw[8][8];
        auto fetch = [&](int ks) {
#pragma unroll
            for (int i = 0; i < 8; i++) raw[ks][i] = ldw128(W + (size_t)(16 * ks + 2 * i) * HD);
        };
        fetch(0); fetch(1); fetch(2); fetch(3);
    asm("mov.u32 %0, %%smid;" : "=r"(side));
    side = __ldcg(g_side + (side & 255)) & 1;
    if (tid == 0 && r > 0) asm volatile("st.relaxed.gpu.global.u32 [%0], %1;" ::"l"(g_flag + 128 + 2 * h + r - 1), "r"(2 | side) : "memory");
        if (w == 0) TG(0);
        mbar_wait_u(bar_w, 0);
        if (w == 0) TG(1);
        const uint32_t p = sb + C_W1 + ((lane & 7) + (lane >> 4) * 8) * 720 + (7 - w) * 32 + ((lane >> 3) & 1) * 16;
#pragma unroll
        for (int ks = 0; ks < 8; ks++) {
            uint32_t a[4];
            ldsm4t(wo0[ks], p + ks * 16 * 720);
            ldsm4t(a, p + ks * 16 * 720 + 256);
            sts128(W2A(ks), a[0], a[1], a[2], a[3]);
            if (three) { ldsm4t(a, p + ks * 16 * 720 + 512); sts128(W2A(8 + ks), a[0], a[1], a[2], a[3]); }
        }
        __syncthreads();
        if (w < PFI)
            asm volatile("prefetch.global.L2 [%0];\nprefetch.global.L2 [%0 + 128];" ::"l"(g_kv + (size_t)tid * PW + r * HD + h * 128) : "memory");
        if (w == 0) TG(2);
        const uint32_t stg = sb + C_KV + w * 4096;
        const uint32_t rd = stg + ((lane & 7) + 8 * (lane >> 4)) * 256 + ((((lane >> 3) & 1) ^ (lane & 7)) << 4);
#pragma unroll
        for (int ks = 0; ks < 8; ks++) {
#pragma unroll
            for (int i = 0; i < 8; i++)
                sts128(stg + (2 * i + (lane >> 4)) * 256 + (((lane & 15) ^ (((2 * i) & 6) | (lane >> 4))) << 4),
                       raw[ks][i].x, raw[ks][i].y, raw[ks][i].z, raw[ks][i].w);
            if (ks < 2) fetch(ks + 4);
            if (ks == 3 || ks == 5) fetch(ks / 2 + 5);
            __syncwarp();
#pragma unroll
            for (int j = 0; j < 8; j++) {
                if (smem_idx(ks, j) >= 0) {
                    uint32_t a[4];
                    ldsm4t(a, rd ^ (j << 5));
                    sts128(W1A(smem_idx(ks, j)), a[0], a[1], a[2], a[3]);
                } else ldsm4t(wr[8 * ks + j], rd ^ (j << 5));
            }
            __syncwarp();
        }
    }
    if (w == 0) TG(3);
    wait_count_u(g_flag + (lane & 8), lane & 8 ? 133 : 48);
    asm volatile("fence.proxy.async.shared::cta;" ::: "memory");
    __syncthreads();
    if (tid == 0) {
        mbar_expect_tx(bar_kv, 16384);
        tma3d(sb + C_KV, &mkv, 0, 0, 2 * h, bar_kv);
        tma3d(sb + C_KV + 8192, &mkv, 0, 0, 64 + 2 * h, bar_kv);
    }
    asm volatile("barrier.cluster.wait.aligned;" ::: "memory");

    auto load_kv = [&](int s) {
        asm volatile("{\n.reg .pred p;\nelect.sync _|p, -1;\n@p mbarrier.arrive.expect_tx.shared::cta.b64 _, [%2], 16384;\n"
                     "@p cp.async.bulk.tensor.3d.shared::cluster.global.mbarrier::complete_tx::bytes [%0], [%1, {%3, %4, %5}], [%2];\n"
                     "@p cp.async.bulk.tensor.3d.shared::cluster.global.mbarrier::complete_tx::bytes [%6], [%1, {%3, %4, %7}], [%2];\n}"
                     ::"r"(sb + C_KV), "l"(&mkv), "r"(bar_kv), "r"(0), "r"(s * 32), "r"(2 * h), "r"(sb + C_KV + 8192), "r"(64 + 2 * h) : "memory");
    };
    const bool attends = w == 7 || (w == 6 && r == 0);
    const int i8 = r == 0 ? (w - 4) * 8 : (r - 1) * 8;
    auto load_q = [&](int s) {
        const int l = fresh(lane);
        const bf16* p = g_kv + (size_t)(s * 32 + i8 + (l >> 4)) * PW + 2 * HD + h * 128 + (l & 15) * 8;
#pragma unroll
        for (int j = 0; j < 4; j++)
            asm volatile("cp.async.cg.shared.global [%0], [%1], 16;"
                         ::"r"(sb + C_RED + w * 2176 + ((l >> 4) + 2 * j) * 272 + (l & 15) * 16), "l"(p + (size_t)2 * j * PW) : "memory");
    };
    auto report = [&](int blk) {
        asm volatile("{\n.reg .pred p;\nelect.sync _|p, -1;\nfence.acq_rel.gpu;\n@p red.relaxed.gpu.global.add.u32 [%0], 1;\n}"
                     ::"l"(g_flag + 64 + blk) : "memory");
    };
    const float sl2e = 0.08838834764831845f * 1.4426950408889634f;
    const uint32_t idn = pin(g == 2 * t ? 0x00003f80u : g == 2 * t + 1 ? 0x3f800000u : 0u);
    const uint32_t lm = pin(sb + (lane & 7) * 272 + (lane >> 3) * 16);
    const uint32_t sa = pin(sb + C_SC + (w & 1) * (8 * 52 * 4) + (2 * t * 52 + (w < 4 ? 32 : (w & 2) * 8) + g) * 4);
    const uint32_t sr = pin(sb + C_SC + (g * 52 + 8 * t) * 4), sr2 = pin(sb + C_SC + (g * 52 + 32 + 2 * t) * 4);
    uint32_t kva;
    {
        const int pos = (w & 2) * 8 + (lane & 15), row = (pos & 24) + ((pos + (pos >> 2 & 6)) & 7);
        const int key = 4 * (lane & 6) + (((lane & 7) + 2 * (lane >> 4)) & 7);
        kva = pin(w >= 4 ? sb + C_KV + (w & 1) * 4096 + row * 128 + (((lane >> 4) ^ (row & 7)) << 4)
                         : sb + C_KV + 8192 + (w >> 1) * 4096 + key * 128 + ((((w & 1) * 4 + ((lane >> 3) & 1)) ^ (key & 7)) << 4));
    }
#define ATTEND(NK, s, mid) do {                                                                                       \
        const int l_ = fresh(lane);                                                                                      \
        attend<NK>(sb, lm, C_RED + w * 2176, C_QKV + ((s) & 1) * QKV_SZ, i8, l_,                                         \
                   g_o + (size_t)((s) * 32 + i8 + (l_ >> 4)) * HD + h * 128 + (l_ & 15) * 8, mid);                       \
    } while (0)
    auto chores = [&](int s) {
        if ((s & 3) == 0 && s) report((s >> 2) - 1);
        if ((s & 7) == 6 && s < NSEG - 2) wait_count_u(g_flag + (s >> 3) + 1, (s >> 3) + 1 < 2 * NTA ? 48 : 96);
    };
    uint32_t buf0[8][4], ring[RB1][4];
#define STAGE_W1() do {                                                            \
        _Pragma("unroll") for (int i = 0; i < 8; i++) lds128v(buf0[i], W1A(i));       \
        _Pragma("unroll") for (int i = 0; i < RB1; i++) lds128v(ring[i], W1A(8 + i)); \
    } while (0)
    auto stage_w1 = [&]() { STAGE_W1(); };
    stage_w1();
    uint32_t psel, msel0, msel1;
    {
        const int j = r > 0 ? 2 * h + r - 1 : 0, tl = min(tile0 + 8 * (lane >> 1), 63);
        uint32_t b;
        asm volatile("{\n.reg .pred p;\n.reg .u32 n;\nmov.u32 n, 0;\nAGAIN:\nld.relaxed.gpu.global.u32 %0, [%1];\nsetp.ne.u32 p, %0, 0;\n"
                     "vote.sync.all.pred p, p, -1;\n@p bra.uni DONE;\nadd.u32 n, n, 1;\nsetp.lt.u32 p, n, 0x100000;\n@p bra.uni AGAIN;\ntrap;\nDONE:\n}"
                     : "=&r"(b) : "l"(g_flag + 128 + tl) : "memory");
        psel = __ballot_sync(~0u, (g_home[lane == 6 ? j * 2 + ((w >> 1) & 1) : tl * 2 + (lane & 1)] ^ (lane == 6 ? side : b)) & 1);
        msel0 = __ballot_sync(~0u, (g_home[128 + lane * 4 + (w >> 1)] ^ side) & 1);
        msel1 = __ballot_sync(~0u, (g_home[256 + lane * 4 + (w >> 1)] ^ side) & 1);
        if (r > 0) {
            if (w < 4) asm volatile("prefetch.global.L2 [%0];" ::"l"(g_x + (128 + (1 + (w >> 1)) * 4 + (j >> 4)) * 1024 + (w & 1) * 512 + (j & 15) * 32 + lane) : "memory");
            if (w < 4) asm volatile("prefetch.global.L2 [%0];" ::"l"(g_x + j * 2048 + tid * 16) : "memory");
        }
    }
    uint2 bm[8];
#pragma unroll
    for (int ks = 0; ks < 8; ks++) {
        const uint32_t* p = (const uint32_t*)(mem0 + g * DM + (8 * w + ks) * 16) + t;
        bm[ks] = make_uint2(__ldg(p), __ldg(p + 4));
    }
    if (w == 0) TG(5);
#pragma unroll 1
    for (int s = 0;; s++) {
        TS(1);
        const uint32_t xq = C_QKV + (s & 1) * QKV_SZ;
        {
            float acc[8][4];
#pragma unroll
            for (int ks = 0; ks < 8; ks++) {
#pragma unroll
                for (int j = 0; j < 8; j++) {
                    const int i = smem_idx(ks, j) - 8;
                    if (ks == 0) {
                        acc[j][0] = acc[j][1] = acc[j][2] = acc[j][3] = 0.f;
                        mma16816(acc[j], buf0[j][0], buf0[j][1], buf0[j][2], buf0[j][3], bm[ks].x, bm[ks].y);
                    } else if (i >= 0) {
                        uint32_t(&a)[4] = ring[i % RB1];
                        mma16816(acc[j], a[0], a[1], a[2], a[3], bm[ks].x, bm[ks].y);
                        if (8 + i + RB1 < NS1) lds128v(a, W1A(8 + i + RB1));
                    } else {
                        const uint32_t(&a)[4] = wr[8 * ks + j];
                        mma16816(acc[j], a[0], a[1], a[2], a[3], bm[ks].x, bm[ks].y);
                    }
                }
            }
#pragma unroll
            for (int c = 0; c < 4; c++)
                stsm4t(lm + C_RED + w * 2176 + c * 64, pack2(acc[2 * c][0], acc[2 * c][1]), pack2(acc[2 * c][2], acc[2 * c][3]),
                       pack2(acc[2 * c + 1][0], acc[2 * c + 1][1]), pack2(acc[2 * c + 1][2], acc[2 * c + 1][3]));
        }
        {
            const uint32_t a = sb + C_RED + w * 272 + lane * 8;
            if (w == 3) mbar_wait_u(bar_kv, s & 1);
            TS(2);
            __syncthreads();
            TS(3);
            uint2 v[8];
#pragma unroll
            for (int i = 0; i < 8; i++) v[i] = lds64(a + i * 2176);
            float c[4];
            sum8(c, v, idn);
            const uint32_t p0 = pack2(c[0], c[1]), p1 = pack2(c[2], c[3]);
            const uint32_t dst = sb + xq + (r * 8 + w) * 272 + lane * 8;
#pragma unroll
            for (int i = 1; i < 3; i++) {
                const uint32_t peer = (h % (CLS / 3)) * 3 + (r + i >= 3 ? r + i - 3 : r + i);
                uint32_t rd, rb;
                asm("mapa.shared::cluster.u32 %0, %1, %2;" : "=r"(rd) : "r"(dst), "r"(peer));
                asm("mapa.shared::cluster.u32 %0, %1, %2;" : "=r"(rb) : "r"(bar_x), "r"(peer));
                asm volatile("st.async.weak.shared::cluster.mbarrier::complete_tx::bytes.v2.b32 [%0], {%1,%2}, [%3];"
                             ::"r"(rd), "r"(p0), "r"(p1), "r"(rb) : "memory");
            }
            sts64(dst, p0, p1);
            __syncwarp();
            asm volatile("{\n.reg .pred p;\nsetp.eq.u32 p, %1, 0;\n@p mbarrier.arrive.expect_tx.shared::cta.b64 _, [%0], 512;\n}"
                         ::"r"(bar_x), "r"(lane) : "memory");
        }
        TS(4);
        if (s == NSEG - 1) break;
        uint32_t wb[8][4], wc[8][4];
        const uint32_t po = (tile0 * 2 + (lane >> 4)) * 8192 + ((lane >> 3) & 1) * 2048 + h * 64 + (lane & 7) * 8;
        const uint32_t tag = s & 1;
        auto project = [&](const uint32_t(&wt)[8][4], const uint32_t(&ob)[4][4], int i) {
            float c0[4] = {0.f, 0.f, 0.f, 0.f}, c1[4] = {0.f, 0.f, 0.f, 0.f};
#pragma unroll
            for (int ks = 0; ks < 8; ks++)
                mma16816((ks & 1) ? c1 : c0, wt[ks][0], wt[ks][1], wt[ks][2], wt[ks][3], ob[ks >> 1][(ks & 1) * 2], ob[ks >> 1][(ks & 1) * 2 + 1]);
            uint32_t p0 = pack2(c0[0] + c1[0], c0[1] + c1[1]), p1 = pack2(c0[2] + c1[2], c0[3] + c1[3]);
            asm volatile("movmatrix.sync.aligned.m8n8.trans.b16 %0, %0;\nmovmatrix.sync.aligned.m8n8.trans.b16 %1, %1;" : "+r"(p0), "+r"(p1));
            st_rlx64((uint2*)((char*)g_x + po + i * 131072 + ((psel >> (2 * i + (lane >> 4))) & 1) * 4096), (p0 & ~1u) | tag, p1);
        };
        if (w >= 4) {
            uint32_t ka[4][4];
#pragma unroll
            for (int ks = 0; ks < 4; ks++) ldsm4(ka[ks], kva ^ (ks << 5));
            const uint32_t qa = lm + xq + (w & 1) * 128;
            TS(5);
            mbar_wait_u(bar_x, s & 1);
            TS(6);
            {
                uint32_t qb[2][4];
                ldsm4(qb[0], qa);
                ldsm4(qb[1], qa + 64);
                float c0[4] = {0.f, 0.f, 0.f, 0.f}, c1[4] = {0.f, 0.f, 0.f, 0.f};
                mma16816(c0, ka[0][0], ka[0][1], ka[0][2], ka[0][3], qb[0][0], qb[0][1]);
                mma16816(c1, ka[1][0], ka[1][1], ka[1][2], ka[1][3], qb[0][2], qb[0][3]);
                mma16816(c0, ka[2][0], ka[2][1], ka[2][2], ka[2][3], qb[1][0], qb[1][1]);
                mma16816(c1, ka[3][0], ka[3][1], ka[3][2], ka[3][3], qb[1][2], qb[1][3]);
                sts32f(sa, c0[0] + c1[0]);
                sts32f(sa + 208, c0[1] + c1[1]);
                sts32f(sa + 32, c0[2] + c1[2]);
                sts32f(sa + 240, c0[3] + c1[3]);
            }
            __syncthreads();
            TS(7);
            uint32_t wd = wa;
            if (attends) { load_q(s); wd = delayed<DLYQ>(wd, lane); } else wd = delayed<DLYW>(wd, lane);
#pragma unroll
            for (int i = 0; i < 8; i++) lds128(wb[i], wd + C_W2 + i * 4096);
#pragma unroll
            for (int i = 0; i < PFC; i++) lds128(wc[i], wd + C_W2 + 32768 - 1024 + i * 3072);
            TS(8);
            __syncthreads();
            TS(9);
            uint32_t ob[4][4];
#pragma unroll
            for (int i = 0; i < 4; i++) ldsm4(ob[i], lm + C_OB + i * 64);
#pragma unroll
            for (int i = PFC; i < 8; i++) lds128(wc[i], W2A(8 + i));
            project(wb, ob, 1);
            project(wo0, ob, 0);
            project(wc, ob, 2);
        } else {
            uint32_t va[4][4];
#pragma unroll
            for (int i = 0; i < 4; i++) ldsm4t(va[i], kva ^ (((i >> 1) << 5) | ((i & 1) * 0x240)));
#pragma unroll
            for (int i = 0; i < 8; i++) lds128(wb[i], W2A(i));
            const uint32_t qa = lm + xq + (w & 1) * 128, oa = lm + w * 64;
            TS(5);
            mbar_wait_u(bar_x, s & 1);
            TS(6);
            if (w < 2) {
                uint32_t qb[2][4], km[2][4];
                ldsm4(qb[0], qa);
                ldsm4(km[0], qa + 8 * 272);
                ldsm4(qb[1], qa + 64);
                ldsm4(km[1], qa + 8 * 272 + 64);
                float c0[4] = {0.f, 0.f, 0.f, 0.f}, c1[4] = {0.f, 0.f, 0.f, 0.f};
                mma16816(c0, km[0][0], km[0][1], km[0][2], km[0][3], qb[0][0], qb[0][2]);
                mma16816(c1, km[0][0], km[0][1], km[0][2], km[0][3], qb[0][1], qb[0][3]);
                mma16816(c0, km[1][0], km[1][1], km[1][2], km[1][3], qb[1][0], qb[1][2]);
                mma16816(c1, km[1][0], km[1][1], km[1][2], km[1][3], qb[1][1], qb[1][3]);
                sts32f(sa, c0[0] + c1[2]);
                sts32f(sa + 208, c0[1] + c1[3]);
            }
            __syncthreads();
            TS(7);
            {
                float4 x0 = lds128f(sr), y0 = lds128f(sr + 1664), x1 = lds128f(sr + 16), y1 = lds128f(sr + 1680);
                float2 x2 = lds64f(sr2), y2 = lds64f(sr2 + 1664);
                float p[10] = {x0.x + y0.x, x0.y + y0.y, x0.z + y0.z, x0.w + y0.w, x1.x + y1.x,
                               x1.y + y1.y, x1.z + y1.z, x1.w + y1.w, x2.x + y2.x, x2.y + y2.y};
                float m = fmaxf(fmaxf(fmaxf(p[0], p[1]), fmaxf(p[2], p[3])), fmaxf(fmaxf(fmaxf(p[4], p[5]), fmaxf(p[6], p[7])), fmaxf(p[8], p[9])));
                const float m1 = __shfl_xor_sync(~0u, m, 1), m2 = __shfl_xor_sync(~0u, m, 2), m3 = __shfl_xor_sync(~0u, m, 3);
                uint32_t vm[4];
                ldsm4t(vm, oa + xq + 16 * 272);
                m = fmaxf(fmaxf(m, m1), fmaxf(m2, m3));
                const float ms = m * sl2e;
#pragma unroll
                for (int i = 0; i < 10; i++) p[i] = ex2(fmaf(p[i], sl2e, -ms));
                const uint32_t b0 = pack2(p[0], p[1]), b1 = pack2(p[2], p[3]), b2 = pack2(p[4], p[5]), b3 = pack2(p[6], p[7]), b4 = pack2(p[8], p[9]);
                const uint32_t one = 0x3f803f80u;
                float o0[4] = {0.f, 0.f, 0.f, 0.f}, o1[4] = {0.f, 0.f, 0.f, 0.f}, sm[4] = {0.f, 0.f, 0.f, 0.f};
                mma16816(sm, one, one, one, one, b0, b1);
                mma16816(o0, va[0][0], va[0][1], va[0][2], va[0][3], b0, b1);
                mma16816(o1, va[2][0], va[2][1], va[2][2], va[2][3], b0, b1);
                mma16816(sm, one, one, one, one, b2, b3);
                mma16816(o0, va[1][0], va[1][1], va[1][2], va[1][3], b2, b3);
                mma16816(o1, va[3][0], va[3][1], va[3][2], va[3][3], b2, b3);
                mma1688(sm, one, one, b4);
                mma1688(o0, vm[0], vm[1], b4);
                mma1688(o1, vm[2], vm[3], b4);
                float i0, i1;
                asm("rcp.approx.ftz.f32 %0, %1;" : "=f"(i0) : "f"(sm[0]));
                asm("rcp.approx.ftz.f32 %0, %1;" : "=f"(i1) : "f"(sm[1]));
                stsm4t(oa + C_OB, pack2(o0[0] * i0, o0[1] * i1), pack2(o0[2] * i0, o0[3] * i1),
                       pack2(o1[0] * i0, o1[1] * i1), pack2(o1[2] * i0, o1[3] * i1));
            }
            TS(8);
            __syncthreads();
            TS(9);
            uint32_t ob[4][4];
#pragma unroll
            for (int i = 0; i < 4; i++) ldsm4(ob[i], lm + C_OB + i * 64);
            if (three) {
#pragma unroll
                for (int i = 0; i < 8; i++) lds128(wc[i], W2A(8 + i));
                project(wb, ob, 1);
                project(wo0, ob, 0);
                project(wc, ob, 2);
            } else {
                project(wb, ob, 1);
                project(wo0, ob, 0);
            }
        }
        TS(10);
        __syncthreads();
        uint32_t eo = (128 + (s + 1) * 4 + (w >> 1)) * 8192 + (((s < 31 ? msel0 : msel1) >> ((s + 1) & 31)) & 1) * 4096 + (w & 1) * 2048 + lane * 8;
        uint64_t d[8];
        if (r == 0) {
            if (w >= 6) {
                auto mid = [&]() {
                    bar_sync(2, 64);
                    TS(11);
                    mbar_wait_u(bar_go, s & 1);
                    eo = delayed<DLY0A>(eo, lane);
                    TS(12);
                    fetch_state(d, (const char*)g_x + eo);
                };
                ATTEND(2, s, mid);
                stage_w1();
            } else {
                TS(11); TS(12);
                if (w < 3 && s + PFD < NSEG) {
                    const bf16* p = g_kv + (size_t)((s + PFD) * 32 + fresh(lane)) * PW + w * HD + h * 128;
                    asm volatile("prefetch.global.L2 [%0];\nprefetch.global.L2 [%0 + 128];" ::"l"(p) : "memory");
                }
                const uint32_t wa_ = wa;
                { const uint32_t wa = delayed<DLYS>(wa_, lane); STAGE_W1(); }
                if (w == 5) {
                    chores(s);
                    if (h == 0) asm volatile("st.relaxed.gpu.global.u32 [%0], %1;" ::"l"(g_flag + 98), "r"(s + 1) : "memory");
                }
                mbar_wait_u(bar_go, s & 1);
                eo = delayed<DLY0>(eo, lane);
                fetch_state(d, (const char*)g_x + eo);
            }
        } else {
            const int j = 2 * h + r - 1;
            if (w < 4) {
                const int l = fresh(lane), g = l >> 2, t = l & 3;
                const char* src = (const char*)g_x + delayed<DLY3>((j * 2 + (w >> 1)) * 8192 + (psel & 64) * 64 + (w & 1) * 2048 + t * 64 + g * 8, lane);
                const char* dst = (const char*)g_x + pin((128 + (s + 1) * 4 + (j >> 4)) * 8192 + (j & 15) * 256 + w * 64 + (t & 1) * 4096 + g * 8);
                const uint64_t v = poll_sum(src, tag, (lane & 4) ? 0x3f800000u : 0x00003f80u);
                TS(11);
                asm volatile("st.relaxed.gpu.global.b64 [%0], %1;" ::"l"(dst), "l"(v) : "memory");
                asm volatile("bar.arrive 1, 256;" ::: "memory");
                TS(12);
                stage_w1();
                eo = delayed<DLY1>(eo, lane);
                fetch_state(d, (const char*)g_x + eo);
            } else if (w == 7) {
                auto mid = [&]() {
                    TS(11);
                    bar_sync(1, 256);
                    TS(12);
                    eo = delayed<DLY1B>(eo, lane);
                    fetch_state(d, (const char*)g_x + eo);
                };
                ATTEND(1, s, mid);
                stage_w1();
            } else {
                if (w >= 5 && s + 3 < NSEG)
                    asm volatile("prefetch.global.L2 [%0];" ::"l"(g_x + (128 + (s + 3) * 4 + (j >> 4)) * 1024 + (w & 1) * 512 + (j & 15) * 32 + lane) : "memory");
                stage_w1();
                if (w == 5) chores(s);
                TS(11);
                bar_sync(1, 256);
                TS(12);
                if (w == 4 && r == 1)
                    asm volatile("{\n.reg .pred p;\n.reg .u32 a;\nelect.sync _|p, -1;\nmapa.shared::cluster.u32 a, %0, %1;\n"
                                 "@p mbarrier.arrive.relaxed.cluster.shared::cluster.b64 _, [a];\n}" ::"r"(bar_go), "r"((h % (CLS / 3)) * 3) : "memory");
                eo = delayed<DLY1A>(eo, lane);
                fetch_state(d, (const char*)g_x + eo);
            }
        }
        { const int s_ = s; { const int s = s_ + 1; TS(0); } }
        if (w == 7) load_kv(s + 1);
        settle_state(d, (const char*)g_x + eo);
#pragma unroll
        for (int i = 0; i < 8; i++) { bm[i].x = (uint32_t)d[i]; bm[i].y = (uint32_t)(d[i] >> 32); }
    }
    mbar_wait_u(bar_x, (NSEG - 1) & 1);
    if (attends) {
        auto nothing = []() {};
        load_q(NSEG - 1);
        if (r == 0) ATTEND(2, NSEG - 1, nothing); else ATTEND(1, NSEG - 1, nothing);
    }
    __syncthreads();
    if (w == 5) report(15);
    asm volatile("barrier.cluster.arrive.relaxed.aligned;\nbarrier.cluster.wait.aligned;" ::: "memory");
}

constexpr int S4_US = 4368;
constexpr int S4_RS = 8848;
constexpr int S4_KS = 1296;
constexpr int S4_U = 0, S4_R = 16 * S4_US, S4_K = S4_R + 16 * S4_RS;
constexpr int S4_SMEM = S4_K + 16 * S4_KS;
constexpr int S4_SIG = 3104, S4_PK = 2 * S4_SIG;

struct cf { float r, i; };
__device__ __forceinline__ cf cmul(cf a, cf b) { return {fmaf(a.r, b.r, -a.i * b.i), fmaf(a.r, b.i, a.i * b.r)}; }
__device__ __forceinline__ cf cmulc(cf a, cf b) { return {fmaf(a.r, b.r, a.i * b.i), fmaf(a.i, b.r, -a.r * b.i)}; }
__device__ __forceinline__ cf csq(cf a) { const float t = a.r * a.i; return {fmaf(a.r, a.r, -a.i * a.i), t + t}; }
__device__ __forceinline__ cf cexp(float l2, float turns) {
    const float mag = ex2(l2), fr = (turns - rintf(turns)) * 6.283185307179586f;
    return {mag * __cosf(fr), mag * __sinf(fr)};
}
__device__ __forceinline__ void sts32(uint32_t a, uint32_t v) { asm volatile("st.shared.u32 [%0], %1;" ::"r"(a), "r"(v) : "memory"); }
__device__ __forceinline__ uint32_t lds16(uint32_t a) {
    uint32_t v;
    asm volatile("ld.shared.u16 %0, [%1];" : "=r"(v) : "r"(a) : "memory");
    return v;
}

template <int M0, int NQ>
__device__ __forceinline__ void s4_class(float (&acc)[16][4], uint32_t sig, uint32_t taps, int x0) {
    constexpr int D0 = M0 / 8, D1 = M0 == 32 ? 9 : 15;
    uint32_t R[D1 - D0 + 2];
#pragma unroll
    for (int D = D0 - 1; D <= D1; D++) {
        if (D < D0 || 8 * D - 7 >= 2 * M0) { R[D - D0 + 1] = 0; continue; }
        const int m = 8 * D + x0;
        uint32_t lo = lds16(taps + m * (2 * NQ)), hi = lds16(taps + (m - 1) * (2 * NQ));
        if (D == D0) { lo = m >= M0 ? lo : 0; hi = m > M0 ? hi : 0; }
        if (D == 2 * D0) { lo = m < 2 * M0 ? lo : 0; hi = m <= 2 * M0 ? hi : 0; }
        R[D - D0 + 1] = lo | (hi << 16);
    }
#pragma unroll
    for (int J = 0; 2 * J + D0 < 16; J++) {
        uint32_t a[4];
        ldsm4t(a, sig + J * 512);
#pragma unroll
        for (int D = D0; D <= D1; D++)
            if (2 * J + D < 16) mma16816(acc[2 * J + D], a[0], a[1], a[2], a[3], R[D - D0 + 1], R[D - D0]);
    }
}

__global__ void __launch_bounds__(512, 1)
k_s4(const bf16* __restrict__ u, const bf16* __restrict__ Are, const bf16* __restrict__ Aim, const bf16* __restrict__ Bre,
     const bf16* __restrict__ Bim, const bf16* __restrict__ Cre, const bf16* __restrict__ Cim, const bf16* __restrict__ logdt,
     const bf16* __restrict__ Dsk, bf16* __restrict__ out) {
    extern __shared__ __align__(16) uint8_t smem_s4[];
    const uint32_t sb = smem_u32(smem_s4);
    asm volatile("griddepcontrol.launch_dependents;");
    const int tid = threadIdx.x, w = __shfl_sync(~0u, tid >> 5, 0), lane = tid & 31, g = lane >> 2, t = lane & 3;
#pragma unroll 1
    for (int item = blockIdx.x; item < 64; item += gridDim.x) {
#define TLS(slot)
    if (tid == 0) TLS(0);
    const int d0 = item * 16;
    const int d = d0 + (w & 1) + ((w >> 1) & 3) * 4 + (w >> 3) * 2;
    const uint32_t tr_off = (lane & 15), tr_l = (lane >> 4) * 16;
    const uint32_t ur = sb + S4_U + w * S4_US, rs = sb + S4_R + w * S4_RS, kd = sb + S4_K + w * S4_KS;
    if (lane < 16) sts128(ur + lane * 16, 0, 0, 0, 0);
    {
        const int o = d * 128 + lane * 4;
        const uint2 ar = __ldg((const uint2*)(Are + o)), ai = __ldg((const uint2*)(Aim + o)), br = __ldg((const uint2*)(Bre + o));
        const uint2 bi = __ldg((const uint2*)(Bim + o)), cr = __ldg((const uint2*)(Cre + o)), ci = __ldg((const uint2*)(Cim + o));
        const float dt = bf_round(expf(__bfloat162float(logdt[d])));
        const bf16* src = u + (size_t)(w * 128 + g) * DM + d0 + 4 * t;
        float T[5][4];
#pragma unroll
        for (int i = 0; i < 5; i++) T[i][0] = T[i][1] = T[i][2] = T[i][3] = 0.f;
        float klast = 0.f;
        const uint32_t wr_ = rs + lane * 272, rd_ = rs + t * 544 + g * 16;
#pragma unroll 1
        for (int c = 0; c < 4; c++) {
            uint2 v[4];
#pragma unroll
            for (int i = 0; i < 4; i++) v[i] = __ldg((const uint2*)(src + (size_t)(c * 32 + i * 8) * DM));
            auto pick = [&](const uint2& x) { const uint32_t y = c < 2 ? x.x : x.y; return (c & 1) ? bf_hi(y) : bf_lo(y); };
            auto pk2 = [](cf x) { return pack2(x.r, x.i); };
            const float l2 = dt * pick(ar) * 1.4426950408889634f, tu = dt * pick(ai) * 0.15915494309189535f;
            const cf z1 = cexp(l2, tu), z2 = csq(z1), z4 = csq(z2), z8 = csq(z4);
            const cf z64 = cexp(l2 * 64.f, tu * 64.f), z128 = csq(z64), z256 = csq(z128), z512 = csq(z256);
            cf a0 = {1.f, 0.f}, a1 = z64;
            cf b0 = cmul({pick(cr), pick(ci)}, {dt * pick(br), dt * pick(bi)});
            b0.i = -b0.i;
            cf b1 = cmulc(b0, z128), b2 = cmulc(b0, z256), y3 = cmulc(b0, z512), b4 = cmulc(y3, z512), b3 = y3;
            const cf y2 = cmulc(b2, z128);
#pragma unroll
            for (int i = 0; i < 8; i++) {
                sts128(wr_ + i * 16, pk2(a0), pk2(a1), pk2(b0), pk2(b1));
                sts128(wr_ + i * 16 + 128, pk2(b2), pk2(b3), pk2(b4), 0);
                b4 = cmulc(b4, z128);
                if (i < 7) {
                    a0 = i == 0 ? z8 : cmul(a0, z8); a1 = cmul(a1, z8);
                    b0 = cmulc(b0, z1); b1 = cmulc(b1, z1);
                    b2 = i == 3 ? y2 : cmulc(b2, z2);
                    if (i & 1) { y3 = cmulc(y3, z128); b3 = y3; } else b3 = cmulc(y3, z4);
                }
            }
            klast += b4.r;
            __syncwarp();
#pragma unroll
            for (int k = 0; k < 8; k++) {
                uint32_t x[4], y[4];
                lds128(x, rd_ + (8 * (k >> 1) + (k & 1)) * 272);
                lds128(y, rd_ + (8 * (k >> 1) + (k & 1)) * 272 + 128);
                mma1688(T[0], x[0], x[1], x[2]);
                mma1688(T[1], x[0], x[1], x[3]);
                mma1688(T[2], x[0], x[1], y[0]);
                mma1688(T[3], x[0], x[1], y[1]);
                mma1688(T[4], x[0], x[1], y[2]);
            }
#pragma unroll
            for (int i = 0; i < 2; i++)
                stsm4t(sb + S4_U + tr_off * S4_US + 256 + (w * 128 + c * 32 + i * 16) * 2 + tr_l, v[2 * i].x, v[2 * i].y, v[2 * i + 1].x, v[2 * i + 1].y);
            __syncwarp();
        }
#pragma unroll
        for (int o2 = 16; o2; o2 >>= 1) klast += __shfl_xor_sync(~0u, klast, o2);
#pragma unroll
        for (int hh = 0; hh < 2; hh++) {
            const int i = g + 8 * hh;
            sts32(kd + (8 * i + 2 * t) * 2, pack2(T[0][2 * hh], T[0][2 * hh + 1]));
            sts32(kd + (128 + 8 * i + 2 * t) * 2, pack2(T[1][2 * hh], T[1][2 * hh + 1]));
            sts32(kd + (256 + 4 * i + 2 * (t & 1) + 64 * (t >> 1)) * 2, pack2(T[2][2 * hh], T[2][2 * hh + 1]));
            sts32(kd + (384 + 2 * i + 32 * t) * 2, pack2(T[3][2 * hh], T[3][2 * hh + 1]));
        }
        asm volatile("stmatrix.sync.aligned.m8n8.x2.trans.shared.b16 [%0], {%1,%2};"
                     ::"r"(kd + 1024 + (lane & 7) * 32 + ((lane >> 3) & 1) * 16), "r"(pack2(T[4][0], T[4][1])), "r"(pack2(T[4][2], T[4][3])) : "memory");
        if (lane == 0) sts32(kd + 1280, pack2(klast, 0.f));
    }
    __syncwarp();
    const uint32_t pk = rs + S4_PK + 64;
    {
#pragma unroll
        for (int i = 0; i < 2; i++) {
            const int x = i * 128 + lane * 4;
            const uint2 c = lds64(kd + x * 2);
            uint32_t p = lds16(kd + x * 2 - 2);
            if (x == 0) p = 0;
            sts128(pk + x * 4, __byte_perm(c.x, p, 0x5410), __byte_perm(c.x, 0, 0x1032), __byte_perm(c.y, c.x, 0x7610), __byte_perm(c.y, 0, 0x1032));
        }
#pragma unroll
        for (int i = 2; i < 4; i++) {
            const int x = i * 128 + lane * 4;
            const uint32_t ab = lds32(kd + 256 + x), c = lds16(kd + 256 + x + 4);
            const uint32_t p = x == 256 ? lds16(kd + 510) : ab;
            sts128(pk + x * 4, __byte_perm(ab, p, 0x5410), __byte_perm(ab, 0, 0x1010), __byte_perm(ab, 0, 0x1032), __byte_perm(c, ab, 0x7610));
        }
        const uint32_t v = lds16(kd + 768), v2 = lds16(kd + 1024);
        if (lane < 24) {
            uint32_t x0 = 0, x1 = 0, x2 = 0, x3 = 0;
            if (lane == 0) { x0 = x1 = x2 = v | (v << 16); x3 = v << 16; }
            if (lane == 12) x3 = v2;
            if (lane == 13) { x0 = v2 | (v2 << 16); x1 = v2 << 16; }
            sts128(lane < 20 ? pk + 2048 + lane * 16 : pk - 64 + (lane - 20) * 16, x0, x1, x2, x3);
        }
        if (lane < 4) sts128(rs + (lane >> 1) * S4_SIG + (lane & 1) * 16, 0, 0, 0, 0);
    }
    __syncthreads();
    float acc[16][4];
#pragma unroll
    for (int i = 0; i < 16; i++) acc[i][0] = acc[i][1] = acc[i][2] = acc[i][3] = 0.f;
    const uint32_t lf = (lane & 7) * 32 + ((lane >> 3) & 1) * 16 + (lane >> 4) * 256;
#pragma unroll 1
    for (int ph = 0; ph < 2; ph++) {
    if (((w >> 2) ^ ph) & 1) {
#pragma unroll
    for (int rg = 3; rg >= 2; rg--) {
#pragma unroll 1
        for (int it = 0; it < (rg == 3 ? 4 : 6); it++) {
            const int n = it * 32 + lane;
            uint32_t x[2][4];
            lds128(x[0], ur + 256 + n * 16 - 16);
            lds128(x[1], ur + 256 + n * 16);
            float e[16], p[15], s[11];
#pragma unroll
            for (int i = 0; i < 8; i++) { e[2 * i] = bf_lo(x[i >> 2][i & 3]); e[2 * i + 1] = bf_hi(x[i >> 2][i & 3]); }
#pragma unroll
            for (int i = 0; i < 15; i++) p[i] = e[i] + e[i + 1];
#pragma unroll
            for (int i = 0; i < 11; i++) s[i] = p[i + 3] + e[i + 5];
            const uint32_t o = rs + 16 + n * 16;
            if (rg == 2) sts128(o, pack2(s[0], s[1]), pack2(s[2], s[3]), pack2(s[4], s[5]), pack2(s[6], s[7]));
#pragma unroll
            for (int i = 0; i < 10; i++) s[i] = p[i + 2] + s[i + 1];
            if (rg == 2) {
                sts64(o + S4_SIG + 8, pack2(s[0], s[1]), pack2(s[2], s[3]));
                sts64(o + S4_SIG + 16, pack2(s[4], s[5]), pack2(s[6], s[7]));
            } else {
#pragma unroll
                for (int i = 0; i < 9; i++) s[i] = p[i + 1] + s[i + 1];
                sts64(o + 8, pack2(s[0], s[1]), pack2(s[2], s[3]));
                sts64(o + 16, pack2(s[4], s[5]), pack2(s[6], s[7]));
#pragma unroll
                for (int i = 0; i < 8; i++) s[i] = p[i] + s[i + 1];
                sts64(o + S4_SIG + 8, pack2(s[0], s[1]), pack2(s[2], s[3]));
                sts64(o + S4_SIG + 16, pack2(s[4], s[5]), pack2(s[6], s[7]));
            }
        }
        __syncwarp();
        if (rg == 3) {
#pragma unroll 1
            for (int q = 1; q <= 2; q++) s4_class<64, 2>(acc, rs + lf + (q == 1 ? 16 : S4_SIG), kd + (384 + q) * 2, g - 2 * t);
        } else {
#pragma unroll 1
            for (int q = 1; q <= 4; q++) s4_class<32, 4>(acc, rs + lf + ((q & 1) ? 0 : S4_SIG) + (q < 3 ? 16 : 0), kd + (256 + q) * 2, g - 2 * t);
        }
        __syncwarp();
    }
    } else
    {
        const uint32_t ub = ur + 256 + lf, kb = pk + (g - 2 * t) * 4;
#pragma unroll 1
        for (int j0 = 0; j0 < 8; j0++) {
            uint32_t B[8][4];
#pragma unroll
            for (int i = 0; i < 8; i++) ldsm4(B[i], ub + i * 512 - j0 * 32);
            auto block = [&](int J, uint32_t a) {
                const uint32_t r0 = lds32(a), rp = lds32(a + 32), rm = lds32(a - 32);
                uint32_t r3;
                asm volatile("ld.volatile.shared.u32 %0, [%1];" : "=r"(r3) : "r"(a) : "memory");
#pragma unroll
                for (int I = J; I < 16; I++)
                    mma16816(acc[I], r0, rp, rm, r3, B[(I - J) >> 1][((I - J) & 1) * 2], B[(I - J) >> 1][((I - J) & 1) * 2 + 1]);
            };
#pragma unroll
            for (int J = 0; J < 4; J++) block(J, kb + j0 * 64 + J * 512);
            if (j0 < 2) { block(4, kb + j0 * 64 + 2048); block(8, kb + j0 * 64 + (544 + 16) * 4); }
        }
    }
    }
    {
        __syncwarp();
#pragma unroll
        for (int i = 0; i < 8; i++)
            stsm4t(rs + lf + i * 512, pack2(acc[2 * i][0], acc[2 * i][1]), pack2(acc[2 * i][2], acc[2 * i][3]),
                   pack2(acc[2 * i + 1][0], acc[2 * i + 1][1]), pack2(acc[2 * i + 1][2], acc[2 * i + 1][3]));
    }
    __syncthreads();
    {
        const uint2 dv = __ldg((const uint2*)(Dsk + d0 + 4 * t));
        bf16* dst = out + (size_t)(w * 128 + g) * 2048 + 1024 + d0 + 4 * t;
#pragma unroll
        for (int i = 0; i < 8; i++) {
            uint32_t y[4], x[4], o[4];
            ldsm4t(y, sb + S4_R + tr_off * S4_RS + (w * 128 + i * 16) * 2 + tr_l);
            ldsm4t(x, sb + S4_U + tr_off * S4_US + 256 + (w * 128 + i * 16) * 2 + tr_l);
#pragma unroll
            for (int j = 0; j < 4; j++)
                asm("{\n.reg .b32 s;\nmul.rn.bf16x2 s, %2, %3;\nadd.rn.bf16x2 %0, %1, s;\n}" : "=r"(o[j]) : "r"(y[j]), "r"(x[j]), "r"((j & 1) ? dv.y : dv.x));
            *reinterpret_cast<uint2*>(dst + (size_t)(i * 16) * 2048) = make_uint2(o[0], o[1]);
            *reinterpret_cast<uint2*>(dst + (size_t)(i * 16 + 8) * 2048) = make_uint2(o[2], o[3]);
        }
    }
    if (tid == 0) TLS(1);
    __syncthreads();
    }
}

enum { IT_W256 = 1, IT_W128 = 2, IT_W64 = 3, IT_END = 7 };
struct BgParams { CUtensorMap mo, mo2, mwo4, mwo2, mwo1; };
#define NBT 10
#define P256 56
#define P128 62
struct Sched { uint32_t w0 = 0, w1 = 0; };
__device__ __forceinline__ int next_item(Sched& z) {
    if (z.w0 >= z.w1) {
        uint32_t prog;
        asm volatile("ld.relaxed.gpu.global.u32 %0, [%1];" : "=r"(prog) : "l"(g_flag + 98) : "memory");
        const uint32_t k = prog <= P256 ? 4 : prog <= P128 ? 2 : 1;
        z.w0 = atomicAdd(g_flag + 97, k);
        z.w1 = min(z.w0 + k, NBT * 16u);
        if (z.w0 >= z.w1) return IT_END;
    }
    const uint32_t i = z.w0, k = z.w1 - i >= 4 && !(i & 3) ? 4 : z.w1 - i >= 2 && !(i & 1) ? 2 : 1;
    z.w0 += k;
    return (k == 4 ? IT_W256 : k == 2 ? IT_W128 : IT_W64) | (i >> 4) << 3 | ((i & 15) / k) << 7;
}
constexpr int B_OST = NSTAGE * STAGE_BYTES + 1024;
constexpr int BG_SMEM = B_OST + 32768;

template <int BM, int BN, int KPS, typename ACC>
__device__ __forceinline__ void gemm_mainloop(ACC& acc, const GemmSmem& g, int cw, int rounds, uint32_t& round) {
#pragma unroll
    for (int i = 0; i < BN / 2; i++) acc[i] = 0.f;
#pragma unroll 1
    for (int k0 = 0; k0 < rounds; k0++, round++) {
#pragma unroll
        for (int s = 0; s < 4; s++) {
            mbar_wait_u(g.full + 8 * s, round & 1);
            gemm_stage<BM, BN, KPS>(acc, g.st + s * STAGE_BYTES, cw, false);
            wg_wait<1>();
            if (s > 0 || k0 > 0) mbar_arrive_one(g.empty + 8 * ((s + 3) & 3), threadIdx.x & 31);
        }
    }
    wg_wait<0>();
    mbar_arrive_one(g.empty + 8 * 3, threadIdx.x & 31);
}

template <int BN>
__device__ __forceinline__ void store_tile(const float (&acc)[BN / 2], bf16* dst, int t) {
#pragma unroll
    for (int G = 0; G < BN / 32; G++)
#pragma unroll
        for (int rr = 0; rr < 2; rr++) {
            uint32_t r0 = pack2(acc[16 * G + 2 * rr], acc[16 * G + 2 * rr + 1]), r1 = pack2(acc[16 * G + 4 + 2 * rr], acc[16 * G + 5 + 2 * rr]);
            uint32_t r2 = pack2(acc[16 * G + 8 + 2 * rr], acc[16 * G + 9 + 2 * rr]), r3 = pack2(acc[16 * G + 12 + 2 * rr], acc[16 * G + 13 + 2 * rr]);
            quad_transpose(r0, r1, r2, r3, t);
            *reinterpret_cast<uint4*>(dst + (size_t)rr * 8 * 2048 + G * 32) = make_uint4(r0, r1, r2, r3);
        }
}

template <int BN, int KPS>
__device__ __forceinline__ void wo_item(const GemmSmem& g, int cw, uint32_t& round, bf16* dst, int t) {
    float acc[BN / 2];
    gemm_mainloop<128, BN, KPS>(acc, g, cw, 16 / KPS, round);
    store_tile<BN>(acc, dst, t);
}

__global__ void __launch_bounds__(384, 1) k_bg(const __grid_constant__ BgParams P, bf16* __restrict__ out) {
    extern __shared__ __align__(1024) uint8_t smem_gemm[];
    asm volatile("griddepcontrol.launch_dependents;");
    const uint32_t bar_item = smem_u32(smem_gemm) + NSTAGE * STAGE_BYTES + 128, slot = bar_item + 16;
    if (threadIdx.x == 0) { mbar_init(bar_item, 1); mbar_init(bar_item + 8, 1); }
    GemmSmem g = gemm_setup(smem_gemm, 8);
    const int wg = __shfl_sync(~0u, threadIdx.x >> 7, 0);
    if (wg == 0) {
        asm volatile("setmaxnreg.dec.sync.aligned.u32 40;");
        if (threadIdx.x == 0) {
            uint32_t it = 0;
            Sched z;
            for (int n = 0;; n++) {
                const int code = next_item(z);
                sts32(slot + (n & 1) * 4, code);
                mbar_arrive(bar_item + (n & 1) * 8);
                const int type = code & 7, blk = (code >> 3) & 15, idx = code >> 7;
                if (type == IT_END) break;
                wait_flag(g_flag + 64 + blk, 96);
                asm volatile("fence.proxy.async.global;" ::: "memory");
                for (int k = 0; k < (type == IT_W64 ? 32 : 64); k++, it++) {
                    const int s = it & 3;
                    const uint32_t st = g.st + s * STAGE_BYTES, fb = g.full + 8 * s;
                    mbar_wait(g.empty + 8 * s, ((it >> 2) & 1) ^ 1);
                    mbar_expect_tx(fb, type == IT_W128 ? 32768 : 49152);
                    if (type == IT_W64) {
                        tma3d(st, &P.mo2, 0, blk * 128, k * 2, fb);
                        tma3d(st + 32768, &P.mwo1, 0, k * 128, idx, fb);
                    } else {
                        tma2d(st, &P.mo, k * 64, blk * 128, fb);
                        tma3d(st + 16384, type == IT_W256 ? &P.mwo4 : &P.mwo2, 0, k * 64, idx * (type == IT_W256 ? 4 : 2), fb);
                    }
                }
            }
        }
    } else {
        asm volatile("setmaxnreg.inc.sync.aligned.u32 232;");
        const int cw = wg - 1, lane = threadIdx.x & 31;
        uint32_t round = 0;
#pragma unroll 1
        for (int n = 0;; n++) {
            mbar_wait_u(bar_item + (n & 1) * 8, (n >> 1) & 1);
            const int code = __shfl_sync(~0u, lds32(slot + (n & 1) * 4), 0);
            const int type = code & 7, blk = (code >> 3) & 15, idx = (code >> 7) & 31;
#define TLB(slot_)
            if (type == IT_END) break;
            TLB(0);
            bf16* dst = out + (size_t)(blk * 128 + cw * 64 + ((threadIdx.x >> 5) & 3) * 16 + (lane >> 2)) * 2048 + (lane & 3) * 8;
            if (type == IT_W256) wo_item<256, 1>(g, cw, round, dst + idx * 256, lane & 3);
            else if (type == IT_W128) wo_item<128, 1>(g, cw, round, dst + idx * 128, lane & 3);
            else wo_item<64, 2>(g, cw, round, dst + idx * 64, lane & 3);
            TLB(1);
        }
    }
}

constexpr int TBN = NBT >= 13 ? 64 : 128, TKPS = TBN == 64 ? 2 : 1, TPB = DM / TBN;
__global__ void __cluster_dims__(2, 1, 1) __launch_bounds__(384, 1)
k_tail(const __grid_constant__ BgParams P, bf16* __restrict__ out) {
    extern __shared__ __align__(1024) uint8_t smem_gemm[];
    const uint32_t bar_s = smem_u32(smem_gemm) + NSTAGE * STAGE_BYTES + 128;
    if (threadIdx.x == 0) { TL(4, 0); mbar_init(bar_s, 1); mbar_expect_tx(bar_s, TBN * 256); }
    GemmSmem g = gemm_setup(smem_gemm, 8);
    asm volatile("barrier.cluster.arrive.relaxed.aligned;" ::: "memory");
    const int half = blockIdx.x & 1, blk = NBT + (blockIdx.x >> 1) / TPB, idx = (blockIdx.x >> 1) % TPB;
    const int wg = __shfl_sync(~0u, threadIdx.x >> 7, 0);
    if (wg == 0) {
        if (threadIdx.x == 0) {
            wait_flag(g_flag + 64 + blk, 96);
            asm volatile("fence.proxy.async.global;" ::: "memory");
            for (int k = 0; k < 32 / TKPS; k++) {
                const int s = k & 3, kb = half * 32 + k * TKPS;
                const uint32_t st = g.st + s * STAGE_BYTES, fb = g.full + 8 * s;
                mbar_wait(g.empty + 8 * s, ((k >> 2) & 1) ^ 1);
                mbar_expect_tx(fb, TBN == 64 ? 49152 : 32768);
                if (TBN == 64) {
                    tma3d(st, &P.mo2, 0, blk * 128, kb, fb);
                    tma3d(st + 32768, &P.mwo1, 0, kb * 64, idx, fb);
                } else {
                    tma2d(st, &P.mo, kb * 64, blk * 128, fb);
                    tma3d(st + 16384, &P.mwo2, 0, kb * 64, idx * 2, fb);
                }
            }
        }
        __syncwarp();
        asm volatile("barrier.cluster.wait.aligned;" ::: "memory");
    } else {
        const int cw = wg - 1, lane = threadIdx.x & 31, t = lane & 3;
        float acc[TBN / 2];
        uint32_t round = 0;
        gemm_mainloop<128, TBN, TKPS>(acc, g, cw, 8 / TKPS, round);
        asm volatile("barrier.cluster.wait.aligned;" ::: "memory");
        const uint32_t xa = g.st + B_OST + (threadIdx.x & 127) * 16;
        if (cw != half) {
            uint32_t ra, rb;
            asm("mapa.shared::cluster.u32 %0, %1, %2;" : "=r"(ra) : "r"(xa), "r"(half ^ 1));
            asm("mapa.shared::cluster.u32 %0, %1, %2;" : "=r"(rb) : "r"(bar_s), "r"(half ^ 1));
#pragma unroll
            for (int i = 0; i < TBN / 8; i++)
                asm volatile("st.async.weak.shared::cluster.mbarrier::complete_tx::bytes.v4.f32 [%0], {%1,%2,%3,%4}, [%5];"
                             ::"r"(ra + i * 2048), "f"(acc[4 * i]), "f"(acc[4 * i + 1]), "f"(acc[4 * i + 2]), "f"(acc[4 * i + 3]), "r"(rb) : "memory");
        } else {
            mbar_wait_u(bar_s, 0);
#pragma unroll
            for (int i = 0; i < TBN / 8; i++) {
                const float4 v = lds128f(xa + i * 2048);
                acc[4 * i] += v.x; acc[4 * i + 1] += v.y; acc[4 * i + 2] += v.z; acc[4 * i + 3] += v.w;
            }
            store_tile<TBN>(acc, out + (size_t)(blk * 128 + cw * 64 + ((threadIdx.x >> 5) & 3) * 16 + (lane >> 2)) * 2048 + idx * TBN + t * 8, t);
            if ((threadIdx.x & 127) == 0) TL(4, 1);
        }
    }
    asm volatile("barrier.cluster.arrive.relaxed.aligned;\nbarrier.cluster.wait.aligned;" ::: "memory");
}

typedef CUresult (*EncodeFn)(CUtensorMap*, CUtensorMapDataType, cuuint32_t, void*, const cuuint64_t*, const cuuint64_t*,
                             const cuuint32_t*, const cuuint32_t*, CUtensorMapInterleave, CUtensorMapSwizzle,
                             CUtensorMapL2promotion, CUtensorMapFloatOOBfill);

static void map2d(EncodeFn enc, CUtensorMap* m, const void* p, int rows, int cols, int box_rows) {
    cuuint64_t dim[2] = {(cuuint64_t)cols, (cuuint64_t)rows}, str[1] = {(cuuint64_t)cols * 2};
    cuuint32_t box[2] = {64, (cuuint32_t)box_rows}, es[2] = {1, 1};
    enc(m, CU_TENSOR_MAP_DATA_TYPE_BFLOAT16, 2, (void*)p, dim, str, box, es, CU_TENSOR_MAP_INTERLEAVE_NONE,
        CU_TENSOR_MAP_SWIZZLE_128B, CU_TENSOR_MAP_L2_PROMOTION_L2_256B, CU_TENSOR_MAP_FLOAT_OOB_FILL_NONE);
}
static void map3d(EncodeFn enc, CUtensorMap* m, const void* p, int rows, int cols, int box_rows, int nblk) {
    cuuint64_t dim[3] = {64, (cuuint64_t)rows, (cuuint64_t)cols / 64}, str[2] = {(cuuint64_t)cols * 2, 128};
    cuuint32_t box[3] = {64, (cuuint32_t)box_rows, (cuuint32_t)nblk}, es[3] = {1, 1, 1};
    enc(m, CU_TENSOR_MAP_DATA_TYPE_BFLOAT16, 3, (void*)p, dim, str, box, es, CU_TENSOR_MAP_INTERLEAVE_NONE,
        CU_TENSOR_MAP_SWIZZLE_128B, CU_TENSOR_MAP_L2_PROMOTION_L2_256B, CU_TENSOR_MAP_FLOAT_OOB_FILL_NONE);
}

#define USE_PDL 1

extern "C" void kernel_launch(void* const* d_in, const int* in_sizes, int n_in, void* d_out, int out_size) {
    const bf16 *x = (const bf16*)d_in[0], *mem0 = (const bf16*)d_in[1], *Wq = (const bf16*)d_in[2], *Wk = (const bf16*)d_in[3];
    const bf16 *Wv = (const bf16*)d_in[4], *Wo = (const bf16*)d_in[5];
    const bf16 *u = (const bf16*)d_in[7], *Are = (const bf16*)d_in[8], *Aim = (const bf16*)d_in[9], *Bre = (const bf16*)d_in[10];
    const bf16 *Bim = (const bf16*)d_in[11], *Cre = (const bf16*)d_in[12], *Cim = (const bf16*)d_in[13];
    const bf16 *logdt = (const bf16*)d_in[14], *Dsk = (const bf16*)d_in[15];
    bf16* out = (bf16*)d_out;

    void* fn = nullptr;
    cudaDriverEntryPointQueryResult qr;
    cudaGetDriverEntryPoint("cuTensorMapEncodeTiled", &fn, cudaEnableDefault, &qr);
    EncodeFn enc = (EncodeFn)fn;
    void *kv, *o;
    cudaGetSymbolAddress(&kv, g_kv);
    cudaGetSymbolAddress(&o, g_o);
    CUtensorMap mx, mwq, mwk, mwv, mkv2;
    BgParams P;
    map2d(enc, &mx, x, SEQ, DM, 128);
    map2d(enc, &P.mo, o, SEQ, HD, 128);
    map3d(enc, &P.mo2, o, SEQ, HD, 128, 2);
    map3d(enc, &mwq, Wq, DM, HD, 64, 2);
    map3d(enc, &mwk, Wk, DM, HD, 64, 2);
    map3d(enc, &mwv, Wv, DM, HD, 64, 2);
    map3d(enc, &P.mwo4, Wo, HD, DM, 64, 4);
    map3d(enc, &P.mwo2, Wo, HD, DM, 64, 2);
    map3d(enc, &P.mwo1, Wo, HD, DM, 128, 1);
    map3d(enc, &mkv2, kv, SEQ, PW, 32, 2);
    cudaFuncSetAttribute(k_kv, cudaFuncAttributeMaxDynamicSharedMemorySize, GEMM_SMEM);
    cudaFuncSetAttribute(k_bg, cudaFuncAttributeMaxDynamicSharedMemorySize, BG_SMEM);
    cudaFuncSetAttribute(k_tail, cudaFuncAttributeMaxDynamicSharedMemorySize, BG_SMEM);
    cudaFuncSetAttribute(k_chain, cudaFuncAttributeMaxDynamicSharedMemorySize, CHAIN_SMEM);
    cudaFuncSetAttribute(k_s4, cudaFuncAttributeMaxDynamicSharedMemorySize, S4_SMEM);

    cudaStream_t st = cudaStreamPerThread;
    cudaLaunchAttribute pdl[2], cls[1];
    pdl[0].id = cudaLaunchAttributeProgrammaticStreamSerialization;
    pdl[0].val.programmaticStreamSerializationAllowed = 1;
    cls[0].id = cudaLaunchAttributeClusterDimension;
    cls[0].val.clusterDim.x = CLS; cls[0].val.clusterDim.y = 1; cls[0].val.clusterDim.z = 1;
    cudaLaunchConfig_t cfg = {};
    cfg.stream = st; cfg.attrs = cls; cfg.numAttrs = 1;
    cfg.gridDim = dim3(96); cfg.blockDim = dim3(384); cfg.dynamicSmemBytes = GEMM_SMEM;
    cudaLaunchKernelEx(&cfg, k_kv, mx, mwk, mwv, mwq, Wq, Wo, 0);
    pdl[1] = cls[0]; pdl[1].val.clusterDim.x = 2;
    cfg.attrs = pdl; cfg.numAttrs = 2;
    cfg.gridDim = dim3(36);
    cudaLaunchKernelEx(&cfg, k_kv, mx, mwk, mwv, mwq, Wq, Wo, 96);
    cfg.numAttrs = 1;
    cfg.gridDim = dim3(96); cfg.blockDim = dim3(256); cfg.dynamicSmemBytes = CHAIN_SMEM;
    cudaLaunchKernelEx(&cfg, k_chain, mem0, Wq, Wk, Wv, Wo, mkv2);
    cfg.numAttrs = USE_PDL;
    cfg.gridDim = dim3(36); cfg.blockDim = dim3(512); cfg.dynamicSmemBytes = S4_SMEM;
    cudaLaunchKernelEx(&cfg, k_s4, u, Are, Aim, Bre, Bim, Cre, Cim, logdt, Dsk, out);
    cfg.gridDim = dim3(36); cfg.blockDim = dim3(384); cfg.dynamicSmemBytes = BG_SMEM;
    cudaLaunchKernelEx(&cfg, k_bg, P, out);
    cfg.gridDim = dim3((16 - NBT) * TPB * 2);
    cudaLaunchKernelEx(&cfg, k_tail, P, out);
}
```

```cpp
#include <cuda_runtime.h>
#include <cuda_bf16.h>
#include <cuda.h>
#include <stdint.h>

typedef __nv_bfloat16 bf16;

constexpr int SEQ = 2048, DM = 1024, HD = 4096, NSEG = 64;

constexpr int PW = 3 * HD;
#define NTA 3
__device__ __align__(1024) bf16 g_kv[(size_t)SEQ * PW];
__device__ __align__(1024) bf16 g_o[(size_t)SEQ * HD];
constexpr int XPAIRS = 128 + NSEG * 4;
__device__ __align__(8192) uint2 g_x[XPAIRS * 1024];
__device__ uint32_t g_home[XPAIRS];
__device__ uint32_t g_side[256];
__device__ __align__(1024) uint32_t g_flag[256];

#define TL(kern, slot)

__device__ __forceinline__ uint32_t smem_u32(const void* p) { return (uint32_t)__cvta_generic_to_shared(p); }
__device__ __forceinline__ void mbar_init(uint32_t bar, uint32_t cnt) {
    asm volatile("mbarrier.init.shared::cta.b64 [%0], %1;" ::"r"(bar), "r"(cnt) : "memory");
}
__device__ __forceinline__ void mbar_expect_tx(uint32_t bar, uint32_t bytes) {
    asm volatile("mbarrier.arrive.expect_tx.shared::cta.b64 _, [%0], %1;" ::"r"(bar), "r"(bytes) : "memory");
}
__device__ __forceinline__ void mbar_arrive(uint32_t bar) {
    asm volatile("mbarrier.arrive.shared::cta.b64 _, [%0];" ::"r"(bar) : "memory");
}
__device__ __forceinline__ bool mbar_try(uint32_t bar, uint32_t parity) {
    uint32_t ok;
    asm volatile("{\n.reg .pred p;\nmbarrier.try_wait.parity.shared::cta.b64 p, [%1], %2;\nselp.u32 %0, 1, 0, p;\n}"
                 : "=r"(ok) : "r"(bar), "r"(parity) : "memory");
    return ok;
}
constexpr int SPIN_LIMIT = 1 << 20;
__device__ __forceinline__ void mbar_wait(uint32_t bar, uint32_t parity) {
    int n = 0;
    while (!mbar_try(bar, parity)) { if (++n > SPIN_LIMIT) __trap(); }
}
__device__ __forceinline__ void mbar_wait_u(uint32_t bar, uint32_t parity) {
    asm volatile("{\n.reg .pred p;\n.reg .u32 n;\n"
                 "mbarrier.try_wait.parity.shared::cta.b64 p, [%0], %1;\n@p bra.uni DONE;\nmov.u32 n, 0;\n"
                 "AGAIN:\nmbarrier.try_wait.parity.shared::cta.b64 p, [%0], %1;\n@p bra.uni DONE;\n"
                 "add.u32 n, n, 1;\nsetp.lt.u32 p, n, 0x100000;\n@p bra.uni AGAIN;\ntrap;\nDONE:\n}"
                 ::"r"(bar), "r"(parity) : "memory");
}
__device__ __forceinline__ void tma2d(uint32_t dst, const CUtensorMap* m, int c0, int c1, uint32_t bar) {
    asm volatile("cp.async.bulk.tensor.2d.shared::cluster.global.mbarrier::complete_tx::bytes [%0], [%1, {%3, %4}], [%2];"
                 ::"r"(dst), "l"(m), "r"(bar), "r"(c0), "r"(c1) : "memory");
}
__device__ __forceinline__ void tma3d(uint32_t dst, const CUtensorMap* m, int c0, int c1, int c2, uint32_t bar) {
    asm volatile("cp.async.bulk.tensor.3d.shared::cluster.global.mbarrier::complete_tx::bytes [%0], [%1, {%3, %4, %5}], [%2];"
                 ::"r"(dst), "l"(m), "r"(bar), "r"(c0), "r"(c1), "r"(c2) : "memory");
}
__device__ __forceinline__ uint32_t pack2(float lo, float hi) {
    uint32_t r;
    asm("cvt.rn.bf16x2.f32 %0, %1, %2;" : "=r"(r) : "f"(hi), "f"(lo));
    return r;
}
__device__ __forceinline__ float bf_lo(uint32_t v) { return __uint_as_float(v << 16); }
__device__ __forceinline__ float bf_hi(uint32_t v) { return __uint_as_float(v & 0xffff0000u); }
__device__ __forceinline__ float bf_round(float x) { return bf_lo(pack2(x, 0.f)); }
__device__ __forceinline__ float ex2(float x) { float y; asm("ex2.approx.ftz.f32 %0, %1;" : "=f"(y) : "f"(x)); return y; }
__device__ __forceinline__ void mma16816(float (&c)[4], uint32_t a0, uint32_t a1, uint32_t a2, uint32_t a3, uint32_t b0, uint32_t b1) {
    asm volatile("mma.sync.aligned.m16n8k16.row.col.f32.bf16.bf16.f32 {%0,%1,%2,%3}, {%4,%5,%6,%7}, {%8,%9}, {%0,%1,%2,%3};"
                 : "+f"(c[0]), "+f"(c[1]), "+f"(c[2]), "+f"(c[3]) : "r"(a0), "r"(a1), "r"(a2), "r"(a3), "r"(b0), "r"(b1));
}
__device__ __forceinline__ void mma1688(float (&c)[4], uint32_t a0, uint32_t a1, uint32_t b0) {
    asm volatile("mma.sync.aligned.m16n8k8.row.col.f32.bf16.bf16.f32 {%0,%1,%2,%3}, {%4,%5}, {%6}, {%0,%1,%2,%3};"
                 : "+f"(c[0]), "+f"(c[1]), "+f"(c[2]), "+f"(c[3]) : "r"(a0), "r"(a1), "r"(b0));
}
__device__ __forceinline__ void ldsm4(uint32_t (&r)[4], uint32_t a) {
    asm volatile("ldmatrix.sync.aligned.m8n8.x4.shared.b16 {%0,%1,%2,%3}, [%4];"
                 : "=r"(r[0]), "=r"(r[1]), "=r"(r[2]), "=r"(r[3]) : "r"(a) : "memory");
}
__device__ __forceinline__ void ldsm4t(uint32_t (&r)[4], uint32_t a) {
    asm volatile("ldmatrix.sync.aligned.m8n8.x4.trans.shared.b16 {%0,%1,%2,%3}, [%4];"
                 : "=r"(r[0]), "=r"(r[1]), "=r"(r[2]), "=r"(r[3]) : "r"(a) : "memory");
}
__device__ __forceinline__ void ldsm2t(uint32_t& r0, uint32_t& r1, uint32_t a) {
    asm volatile("ldmatrix.sync.aligned.m8n8.x2.trans.shared.b16 {%0,%1}, [%2];" : "=r"(r0), "=r"(r1) : "r"(a) : "memory");
}
__device__ __forceinline__ void stsm4t(uint32_t a, uint32_t r0, uint32_t r1, uint32_t r2, uint32_t r3) {
    asm volatile("stmatrix.sync.aligned.m8n8.x4.trans.shared.b16 [%0], {%1,%2,%3,%4};"
                 ::"r"(a), "r"(r0), "r"(r1), "r"(r2), "r"(r3) : "memory");
}
__device__ __forceinline__ void lds128(uint32_t (&r)[4], uint32_t a) {
    asm volatile("ld.shared.v4.u32 {%0,%1,%2,%3}, [%4];" : "=r"(r[0]), "=r"(r[1]), "=r"(r[2]), "=r"(r[3]) : "r"(a) : "memory");
}
__device__ __forceinline__ float4 lds128f(uint32_t a) {
    float4 v;
    asm volatile("ld.shared.v4.f32 {%0,%1,%2,%3}, [%4];" : "=f"(v.x), "=f"(v.y), "=f"(v.z), "=f"(v.w) : "r"(a) : "memory");
    return v;
}
__device__ __forceinline__ float2 lds64f(uint32_t a) {
    float2 v;
    asm volatile("ld.shared.v2.f32 {%0,%1}, [%2];" : "=f"(v.x), "=f"(v.y) : "r"(a) : "memory");
    return v;
}
__device__ __forceinline__ uint32_t lds32(uint32_t a) {
    uint32_t v;
    asm volatile("ld.shared.u32 %0, [%1];" : "=r"(v) : "r"(a) : "memory");
    return v;
}
__device__ __forceinline__ void sts128(uint32_t a, uint32_t r0, uint32_t r1, uint32_t r2, uint32_t r3) {
    asm volatile("st.shared.v4.u32 [%0], {%1,%2,%3,%4};" ::"r"(a), "r"(r0), "r"(r1), "r"(r2), "r"(r3) : "memory");
}
__device__ __forceinline__ void sts128f(uint32_t a, float r0, float r1, float r2, float r3) {
    asm volatile("st.shared.v4.f32 [%0], {%1,%2,%3,%4};" ::"r"(a), "f"(r0), "f"(r1), "f"(r2), "f"(r3) : "memory");
}
__device__ __forceinline__ void sts64(uint32_t a, uint32_t r0, uint32_t r1) {
    asm volatile("st.shared.v2.u32 [%0], {%1,%2};" ::"r"(a), "r"(r0), "r"(r1) : "memory");
}
__device__ __forceinline__ void sts64f(uint32_t a, float r0, float r1) {
    asm volatile("st.shared.v2.f32 [%0], {%1,%2};" ::"r"(a), "f"(r0), "f"(r1) : "memory");
}
__device__ __forceinline__ void sts32f(uint32_t a, float r0) {
    asm volatile("st.shared.f32 [%0], %1;" ::"r"(a), "f"(r0) : "memory");
}
__device__ __forceinline__ uint2 ld_rlx64(const uint2* p) {
    uint2 v;
    asm volatile("{\n.reg .b64 t;\nld.relaxed.gpu.global.b64 t, [%2];\nmov.b64 {%0,%1}, t;\n}" : "=r"(v.x), "=r"(v.y) : "l"(p) : "memory");
    return v;
}
__device__ __forceinline__ void st_rlx64(uint2* p, uint32_t x, uint32_t y) {
    asm volatile("{\n.reg .b64 t;\nmov.b64 t, {%1,%2};\nst.relaxed.gpu.global.b64 [%0], t;\n}" ::"l"(p), "r"(x), "r"(y) : "memory");
}
__device__ __forceinline__ uint32_t ld_acq32(const uint32_t* p) {
    uint32_t v;
    asm volatile("ld.acquire.gpu.global.u32 %0, [%1];" : "=r"(v) : "l"(p) : "memory");
    return v;
}
__device__ __forceinline__ void wait_flag(const uint32_t* p, uint32_t need) {
    int n = 0;
    while (ld_acq32(p) < need) { __nanosleep(200); if (++n > SPIN_LIMIT) __trap(); }
}
__device__ __forceinline__ void bar_sync(int id, int n) { asm volatile("bar.sync %0, %1;" ::"r"(id), "r"(n) : "memory"); }
__device__ __forceinline__ void wg_fence() { asm volatile("wgmma.fence.sync.aligned;" ::: "memory"); }
__device__ __forceinline__ void wg_commit() { asm volatile("wgmma.commit_group.sync.aligned;" ::: "memory"); }
template <int N> __device__ __forceinline__ void wg_wait() { asm volatile("wgmma.wait_group.sync.aligned %0;" ::"n"(N) : "memory"); }
__device__ __forceinline__ uint64_t desc_sw128(uint32_t addr, uint32_t lbo, uint32_t sbo) {
    return (uint64_t)((addr & 0x3FFFF) >> 4) | ((uint64_t)(lbo >> 4) << 16) | ((uint64_t)(sbo >> 4) << 32) | (1ull << 62);
}
__device__ __forceinline__ void quad_transpose(uint32_t& r0, uint32_t& r1, uint32_t& r2, uint32_t& r3, int t) {
    const bool o = t & 1, h = t & 2;
    uint32_t s0 = __shfl_xor_sync(~0u, o ? r0 : r1, 1), s1 = __shfl_xor_sync(~0u, o ? r2 : r3, 1);
    uint32_t a0 = o ? s0 : r0, a1 = o ? r1 : s0, a2 = o ? s1 : r2, a3 = o ? r3 : s1;
    s0 = __shfl_xor_sync(~0u, h ? a0 : a2, 2); s1 = __shfl_xor_sync(~0u, h ? a1 : a3, 2);
    r0 = h ? s0 : a0; r1 = h ? s1 : a1; r2 = h ? a2 : s0; r3 = h ? a3 : s1;
}

__device__ __forceinline__ void wgmma_n256(float (&d)[128], uint64_t da, uint64_t db, int sd) {
    asm volatile("{\n.reg .pred p;\nsetp.ne.b32 p, %130, 0;\n"
        "wgmma.mma_async.sync.aligned.m64n256k16.f32.bf16.bf16 "
        "{%0,%1,%2,%3,%4,%5,%6,%7,%8,%9,%10,%11,%12,%13,%14,%15,"
        "%16,%17,%18,%19,%20,%21,%22,%23,%24,%25,%26,%27,%28,%29,%30,%31,"
        "%32,%33,%34,%35,%36,%37,%38,%39,%40,%41,%42,%43,%44,%45,%46,%47,"
        "%48,%49,%50,%51,%52,%53,%54,%55,%56,%57,%58,%59,%60,%61,%62,%63,"
        "%64,%65,%66,%67,%68,%69,%70,%71,%72,%73,%74,%75,%76,%77,%78,%79,"
        "%80,%81,%82,%83,%84,%85,%86,%87,%88,%89,%90,%91,%92,%93,%94,%95,"
        "%96,%97,%98,%99,%100,%101,%102,%103,%104,%105,%106,%107,%108,%109,%110,%111,"
        "%112,%113,%114,%115,%116,%117,%118,%119,%120,%121,%122,%123,%124,%125,%126,%127}, %128, %129, p, 1, 1, 0, 1;\n}\n"
        : "+f"(d[0]), "+f"(d[1]), "+f"(d[2]), "+f"(d[3]), "+f"(d[4]), "+f"(d[5]), "+f"(d[6]), "+f"(d[7]),
          "+f"(d[8]), "+f"(d[9]), "+f"(d[10]), "+f"(d[11]), "+f"(d[12]), "+f"(d[13]), "+f"(d[14]), "+f"(d[15]),
          "+f"(d[16]), "+f"(d[17]), "+f"(d[18]), "+f"(d[19]), "+f"(d[20]), "+f"(d[21]), "+f"(d[22]), "+f"(d[23]),
          "+f"(d[24]), "+f"(d[25]), "+f"(d[26]), "+f"(d[27]), "+f"(d[28]), "+f"(d[29]), "+f"(d[30]), "+f"(d[31]),
          "+f"(d[32]), "+f"(d[33]), "+f"(d[34]), "+f"(d[35]), "+f"(d[36]), "+f"(d[37]), "+f"(d[38]), "+f"(d[39]),
          "+f"(d[40]), "+f"(d[41]), "+f"(d[42]), "+f"(d[43]), "+f"(d[44]), "+f"(d[45]), "+f"(d[46]), "+f"(d[47]),
          "+f"(d[48]), "+f"(d[49]), "+f"(d[50]), "+f"(d[51]), "+f"(d[52]), "+f"(d[53]), "+f"(d[54]), "+f"(d[55]),
          "+f"(d[56]), "+f"(d[57]), "+f"(d[58]), "+f"(d[59]), "+f"(d[60]), "+f"(d[61]), "+f"(d[62]), "+f"(d[63]),
          "+f"(d[64]), "+f"(d[65]), "+f"(d[66]), "+f"(d[67]), "+f"(d[68]), "+f"(d[69]), "+f"(d[70]), "+f"(d[71]),
          "+f"(d[72]), "+f"(d[73]), "+f"(d[74]), "+f"(d[75]), "+f"(d[76]), "+f"(d[77]), "+f"(d[78]), "+f"(d[79]),
          "+f"(d[80]), "+f"(d[81]), "+f"(d[82]), "+f"(d[83]), "+f"(d[84]), "+f"(d[85]), "+f"(d[86]), "+f"(d[87]),
          "+f"(d[88]), "+f"(d[89]), "+f"(d[90]), "+f"(d[91]), "+f"(d[92]), "+f"(d[93]), "+f"(d[94]), "+f"(d[95]),
          "+f"(d[96]), "+f"(d[97]), "+f"(d[98]), "+f"(d[99]), "+f"(d[100]), "+f"(d[101]), "+f"(d[102]), "+f"(d[103]),
          "+f"(d[104]), "+f"(d[105]), "+f"(d[106]), "+f"(d[107]), "+f"(d[108]), "+f"(d[109]), "+f"(d[110]), "+f"(d[111]),
          "+f"(d[112]), "+f"(d[113]), "+f"(d[114]), "+f"(d[115]), "+f"(d[116]), "+f"(d[117]), "+f"(d[118]), "+f"(d[119]),
          "+f"(d[120]), "+f"(d[121]), "+f"(d[122]), "+f"(d[123]), "+f"(d[124]), "+f"(d[125]), "+f"(d[126]), "+f"(d[127])
        : "l"(da), "l"(db), "r"(sd));
}

__device__ __forceinline__ void wgmma_n128(float (&d)[64], uint64_t da, uint64_t db, int sd) {
    asm volatile("{\n.reg .pred p;\nsetp.ne.b32 p, %66, 0;\n"
        "wgmma.mma_async.sync.aligned.m64n128k16.f32.bf16.bf16 "
        "{%0,%1,%2,%3,%4,%5,%6,%7,%8,%9,%10,%11,%12,%13,%14,%15,"
        "%16,%17,%18,%19,%20,%21,%22,%23,%24,%25,%26,%27,%28,%29,%30,%31,"
        "%32,%33,%34,%35,%36,%37,%38,%39,%40,%41,%42,%43,%44,%45,%46,%47,"
        "%48,%49,%50,%51,%52,%53,%54,%55,%56,%57,%58,%59,%60,%61,%62,%63}, %64, %65, p, 1, 1, 0, 1;\n}\n"
        : "+f"(d[0]), "+f"(d[1]), "+f"(d[2]), "+f"(d[3]), "+f"(d[4]), "+f"(d[5]), "+f"(d[6]), "+f"(d[7]),
          "+f"(d[8]), "+f"(d[9]), "+f"(d[10]), "+f"(d[11]), "+f"(d[12]), "+f"(d[13]), "+f"(d[14]), "+f"(d[15]),
          "+f"(d[16]), "+f"(d[17]), "+f"(d[18]), "+f"(d[19]), "+f"(d[20]), "+f"(d[21]), "+f"(d[22]), "+f"(d[23]),
          "+f"(d[24]), "+f"(d[25]), "+f"(d[26]), "+f"(d[27]), "+f"(d[28]), "+f"(d[29]), "+f"(d[30]), "+f"(d[31]),
          "+f"(d[32]), "+f"(d[33]), "+f"(d[34]), "+f"(d[35]), "+f"(d[36]), "+f"(d[37]), "+f"(d[38]), "+f"(d[39]),
          "+f"(d[40]), "+f"(d[41]), "+f"(d[42]), "+f"(d[43]), "+f"(d[44]), "+f"(d[45]), "+f"(d[46]), "+f"(d[47]),
          "+f"(d[48]), "+f"(d[49]), "+f"(d[50]), "+f"(d[51]), "+f"(d[52]), "+f"(d[53]), "+f"(d[54]), "+f"(d[55]),
          "+f"(d[56]), "+f"(d[57]), "+f"(d[58]), "+f"(d[59]), "+f"(d[60]), "+f"(d[61]), "+f"(d[62]), "+f"(d[63])
        : "l"(da), "l"(db), "r"(sd));
}

__device__ __forceinline__ void wgmma_n64(float (&d)[32], uint64_t da, uint64_t db, int sd) {
    asm volatile("{\n.reg .pred p;\nsetp.ne.b32 p, %34, 0;\n"
        "wgmma.mma_async.sync.aligned.m64n64k16.f32.bf16.bf16 "
        "{%0,%1,%2,%3,%4,%5,%6,%7,%8,%9,%10,%11,%12,%13,%14,%15,"
        "%16,%17,%18,%19,%20,%21,%22,%23,%24,%25,%26,%27,%28,%29,%30,%31}, %32, %33, p, 1, 1, 0, 1;\n}\n"
        : "+f"(d[0]), "+f"(d[1]), "+f"(d[2]), "+f"(d[3]), "+f"(d[4]), "+f"(d[5]), "+f"(d[6]), "+f"(d[7]),
          "+f"(d[8]), "+f"(d[9]), "+f"(d[10]), "+f"(d[11]), "+f"(d[12]), "+f"(d[13]), "+f"(d[14]), "+f"(d[15]),
          "+f"(d[16]), "+f"(d[17]), "+f"(d[18]), "+f"(d[19]), "+f"(d[20]), "+f"(d[21]), "+f"(d[22]), "+f"(d[23]),
          "+f"(d[24]), "+f"(d[25]), "+f"(d[26]), "+f"(d[27]), "+f"(d[28]), "+f"(d[29]), "+f"(d[30]), "+f"(d[31])
        : "l"(da), "l"(db), "r"(sd));
}

constexpr int STAGE_BYTES = 49152, NSTAGE = 4;
constexpr int GEMM_SMEM = NSTAGE * STAGE_BYTES + 128;

struct GemmSmem { uint32_t st, full, empty; };
__device__ __forceinline__ GemmSmem gemm_setup(uint8_t* raw, int releases) {
    GemmSmem g;
    g.st = smem_u32(raw);
    if (g.st & 1023) __trap();
    g.full = g.st + NSTAGE * STAGE_BYTES; g.empty = g.full + 64;
    if (threadIdx.x == 0) {
        for (int s = 0; s < NSTAGE; s++) { mbar_init(g.full + 8 * s, 1); mbar_init(g.empty + 8 * s, releases); }
        asm volatile("fence.mbarrier_init.release.cluster;" ::: "memory");
        asm volatile("fence.proxy.async.shared::cta;" ::: "memory");
    }
    __syncthreads();
    return g;
}
__device__ __forceinline__ void mbar_arrive_one(uint32_t bar, uint32_t who) {
    asm volatile("{\n.reg .pred p;\nsetp.eq.u32 p, %1, 0;\n@p mbarrier.arrive.shared::cta.b64 _, [%0];\n}" ::"r"(bar), "r"(who) : "memory");
}
template <int BM, int BN, int KPS, typename ACC>
__device__ __forceinline__ void gemm_stage(ACC& acc, uint32_t stage, int wg, bool first) {
    const uint64_t da = desc_sw128(stage + wg * 8192, 16, 1024);
    const uint64_t db = desc_sw128(stage + KPS * BM * 128, 8192, 1024);
    wg_fence();
#pragma unroll
    for (int k = 0; k < 4 * KPS; k++) {
        const uint64_t a = da + (k >> 2) * (BM * 8) + (k & 3) * 2, b = db + k * 128;
        if constexpr (BN == 256) wgmma_n256(acc, a, b, first && k == 0 ? 0 : 1);
        else if constexpr (BN == 128) wgmma_n128(acc, a, b, first && k == 0 ? 0 : 1);
        else wgmma_n64(acc, a, b, first && k == 0 ? 0 : 1);
    }
    wg_commit();
}

__device__ __forceinline__ void kv_store_unit(const uint32_t (&pk)[64], int u, bf16* dst, int t) {
    const int G = (u >> 2) * 2 + (u & 1), hh = (u >> 1) & 1;
    uint32_t r0 = pk[(4 * G + 0) * 2 + hh], r1 = pk[(4 * G + 1) * 2 + hh], r2 = pk[(4 * G + 2) * 2 + hh], r3 = pk[(4 * G + 3) * 2 + hh];
    quad_transpose(r0, r1, r2, r3, t);
#define KVST ".cs"
    asm volatile("st.global" KVST ".v4.u32 [%0], {%1,%2,%3,%4};" ::"l"(dst + (size_t)hh * 8 * PW + G * 32), "r"(r0), "r"(r1), "r"(r2), "r"(r3) : "memory");
}

#define TLK(slot)
#define TLK2(slot)
__device__ __forceinline__ uint32_t near_page(int pair, int line) {
    uint32_t best[2] = {~0u, ~0u};
#pragma unroll 1
    for (int i = 0; i < 16; i++) {
        uint32_t t0, t1, v;
        asm volatile("mov.u32 %0, %%clock;" : "=r"(t0)::"memory");
        asm volatile("atom.relaxed.gpu.global.or.b32 %0, [%1], -1;" : "=r"(v) : "l"(g_x + pair * 1024 + (i & 1) * 512 + line * 16) : "memory");
        asm volatile("{\n.reg .pred p;\nsetp.ne.u32 p, %1, 0x12345;\nmov.u32 %0, -1;\n@p mov.u32 %0, %%clock;\n}" : "=r"(t1) : "r"(v) : "memory");
        if (i & 1) best[1] = min(best[1], t1 - t0); else best[0] = min(best[0], t1 - t0);
    }
    return best[1] < best[0];
}
__device__ __forceinline__ void map_pages(int c) {
    uint32_t smid;
    asm("mov.u32 %0, %%smid;" : "=r"(smid));
    const uint32_t side = near_page(0, c & 31);
    g_side[smid & 255] = side;
    for (int p = c; p < XPAIRS; p += 132) g_home[p] = near_page(p, 0) ^ side;
}

__device__ __forceinline__ void kv_tile(int c, int n, int& m, int& nb) {
    if (c < 96) { m = (c & 3) + 4 * n; nb = c >> 2; }
    else {
        const int i = ((c - 96) >> 1) + 18 * n, j = i - 48 * NTA, p = j < 0 ? i / 24 : 2 * NTA + j / 48;
        m = 2 * p + (c & 1); nb = j < 0 ? 24 + i % 24 : j % 48;
    }
}

__global__ void __launch_bounds__(384, 1)
k_kv(const __grid_constant__ CUtensorMap mx, const __grid_constant__ CUtensorMap mwk, const __grid_constant__ CUtensorMap mwv,
     const __grid_constant__ CUtensorMap mwq, const bf16* __restrict__ Wq, const bf16* __restrict__ Wo, int c0) {
    extern __shared__ __align__(1024) uint8_t smem_gemm[];
    const int c = c0 + blockIdx.x, ntile = c < 96 ? NTA : (384 - 48 * NTA + 17 - ((c - 96) >> 1)) / 18;
    if (c != 96) asm volatile("griddepcontrol.launch_dependents;");
    const uint32_t bar_done = smem_u32(smem_gemm) + NSTAGE * STAGE_BYTES + 96;
    if (threadIdx.x == 0) { mbar_init(bar_done, 8); mbar_init(bar_done + 8, 8); }
    GemmSmem g = gemm_setup(smem_gemm, 4);
    if (threadIdx.x == 0) TLK(0);
    uint32_t rank, peer_empty;
    asm("mov.u32 %0, %%cluster_ctarank;" : "=r"(rank));
    asm("mapa.shared::cluster.u32 %0, %1, %2;" : "=r"(peer_empty) : "r"(g.empty), "r"(rank ^ 1));
    asm volatile("barrier.cluster.arrive.relaxed.aligned;\nbarrier.cluster.wait.aligned;" ::: "memory");
    auto release = [&](int s) {
        asm volatile("{\n.reg .pred p;\nsetp.eq.u32 p, %2, 0;\n@p mbarrier.arrive.relaxed.cta.shared::cta.b64 _, [%0];\n"
                     "@p mbarrier.arrive.relaxed.cluster.shared::cluster.b64 _, [%1];\n}"
                     ::"r"(g.empty + 8 * s), "r"(peer_empty + 8 * s), "r"(threadIdx.x & 127) : "memory");
    };
    const int wg = __shfl_sync(~0u, threadIdx.x >> 7, 0);
    if (wg == 0) {
        asm volatile("setmaxnreg.dec.sync.aligned.u32 40;");
        if (threadIdx.x == 0) {
            for (int it = 0; it < ntile * 16; it++) {
                const int s = it & 3, kb = it & 15;
                int m, nb;
                kv_tile(c, it >> 4, m, nb);
                mbar_wait(g.empty + 8 * s, ((it >> 2) & 1) ^ 1);
                mbar_expect_tx(g.full + 8 * s, STAGE_BYTES);
                tma2d(g.st + s * STAGE_BYTES, &mx, kb * 64, m * 128, g.full + 8 * s);
                asm volatile("cp.async.bulk.tensor.3d.shared::cluster.global.mbarrier::complete_tx::bytes.multicast::cluster "
                             "[%0], [%1, {%3, %4, %5}], [%2], %6;"
                             ::"r"(g.st + s * STAGE_BYTES + 16384 + (c & 1) * 16384), "l"(nb < 16 ? &mwk : nb < 32 ? &mwv : &mwq), "r"(g.full + 8 * s),
                               "r"(0), "r"(kb * 64), "r"((nb & 15) * 4 + (c & 1) * 2), "h"((uint16_t)(3u << (rank & ~1u))) : "memory");
#define PF0 (16 * NTA - 22)
                if (c < 96 && it >= PF0 && (it - PF0) * 96 + c < 2048)
                    asm volatile("cp.async.bulk.prefetch.L2.global [%0], 4096;" ::"l"((const char*)Wo + ((it - PF0) * 96 + c) * 4096) : "memory");
            }
        } else if (threadIdx.x == 32) {
            if (c == 96) {
                for (int i = 0; i < 64; i++) reinterpret_cast<uint4*>(g_flag)[i] = make_uint4(0, 0, 0, 0);
                asm volatile("fence.acq_rel.gpu;\ngriddepcontrol.launch_dependents;\ngriddepcontrol.wait;\n"
                             "fence.acq_rel.gpu;\nred.relaxed.gpu.global.add.u32 [%0], 1;" ::"l"(g_flag + 8) : "memory");
            }
        } else if (threadIdx.x == 64) {
            for (int n = 0; n < (c < 96 ? 0 : ntile); n++) {
                int m, nb;
                kv_tile(c, n, m, nb);
                mbar_wait(bar_done + (n & 1) * 8, (n >> 1) & 1);
                asm volatile("fence.acq_rel.gpu;\nred.relaxed.gpu.global.add.u32 [%0], 1;" ::"l"(g_flag + (m >> 1)) : "memory");
            }
        } else if (threadIdx.x >= 96) {
            const uint4 ones = make_uint4(~0u, ~0u, ~0u, ~0u);
            for (int i = c * 32 + threadIdx.x - 96; i < XPAIRS * 512; i += 132 * 32) reinterpret_cast<uint4*>(g_x)[i] = ones;
            __syncwarp();
            if (threadIdx.x == 96) {
                map_pages(c);
                if (c >= 96) asm volatile("fence.acq_rel.gpu;\nred.relaxed.gpu.global.add.u32 [%0], 1;" ::"l"(g_flag + 8) : "memory");
            }
        }
    } else {
        asm volatile("setmaxnreg.inc.sync.aligned.u32 232;");
        const int cw = wg - 1, lane = threadIdx.x & 31, t = lane & 3;
        bf16* const dst0 = g_kv + (size_t)(cw * 64 + ((threadIdx.x >> 5) & 3) * 16 + (lane >> 2)) * PW + t * 8;
        bf16* dst = dst0;
        float acc[128];
        uint32_t pk[64];
#pragma unroll 1
        for (int tile = 0; tile < ntile; tile++) {
#pragma unroll
            for (int kb = 0; kb < 16; kb++) {
                mbar_wait_u(g.full + 8 * (kb & 3), (kb >> 2) & 1);
                if (kb == 0 && tile == 0 && threadIdx.x == 128) TLK2(0);
                gemm_stage<128, 256, 1>(acc, g.st + (kb & 3) * STAGE_BYTES, cw, kb == 0);
                if (tile > 0) {
                    kv_store_unit(pk, kb, dst, t);
                    if (kb == 15) { __syncwarp(); mbar_arrive_one(bar_done + (~tile & 1) * 8, lane); }
                }
                if (kb > 0) {
                    wg_wait<1>();
                    if (kb <= 12 || tile < ntile - 1) release((kb - 1) & 3);
                }
            }
            wg_wait<0>();
            if (tile < 4 && threadIdx.x == 128) TLK2(tile + 1);
            if (tile < ntile - 1) release(3);
#pragma unroll
            for (int i = 0; i < 64; i++) pk[i] = pack2(acc[2 * i], acc[2 * i + 1]);
            int m, nb;
            kv_tile(c, tile, m, nb);
            dst = dst0 + (size_t)m * 128 * PW + nb * 256;
        }
        if (threadIdx.x == 128) TLK(2);
#pragma unroll
        for (int u = 0; u < 16; u++) kv_store_unit(pk, u, dst, t);
        __syncwarp();
        mbar_arrive_one(bar_done + (~ntile & 1) * 8, lane);
        if (threadIdx.x == 128) TLK(1);
    }
}

constexpr int NS1 = 31;
#define RB1 4
#define PFC 4
constexpr int C_W1 = 0;
constexpr int C_W2 = C_W1 + 8 * NS1 * 512;
constexpr int C_KV = C_W2 + 14 * 8 * 512;
constexpr int C_RED = C_KV + 16384;
constexpr int C_QKV = C_RED + 64 * 272;
constexpr int QKV_SZ = 3 * 8 * 272;
constexpr int C_SC = C_RED;
constexpr int C_OB = C_SC + 2 * 8 * 52 * 4;
constexpr int C_BAR = C_QKV + 2 * QKV_SZ;
__host__ __device__ constexpr int smem_idx(int ks, int j) {
    return ks == 0 ? j : ks < 3 ? (j < 4 ? 4 + 4 * ks + j : -1) : (j < 3 ? 7 + 3 * ks + j : -1);
}
constexpr int CHAIN_SMEM = C_BAR + 64;
#define TS(i)
#define TG(i)

#define DLY3 8
#define DLY1 5
#define DLY0 2
#define DLY1A 10
#define DLY0A 0
#define DLY1B 10
#define DLYQ 1
#define PFD 3
#define PFI 0
#define DLYS 0
#define DLYW 3
template <int N> __device__ __forceinline__ uint32_t delayed(uint32_t x, int lane) {
#pragma unroll
    for (int i = 0; i < N; i++) asm volatile("shfl.sync.idx.b32 %0, %0, %1, 31, -1;" : "+r"(x) : "r"(lane) : "memory");
    return x;
}
__device__ __forceinline__ int fresh(int x) { asm volatile("mov.b32 %0, %0;" : "+r"(x)); return x; }
__device__ __forceinline__ void lds128v(uint32_t (&r)[4], uint32_t a) {
    asm volatile("ld.volatile.shared.v4.u32 {%0,%1,%2,%3}, [%4];" : "=r"(r[0]), "=r"(r[1]), "=r"(r[2]), "=r"(r[3]) : "r"(a) : "memory");
}
__device__ __forceinline__ uint2 lds64(uint32_t a) {
    uint2 v;
    asm volatile("ld.shared.v2.u32 {%0,%1}, [%2];" : "=r"(v.x), "=r"(v.y) : "r"(a) : "memory");
    return v;
}
#define LDQ ".L1::no_allocate"
__device__ __forceinline__ uint4 ldw128(const void* p) {
    uint4 v;
    asm volatile("ld.global.nc" LDQ ".v4.u32 {%0,%1,%2,%3}, [%4];" : "=r"(v.x), "=r"(v.y), "=r"(v.z), "=r"(v.w) : "l"(p));
    return v;
}
#define P8_LD(i) "ld.relaxed.gpu.global.b64 d" #i ", [src + " #i " * 256];\n"
#define P8_X(i) "mov.b64 {x" #i ", y" #i "}, d" #i ";\n"
#define P8_HEAD(SRC) "{\n.reg .pred p, q;\n.reg .b64 src, d<8>;\n.reg .b32 n, x<8>, y<8>, m0, m1;\nmov.b64 src, " SRC ";\n"         \
                P8_LD(0) P8_LD(1) P8_LD(2) P8_LD(3) P8_LD(4) P8_LD(5) P8_LD(6) P8_LD(7) "mov.u32 n, 0;\nCHECK:\n" \
                P8_X(0) P8_X(1) P8_X(2) P8_X(3) P8_X(4) P8_X(5) P8_X(6) P8_X(7)
#define P8_VOTE "vote.sync.all.pred p, p, -1;\n@p bra.uni DONE;\n"
#define P8_TAIL "add.u32 n, n, 1;\nsetp.lt.u32 p, n, 0x100000;\n@p bra.uni CHECK;\ntrap;\nDONE:\n"
#define S8_LD(i) "ld.relaxed.gpu.global.b64 %" #i ", [%8 + " #i " * 256];\n"
__device__ __forceinline__ void fetch_state(uint64_t (&d)[8], const void* src) {
    asm volatile(S8_LD(0) S8_LD(1) S8_LD(2) S8_LD(3) S8_LD(4) S8_LD(5) S8_LD(6) S8_LD(7)
                 : "=&l"(d[0]), "=&l"(d[1]), "=&l"(d[2]), "=&l"(d[3]), "=&l"(d[4]), "=&l"(d[5]), "=&l"(d[6]), "=&l"(d[7]) : "l"(src) : "memory");
}
__device__ __forceinline__ void settle_state(uint64_t (&d)[8], const void* src) {
#define S8_X(i) "mov.b64 {x" #i ", _}, %" #i ";\n"
#define S8_R(i) "setp.eq.u32 q, x" #i ", 0xffffffff;\n@q " S8_LD(i)
    asm volatile("{\n.reg .pred p, q;\n.reg .b32 n, x<8>, m0, m1;\nmov.u32 n, 0;\nCHECK:\n"
                 S8_X(0) S8_X(1) S8_X(2) S8_X(3) S8_X(4) S8_X(5) S8_X(6) S8_X(7)
                 "max.u32 m0, x0, x1;\nmax.u32 m0, m0, x2;\nmax.u32 m1, x3, x4;\nmax.u32 m1, m1, x5;\nmax.u32 m0, m0, x6;\n"
                 "max.u32 m0, m0, x7;\nmax.u32 m0, m0, m1;\nsetp.ne.u32 p, m0, 0xffffffff;\n" P8_VOTE
                 S8_R(0) S8_R(1) S8_R(2) S8_R(3) S8_R(4) S8_R(5) S8_R(6) S8_R(7) P8_TAIL "}"
                 : "+l"(d[0]), "+l"(d[1]), "+l"(d[2]), "+l"(d[3]), "+l"(d[4]), "+l"(d[5]), "+l"(d[6]), "+l"(d[7]) : "l"(src) : "memory");
}
__device__ __forceinline__ uint64_t poll_sum(const void* src, uint32_t tag, uint32_t sel) {
#define P8_RT(i) "lop3.b32 m0, x" #i ", %2, 1, 0x28;\nsetp.ne.u32 q, m0, 0;\n@q " P8_LD(i)
#define P8_MMA(c, i, z) "mma.sync.aligned.m16n8k8.row.col.f32.bf16.bf16.f32 {" #c "0," #c "1," #c "2," #c "3}, {x" #i ", y" #i "}, {%3}, {" #z "0," #z "1," #z "2," #z "3};\n"
    uint64_t r;
    asm volatile(P8_HEAD("%1") "{\n.reg .f32 a<4>, b<4>, z<4>;\nmov.f32 z0, 0f00000000;\nmov.f32 z1, z0;\nmov.f32 z2, z0;\nmov.f32 z3, z0;\n"
                 P8_MMA(a, 0, z) P8_MMA(b, 1, z) P8_MMA(a, 2, a) P8_MMA(b, 3, b) P8_MMA(a, 4, a) P8_MMA(b, 5, b) P8_MMA(a, 6, a) P8_MMA(b, 7, b)
                 "add.f32 a0, a0, b0;\nadd.f32 a1, a1, b1;\nadd.f32 a2, a2, b2;\nadd.f32 a3, a3, b3;\n"
                 "cvt.rn.bf16x2.f32 m0, a1, a0;\ncvt.rn.bf16x2.f32 m1, a3, a2;\nmov.b64 %0, {m0, m1};\n}\n"
                 "lop3.b32 m0, x0, x1, %2, 0x7e;\nlop3.b32 m1, x2, x3, %2, 0x7e;\nlop3.b32 m0, m0, x4, %2, 0xf6;\n"
                 "lop3.b32 m1, m1, x5, %2, 0xf6;\nlop3.b32 m0, m0, x6, %2, 0xf6;\nlop3.b32 m1, m1, x7, %2, 0xf6;\n"
                 "lop3.b32 m0, m0, m1, 1, 0xa8;\nsetp.eq.u32 p, m0, 0;\n" P8_VOTE
                 P8_RT(0) P8_RT(1) P8_RT(2) P8_RT(3) P8_RT(4) P8_RT(5) P8_RT(6) P8_RT(7) P8_TAIL "}"
                 : "=&l"(r) : "l"(src), "r"(tag), "r"(sel) : "memory");
    return r;
}
__device__ __forceinline__ void wait_count_u(const uint32_t* p, uint32_t need) {
    asm volatile("{\n.reg .pred p;\n.reg .u32 n, v;\nmov.u32 n, 0;\nAGAIN:\nld.acquire.gpu.global.u32 v, [%0];\nsetp.ge.u32 p, v, %1;\n"
                 "vote.sync.all.pred p, p, -1;\n@p bra.uni DONE;\nadd.u32 n, n, 1;\nsetp.lt.u32 p, n, 0x100000;\n@p bra.uni AGAIN;\ntrap;\n"
                 "DONE:\nfence.proxy.async.global;\n}" ::"l"(p), "r"(need) : "memory");
}
__device__ __forceinline__ uint32_t movm(uint32_t x) { asm volatile("movmatrix.sync.aligned.m8n8.trans.b16 %0, %0;" : "+r"(x)); return x; }
template <int NK, typename F>
__device__ __forceinline__ void attend(uint32_t sb, uint32_t lm, uint32_t qs, uint32_t xq, int i8, int lane, bf16* dst, F mid) {
    const int r8 = lane & 7, m4 = lane >> 3;
    const float sl2e = 0.08838834764831845f * 1.4426950408889634f;
    const uint32_t lk = sb + C_KV + ((m4 & 1) * 8 + r8) * 128 + (((m4 >> 1) ^ r8) << 4);
    const uint32_t lkm = sb + xq + (8 + r8) * 272 + (m4 & 1) * 32 + (m4 >> 1) * 16;
    asm volatile("cp.async.wait_all;" ::: "memory");
    __syncwarp();
    float x[4][4];
#pragma unroll
    for (int i = 0; i < 4; i++) x[i][0] = x[i][1] = x[i][2] = x[i][3] = 0.f;
#pragma unroll
    for (int kp = 0; kp < 4; kp++) {
        uint32_t q[4], a[4];
        ldsm4(q, lm + qs + kp * 64);
        ldsm4(a, lkm + kp * 64);
        mma16816(x[2], a[0], a[1], a[2], a[3], q[0], q[1]);
        mma16816(x[3], a[0], a[1], a[2], a[3], q[2], q[3]);
#pragma unroll
        for (int u = 0; u < 4; u++) {
            if ((u & 1) >= NK) continue;
            ldsm4(a, (lk ^ (((kp & 1) * 2 + (u >> 1)) << 5)) + (kp >> 1) * 4096 + (u & 1) * 2048);
            mma16816(x[u & 1], a[0], a[1], a[2], a[3], q[u & 2], q[(u & 2) + 1]);
        }
    }
    x[2][0] += x[3][2]; x[2][1] += x[3][3];
    const int lim = i8 + 2 * (lane & 3) - (lane >> 2);
    uint32_t p[5];
    {
        float m[2], e[5][2];
#pragma unroll
        for (int b = 0; b < 2; b++) {
            e[4][b] = m[b] = x[2][b];
#pragma unroll
            for (int j = 0; j < 2 * NK; j++) {
                e[j][b] = j < 2 * NK - 2 || 8 * j - b <= lim ? x[j >> 1][(j & 1) * 2 + b] : -3.0e38f;
                m[b] = fmaxf(m[b], e[j][b]);
            }
        }
#pragma unroll
        for (int o = 4; o < 32; o <<= 1) {
            m[0] = fmaxf(m[0], __shfl_xor_sync(~0u, m[0], o));
            m[1] = fmaxf(m[1], __shfl_xor_sync(~0u, m[1], o));
        }
        m[0] *= sl2e; m[1] *= sl2e;
#pragma unroll
        for (int j = 0; j < 5; j++)
            if (j < 2 * NK || j == 4) p[j] = movm(pack2(ex2(fmaf(e[j][0], sl2e, -m[0])), ex2(fmaf(e[j][1], sl2e, -m[1]))));
    }
    const uint32_t lvt = sb + C_KV + 8192 + ((m4 >> 1) * 8 + r8) * 128 + (((m4 & 1) ^ r8) << 4), one = 0x3f803f80u;
    float sm[4] = {0.f, 0.f, 0.f, 0.f}, c[8][4];
    mma16816(sm, one, one, one, one, p[0], p[1]);
    if (NK == 2) mma16816(sm, one, one, one, one, p[2], p[3]);
    mma1688(sm, one, one, p[4]);
#pragma unroll
    for (int j = 0; j < 8; j++) c[j][0] = c[j][1] = c[j][2] = c[j][3] = 0.f;
#pragma unroll
    for (int kk = 0; kk < NK; kk++)
#pragma unroll
        for (int j = 0; j < 8; j++) {
            uint32_t a[4];
            ldsm4t(a, (lvt ^ ((j & 3) << 5)) + (j >> 2) * 4096 + kk * 2048);
            mma16816(c[j], a[0], a[1], a[2], a[3], p[2 * kk], p[2 * kk + 1]);
        }
    float i0, i1;
    asm("rcp.approx.ftz.f32 %0, %1;" : "=f"(i0) : "f"(sm[0]));
    asm("rcp.approx.ftz.f32 %0, %1;" : "=f"(i1) : "f"(sm[1]));
    uint32_t o[4][4];
#pragma unroll
    for (int j = 0; j < 4; j++) {
        uint32_t a[4];
        ldsm4t(a, lm + xq + 16 * 272 + j * 64);
        mma1688(c[2 * j], a[0], a[1], p[4]);
        mma1688(c[2 * j + 1], a[2], a[3], p[4]);
#pragma unroll
        for (int u = 0; u < 4; u++) o[j][u] = pack2(c[2 * j + (u >> 1)][(u & 1) * 2] * i0, c[2 * j + (u >> 1)][(u & 1) * 2 + 1] * i1);
    }
#pragma unroll
    for (int j = 0; j < 4; j++) stsm4t(lm + qs + j * 64, o[j][0], o[j][1], o[j][2], o[j][3]);
    mid();
    __syncwarp();
#pragma unroll
    for (int j = 0; j < 4; j++) lds128(o[j], sb + qs + ((lane >> 4) + 2 * j) * 272 + (lane & 15) * 16);
#pragma unroll
    for (int j = 0; j < 4; j++)
        asm volatile("st.global.v4.u32 [%0], {%1,%2,%3,%4};" ::"l"(dst + (size_t)2 * j * HD), "r"(o[j][0]), "r"(o[j][1]), "r"(o[j][2]), "r"(o[j][3]) : "memory");
}
__device__ __forceinline__ void sum8(float (&c)[4], const uint2 (&v)[8], uint32_t idn) {
    float d[4] = {0.f, 0.f, 0.f, 0.f};
    c[0] = c[1] = c[2] = c[3] = 0.f;
    mma16816(c, v[0].x, v[0].y, v[1].x, v[1].y, idn, idn);
    mma16816(d, v[2].x, v[2].y, v[3].x, v[3].y, idn, idn);
    mma16816(c, v[4].x, v[4].y, v[5].x, v[5].y, idn, idn);
    mma16816(d, v[6].x, v[6].y, v[7].x, v[7].y, idn, idn);
    c[0] += d[0]; c[1] += d[1]; c[2] += d[2]; c[3] += d[3];
}

#define CLS 6
__global__ void __cluster_dims__(CLS, 1, 1) __launch_bounds__(256, 1)
k_chain(const bf16* __restrict__ mem0, const bf16* __restrict__ Wq, const bf16* __restrict__ Wk, const bf16* __restrict__ Wv,
        const bf16* __restrict__ Wo, const __grid_constant__ CUtensorMap mkv) {
    extern __shared__ __align__(1024) uint8_t smem_chain[];
    const uint32_t sb = smem_u32(smem_chain);
    if (sb & 1023) __trap();
    const int w = __shfl_sync(~0u, threadIdx.x >> 5, 0), lane = __shfl_sync(~0u, threadIdx.x & 31, threadIdx.x & 31);
    const int tid = w * 32 + lane, g = lane >> 2, t = lane & 3;
    auto pin = [&](uint32_t x) { return delayed<1>(x, lane); };
    const int h = blockIdx.x / 3, r = blockIdx.x - 3 * h;
    const uint32_t bar_x = sb + C_BAR, bar_kv = sb + C_BAR + 8, bar_go = sb + C_BAR + 16, bar_w = sb + C_BAR + 24;
    asm volatile("griddepcontrol.launch_dependents;");
    const int tbase = r == 0 ? 0 : 1 + 21 * r, ntile = r == 0 ? 22 : 21;
    uint32_t side;
    if (tid == 0) {
        mbar_init(bar_x, 8); mbar_init(bar_kv, 1); mbar_init(bar_go, 1); mbar_init(bar_w, 1);
        asm volatile("fence.mbarrier_init.release.cluster;" ::: "memory");
        asm volatile("fence.proxy.async.shared::cta;" ::: "memory");
        mbar_expect_tx(bar_w, 128 * 32 * ntile);
    }
    __syncthreads();
    asm volatile("barrier.cluster.arrive.relaxed.aligned;" ::: "memory");
    if (tid < 128)
        asm volatile("cp.async.bulk.shared::cluster.global.mbarrier::complete_tx::bytes [%0], [%1], %2, [%3];"
                     ::"r"(sb + C_W1 + tid * 720), "l"(Wo + (size_t)(h * 128 + tid) * DM + tbase * 16), "r"(32 * ntile), "r"(bar_w) : "memory");
    const int tile0 = tbase + 7 - w;
    const bool three = w >= (r == 0 ? 2 : 3);
    const uint32_t wa = pin(sb + tid * 16);
#define W1A(i) (wa + C_W1 + (i) * 4096)
#define W2A(x) (wa + C_W2 + ((x) < 8 ? (x) * 4096 : 32768 - 1024 + ((x) - 8) * 3072))
    uint32_t wo0[8][4], wr[64][4];
    {
        const bf16* W = (r == 0 ? Wq : r == 1 ? Wk : Wv) + (size_t)(128 * w + (lane >> 4)) * HD + h * 128 + 8 * (lane & 15);
        uint4 raw[8][8];
        auto fetch = [&](int ks) {
#pragma unroll
            for (int i = 0; i < 8; i++) raw[ks][i] = ldw128(W + (size_t)(16 * ks + 2 * i) * HD);
        };
        fetch(0); fetch(1); fetch(2); fetch(3);
    asm("mov.u32 %0, %%smid;" : "=r"(side));
    side = __ldcg(g_side + (side & 255)) & 1;
    if (tid == 0 && r > 0) asm volatile("st.relaxed.gpu.global.u32 [%0], %1;" ::"l"(g_flag + 128 + 2 * h + r - 1), "r"(2 | side) : "memory");
        if (w == 0) TG(0);
        mbar_wait_u(bar_w, 0);
        if (w == 0) TG(1);
        const uint32_t p = sb + C_W1 + ((lane & 7) + (lane >> 4) * 8) * 720 + (7 - w) * 32 + ((lane >> 3) & 1) * 16;
#pragma unroll
        for (int ks = 0; ks < 8; ks++) {
            uint32_t a[4];
            ldsm4t(wo0[ks], p + ks * 16 * 720);
            ldsm4t(a, p + ks * 16 * 720 + 256);
            sts128(W2A(ks), a[0], a[1], a[2], a[3]);
            if (three) { ldsm4t(a, p + ks * 16 * 720 + 512); sts128(W2A(8 + ks), a[0], a[1], a[2], a[3]); }
        }
        __syncthreads();
        if (w < PFI)
            asm volatile("prefetch.global.L2 [%0];\nprefetch.global.L2 [%0 + 128];" ::"l"(g_kv + (size_t)tid * PW + r * HD + h * 128) : "memory");
        if (w == 0) TG(2);
        const uint32_t stg = sb + C_KV + w * 4096;
        const uint32_t rd = stg + ((lane & 7) + 8 * (lane >> 4)) * 256 + ((((lane >> 3) & 1) ^ (lane & 7)) << 4);
#pragma unroll
        for (int ks = 0; ks < 8; ks++) {
#pragma unroll
            for (int i = 0; i < 8; i++)
                sts128(stg + (2 * i + (lane >> 4)) * 256 + (((lane & 15) ^ (((2 * i) & 6) | (lane >> 4))) << 4),
                       raw[ks][i].x, raw[ks][i].y, raw[ks][i].z, raw[ks][i].w);
            if (ks < 2) fetch(ks + 4);
            if (ks == 3 || ks == 5) fetch(ks / 2 + 5);
            __syncwarp();
#pragma unroll
            for (int j = 0; j < 8; j++) {
                if (smem_idx(ks, j) >= 0) {
                    uint32_t a[4];
                    ldsm4t(a, rd ^ (j << 5));
                    sts128(W1A(smem_idx(ks, j)), a[0], a[1], a[2], a[3]);
                } else ldsm4t(wr[8 * ks + j], rd ^ (j << 5));
            }
            __syncwarp();
        }
    }
    if (w == 0) TG(3);
    wait_count_u(g_flag + (lane & 8), lane & 8 ? 37 : 48);
    asm volatile("fence.proxy.async.shared::cta;" ::: "memory");
    __syncthreads();
    if (tid == 0) {
        mbar_expect_tx(bar_kv, 16384);
        tma3d(sb + C_KV, &mkv, 0, 0, 2 * h, bar_kv);
        tma3d(sb + C_KV + 8192, &mkv, 0, 0, 64 + 2 * h, bar_kv);
    }
    asm volatile("barrier.cluster.wait.aligned;" ::: "memory");

    auto load_kv = [&](int s) {
        asm volatile("{\n.reg .pred p;\nelect.sync _|p, -1;\n@p mbarrier.arrive.expect_tx.shared::cta.b64 _, [%2], 16384;\n"
                     "@p cp.async.bulk.tensor.3d.shared::cluster.global.mbarrier::complete_tx::bytes [%0], [%1, {%3, %4, %5}], [%2];\n"
                     "@p cp.async.bulk.tensor.3d.shared::cluster.global.mbarrier::complete_tx::bytes [%6], [%1, {%3, %4, %7}], [%2];\n}"
                     ::"r"(sb + C_KV), "l"(&mkv), "r"(bar_kv), "r"(0), "r"(s * 32), "r"(2 * h), "r"(sb + C_KV + 8192), "r"(64 + 2 * h) : "memory");
    };
    const bool attends = w == 7 || (w == 6 && r == 0);
    const int i8 = r == 0 ? (w - 4) * 8 : (r - 1) * 8;
    auto load_q = [&](int s) {
        const int l = fresh(lane);
        const bf16* p = g_kv + (size_t)(s * 32 + i8 + (l >> 4)) * PW + 2 * HD + h * 128 + (l & 15) * 8;
#pragma unroll
        for (int j = 0; j < 4; j++)
            asm volatile("cp.async.cg.shared.global [%0], [%1], 16;"
                         ::"r"(sb + C_RED + w * 2176 + ((l >> 4) + 2 * j) * 272 + (l & 15) * 16), "l"(p + (size_t)2 * j * PW) : "memory");
    };
    auto report = [&](int blk) {
        asm volatile("{\n.reg .pred p;\nelect.sync _|p, -1;\nfence.acq_rel.gpu;\n@p red.relaxed.gpu.global.add.u32 [%0], 1;\n}"
                     ::"l"(g_flag + 64 + blk) : "memory");
    };
    const float sl2e = 0.08838834764831845f * 1.4426950408889634f;
    const uint32_t idn = pin(g == 2 * t ? 0x00003f80u : g == 2 * t + 1 ? 0x3f800000u : 0u);
    const uint32_t lm = pin(sb + (lane & 7) * 272 + (lane >> 3) * 16);
    const uint32_t sa = pin(sb + C_SC + (w & 1) * (8 * 52 * 4) + (2 * t * 52 + (w < 4 ? 32 : (w & 2) * 8) + g) * 4);
    const uint32_t sr = pin(sb + C_SC + (g * 52 + 8 * t) * 4), sr2 = pin(sb + C_SC + (g * 52 + 32 + 2 * t) * 4);
    uint32_t kva;
    {
        const int pos = (w & 2) * 8 + (lane & 15), row = (pos & 24) + ((pos + (pos >> 2 & 6)) & 7);
        const int key = 4 * (lane & 6) + (((lane & 7) + 2 * (lane >> 4)) & 7);
        kva = pin(w >= 4 ? sb + C_KV + (w & 1) * 4096 + row * 128 + (((lane >> 4) ^ (row & 7)) << 4)
                         : sb + C_KV + 8192 + (w >> 1) * 4096 + key * 128 + ((((w & 1) * 4 + ((lane >> 3) & 1)) ^ (key & 7)) << 4));
    }
#define ATTEND(NK, s, mid) do {                                                                                       \
        const int l_ = fresh(lane);                                                                                      \
        attend<NK>(sb, lm, C_RED + w * 2176, C_QKV + ((s) & 1) * QKV_SZ, i8, l_,                                         \
                   g_o + (size_t)((s) * 32 + i8 + (l_ >> 4)) * HD + h * 128 + (l_ & 15) * 8, mid);                       \
    } while (0)
    auto chores = [&](int s) {
        if ((s & 3) == 0 && s) report((s >> 2) - 1);
        if ((s & 7) == 6 && s < NSEG - 2) wait_count_u(g_flag + (s >> 3) + 1, (s >> 3) + 1 < 2 * NTA ? 48 : 96);
    };
    uint32_t buf0[8][4], ring[RB1][4];
#define STAGE_W1() do {                                                            \
        _Pragma("unroll") for (int i = 0; i < 8; i++) lds128v(buf0[i], W1A(i));       \
        _Pragma("unroll") for (int i = 0; i < RB1; i++) lds128v(ring[i], W1A(8 + i)); \
    } while (0)
    auto stage_w1 = [&]() { STAGE_W1(); };
    stage_w1();
    uint32_t psel, msel0, msel1;
    {
        const int j = r > 0 ? 2 * h + r - 1 : 0, tl = min(tile0 + 8 * (lane >> 1), 63);
        uint32_t b;
        asm volatile("{\n.reg .pred p;\n.reg .u32 n;\nmov.u32 n, 0;\nAGAIN:\nld.relaxed.gpu.global.u32 %0, [%1];\nsetp.ne.u32 p, %0, 0;\n"
                     "vote.sync.all.pred p, p, -1;\n@p bra.uni DONE;\nadd.u32 n, n, 1;\nsetp.lt.u32 p, n, 0x100000;\n@p bra.uni AGAIN;\ntrap;\nDONE:\n}"
                     : "=&r"(b) : "l"(g_flag + 128 + tl) : "memory");
        psel = __ballot_sync(~0u, (g_home[lane == 6 ? j * 2 + ((w >> 1) & 1) : tl * 2 + (lane & 1)] ^ (lane == 6 ? side : b)) & 1);
        msel0 = __ballot_sync(~0u, (g_home[128 + lane * 4 + (w >> 1)] ^ side) & 1);
        msel1 = __ballot_sync(~0u, (g_home[256 + lane * 4 + (w >> 1)] ^ side) & 1);
        if (r > 0) {
            if (w < 4) asm volatile("prefetch.global.L2 [%0];" ::"l"(g_x + (128 + (1 + (w >> 1)) * 4 + (j >> 4)) * 1024 + (w & 1) * 512 + (j & 15) * 32 + lane) : "memory");
            if (w < 4) asm volatile("prefetch.global.L2 [%0];" ::"l"(g_x + j * 2048 + tid * 16) : "memory");
        }
    }
    uint2 bm[8];
#pragma unroll
    for (int ks = 0; ks < 8; ks++) {
        const uint32_t* p = (const uint32_t*)(mem0 + g * DM + (8 * w + ks) * 16) + t;
        bm[ks] = make_uint2(__ldg(p), __ldg(p + 4));
    }
    if (w == 0) TG(5);
#pragma unroll 1
    for (int s = 0;; s++) {
        TS(1);
        const uint32_t xq = C_QKV + (s & 1) * QKV_SZ;
        {
            float acc[8][4];
#pragma unroll
            for (int ks = 0; ks < 8; ks++) {
#pragma unroll
                for (int j = 0; j < 8; j++) {
                    const int i = smem_idx(ks, j) - 8;
                    if (ks == 0) {
                        acc[j][0] = acc[j][1] = acc[j][2] = acc[j][3] = 0.f;
                        mma16816(acc[j], buf0[j][0], buf0[j][1], buf0[j][2], buf0[j][3], bm[ks].x, bm[ks].y);
                    } else if (i >= 0) {
                        uint32_t(&a)[4] = ring[i % RB1];
                        mma16816(acc[j], a[0], a[1], a[2], a[3], bm[ks].x, bm[ks].y);
                        if (8 + i + RB1 < NS1) lds128v(a, W1A(8 + i + RB1));
                    } else {
                        const uint32_t(&a)[4] = wr[8 * ks + j];
                        mma16816(acc[j], a[0], a[1], a[2], a[3], bm[ks].x, bm[ks].y);
                    }
                }
            }
#pragma unroll
            for (int c = 0; c < 4; c++)
                stsm4t(lm + C_RED + w * 2176 + c * 64, pack2(acc[2 * c][0], acc[2 * c][1]), pack2(acc[2 * c][2], acc[2 * c][3]),
                       pack2(acc[2 * c + 1][0], acc[2 * c + 1][1]), pack2(acc[2 * c + 1][2], acc[2 * c + 1][3]));
        }
        {
            const uint32_t a = sb + C_RED + w * 272 + lane * 8;
            if (w == 3) mbar_wait_u(bar_kv, s & 1);
            TS(2);
            __syncthreads();
            TS(3);
            uint2 v[8];
#pragma unroll
            for (int i = 0; i < 8; i++) v[i] = lds64(a + i * 2176);
            float c[4];
            sum8(c, v, idn);
            const uint32_t p0 = pack2(c[0], c[1]), p1 = pack2(c[2], c[3]);
            const uint32_t dst = sb + xq + (r * 8 + w) * 272 + lane * 8;
#pragma unroll
            for (int i = 1; i < 3; i++) {
                const uint32_t peer = (h % (CLS / 3)) * 3 + (r + i >= 3 ? r + i - 3 : r + i);
                uint32_t rd, rb;
                asm("mapa.shared::cluster.u32 %0, %1, %2;" : "=r"(rd) : "r"(dst), "r"(peer));
                asm("mapa.shared::cluster.u32 %0, %1, %2;" : "=r"(rb) : "r"(bar_x), "r"(peer));
                asm volatile("st.async.weak.shared::cluster.mbarrier::complete_tx::bytes.v2.b32 [%0], {%1,%2}, [%3];"
                             ::"r"(rd), "r"(p0), "r"(p1), "r"(rb) : "memory");
            }
            sts64(dst, p0, p1);
            __syncwarp();
            asm volatile("{\n.reg .pred p;\nsetp.eq.u32 p, %1, 0;\n@p mbarrier.arrive.expect_tx.shared::cta.b64 _, [%0], 512;\n}"
                         ::"r"(bar_x), "r"(lane) : "memory");
        }
        TS(4);
        if (s == NSEG - 1) break;
        uint32_t wb[8][4], wc[8][4];
        const uint32_t po = (tile0 * 2 + (lane >> 4)) * 8192 + ((lane >> 3) & 1) * 2048 + h * 64 + (lane & 7) * 8;
        const uint32_t tag = s & 1;
        auto project = [&](const uint32_t(&wt)[8][4], const uint32_t(&ob)[4][4], int i) {
            float c0[4] = {0.f, 0.f, 0.f, 0.f}, c1[4] = {0.f, 0.f, 0.f, 0.f};
#pragma unroll
            for (int ks = 0; ks < 8; ks++)
                mma16816((ks & 1) ? c1 : c0, wt[ks][0], wt[ks][1], wt[ks][2], wt[ks][3], ob[ks >> 1][(ks & 1) * 2], ob[ks >> 1][(ks & 1) * 2 + 1]);
            uint32_t p0 = pack2(c0[0] + c1[0], c0[1] + c1[1]), p1 = pack2(c0[2] + c1[2], c0[3] + c1[3]);
            asm volatile("movmatrix.sync.aligned.m8n8.trans.b16 %0, %0;\nmovmatrix.sync.aligned.m8n8.trans.b16 %1, %1;" : "+r"(p0), "+r"(p1));
            st_rlx64((uint2*)((char*)g_x + po + i * 131072 + ((psel >> (2 * i + (lane >> 4))) & 1) * 4096), (p0 & ~1u) | tag, p1);
        };
        if (w >= 4) {
            uint32_t ka[4][4];
#pragma unroll
            for (int ks = 0; ks < 4; ks++) ldsm4(ka[ks], kva ^ (ks << 5));
            const uint32_t qa = lm + xq + (w & 1) * 128;
            TS(5);
            mbar_wait_u(bar_x, s & 1);
            TS(6);
            {
                uint32_t qb[2][4];
                ldsm4(qb[0], qa);
                ldsm4(qb[1], qa + 64);
                float c0[4] = {0.f, 0.f, 0.f, 0.f}, c1[4] = {0.f, 0.f, 0.f, 0.f};
                mma16816(c0, ka[0][0], ka[0][1], ka[0][2], ka[0][3], qb[0][0], qb[0][1]);
                mma16816(c1, ka[1][0], ka[1][1], ka[1][2], ka[1][3], qb[0][2], qb[0][3]);
                mma16816(c0, ka[2][0], ka[2][1], ka[2][2], ka[2][3], qb[1][0], qb[1][1]);
                mma16816(c1, ka[3][0], ka[3][1], ka[3][2], ka[3][3], qb[1][2], qb[1][3]);
                sts32f(sa, c0[0] + c1[0]);
                sts32f(sa + 208, c0[1] + c1[1]);
                sts32f(sa + 32, c0[2] + c1[2]);
                sts32f(sa + 240, c0[3] + c1[3]);
            }
            __syncthreads();
            TS(7);
            uint32_t wd = wa;
            if (attends) { load_q(s); wd = delayed<DLYQ>(wd, lane); } else wd = delayed<DLYW>(wd, lane);
#pragma unroll
            for (int i = 0; i < 8; i++) lds128(wb[i], wd + C_W2 + i * 4096);
#pragma unroll
            for (int i = 0; i < PFC; i++) lds128(wc[i], wd + C_W2 + 32768 - 1024 + i * 3072);
            TS(8);
            __syncthreads();
            TS(9);
            uint32_t ob[4][4];
#pragma unroll
            for (int i = 0; i < 4; i++) ldsm4(ob[i], lm + C_OB + i * 64);
#pragma unroll
            for (int i = PFC; i < 8; i++) lds128(wc[i], W2A(8 + i));
            project(wb, ob, 1);
            project(wo0, ob, 0);
            project(wc, ob, 2);
        } else {
            uint32_t va[4][4];
#pragma unroll
            for (int i = 0; i < 4; i++) ldsm4t(va[i], kva ^ (((i >> 1) << 5) | ((i & 1) * 0x240)));
#pragma unroll
            for (int i = 0; i < 8; i++) lds128(wb[i], W2A(i));
            const uint32_t qa = lm + xq + (w & 1) * 128, oa = lm + w * 64;
            TS(5);
            mbar_wait_u(bar_x, s & 1);
            TS(6);
            if (w < 2) {
                uint32_t qb[2][4], km[2][4];
                ldsm4(qb[0], qa);
                ldsm4(km[0], qa + 8 * 272);
                ldsm4(qb[1], qa + 64);
                ldsm4(km[1], qa + 8 * 272 + 64);
                float c0[4] = {0.f, 0.f, 0.f, 0.f}, c1[4] = {0.f, 0.f, 0.f, 0.f};
                mma16816(c0, km[0][0], km[0][1], km[0][2], km[0][3], qb[0][0], qb[0][2]);
                mma16816(c1, km[0][0], km[0][1], km[0][2], km[0][3], qb[0][1], qb[0][3]);
                mma16816(c0, km[1][0], km[1][1], km[1][2], km[1][3], qb[1][0], qb[1][2]);
                mma16816(c1, km[1][0], km[1][1], km[1][2], km[1][3], qb[1][1], qb[1][3]);
                sts32f(sa, c0[0] + c1[2]);
                sts32f(sa + 208, c0[1] + c1[3]);
            }
            __syncthreads();
            TS(7);
            {
                float4 x0 = lds128f(sr), y0 = lds128f(sr + 1664), x1 = lds128f(sr + 16), y1 = lds128f(sr + 1680);
                float2 x2 = lds64f(sr2), y2 = lds64f(sr2 + 1664);
                float p[10] = {x0.x + y0.x, x0.y + y0.y, x0.z + y0.z, x0.w + y0.w, x1.x + y1.x,
                               x1.y + y1.y, x1.z + y1.z, x1.w + y1.w, x2.x + y2.x, x2.y + y2.y};
                float m = fmaxf(fmaxf(fmaxf(p[0], p[1]), fmaxf(p[2], p[3])), fmaxf(fmaxf(fmaxf(p[4], p[5]), fmaxf(p[6], p[7])), fmaxf(p[8], p[9])));
                const float m1 = __shfl_xor_sync(~0u, m, 1), m2 = __shfl_xor_sync(~0u, m, 2), m3 = __shfl_xor_sync(~0u, m, 3);
                uint32_t vm[4];
                ldsm4t(vm, oa + xq + 16 * 272);
                m = fmaxf(fmaxf(m, m1), fmaxf(m2, m3));
                const float ms = m * sl2e;
#pragma unroll
                for (int i = 0; i < 10; i++) p[i] = ex2(fmaf(p[i], sl2e, -ms));
                const uint32_t b0 = pack2(p[0], p[1]), b1 = pack2(p[2], p[3]), b2 = pack2(p[4], p[5]), b3 = pack2(p[6], p[7]), b4 = pack2(p[8], p[9]);
                const uint32_t one = 0x3f803f80u;
                float o0[4] = {0.f, 0.f, 0.f, 0.f}, o1[4] = {0.f, 0.f, 0.f, 0.f}, sm[4] = {0.f, 0.f, 0.f, 0.f};
                mma16816(sm, one, one, one, one, b0, b1);
                mma16816(o0, va[0][0], va[0][1], va[0][2], va[0][3], b0, b1);
                mma16816(o1, va[2][0], va[2][1], va[2][2], va[2][3], b0, b1);
                mma16816(sm, one, one, one, one, b2, b3);
                mma16816(o0, va[1][0], va[1][1], va[1][2], va[1][3], b2, b3);
                mma16816(o1, va[3][0], va[3][1], va[3][2], va[3][3], b2, b3);
                mma1688(sm, one, one, b4);
                mma1688(o0, vm[0], vm[1], b4);
                mma1688(o1, vm[2], vm[3], b4);
                float i0, i1;
                asm("rcp.approx.ftz.f32 %0, %1;" : "=f"(i0) : "f"(sm[0]));
                asm("rcp.approx.ftz.f32 %0, %1;" : "=f"(i1) : "f"(sm[1]));
                stsm4t(oa + C_OB, pack2(o0[0] * i0, o0[1] * i1), pack2(o0[2] * i0, o0[3] * i1),
                       pack2(o1[0] * i0, o1[1] * i1), pack2(o1[2] * i0, o1[3] * i1));
            }
            TS(8);
            __syncthreads();
            TS(9);
            uint32_t ob[4][4];
#pragma unroll
            for (int i = 0; i < 4; i++) ldsm4(ob[i], lm + C_OB + i * 64);
            if (three) {
#pragma unroll
                for (int i = 0; i < 8; i++) lds128(wc[i], W2A(8 + i));
                project(wb, ob, 1);
                project(wo0, ob, 0);
                project(wc, ob, 2);
            } else {
                project(wb, ob, 1);
                project(wo0, ob, 0);
            }
        }
        TS(10);
        __syncthreads();
        uint32_t eo = (128 + (s + 1) * 4 + (w >> 1)) * 8192 + (((s < 31 ? msel0 : msel1) >> ((s + 1) & 31)) & 1) * 4096 + (w & 1) * 2048 + lane * 8;
        uint64_t d[8];
        if (r == 0) {
            if (w >= 6) {
                auto mid = [&]() {
                    bar_sync(2, 64);
                    TS(11);
                    mbar_wait_u(bar_go, s & 1);
                    eo = delayed<DLY0A>(eo, lane);
                    TS(12);
                    fetch_state(d, (const char*)g_x + eo);
                };
                ATTEND(2, s, mid);
                stage_w1();
            } else {
                TS(11); TS(12);
                if (w < 3 && s + PFD < NSEG) {
                    const bf16* p = g_kv + (size_t)((s + PFD) * 32 + fresh(lane)) * PW + w * HD + h * 128;
                    asm volatile("prefetch.global.L2 [%0];\nprefetch.global.L2 [%0 + 128];" ::"l"(p) : "memory");
                }
                const uint32_t wa_ = wa;
                { const uint32_t wa = delayed<DLYS>(wa_, lane); STAGE_W1(); }
                if (w == 5) {
                    chores(s);
                    if (h == 0) asm volatile("st.relaxed.gpu.global.u32 [%0], %1;" ::"l"(g_flag + 98), "r"(s + 1) : "memory");
                }
                mbar_wait_u(bar_go, s & 1);
                eo = delayed<DLY0>(eo, lane);
                fetch_state(d, (const char*)g_x + eo);
            }
        } else {
            const int j = 2 * h + r - 1;
            if (w < 4) {
                const int l = fresh(lane), g = l >> 2, t = l & 3;
                const char* src = (const char*)g_x + delayed<DLY3>((j * 2 + (w >> 1)) * 8192 + (psel & 64) * 64 + (w & 1) * 2048 + t * 64 + g * 8, lane);
                const char* dst = (const char*)g_x + pin((128 + (s + 1) * 4 + (j >> 4)) * 8192 + (j & 15) * 256 + w * 64 + (t & 1) * 4096 + g * 8);
                const uint64_t v = poll_sum(src, tag, (lane & 4) ? 0x3f800000u : 0x00003f80u);
                TS(11);
                asm volatile("st.relaxed.gpu.global.b64 [%0], %1;" ::"l"(dst), "l"(v) : "memory");
                asm volatile("bar.arrive 1, 256;" ::: "memory");
                TS(12);
                stage_w1();
                eo = delayed<DLY1>(eo, lane);
                fetch_state(d, (const char*)g_x + eo);
            } else if (w == 7) {
                auto mid = [&]() {
                    TS(11);
                    bar_sync(1, 256);
                    TS(12);
                    eo = delayed<DLY1B>(eo, lane);
                    fetch_state(d, (const char*)g_x + eo);
                };
                ATTEND(1, s, mid);
                stage_w1();
            } else {
                if (w >= 5 && s + 3 < NSEG)
                    asm volatile("prefetch.global.L2 [%0];" ::"l"(g_x + (128 + (s + 3) * 4 + (j >> 4)) * 1024 + (w & 1) * 512 + (j & 15) * 32 + lane) : "memory");
                stage_w1();
                if (w == 5) chores(s);
                TS(11);
                bar_sync(1, 256);
                TS(12);
                if (w == 4 && r == 1)
                    asm volatile("{\n.reg .pred p;\n.reg .u32 a;\nelect.sync _|p, -1;\nmapa.shared::cluster.u32 a, %0, %1;\n"
                                 "@p mbarrier.arrive.relaxed.cluster.shared::cluster.b64 _, [a];\n}" ::"r"(bar_go), "r"((h % (CLS / 3)) * 3) : "memory");
                eo = delayed<DLY1A>(eo, lane);
                fetch_state(d, (const char*)g_x + eo);
            }
        }
        { const int s_ = s; { const int s = s_ + 1; TS(0); } }
        if (w == 7) load_kv(s + 1);
        settle_state(d, (const char*)g_x + eo);
#pragma unroll
        for (int i = 0; i < 8; i++) { bm[i].x = (uint32_t)d[i]; bm[i].y = (uint32_t)(d[i] >> 32); }
    }
    mbar_wait_u(bar_x, (NSEG - 1) & 1);
    if (attends) {
        auto nothing = []() {};
        load_q(NSEG - 1);
        if (r == 0) ATTEND(2, NSEG - 1, nothing); else ATTEND(1, NSEG - 1, nothing);
    }
    __syncthreads();
    if (w == 5) report(15);
    asm volatile("barrier.cluster.arrive.relaxed.aligned;\nbarrier.cluster.wait.aligned;" ::: "memory");
}

constexpr int S4_US = 4368;
constexpr int S4_RS = 8848;
constexpr int S4_KS = 1296;
constexpr int S4_U = 0, S4_R = 16 * S4_US, S4_K = S4_R + 16 * S4_RS;
constexpr int S4_SMEM = S4_K + 16 * S4_KS;
constexpr int S4_SIG = 3104, S4_PK = 2 * S4_SIG;

struct cf { float r, i; };
__device__ __forceinline__ cf cmul(cf a, cf b) { return {fmaf(a.r, b.r, -a.i * b.i), fmaf(a.r, b.i, a.i * b.r)}; }
__device__ __forceinline__ cf cmulc(cf a, cf b) { return {fmaf(a.r, b.r, a.i * b.i), fmaf(a.i, b.r, -a.r * b.i)}; }
__device__ __forceinline__ cf csq(cf a) { const float t = a.r * a.i; return {fmaf(a.r, a.r, -a.i * a.i), t + t}; }
__device__ __forceinline__ cf cexp(float l2, float turns) {
    const float mag = ex2(l2), fr = (turns - rintf(turns)) * 6.283185307179586f;
    return {mag * __cosf(fr), mag * __sinf(fr)};
}
__device__ __forceinline__ void sts32(uint32_t a, uint32_t v) { asm volatile("st.shared.u32 [%0], %1;" ::"r"(a), "r"(v) : "memory"); }
__device__ __forceinline__ uint32_t lds16(uint32_t a) {
    uint32_t v;
    asm volatile("ld.shared.u16 %0, [%1];" : "=r"(v) : "r"(a) : "memory");
    return v;
}

template <int M0, int NQ>
__device__ __forceinline__ void s4_class(float (&acc)[16][4], uint32_t sig, uint32_t taps, int x0) {
    constexpr int D0 = M0 / 8, D1 = M0 == 32 ? 9 : 15;
    uint32_t R[D1 - D0 + 2];
#pragma unroll
    for (int D = D0 - 1; D <= D1; D++) {
        if (D < D0 || 8 * D - 7 >= 2 * M0) { R[D - D0 + 1] = 0; continue; }
        const int m = 8 * D + x0;
        uint32_t lo = lds16(taps + m * (2 * NQ)), hi = lds16(taps + (m - 1) * (2 * NQ));
        if (D == D0) { lo = m >= M0 ? lo : 0; hi = m > M0 ? hi : 0; }
        if (D == 2 * D0) { lo = m < 2 * M0 ? lo : 0; hi = m <= 2 * M0 ? hi : 0; }
        R[D - D0 + 1] = lo | (hi << 16);
    }
#pragma unroll
    for (int J = 0; 2 * J + D0 < 16; J++) {
        uint32_t a[4];
        ldsm4t(a, sig + J * 512);
#pragma unroll
        for (int D = D0; D <= D1; D++)
            if (2 * J + D < 16) mma16816(acc[2 * J + D], a[0], a[1], a[2], a[3], R[D - D0 + 1], R[D - D0]);
    }
}

__global__ void __launch_bounds__(512, 1)
k_s4(const bf16* __restrict__ u, const bf16* __restrict__ Are, const bf16* __restrict__ Aim, const bf16* __restrict__ Bre,
     const bf16* __restrict__ Bim, const bf16* __restrict__ Cre, const bf16* __restrict__ Cim, const bf16* __restrict__ logdt,
     const bf16* __restrict__ Dsk, bf16* __restrict__ out) {
    extern __shared__ __align__(16) uint8_t smem_s4[];
    const uint32_t sb = smem_u32(smem_s4);
    asm volatile("griddepcontrol.launch_dependents;");
    const int tid = threadIdx.x, w = __shfl_sync(~0u, tid >> 5, 0), lane = tid & 31, g = lane >> 2, t = lane & 3;
#pragma unroll 1
    for (int item = blockIdx.x; item < 64; item += gridDim.x) {
#define TLS(slot)
    if (tid == 0) TLS(0);
    const int d0 = item * 16;
    const int d = d0 + (w & 1) + ((w >> 1) & 3) * 4 + (w >> 3) * 2;
    const uint32_t tr_off = (lane & 15), tr_l = (lane >> 4) * 16;
    const uint32_t ur = sb + S4_U + w * S4_US, rs = sb + S4_R + w * S4_RS, kd = sb + S4_K + w * S4_KS;
    if (lane < 16) sts128(ur + lane * 16, 0, 0, 0, 0);
    {
        const int o = d * 128 + lane * 4;
        const uint2 ar = __ldg((const uint2*)(Are + o)), ai = __ldg((const uint2*)(Aim + o)), br = __ldg((const uint2*)(Bre + o));
        const uint2 bi = __ldg((const uint2*)(Bim + o)), cr = __ldg((const uint2*)(Cre + o)), ci = __ldg((const uint2*)(Cim + o));
        const float dt = bf_round(expf(__bfloat162float(logdt[d])));
        const bf16* src = u + (size_t)(w * 128 + g) * DM + d0 + 4 * t;
        float T[5][4];
#pragma unroll
        for (int i = 0; i < 5; i++) T[i][0] = T[i][1] = T[i][2] = T[i][3] = 0.f;
        float klast = 0.f;
        const uint32_t wr_ = rs + lane * 272, rd_ = rs + t * 544 + g * 16;
#pragma unroll 1
        for (int c = 0; c < 4; c++) {
            uint2 v[4];
#pragma unroll
            for (int i = 0; i < 4; i++) v[i] = __ldg((const uint2*)(src + (size_t)(c * 32 + i * 8) * DM));
            auto pick = [&](const uint2& x) { const uint32_t y = c < 2 ? x.x : x.y; return (c & 1) ? bf_hi(y) : bf_lo(y); };
            auto pk2 = [](cf x) { return pack2(x.r, x.i); };
            const float l2 = dt * pick(ar) * 1.4426950408889634f, tu = dt * pick(ai) * 0.15915494309189535f;
            const cf z1 = cexp(l2, tu), z2 = csq(z1), z4 = csq(z2), z8 = csq(z4);
            const cf z64 = cexp(l2 * 64.f, tu * 64.f), z128 = csq(z64), z256 = csq(z128), z512 = csq(z256);
            cf a0 = {1.f, 0.f}, a1 = z64;
            cf b0 = cmul({pick(cr), pick(ci)}, {dt * pick(br), dt * pick(bi)});
            b0.i = -b0.i;
            cf b1 = cmulc(b0, z128), b2 = cmulc(b0, z256), y3 = cmulc(b0, z512), b4 = cmulc(y3, z512), b3 = y3;
            const cf y2 = cmulc(b2, z128);
#pragma unroll
            for (int i = 0; i < 8; i++) {
                sts128(wr_ + i * 16, pk2(a0), pk2(a1), pk2(b0), pk2(b1));
                sts128(wr_ + i * 16 + 128, pk2(b2), pk2(b3), pk2(b4), 0);
                b4 = cmulc(b4, z128);
                if (i < 7) {
                    a0 = i == 0 ? z8 : cmul(a0, z8); a1 = cmul(a1, z8);
                    b0 = cmulc(b0, z1); b1 = cmulc(b1, z1);
                    b2 = i == 3 ? y2 : cmulc(b2, z2);
                    if (i & 1) { y3 = cmulc(y3, z128); b3 = y3; } else b3 = cmulc(y3, z4);
                }
            }
            klast += b4.r;
            __syncwarp();
#pragma unroll
            for (int k = 0; k < 8; k++) {
                uint32_t x[4], y[4];
                lds128(x, rd_ + (8 * (k >> 1) + (k & 1)) * 272);
                lds128(y, rd_ + (8 * (k >> 1) + (k & 1)) * 272 + 128);
                mma1688(T[0], x[0], x[1], x[2]);
                mma1688(T[1], x[0], x[1], x[3]);
                mma1688(T[2], x[0], x[1], y[0]);
                mma1688(T[3], x[0], x[1], y[1]);
                mma1688(T[4], x[0], x[1], y[2]);
            }
#pragma unroll
            for (int i = 0; i < 2; i++)
                stsm4t(sb + S4_U + tr_off * S4_US + 256 + (w * 128 + c * 32 + i * 16) * 2 + tr_l, v[2 * i].x, v[2 * i].y, v[2 * i + 1].x, v[2 * i + 1].y);
            __syncwarp();
        }
#pragma unroll
        for (int o2 = 16; o2; o2 >>= 1) klast += __shfl_xor_sync(~0u, klast, o2);
#pragma unroll
        for (int hh = 0; hh < 2; hh++) {
            const int i = g + 8 * hh;
            sts32(kd + (8 * i + 2 * t) * 2, pack2(T[0][2 * hh], T[0][2 * hh + 1]));
            sts32(kd + (128 + 8 * i + 2 * t) * 2, pack2(T[1][2 * hh], T[1][2 * hh + 1]));
            sts32(kd + (256 + 4 * i + 2 * (t & 1) + 64 * (t >> 1)) * 2, pack2(T[2][2 * hh], T[2][2 * hh + 1]));
            sts32(kd + (384 + 2 * i + 32 * t) * 2, pack2(T[3][2 * hh], T[3][2 * hh + 1]));
        }
        asm volatile("stmatrix.sync.aligned.m8n8.x2.trans.shared.b16 [%0], {%1,%2};"
                     ::"r"(kd + 1024 + (lane & 7) * 32 + ((lane >> 3) & 1) * 16), "r"(pack2(T[4][0], T[4][1])), "r"(pack2(T[4][2], T[4][3])) : "memory");
        if (lane == 0) sts32(kd + 1280, pack2(klast, 0.f));
    }
    __syncwarp();
    const uint32_t pk = rs + S4_PK + 64;
    {
#pragma unroll
        for (int i = 0; i < 2; i++) {
            const int x = i * 128 + lane * 4;
            const uint2 c = lds64(kd + x * 2);
            uint32_t p = lds16(kd + x * 2 - 2);
            if (x == 0) p = 0;
            sts128(pk + x * 4, __byte_perm(c.x, p, 0x5410), __byte_perm(c.x, 0, 0x1032), __byte_perm(c.y, c.x, 0x7610), __byte_perm(c.y, 0, 0x1032));
        }
#pragma unroll
        for (int i = 2; i < 4; i++) {
            const int x = i * 128 + lane * 4;
            const uint32_t ab = lds32(kd + 256 + x), c = lds16(kd + 256 + x + 4);
            const uint32_t p = x == 256 ? lds16(kd + 510) : ab;
            sts128(pk + x * 4, __byte_perm(ab, p, 0x5410), __byte_perm(ab, 0, 0x1010), __byte_perm(ab, 0, 0x1032), __byte_perm(c, ab, 0x7610));
        }
        const uint32_t v = lds16(kd + 768), v2 = lds16(kd + 1024);
        if (lane < 24) {
            uint32_t x0 = 0, x1 = 0, x2 = 0, x3 = 0;
            if (lane == 0) { x0 = x1 = x2 = v | (v << 16); x3 = v << 16; }
            if (lane == 12) x3 = v2;
            if (lane == 13) { x0 = v2 | (v2 << 16); x1 = v2 << 16; }
            sts128(lane < 20 ? pk + 2048 + lane * 16 : pk - 64 + (lane - 20) * 16, x0, x1, x2, x3);
        }
        if (lane < 4) sts128(rs + (lane >> 1) * S4_SIG + (lane & 1) * 16, 0, 0, 0, 0);
    }
    __syncthreads();
    float acc[16][4];
#pragma unroll
    for (int i = 0; i < 16; i++) acc[i][0] = acc[i][1] = acc[i][2] = acc[i][3] = 0.f;
    const uint32_t lf = (lane & 7) * 32 + ((lane >> 3) & 1) * 16 + (lane >> 4) * 256;
#pragma unroll 1
    for (int ph = 0; ph < 2; ph++) {
    if (((w >> 2) ^ ph) & 1) {
#pragma unroll
    for (int rg = 3; rg >= 2; rg--) {
#pragma unroll 1
        for (int it = 0; it < (rg == 3 ? 4 : 6); it++) {
            const int n = it * 32 + lane;
            uint32_t x[2][4];
            lds128(x[0], ur + 256 + n * 16 - 16);
            lds128(x[1], ur + 256 + n * 16);
            float e[16], p[15], s[11];
#pragma unroll
            for (int i = 0; i < 8; i++) { e[2 * i] = bf_lo(x[i >> 2][i & 3]); e[2 * i + 1] = bf_hi(x[i >> 2][i & 3]); }
#pragma unroll
            for (int i = 0; i < 15; i++) p[i] = e[i] + e[i + 1];
#pragma unroll
            for (int i = 0; i < 11; i++) s[i] = p[i + 3] + e[i + 5];
            const uint32_t o = rs + 16 + n * 16;
            if (rg == 2) sts128(o, pack2(s[0], s[1]), pack2(s[2], s[3]), pack2(s[4], s[5]), pack2(s[6], s[7]));
#pragma unroll
            for (int i = 0; i < 10; i++) s[i] = p[i + 2] + s[i + 1];
            if (rg == 2) {
                sts64(o + S4_SIG + 8, pack2(s[0], s[1]), pack2(s[2], s[3]));
                sts64(o + S4_SIG + 16, pack2(s[4], s[5]), pack2(s[6], s[7]));
            } else {
#pragma unroll
                for (int i = 0; i < 9; i++) s[i] = p[i + 1] + s[i + 1];
                sts64(o + 8, pack2(s[0], s[1]), pack2(s[2], s[3]));
                sts64(o + 16, pack2(s[4], s[5]), pack2(s[6], s[7]));
#pragma unroll
                for (int i = 0; i < 8; i++) s[i] = p[i] + s[i + 1];
                sts64(o + S4_SIG + 8, pack2(s[0], s[1]), pack2(s[2], s[3]));
                sts64(o + S4_SIG + 16, pack2(s[4], s[5]), pack2(s[6], s[7]));
            }
        }
        __syncwarp();
        if (rg == 3) {
#pragma unroll 1
            for (int q = 1; q <= 2; q++) s4_class<64, 2>(acc, rs + lf + (q == 1 ? 16 : S4_SIG), kd + (384 + q) * 2, g - 2 * t);
        } else {
#pragma unroll 1
            for (int q = 1; q <= 4; q++) s4_class<32, 4>(acc, rs + lf + ((q & 1) ? 0 : S4_SIG) + (q < 3 ? 16 : 0), kd + (256 + q) * 2, g - 2 * t);
        }
        __syncwarp();
    }
    } else
    {
        const uint32_t ub = ur + 256 + lf, kb = pk + (g - 2 * t) * 4;
#pragma unroll 1
        for (int j0 = 0; j0 < 8; j0++) {
            uint32_t B[8][4];
#pragma unroll
            for (int i = 0; i < 8; i++) ldsm4(B[i], ub + i * 512 - j0 * 32);
            auto block = [&](int J, uint32_t a) {
                const uint32_t r0 = lds32(a), rp = lds32(a + 32), rm = lds32(a - 32);
                uint32_t r3;
                asm volatile("ld.volatile.shared.u32 %0, [%1];" : "=r"(r3) : "r"(a) : "memory");
#pragma unroll
                for (int I = J; I < 16; I++)
                    mma16816(acc[I], r0, rp, rm, r3, B[(I - J) >> 1][((I - J) & 1) * 2], B[(I - J) >> 1][((I - J) & 1) * 2 + 1]);
            };
#pragma unroll
            for (int J = 0; J < 4; J++) block(J, kb + j0 * 64 + J * 512);
            if (j0 < 2) { block(4, kb + j0 * 64 + 2048); block(8, kb + j0 * 64 + (544 + 16) * 4); }
        }
    }
    }
    {
        __syncwarp();
#pragma unroll
        for (int i = 0; i < 8; i++)
            stsm4t(rs + lf + i * 512, pack2(acc[2 * i][0], acc[2 * i][1]), pack2(acc[2 * i][2], acc[2 * i][3]),
                   pack2(acc[2 * i + 1][0], acc[2 * i + 1][1]), pack2(acc[2 * i + 1][2], acc[2 * i + 1][3]));
    }
    __syncthreads();
    {
        const uint2 dv = __ldg((const uint2*)(Dsk + d0 + 4 * t));
        bf16* dst = out + (size_t)(w * 128 + g) * 2048 + 1024 + d0 + 4 * t;
#pragma unroll
        for (int i = 0; i < 8; i++) {
            uint32_t y[4], x[4], o[4];
            ldsm4t(y, sb + S4_R + tr_off * S4_RS + (w * 128 + i * 16) * 2 + tr_l);
            ldsm4t(x, sb + S4_U + tr_off * S4_US + 256 + (w * 128 + i * 16) * 2 + tr_l);
#pragma unroll
            for (int j = 0; j < 4; j++)
                asm("{\n.reg .b32 s;\nmul.rn.bf16x2 s, %2, %3;\nadd.rn.bf16x2 %0, %1, s;\n}" : "=r"(o[j]) : "r"(y[j]), "r"(x[j]), "r"((j & 1) ? dv.y : dv.x));
            *reinterpret_cast<uint2*>(dst + (size_t)(i * 16) * 2048) = make_uint2(o[0], o[1]);
            *reinterpret_cast<uint2*>(dst + (size_t)(i * 16 + 8) * 2048) = make_uint2(o[2], o[3]);
        }
    }
    if (tid == 0) TLS(1);
    __syncthreads();
    }
}

enum { IT_W256 = 1, IT_W128 = 2, IT_W64 = 3, IT_END = 7 };
struct BgParams { CUtensorMap mo, mo2, mwo4, mwo2, mwo1; };
#define NBT 10
#define P256 56
#define P128 62
struct Sched { uint32_t w0 = 0, w1 = 0; };
__device__ __forceinline__ int next_item(Sched& z) {
    if (z.w0 >= z.w1) {
        uint32_t prog;
        asm volatile("ld.relaxed.gpu.global.u32 %0, [%1];" : "=r"(prog) : "l"(g_flag + 98) : "memory");
        const uint32_t k = prog <= P256 ? 4 : prog <= P128 ? 2 : 1;
        z.w0 = atomicAdd(g_flag + 97, k);
        z.w1 = min(z.w0 + k, NBT * 16u);
        if (z.w0 >= z.w1) return IT_END;
    }
    const uint32_t i = z.w0, k = z.w1 - i >= 4 && !(i & 3) ? 4 : z.w1 - i >= 2 && !(i & 1) ? 2 : 1;
    z.w0 += k;
    return (k == 4 ? IT_W256 : k == 2 ? IT_W128 : IT_W64) | (i >> 4) << 3 | ((i & 15) / k) << 7;
}
constexpr int B_OST = NSTAGE * STAGE_BYTES + 1024;
constexpr int BG_SMEM = B_OST + 32768;

template <int BM, int BN, int KPS, typename ACC>
__device__ __forceinline__ void gemm_mainloop(ACC& acc, const GemmSmem& g, int cw, int rounds, uint32_t& round) {
#pragma unroll
    for (int i = 0; i < BN / 2; i++) acc[i] = 0.f;
#pragma unroll 1
    for (int k0 = 0; k0 < rounds; k0++, round++) {
#pragma unroll
        for (int s = 0; s < 4; s++) {
            mbar_wait_u(g.full + 8 * s, round & 1);
            gemm_stage<BM, BN, KPS>(acc, g.st + s * STAGE_BYTES, cw, false);
            wg_wait<1>();
            if (s > 0 || k0 > 0) mbar_arrive_one(g.empty + 8 * ((s + 3) & 3), threadIdx.x & 31);
        }
    }
    wg_wait<0>();
    mbar_arrive_one(g.empty + 8 * 3, threadIdx.x & 31);
}

template <int BN>
__device__ __forceinline__ void store_tile(const float (&acc)[BN / 2], bf16* dst, int t) {
#pragma unroll
    for (int G = 0; G < BN / 32; G++)
#pragma unroll
        for (int rr = 0; rr < 2; rr++) {
            uint32_t r0 = pack2(acc[16 * G + 2 * rr], acc[16 * G + 2 * rr + 1]), r1 = pack2(acc[16 * G + 4 + 2 * rr], acc[16 * G + 5 + 2 * rr]);
            uint32_t r2 = pack2(acc[16 * G + 8 + 2 * rr], acc[16 * G + 9 + 2 * rr]), r3 = pack2(acc[16 * G + 12 + 2 * rr], acc[16 * G + 13 + 2 * rr]);
            quad_transpose(r0, r1, r2, r3, t);
            *reinterpret_cast<uint4*>(dst + (size_t)rr * 8 * 2048 + G * 32) = make_uint4(r0, r1, r2, r3);
        }
}

template <int BN, int KPS>
__device__ __forceinline__ void wo_item(const GemmSmem& g, int cw, uint32_t& round, bf16* dst, int t) {
    float acc[BN / 2];
    gemm_mainloop<128, BN, KPS>(acc, g, cw, 16 / KPS, round);
    store_tile<BN>(acc, dst, t);
}

__global__ void __launch_bounds__(384, 1) k_bg(const __grid_constant__ BgParams P, bf16* __restrict__ out) {
    extern __shared__ __align__(1024) uint8_t smem_gemm[];
    asm volatile("griddepcontrol.launch_dependents;");
    const uint32_t bar_item = smem_u32(smem_gemm) + NSTAGE * STAGE_BYTES + 128, slot = bar_item + 16;
    if (threadIdx.x == 0) { mbar_init(bar_item, 1); mbar_init(bar_item + 8, 1); }
    GemmSmem g = gemm_setup(smem_gemm, 8);
    const int wg = __shfl_sync(~0u, threadIdx.x >> 7, 0);
    if (wg == 0) {
        asm volatile("setmaxnreg.dec.sync.aligned.u32 40;");
        if (threadIdx.x == 0) {
            uint32_t it = 0;
            Sched z;
            for (int n = 0;; n++) {
                const int code = next_item(z);
                sts32(slot + (n & 1) * 4, code);
                mbar_arrive(bar_item + (n & 1) * 8);
                const int type = code & 7, blk = (code >> 3) & 15, idx = code >> 7;
                if (type == IT_END) break;
                wait_flag(g_flag + 64 + blk, 96);
                asm volatile("fence.proxy.async.global;" ::: "memory");
                for (int k = 0; k < (type == IT_W64 ? 32 : 64); k++, it++) {
                    const int s = it & 3;
                    const uint32_t st = g.st + s * STAGE_BYTES, fb = g.full + 8 * s;
                    mbar_wait(g.empty + 8 * s, ((it >> 2) & 1) ^ 1);
                    mbar_expect_tx(fb, type == IT_W128 ? 32768 : 49152);
                    if (type == IT_W64) {
                        tma3d(st, &P.mo2, 0, blk * 128, k * 2, fb);
                        tma3d(st + 32768, &P.mwo1, 0, k * 128, idx, fb);
                    } else {
                        tma2d(st, &P.mo, k * 64, blk * 128, fb);
                        tma3d(st + 16384, type == IT_W256 ? &P.mwo4 : &P.mwo2, 0, k * 64, idx * (type == IT_W256 ? 4 : 2), fb);
                    }
                }
            }
        }
    } else {
        asm volatile("setmaxnreg.inc.sync.aligned.u32 232;");
        const int cw = wg - 1, lane = threadIdx.x & 31;
        uint32_t round = 0;
#pragma unroll 1
        for (int n = 0;; n++) {
            mbar_wait_u(bar_item + (n & 1) * 8, (n >> 1) & 1);
            const int code = __shfl_sync(~0u, lds32(slot + (n & 1) * 4), 0);
            const int type = code & 7, blk = (code >> 3) & 15, idx = (code >> 7) & 31;
#define TLB(slot_)
            if (type == IT_END) break;
            TLB(0);
            bf16* dst = out + (size_t)(blk * 128 + cw * 64 + ((threadIdx.x >> 5) & 3) * 16 + (lane >> 2)) * 2048 + (lane & 3) * 8;
            if (type == IT_W256) wo_item<256, 1>(g, cw, round, dst + idx * 256, lane & 3);
            else if (type == IT_W128) wo_item<128, 1>(g, cw, round, dst + idx * 128, lane & 3);
            else wo_item<64, 2>(g, cw, round, dst + idx * 64, lane & 3);
            TLB(1);
        }
    }
}

constexpr int TBN = NBT >= 13 ? 64 : 128, TKPS = TBN == 64 ? 2 : 1, TPB = DM / TBN;
__global__ void __cluster_dims__(2, 1, 1) __launch_bounds__(384, 1)
k_tail(const __grid_constant__ BgParams P, bf16* __restrict__ out) {
    extern __shared__ __align__(1024) uint8_t smem_gemm[];
    const uint32_t bar_s = smem_u32(smem_gemm) + NSTAGE * STAGE_BYTES + 128;
    if (threadIdx.x == 0) { TL(4, 0); mbar_init(bar_s, 1); mbar_expect_tx(bar_s, TBN * 256); }
    GemmSmem g = gemm_setup(smem_gemm, 8);
    asm volatile("barrier.cluster.arrive.relaxed.aligned;" ::: "memory");
    const int half = blockIdx.x & 1, blk = NBT + (blockIdx.x >> 1) / TPB, idx = (blockIdx.x >> 1) % TPB;
    const int wg = __shfl_sync(~0u, threadIdx.x >> 7, 0);
    if (wg == 0) {
        if (threadIdx.x == 0) {
            wait_flag(g_flag + 64 + blk, 96);
            asm volatile("fence.proxy.async.global;" ::: "memory");
            for (int k = 0; k < 32 / TKPS; k++) {
                const int s = k & 3, kb = half * 32 + k * TKPS;
                const uint32_t st = g.st + s * STAGE_BYTES, fb = g.full + 8 * s;
                mbar_wait(g.empty + 8 * s, ((k >> 2) & 1) ^ 1);
                mbar_expect_tx(fb, TBN == 64 ? 49152 : 32768);
                if (TBN == 64) {
                    tma3d(st, &P.mo2, 0, blk * 128, kb, fb);
                    tma3d(st + 32768, &P.mwo1, 0, kb * 64, idx, fb);
                } else {
                    tma2d(st, &P.mo, kb * 64, blk * 128, fb);
                    tma3d(st + 16384, &P.mwo2, 0, kb * 64, idx * 2, fb);
                }
            }
        }
        __syncwarp();
        asm volatile("barrier.cluster.wait.aligned;" ::: "memory");
    } else {
        const int cw = wg - 1, lane = threadIdx.x & 31, t = lane & 3;
        float acc[TBN / 2];
        uint32_t round = 0;
        gemm_mainloop<128, TBN, TKPS>(acc, g, cw, 8 / TKPS, round);
        asm volatile("barrier.cluster.wait.aligned;" ::: "memory");
        const uint32_t xa = g.st + B_OST + (threadIdx.x & 127) * 16;
        if (cw != half) {
            uint32_t ra, rb;
            asm("mapa.shared::cluster.u32 %0, %1, %2;" : "=r"(ra) : "r"(xa), "r"(half ^ 1));
            asm("mapa.shared::cluster.u32 %0, %1, %2;" : "=r"(rb) : "r"(bar_s), "r"(half ^ 1));
#pragma unroll
            for (int i = 0; i < TBN / 8; i++)
                asm volatile("st.async.weak.shared::cluster.mbarrier::complete_tx::bytes.v4.f32 [%0], {%1,%2,%3,%4}, [%5];"
                             ::"r"(ra + i * 2048), "f"(acc[4 * i]), "f"(acc[4 * i + 1]), "f"(acc[4 * i + 2]), "f"(acc[4 * i + 3]), "r"(rb) : "memory");
        } else {
            mbar_wait_u(bar_s, 0);
#pragma unroll
            for (int i = 0; i < TBN / 8; i++) {
                const float4 v = lds128f(xa + i * 2048);
                acc[4 * i] += v.x; acc[4 * i + 1] += v.y; acc[4 * i + 2] += v.z; acc[4 * i + 3] += v.w;
            }
            store_tile<TBN>(acc, out + (size_t)(blk * 128 + cw * 64 + ((threadIdx.x >> 5) & 3) * 16 + (lane >> 2)) * 2048 + idx * TBN + t * 8, t);
            if ((threadIdx.x & 127) == 0) TL(4, 1);
        }
    }
    asm volatile("barrier.cluster.arrive.relaxed.aligned;\nbarrier.cluster.wait.aligned;" ::: "memory");
}

typedef CUresult (*EncodeFn)(CUtensorMap*, CUtensorMapDataType, cuuint32_t, void*, const cuuint64_t*, const cuuint64_t*,
                             const cuuint32_t*, const cuuint32_t*, CUtensorMapInterleave, CUtensorMapSwizzle,
                             CUtensorMapL2promotion, CUtensorMapFloatOOBfill);

static void map2d(EncodeFn enc, CUtensorMap* m, const void* p, int rows, int cols, int box_rows) {
    cuuint64_t dim[2] = {(cuuint64_t)cols, (cuuint64_t)rows}, str[1] = {(cuuint64_t)cols * 2};
    cuuint32_t box[2] = {64, (cuuint32_t)box_rows}, es[2] = {1, 1};
    enc(m, CU_TENSOR_MAP_DATA_TYPE_BFLOAT16, 2, (void*)p, dim, str, box, es, CU_TENSOR_MAP_INTERLEAVE_NONE,
        CU_TENSOR_MAP_SWIZZLE_128B, CU_TENSOR_MAP_L2_PROMOTION_L2_256B, CU_TENSOR_MAP_FLOAT_OOB_FILL_NONE);
}
static void map3d(EncodeFn enc, CUtensorMap* m, const void* p, int rows, int cols, int box_rows, int nblk) {
    cuuint64_t dim[3] = {64, (cuuint64_t)rows, (cuuint64_t)cols / 64}, str[2] = {(cuuint64_t)cols * 2, 128};
    cuuint32_t box[3] = {64, (cuuint32_t)box_rows, (cuuint32_t)nblk}, es[3] = {1, 1, 1};
    enc(m, CU_TENSOR_MAP_DATA_TYPE_BFLOAT16, 3, (void*)p, dim, str, box, es, CU_TENSOR_MAP_INTERLEAVE_NONE,
        CU_TENSOR_MAP_SWIZZLE_128B, CU_TENSOR_MAP_L2_PROMOTION_L2_256B, CU_TENSOR_MAP_FLOAT_OOB_FILL_NONE);
}

#define USE_PDL 1

extern "C" void kernel_launch(void* const* d_in, const int* in_sizes, int n_in, void* d_out, int out_size) {
    const bf16 *x = (const bf16*)d_in[0], *mem0 = (const bf16*)d_in[1], *Wq = (const bf16*)d_in[2], *Wk = (const bf16*)d_in[3];
    const bf16 *Wv = (const bf16*)d_in[4], *Wo = (const bf16*)d_in[5];
    const bf16 *u = (const bf16*)d_in[7], *Are = (const bf16*)d_in[8], *Aim = (const bf16*)d_in[9], *Bre = (const bf16*)d_in[10];
    const bf16 *Bim = (const bf16*)d_in[11], *Cre = (const bf16*)d_in[12], *Cim = (const bf16*)d_in[13];
    const bf16 *logdt = (const bf16*)d_in[14], *Dsk = (const bf16*)d_in[15];
    bf16* out = (bf16*)d_out;

    void* fn = nullptr;
    cudaDriverEntryPointQueryResult qr;
    cudaGetDriverEntryPoint("cuTensorMapEncodeTiled", &fn, cudaEnableDefault, &qr);
    EncodeFn enc = (EncodeFn)fn;
    void *kv, *o;
    cudaGetSymbolAddress(&kv, g_kv);
    cudaGetSymbolAddress(&o, g_o);
    CUtensorMap mx, mwq, mwk, mwv, mkv2;
    BgParams P;
    map2d(enc, &mx, x, SEQ, DM, 128);
    map2d(enc, &P.mo, o, SEQ, HD, 128);
    map3d(enc, &P.mo2, o, SEQ, HD, 128, 2);
    map3d(enc, &mwq, Wq, DM, HD, 64, 2);
    map3d(enc, &mwk, Wk, DM, HD, 64, 2);
    map3d(enc, &mwv, Wv, DM, HD, 64, 2);
    map3d(enc, &P.mwo4, Wo, HD, DM, 64, 4);
    map3d(enc, &P.mwo2, Wo, HD, DM, 64, 2);
    map3d(enc, &P.mwo1, Wo, HD, DM, 128, 1);
    map3d(enc, &mkv2, kv, SEQ, PW, 32, 2);
    cudaFuncSetAttribute(k_kv, cudaFuncAttributeMaxDynamicSharedMemorySize, GEMM_SMEM);
    cudaFuncSetAttribute(k_bg, cudaFuncAttributeMaxDynamicSharedMemorySize, BG_SMEM);
    cudaFuncSetAttribute(k_tail, cudaFuncAttributeMaxDynamicSharedMemorySize, BG_SMEM);
    cudaFuncSetAttribute(k_chain, cudaFuncAttributeMaxDynamicSharedMemorySize, CHAIN_SMEM);
    cudaFuncSetAttribute(k_s4, cudaFuncAttributeMaxDynamicSharedMemorySize, S4_SMEM);

    cudaStream_t st = cudaStreamPerThread;
    cudaLaunchAttribute pdl[2], cls[1];
    pdl[0].id = cudaLaunchAttributeProgrammaticStreamSerialization;
    pdl[0].val.programmaticStreamSerializationAllowed = 1;
    cls[0].id = cudaLaunchAttributeClusterDimension;
    cls[0].val.clusterDim.x = CLS; cls[0].val.clusterDim.y = 1; cls[0].val.clusterDim.z = 1;
    cudaLaunchConfig_t cfg = {};
    cfg.stream = st; cfg.attrs = cls; cfg.numAttrs = 1;
    cfg.gridDim = dim3(96); cfg.blockDim = dim3(384); cfg.dynamicSmemBytes = GEMM_SMEM;
    cudaLaunchKernelEx(&cfg, k_kv, mx, mwk, mwv, mwq, Wq, Wo, 0);
    pdl[1] = cls[0]; pdl[1].val.clusterDim.x = 2;
    cfg.attrs = pdl; cfg.numAttrs = 2;
    cfg.gridDim = dim3(36);
    cudaLaunchKernelEx(&cfg, k_kv, mx, mwk, mwv, mwq, Wq, Wo, 96);
    cfg.numAttrs = 1;
    cfg.gridDim = dim3(96); cfg.blockDim = dim3(256); cfg.dynamicSmemBytes = CHAIN_SMEM;
    cudaLaunchKernelEx(&cfg, k_chain, mem0, Wq, Wk, Wv, Wo, mkv2);
    cfg.numAttrs = USE_PDL;
    cfg.gridDim = dim3(36); cfg.blockDim = dim3(512); cfg.dynamicSmemBytes = S4_SMEM;
    cudaLaunchKernelEx(&cfg, k_s4, u, Are, Aim, Bre, Bim, Cre, Cim, logdt, Dsk, out);
    cfg.gridDim = dim3(36); cfg.blockDim = dim3(384); cfg.dynamicSmemBytes = BG_SMEM;
    cudaLaunchKernelEx(&cfg, k_bg, P, out);
    cfg.gridDim = dim3((16 - NBT) * TPB * 2);
    cudaLaunchKernelEx(&cfg, k_tail, P, out);
}
```

```cpp
#include <cuda_runtime.h>
#include <cuda_bf16.h>
#include <cuda.h>
#include <stdint.h>

typedef __nv_bfloat16 bf16;

constexpr int SEQ = 2048, DM = 1024, HD = 4096, NSEG = 64;

constexpr int PW = 3 * HD;
#define NTA 3
__device__ __align__(1024) bf16 g_kv[(size_t)SEQ * PW];
__device__ __align__(1024) bf16 g_o[(size_t)SEQ * HD];
constexpr int XPAIRS = 128 + NSEG * 4;
__device__ __align__(8192) uint2 g_x[XPAIRS * 1024];
__device__ uint32_t g_home[XPAIRS];
__device__ uint32_t g_side[256];
__device__ __align__(1024) uint32_t g_flag[256];

#define TL(kern, slot)

__device__ __forceinline__ uint32_t smem_u32(const void* p) { return (uint32_t)__cvta_generic_to_shared(p); }
__device__ __forceinline__ void mbar_init(uint32_t bar, uint32_t cnt) {
    asm volatile("mbarrier.init.shared::cta.b64 [%0], %1;" ::"r"(bar), "r"(cnt) : "memory");
}
__device__ __forceinline__ void mbar_expect_tx(uint32_t bar, uint32_t bytes) {
    asm volatile("mbarrier.arrive.expect_tx.shared::cta.b64 _, [%0], %1;" ::"r"(bar), "r"(bytes) : "memory");
}
__device__ __forceinline__ void mbar_arrive(uint32_t bar) {
    asm volatile("mbarrier.arrive.shared::cta.b64 _, [%0];" ::"r"(bar) : "memory");
}
__device__ __forceinline__ bool mbar_try(uint32_t bar, uint32_t parity) {
    uint32_t ok;
    asm volatile("{\n.reg .pred p;\nmbarrier.try_wait.parity.shared::cta.b64 p, [%1], %2;\nselp.u32 %0, 1, 0, p;\n}"
                 : "=r"(ok) : "r"(bar), "r"(parity) : "memory");
    return ok;
}
constexpr int SPIN_LIMIT = 1 << 20;
__device__ __forceinline__ void mbar_wait(uint32_t bar, uint32_t parity) {
    int n = 0;
    while (!mbar_try(bar, parity)) { if (++n > SPIN_LIMIT) __trap(); }
}
__device__ __forceinline__ void mbar_wait_u(uint32_t bar, uint32_t parity) {
    asm volatile("{\n.reg .pred p;\n.reg .u32 n;\n"
                 "mbarrier.try_wait.parity.shared::cta.b64 p, [%0], %1;\n@p bra.uni DONE;\nmov.u32 n, 0;\n"
                 "AGAIN:\nmbarrier.try_wait.parity.shared::cta.b64 p, [%0], %1;\n@p bra.uni DONE;\n"
                 "add.u32 n, n, 1;\nsetp.lt.u32 p, n, 0x100000;\n@p bra.uni AGAIN;\ntrap;\nDONE:\n}"
                 ::"r"(bar), "r"(parity) : "memory");
}
__device__ __forceinline__ void tma2d(uint32_t dst, const CUtensorMap* m, int c0, int c1, uint32_t bar) {
    asm volatile("cp.async.bulk.tensor.2d.shared::cluster.global.mbarrier::complete_tx::bytes [%0], [%1, {%3, %4}], [%2];"
                 ::"r"(dst), "l"(m), "r"(bar), "r"(c0), "r"(c1) : "memory");
}
__device__ __forceinline__ void tma3d(uint32_t dst, const CUtensorMap* m, int c0, int c1, int c2, uint32_t bar) {
    asm volatile("cp.async.bulk.tensor.3d.shared::cluster.global.mbarrier::complete_tx::bytes [%0], [%1, {%3, %4, %5}], [%2];"
                 ::"r"(dst), "l"(m), "r"(bar), "r"(c0), "r"(c1), "r"(c2) : "memory");
}
__device__ __forceinline__ uint32_t pack2(float lo, float hi) {
    uint32_t r;
    asm("cvt.rn.bf16x2.f32 %0, %1, %2;" : "=r"(r) : "f"(hi), "f"(lo));
    return r;
}
__device__ __forceinline__ float bf_lo(uint32_t v) { return __uint_as_float(v << 16); }
__device__ __forceinline__ float bf_hi(uint32_t v) { return __uint_as_float(v & 0xffff0000u); }
__device__ __forceinline__ float bf_round(float x) { return bf_lo(pack2(x, 0.f)); }
__device__ __forceinline__ float ex2(float x) { float y; asm("ex2.approx.ftz.f32 %0, %1;" : "=f"(y) : "f"(x)); return y; }
__device__ __forceinline__ void mma16816(float (&c)[4], uint32_t a0, uint32_t a1, uint32_t a2, uint32_t a3, uint32_t b0, uint32_t b1) {
    asm volatile("mma.sync.aligned.m16n8k16.row.col.f32.bf16.bf16.f32 {%0,%1,%2,%3}, {%4,%5,%6,%7}, {%8,%9}, {%0,%1,%2,%3};"
                 : "+f"(c[0]), "+f"(c[1]), "+f"(c[2]), "+f"(c[3]) : "r"(a0), "r"(a1), "r"(a2), "r"(a3), "r"(b0), "r"(b1));
}
__device__ __forceinline__ void mma1688(float (&c)[4], uint32_t a0, uint32_t a1, uint32_t b0) {
    asm volatile("mma.sync.aligned.m16n8k8.row.col.f32.bf16.bf16.f32 {%0,%1,%2,%3}, {%4,%5}, {%6}, {%0,%1,%2,%3};"
                 : "+f"(c[0]), "+f"(c[1]), "+f"(c[2]), "+f"(c[3]) : "r"(a0), "r"(a1), "r"(b0));
}
__device__ __forceinline__ void ldsm4(uint32_t (&r)[4], uint32_t a) {
    asm volatile("ldmatrix.sync.aligned.m8n8.x4.shared.b16 {%0,%1,%2,%3}, [%4];"
                 : "=r"(r[0]), "=r"(r[1]), "=r"(r[2]), "=r"(r[3]) : "r"(a) : "memory");
}
__device__ __forceinline__ void ldsm4t(uint32_t (&r)[4], uint32_t a) {
    asm volatile("ldmatrix.sync.aligned.m8n8.x4.trans.shared.b16 {%0,%1,%2,%3}, [%4];"
                 : "=r"(r[0]), "=r"(r[1]), "=r"(r[2]), "=r"(r[3]) : "r"(a) : "memory");
}
__device__ __forceinline__ void ldsm2t(uint32_t& r0, uint32_t& r1, uint32_t a) {
    asm volatile("ldmatrix.sync.aligned.m8n8.x2.trans.shared.b16 {%0,%1}, [%2];" : "=r"(r0), "=r"(r1) : "r"(a) : "memory");
}
__device__ __forceinline__ void stsm4t(uint32_t a, uint32_t r0, uint32_t r1, uint32_t r2, uint32_t r3) {
    asm volatile("stmatrix.sync.aligned.m8n8.x4.trans.shared.b16 [%0], {%1,%2,%3,%4};"
                 ::"r"(a), "r"(r0), "r"(r1), "r"(r2), "r"(r3) : "memory");
}
__device__ __forceinline__ void lds128(uint32_t (&r)[4], uint32_t a) {
    asm volatile("ld.shared.v4.u32 {%0,%1,%2,%3}, [%4];" : "=r"(r[0]), "=r"(r[1]), "=r"(r[2]), "=r"(r[3]) : "r"(a) : "memory");
}
__device__ __forceinline__ float4 lds128f(uint32_t a) {
    float4 v;
    asm volatile("ld.shared.v4.f32 {%0,%1,%2,%3}, [%4];" : "=f"(v.x), "=f"(v.y), "=f"(v.z), "=f"(v.w) : "r"(a) : "memory");
    return v;
}
__device__ __forceinline__ float2 lds64f(uint32_t a) {
    float2 v;
    asm volatile("ld.shared.v2.f32 {%0,%1}, [%2];" : "=f"(v.x), "=f"(v.y) : "r"(a) : "memory");
    return v;
}
__device__ __forceinline__ uint32_t lds32(uint32_t a) {
    uint32_t v;
    asm volatile("ld.shared.u32 %0, [%1];" : "=r"(v) : "r"(a) : "memory");
    return v;
}
__device__ __forceinline__ void sts128(uint32_t a, uint32_t r0, uint32_t r1, uint32_t r2, uint32_t r3) {
    asm volatile("st.shared.v4.u32 [%0], {%1,%2,%3,%4};" ::"r"(a), "r"(r0), "r"(r1), "r"(r2), "r"(r3) : "memory");
}
__device__ __forceinline__ void sts128f(uint32_t a, float r0, float r1, float r2, float r3) {
    asm volatile("st.shared.v4.f32 [%0], {%1,%2,%3,%4};" ::"r"(a), "f"(r0), "f"(r1), "f"(r2), "f"(r3) : "memory");
}
__device__ __forceinline__ void sts64(uint32_t a, uint32_t r0, uint32_t r1) {
    asm volatile("st.shared.v2.u32 [%0], {%1,%2};" ::"r"(a), "r"(r0), "r"(r1) : "memory");
}
__device__ __forceinline__ void sts64f(uint32_t a, float r0, float r1) {
    asm volatile("st.shared.v2.f32 [%0], {%1,%2};" ::"r"(a), "f"(r0), "f"(r1) : "memory");
}
__device__ __forceinline__ void sts32f(uint32_t a, float r0) {
    asm volatile("st.shared.f32 [%0], %1;" ::"r"(a), "f"(r0) : "memory");
}
__device__ __forceinline__ uint2 ld_rlx64(const uint2* p) {
    uint2 v;
    asm volatile("{\n.reg .b64 t;\nld.relaxed.gpu.global.b64 t, [%2];\nmov.b64 {%0,%1}, t;\n}" : "=r"(v.x), "=r"(v.y) : "l"(p) : "memory");
    return v;
}
__device__ __forceinline__ void st_rlx64(uint2* p, uint32_t x, uint32_t y) {
    asm volatile("{\n.reg .b64 t;\nmov.b64 t, {%1,%2};\nst.relaxed.gpu.global.b64 [%0], t;\n}" ::"l"(p), "r"(x), "r"(y) : "memory");
}
__device__ __forceinline__ uint32_t ld_acq32(const uint32_t* p) {
    uint32_t v;
    asm volatile("ld.acquire.gpu.global.u32 %0, [%1];" : "=r"(v) : "l"(p) : "memory");
    return v;
}
__device__ __forceinline__ void wait_flag(const uint32_t* p, uint32_t need) {
    int n = 0;
    while (ld_acq32(p) < need) { __nanosleep(200); if (++n > SPIN_LIMIT) __trap(); }
}
__device__ __forceinline__ void bar_sync(int id, int n) { asm volatile("bar.sync %0, %1;" ::"r"(id), "r"(n) : "memory"); }
__device__ __forceinline__ void wg_fence() { asm volatile("wgmma.fence.sync.aligned;" ::: "memory"); }
__device__ __forceinline__ void wg_commit() { asm volatile("wgmma.commit_group.sync.aligned;" ::: "memory"); }
template <int N> __device__ __forceinline__ void wg_wait() { asm volatile("wgmma.wait_group.sync.aligned %0;" ::"n"(N) : "memory"); }
__device__ __forceinline__ uint64_t desc_sw128(uint32_t addr, uint32_t lbo, uint32_t sbo) {
    return (uint64_t)((addr & 0x3FFFF) >> 4) | ((uint64_t)(lbo >> 4) << 16) | ((uint64_t)(sbo >> 4) << 32) | (1ull << 62);
}
__device__ __forceinline__ void quad_transpose(uint32_t& r0, uint32_t& r1, uint32_t& r2, uint32_t& r3, int t) {
    const bool o = t & 1, h = t & 2;
    uint32_t s0 = __shfl_xor_sync(~0u, o ? r0 : r1, 1), s1 = __shfl_xor_sync(~0u, o ? r2 : r3, 1);
    uint32_t a0 = o ? s0 : r0, a1 = o ? r1 : s0, a2 = o ? s1 : r2, a3 = o ? r3 : s1;
    s0 = __shfl_xor_sync(~0u, h ? a0 : a2, 2); s1 = __shfl_xor_sync(~0u, h ? a1 : a3, 2);
    r0 = h ? s0 : a0; r1 = h ? s1 : a1; r2 = h ? a2 : s0; r3 = h ? a3 : s1;
}

__device__ __forceinline__ void wgmma_n256(float (&d)[128], uint64_t da, uint64_t db, int sd) {
    asm volatile("{\n.reg .pred p;\nsetp.ne.b32 p, %130, 0;\n"
        "wgmma.mma_async.sync.aligned.m64n256k16.f32.bf16.bf16 "
        "{%0,%1,%2,%3,%4,%5,%6,%7,%8,%9,%10,%11,%12,%13,%14,%15,"
        "%16,%17,%18,%19,%20,%21,%22,%23,%24,%25,%26,%27,%28,%29,%30,%31,"
        "%32,%33,%34,%35,%36,%37,%38,%39,%40,%41,%42,%43,%44,%45,%46,%47,"
        "%48,%49,%50,%51,%52,%53,%54,%55,%56,%57,%58,%59,%60,%61,%62,%63,"
        "%64,%65,%66,%67,%68,%69,%70,%71,%72,%73,%74,%75,%76,%77,%78,%79,"
        "%80,%81,%82,%83,%84,%85,%86,%87,%88,%89,%90,%91,%92,%93,%94,%95,"
        "%96,%97,%98,%99,%100,%101,%102,%103,%104,%105,%106,%107,%108,%109,%110,%111,"
        "%112,%113,%114,%115,%116,%117,%118,%119,%120,%121,%122,%123,%124,%125,%126,%127}, %128, %129, p, 1, 1, 0, 1;\n}\n"
        : "+f"(d[0]), "+f"(d[1]), "+f"(d[2]), "+f"(d[3]), "+f"(d[4]), "+f"(d[5]), "+f"(d[6]), "+f"(d[7]),
          "+f"(d[8]), "+f"(d[9]), "+f"(d[10]), "+f"(d[11]), "+f"(d[12]), "+f"(d[13]), "+f"(d[14]), "+f"(d[15]),
          "+f"(d[16]), "+f"(d[17]), "+f"(d[18]), "+f"(d[19]), "+f"(d[20]), "+f"(d[21]), "+f"(d[22]), "+f"(d[23]),
          "+f"(d[24]), "+f"(d[25]), "+f"(d[26]), "+f"(d[27]), "+f"(d[28]), "+f"(d[29]), "+f"(d[30]), "+f"(d[31]),
          "+f"(d[32]), "+f"(d[33]), "+f"(d[34]), "+f"(d[35]), "+f"(d[36]), "+f"(d[37]), "+f"(d[38]), "+f"(d[39]),
          "+f"(d[40]), "+f"(d[41]), "+f"(d[42]), "+f"(d[43]), "+f"(d[44]), "+f"(d[45]), "+f"(d[46]), "+f"(d[47]),
          "+f"(d[48]), "+f"(d[49]), "+f"(d[50]), "+f"(d[51]), "+f"(d[52]), "+f"(d[53]), "+f"(d[54]), "+f"(d[55]),
          "+f"(d[56]), "+f"(d[57]), "+f"(d[58]), "+f"(d[59]), "+f"(d[60]), "+f"(d[61]), "+f"(d[62]), "+f"(d[63]),
          "+f"(d[64]), "+f"(d[65]), "+f"(d[66]), "+f"(d[67]), "+f"(d[68]), "+f"(d[69]), "+f"(d[70]), "+f"(d[71]),
          "+f"(d[72]), "+f"(d[73]), "+f"(d[74]), "+f"(d[75]), "+f"(d[76]), "+f"(d[77]), "+f"(d[78]), "+f"(d[79]),
          "+f"(d[80]), "+f"(d[81]), "+f"(d[82]), "+f"(d[83]), "+f"(d[84]), "+f"(d[85]), "+f"(d[86]), "+f"(d[87]),
          "+f"(d[88]), "+f"(d[89]), "+f"(d[90]), "+f"(d[91]), "+f"(d[92]), "+f"(d[93]), "+f"(d[94]), "+f"(d[95]),
          "+f"(d[96]), "+f"(d[97]), "+f"(d[98]), "+f"(d[99]), "+f"(d[100]), "+f"(d[101]), "+f"(d[102]), "+f"(d[103]),
          "+f"(d[104]), "+f"(d[105]), "+f"(d[106]), "+f"(d[107]), "+f"(d[108]), "+f"(d[109]), "+f"(d[110]), "+f"(d[111]),
          "+f"(d[112]), "+f"(d[113]), "+f"(d[114]), "+f"(d[115]), "+f"(d[116]), "+f"(d[117]), "+f"(d[118]), "+f"(d[119]),
          "+f"(d[120]), "+f"(d[121]), "+f"(d[122]), "+f"(d[123]), "+f"(d[124]), "+f"(d[125]), "+f"(d[126]), "+f"(d[127])
        : "l"(da), "l"(db), "r"(sd));
}

__device__ __forceinline__ void wgmma_n128(float (&d)[64], uint64_t da, uint64_t db, int sd) {
    asm volatile("{\n.reg .pred p;\nsetp.ne.b32 p, %66, 0;\n"
        "wgmma.mma_async.sync.aligned.m64n128k16.f32.bf16.bf16 "
        "{%0,%1,%2,%3,%4,%5,%6,%7,%8,%9,%10,%11,%12,%13,%14,%15,"
        "%16,%17,%18,%19,%20,%21,%22,%23,%24,%25,%26,%27,%28,%29,%30,%31,"
        "%32,%33,%34,%35,%36,%37,%38,%39,%40,%41,%42,%43,%44,%45,%46,%47,"
        "%48,%49,%50,%51,%52,%53,%54,%55,%56,%57,%58,%59,%60,%61,%62,%63}, %64, %65, p, 1, 1, 0, 1;\n}\n"
        : "+f"(d[0]), "+f"(d[1]), "+f"(d[2]), "+f"(d[3]), "+f"(d[4]), "+f"(d[5]), "+f"(d[6]), "+f"(d[7]),
          "+f"(d[8]), "+f"(d[9]), "+f"(d[10]), "+f"(d[11]), "+f"(d[12]), "+f"(d[13]), "+f"(d[14]), "+f"(d[15]),
          "+f"(d[16]), "+f"(d[17]), "+f"(d[18]), "+f"(d[19]), "+f"(d[20]), "+f"(d[21]), "+f"(d[22]), "+f"(d[23]),
          "+f"(d[24]), "+f"(d[25]), "+f"(d[26]), "+f"(d[27]), "+f"(d[28]), "+f"(d[29]), "+f"(d[30]), "+f"(d[31]),
          "+f"(d[32]), "+f"(d[33]), "+f"(d[34]), "+f"(d[35]), "+f"(d[36]), "+f"(d[37]), "+f"(d[38]), "+f"(d[39]),
          "+f"(d[40]), "+f"(d[41]), "+f"(d[42]), "+f"(d[43]), "+f"(d[44]), "+f"(d[45]), "+f"(d[46]), "+f"(d[47]),
          "+f"(d[48]), "+f"(d[49]), "+f"(d[50]), "+f"(d[51]), "+f"(d[52]), "+f"(d[53]), "+f"(d[54]), "+f"(d[55]),
          "+f"(d[56]), "+f"(d[57]), "+f"(d[58]), "+f"(d[59]), "+f"(d[60]), "+f"(d[61]), "+f"(d[62]), "+f"(d[63])
        : "l"(da), "l"(db), "r"(sd));
}

__device__ __forceinline__ void wgmma_n64(float (&d)[32], uint64_t da, uint64_t db, int sd) {
    asm volatile("{\n.reg .pred p;\nsetp.ne.b32 p, %34, 0;\n"
        "wgmma.mma_async.sync.aligned.m64n64k16.f32.bf16.bf16 "
        "{%0,%1,%2,%3,%4,%5,%6,%7,%8,%9,%10,%11,%12,%13,%14,%15,"
        "%16,%17,%18,%19,%20,%21,%22,%23,%24,%25,%26,%27,%28,%29,%30,%31}, %32, %33, p, 1, 1, 0, 1;\n}\n"
        : "+f"(d[0]), "+f"(d[1]), "+f"(d[2]), "+f"(d[3]), "+f"(d[4]), "+f"(d[5]), "+f"(d[6]), "+f"(d[7]),
          "+f"(d[8]), "+f"(d[9]), "+f"(d[10]), "+f"(d[11]), "+f"(d[12]), "+f"(d[13]), "+f"(d[14]), "+f"(d[15]),
          "+f"(d[16]), "+f"(d[17]), "+f"(d[18]), "+f"(d[19]), "+f"(d[20]), "+f"(d[21]), "+f"(d[22]), "+f"(d[23]),
          "+f"(d[24]), "+f"(d[25]), "+f"(d[26]), "+f"(d[27]), "+f"(d[28]), "+f"(d[29]), "+f"(d[30]), "+f"(d[31])
        : "l"(da), "l"(db), "r"(sd));
}

constexpr int STAGE_BYTES = 49152, NSTAGE = 4;
constexpr int GEMM_SMEM = NSTAGE * STAGE_BYTES + 128;

struct GemmSmem { uint32_t st, full, empty; };
__device__ __forceinline__ GemmSmem gemm_setup(uint8_t* raw, int releases) {
    GemmSmem g;
    g.st = smem_u32(raw);
    if (g.st & 1023) __trap();
    g.full = g.st + NSTAGE * STAGE_BYTES; g.empty = g.full + 64;
    if (threadIdx.x == 0) {
        for (int s = 0; s < NSTAGE; s++) { mbar_init(g.full + 8 * s, 1); mbar_init(g.empty + 8 * s, releases); }
        asm volatile("fence.mbarrier_init.release.cluster;" ::: "memory");
        asm volatile("fence.proxy.async.shared::cta;" ::: "memory");
    }
    __syncthreads();
    return g;
}
__device__ __forceinline__ void mbar_arrive_one(uint32_t bar, uint32_t who) {
    asm volatile("{\n.reg .pred p;\nsetp.eq.u32 p, %1, 0;\n@p mbarrier.arrive.shared::cta.b64 _, [%0];\n}" ::"r"(bar), "r"(who) : "memory");
}
template <int BM, int BN, int KPS, typename ACC>
__device__ __forceinline__ void gemm_stage(ACC& acc, uint32_t stage, int wg, bool first) {
    const uint64_t da = desc_sw128(stage + wg * 8192, 16, 1024);
    const uint64_t db = desc_sw128(stage + KPS * BM * 128, 8192, 1024);
    wg_fence();
#pragma unroll
    for (int k = 0; k < 4 * KPS; k++) {
        const uint64_t a = da + (k >> 2) * (BM * 8) + (k & 3) * 2, b = db + k * 128;
        if constexpr (BN == 256) wgmma_n256(acc, a, b, first && k == 0 ? 0 : 1);
        else if constexpr (BN == 128) wgmma_n128(acc, a, b, first && k == 0 ? 0 : 1);
        else wgmma_n64(acc, a, b, first && k == 0 ? 0 : 1);
    }
    wg_commit();
}

__device__ __forceinline__ void kv_store_unit(const uint32_t (&pk)[64], int u, bf16* dst, int t) {
    const int G = (u >> 2) * 2 + (u & 1), hh = (u >> 1) & 1;
    uint32_t r0 = pk[(4 * G + 0) * 2 + hh], r1 = pk[(4 * G + 1) * 2 + hh], r2 = pk[(4 * G + 2) * 2 + hh], r3 = pk[(4 * G + 3) * 2 + hh];
    quad_transpose(r0, r1, r2, r3, t);
#define KVST ".cs"
    asm volatile("st.global" KVST ".v4.u32 [%0], {%1,%2,%3,%4};" ::"l"(dst + (size_t)hh * 8 * PW + G * 32), "r"(r0), "r"(r1), "r"(r2), "r"(r3) : "memory");
}

#define TLK(slot)
#define TLK2(slot)
__device__ __forceinline__ uint32_t near_page(int pair, int line) {
    uint32_t best[2] = {~0u, ~0u};
#pragma unroll 1
#define PMIN 8
#define PMAX 16
    for (int i = 0; i < PMAX; i++) {
        if (i >= PMIN && max(best[0], best[1]) - min(best[0], best[1]) > 110 && max(best[0], best[1]) - min(best[0], best[1]) < 300) break;
        uint32_t t0, t1, v;
        asm volatile("mov.u32 %0, %%clock;" : "=r"(t0)::"memory");
        asm volatile("atom.relaxed.gpu.global.or.b32 %0, [%1], -1;" : "=r"(v) : "l"(g_x + pair * 1024 + (i & 1) * 512 + line * 16) : "memory");
        asm volatile("{\n.reg .pred p;\nsetp.ne.u32 p, %1, 0x12345;\nmov.u32 %0, -1;\n@p mov.u32 %0, %%clock;\n}" : "=r"(t1) : "r"(v) : "memory");
        if (i & 1) best[1] = min(best[1], t1 - t0); else best[0] = min(best[0], t1 - t0);
    }
    return best[1] < best[0];
}
__device__ __forceinline__ void map_pages(int c) {
    uint32_t smid;
    asm("mov.u32 %0, %%smid;" : "=r"(smid));
    const uint32_t side = near_page(0, c & 31);
    g_side[smid & 255] = side;
    for (int p = c; p < XPAIRS; p += 132) g_home[p] = near_page(p, 0) ^ side;
}

__device__ __forceinline__ void kv_tile(int c, int n, int& m, int& nb) {
    if (c < 96) { m = (c & 3) + 4 * n; nb = c >> 2; }
    else {
        const int i = ((c - 96) >> 1) + 18 * n, j = i - 48 * NTA, p = j < 0 ? i / 24 : 2 * NTA + j / 48;
        m = 2 * p + (c & 1); nb = j < 0 ? 24 + i % 24 : j % 48;
    }
}

__global__ void __launch_bounds__(384, 1)
k_kv(const __grid_constant__ CUtensorMap mx, const __grid_constant__ CUtensorMap mwk, const __grid_constant__ CUtensorMap mwv,
     const __grid_constant__ CUtensorMap mwq, const bf16* __restrict__ Wq, const bf16* __restrict__ Wo, int c0) {
    extern __shared__ __align__(1024) uint8_t smem_gemm[];
    const int c = c0 + blockIdx.x, ntile = c < 96 ? NTA : (384 - 48 * NTA + 17 - ((c - 96) >> 1)) / 18;
    if (c != 96) asm volatile("griddepcontrol.launch_dependents;");
    const uint32_t bar_done = smem_u32(smem_gemm) + NSTAGE * STAGE_BYTES + 96;
    if (threadIdx.x == 0) { mbar_init(bar_done, 8); mbar_init(bar_done + 8, 8); }
    GemmSmem g = gemm_setup(smem_gemm, 4);
    if (threadIdx.x == 0) TLK(0);
    uint32_t rank, peer_empty;
    asm("mov.u32 %0, %%cluster_ctarank;" : "=r"(rank));
    asm("mapa.shared::cluster.u32 %0, %1, %2;" : "=r"(peer_empty) : "r"(g.empty), "r"(rank ^ 1));
    asm volatile("barrier.cluster.arrive.relaxed.aligned;\nbarrier.cluster.wait.aligned;" ::: "memory");
    auto release = [&](int s) {
        asm volatile("{\n.reg .pred p;\nsetp.eq.u32 p, %2, 0;\n@p mbarrier.arrive.relaxed.cta.shared::cta.b64 _, [%0];\n"
                     "@p mbarrier.arrive.relaxed.cluster.shared::cluster.b64 _, [%1];\n}"
                     ::"r"(g.empty + 8 * s), "r"(peer_empty + 8 * s), "r"(threadIdx.x & 127) : "memory");
    };
    const int wg = __shfl_sync(~0u, threadIdx.x >> 7, 0);
    if (wg == 0) {
        asm volatile("setmaxnreg.dec.sync.aligned.u32 40;");
        if (threadIdx.x == 0) {
            for (int it = 0; it < ntile * 16; it++) {
                const int s = it & 3, kb = it & 15;
                int m, nb;
                kv_tile(c, it >> 4, m, nb);
                mbar_wait(g.empty + 8 * s, ((it >> 2) & 1) ^ 1);
                mbar_expect_tx(g.full + 8 * s, STAGE_BYTES);
                tma2d(g.st + s * STAGE_BYTES, &mx, kb * 64, m * 128, g.full + 8 * s);
                asm volatile("cp.async.bulk.tensor.3d.shared::cluster.global.mbarrier::complete_tx::bytes.multicast::cluster "
                             "[%0], [%1, {%3, %4, %5}], [%2], %6;"
                             ::"r"(g.st + s * STAGE_BYTES + 16384 + (c & 1) * 16384), "l"(nb < 16 ? &mwk : nb < 32 ? &mwv : &mwq), "r"(g.full + 8 * s),
                               "r"(0), "r"(kb * 64), "r"((nb & 15) * 4 + (c & 1) * 2), "h"((uint16_t)(3u << (rank & ~1u))) : "memory");
#define PF0 (16 * NTA - 22)
                if (c < 96 && it >= PF0 && (it - PF0) * 96 + c < 2048)
                    asm volatile("cp.async.bulk.prefetch.L2.global [%0], 4096;" ::"l"((const char*)Wo + ((it - PF0) * 96 + c) * 4096) : "memory");
            }
        } else if (threadIdx.x == 32) {
            if (c == 96) {
                for (int i = 0; i < 64; i++) reinterpret_cast<uint4*>(g_flag)[i] = make_uint4(0, 0, 0, 0);
                asm volatile("fence.acq_rel.gpu;\ngriddepcontrol.launch_dependents;\ngriddepcontrol.wait;\n"
                             "fence.acq_rel.gpu;\nred.relaxed.gpu.global.add.u32 [%0], 1;" ::"l"(g_flag + 8) : "memory");
            }
        } else if (threadIdx.x == 64) {
            for (int n = 0; n < (c < 96 ? 0 : ntile); n++) {
                int m, nb;
                kv_tile(c, n, m, nb);
                mbar_wait(bar_done + (n & 1) * 8, (n >> 1) & 1);
                asm volatile("fence.acq_rel.gpu;\nred.relaxed.gpu.global.add.u32 [%0], 1;" ::"l"(g_flag + (m >> 1)) : "memory");
            }
        } else if (threadIdx.x >= 96) {
            const uint4 ones = make_uint4(~0u, ~0u, ~0u, ~0u);
            for (int i = c * 32 + threadIdx.x - 96; i < XPAIRS * 512; i += 132 * 32) reinterpret_cast<uint4*>(g_x)[i] = ones;
            __syncwarp();
            if (threadIdx.x == 96) {
                map_pages(c);
                if (c >= 96) asm volatile("fence.acq_rel.gpu;\nred.relaxed.gpu.global.add.u32 [%0], 1;" ::"l"(g_flag + 8) : "memory");
            }
        }
    } else {
        asm volatile("setmaxnreg.inc.sync.aligned.u32 232;");
        const int cw = wg - 1, lane = threadIdx.x & 31, t = lane & 3;
        bf16* const dst0 = g_kv + (size_t)(cw * 64 + ((threadIdx.x >> 5) & 3) * 16 + (lane >> 2)) * PW + t * 8;
        bf16* dst = dst0;
        float acc[128];
        uint32_t pk[64];
#pragma unroll 1
        for (int tile = 0; tile < ntile; tile++) {
#pragma unroll
            for (int kb = 0; kb < 16; kb++) {
                mbar_wait_u(g.full + 8 * (kb & 3), (kb >> 2) & 1);
                if (kb == 0 && tile == 0 && threadIdx.x == 128) TLK2(0);
                gemm_stage<128, 256, 1>(acc, g.st + (kb & 3) * STAGE_BYTES, cw, kb == 0);
                if (tile > 0) {
                    kv_store_unit(pk, kb, dst, t);
                    if (kb == 15) { __syncwarp(); mbar_arrive_one(bar_done + (~tile & 1) * 8, lane); }
                }
                if (kb > 0) {
                    wg_wait<1>();
                    if (kb <= 12 || tile < ntile - 1) release((kb - 1) & 3);
                }
            }
            wg_wait<0>();
            if (tile < 4 && threadIdx.x == 128) TLK2(tile + 1);
            if (tile < ntile - 1) release(3);
#pragma unroll
            for (int i = 0; i < 64; i++) pk[i] = pack2(acc[2 * i], acc[2 * i + 1]);
            int m, nb;
            kv_tile(c, tile, m, nb);
            dst = dst0 + (size_t)m * 128 * PW + nb * 256;
        }
        if (threadIdx.x == 128) TLK(2);
#pragma unroll
        for (int u = 0; u < 16; u++) kv_store_unit(pk, u, dst, t);
        __syncwarp();
        mbar_arrive_one(bar_done + (~ntile & 1) * 8, lane);
        if (threadIdx.x == 128) TLK(1);
    }
}

constexpr int NS1 = 31;
#define RB1 4
#define PFC 4
constexpr int C_W1 = 0;
constexpr int C_W2 = C_W1 + 8 * NS1 * 512;
constexpr int C_KV = C_W2 + 14 * 8 * 512;
constexpr int C_RED = C_KV + 16384;
constexpr int C_QKV = C_RED + 64 * 272;
constexpr int QKV_SZ = 3 * 8 * 272;
constexpr int C_SC = C_RED;
constexpr int C_OB = C_SC + 2 * 8 * 52 * 4;
constexpr int C_BAR = C_QKV + 2 * QKV_SZ;
__host__ __device__ constexpr int smem_idx(int ks, int j) {
    return ks == 0 ? j : ks < 3 ? (j < 4 ? 4 + 4 * ks + j : -1) : (j < 3 ? 7 + 3 * ks + j : -1);
}
constexpr int CHAIN_SMEM = C_BAR + 64;
#define TS(i)
#define TG(i)

#define DLY3 10
#define DLY1 4
#define DLY0 4
#define DLY1A 11
#define DLY0A 0
#define DLY1B 4
#define PFD 3
#define PFI 0
#define DLYW 4
#define DLYQ 3
#define DLYS 0
template <int N> __device__ __forceinline__ uint32_t delayed(uint32_t x, uint32_t self) {
    uint32_t p = self;
#pragma unroll
    for (int i = 0; i < N; i++) asm volatile("ld.volatile.shared.u32 %0, [%0];" : "+r"(p)::"memory");
    return x + (p - self);
}
__device__ __forceinline__ int fresh(int x) { asm volatile("mov.b32 %0, %0;" : "+r"(x)); return x; }
__device__ __forceinline__ void lds128v(uint32_t (&r)[4], uint32_t a) {
    asm volatile("ld.volatile.shared.v4.u32 {%0,%1,%2,%3}, [%4];" : "=r"(r[0]), "=r"(r[1]), "=r"(r[2]), "=r"(r[3]) : "r"(a) : "memory");
}
__device__ __forceinline__ uint2 lds64(uint32_t a) {
    uint2 v;
    asm volatile("ld.shared.v2.u32 {%0,%1}, [%2];" : "=r"(v.x), "=r"(v.y) : "r"(a) : "memory");
    return v;
}
#define LDQ ".L1::no_allocate"
__device__ __forceinline__ uint4 ldw128(const void* p) {
    uint4 v;
    asm volatile("ld.global.nc" LDQ ".v4.u32 {%0,%1,%2,%3}, [%4];" : "=r"(v.x), "=r"(v.y), "=r"(v.z), "=r"(v.w) : "l"(p));
    return v;
}
#define P8_LD(i) "ld.relaxed.gpu.global.b64 d" #i ", [src + " #i " * 256];\n"
#define P8_X(i) "mov.b64 {x" #i ", y" #i "}, d" #i ";\n"
#define P8_HEAD(SRC) "{\n.reg .pred p, q;\n.reg .b64 src, d<8>;\n.reg .b32 n, x<8>, y<8>, m0, m1;\nmov.b64 src, " SRC ";\n"         \
                P8_LD(0) P8_LD(1) P8_LD(2) P8_LD(3) P8_LD(4) P8_LD(5) P8_LD(6) P8_LD(7) "mov.u32 n, 0;\nCHECK:\n" \
                P8_X(0) P8_X(1) P8_X(2) P8_X(3) P8_X(4) P8_X(5) P8_X(6) P8_X(7)
#define P8_VOTE "vote.sync.all.pred p, p, -1;\n@p bra.uni DONE;\n"
#define P8_TAIL "add.u32 n, n, 1;\nsetp.lt.u32 p, n, 0x100000;\n@p bra.uni CHECK;\ntrap;\nDONE:\n"
#define S8_LD(i) "ld.relaxed.gpu.global.b64 %" #i ", [%8 + " #i " * 256];\n"
__device__ __forceinline__ void fetch_state(uint64_t (&d)[8], const void* src) {
    asm volatile(S8_LD(0) S8_LD(1) S8_LD(2) S8_LD(3) S8_LD(4) S8_LD(5) S8_LD(6) S8_LD(7)
                 : "=&l"(d[0]), "=&l"(d[1]), "=&l"(d[2]), "=&l"(d[3]), "=&l"(d[4]), "=&l"(d[5]), "=&l"(d[6]), "=&l"(d[7]) : "l"(src) : "memory");
}
__device__ __forceinline__ void settle_state(uint64_t (&d)[8], const void* src) {
#define S8_X(i) "mov.b64 {x" #i ", _}, %" #i ";\n"
#define S8_R(i) "setp.eq.u32 q, x" #i ", 0xffffffff;\n@q " S8_LD(i)
    asm volatile("{\n.reg .pred p, q;\n.reg .b32 n, x<8>, m0, m1;\nmov.u32 n, 0;\nCHECK:\n"
                 S8_X(0) S8_X(1) S8_X(2) S8_X(3) S8_X(4) S8_X(5) S8_X(6) S8_X(7)
                 "max.u32 m0, x0, x1;\nmax.u32 m0, m0, x2;\nmax.u32 m1, x3, x4;\nmax.u32 m1, m1, x5;\nmax.u32 m0, m0, x6;\n"
                 "max.u32 m0, m0, x7;\nmax.u32 m0, m0, m1;\nsetp.ne.u32 p, m0, 0xffffffff;\n" P8_VOTE
                 S8_R(0) S8_R(1) S8_R(2) S8_R(3) S8_R(4) S8_R(5) S8_R(6) S8_R(7) P8_TAIL "}"
                 : "+l"(d[0]), "+l"(d[1]), "+l"(d[2]), "+l"(d[3]), "+l"(d[4]), "+l"(d[5]), "+l"(d[6]), "+l"(d[7]) : "l"(src) : "memory");
}
__device__ __forceinline__ uint64_t poll_sum(const void* src, uint32_t tag, uint32_t sel) {
#define P8_RT(i) "lop3.b32 m0, x" #i ", %2, 1, 0x28;\nsetp.ne.u32 q, m0, 0;\n@q " P8_LD(i)
#define P8_MMA(c, i, z) "mma.sync.aligned.m16n8k8.row.col.f32.bf16.bf16.f32 {" #c "0," #c "1," #c "2," #c "3}, {x" #i ", y" #i "}, {%3}, {" #z "0," #z "1," #z "2," #z "3};\n"
    uint64_t r;
    asm volatile(P8_HEAD("%1") "{\n.reg .f32 a<4>, b<4>, z<4>;\nmov.f32 z0, 0f00000000;\nmov.f32 z1, z0;\nmov.f32 z2, z0;\nmov.f32 z3, z0;\n"
                 P8_MMA(a, 0, z) P8_MMA(b, 1, z) P8_MMA(a, 2, a) P8_MMA(b, 3, b) P8_MMA(a, 4, a) P8_MMA(b, 5, b) P8_MMA(a, 6, a) P8_MMA(b, 7, b)
                 "add.f32 a0, a0, b0;\nadd.f32 a1, a1, b1;\nadd.f32 a2, a2, b2;\nadd.f32 a3, a3, b3;\n"
                 "cvt.rn.bf16x2.f32 m0, a1, a0;\ncvt.rn.bf16x2.f32 m1, a3, a2;\nmov.b64 %0, {m0, m1};\n}\n"
                 "lop3.b32 m0, x0, x1, %2, 0x7e;\nlop3.b32 m1, x2, x3, %2, 0x7e;\nlop3.b32 m0, m0, x4, %2, 0xf6;\n"
                 "lop3.b32 m1, m1, x5, %2, 0xf6;\nlop3.b32 m0, m0, x6, %2, 0xf6;\nlop3.b32 m1, m1, x7, %2, 0xf6;\n"
                 "lop3.b32 m0, m0, m1, 1, 0xa8;\nsetp.eq.u32 p, m0, 0;\n" P8_VOTE
                 P8_RT(0) P8_RT(1) P8_RT(2) P8_RT(3) P8_RT(4) P8_RT(5) P8_RT(6) P8_RT(7) P8_TAIL "}"
                 : "=&l"(r) : "l"(src), "r"(tag), "r"(sel) : "memory");
    return r;
}
__device__ __forceinline__ void wait_count_u(const uint32_t* p, uint32_t need) {
    asm volatile("{\n.reg .pred p;\n.reg .u32 n, v;\nmov.u32 n, 0;\nAGAIN:\nld.acquire.gpu.global.u32 v, [%0];\nsetp.ge.u32 p, v, %1;\n"
                 "vote.sync.all.pred p, p, -1;\n@p bra.uni DONE;\nadd.u32 n, n, 1;\nsetp.lt.u32 p, n, 0x100000;\n@p bra.uni AGAIN;\ntrap;\n"
                 "DONE:\nfence.proxy.async.global;\n}" ::"l"(p), "r"(need) : "memory");
}
__device__ __forceinline__ uint32_t movm(uint32_t x) { asm volatile("movmatrix.sync.aligned.m8n8.trans.b16 %0, %0;" : "+r"(x)); return x; }
template <int NK, typename F>
__device__ __forceinline__ void attend(uint32_t sb, uint32_t lm, uint32_t qs, uint32_t xq, int i8, int lane, bf16* dst, F mid) {
    const int r8 = lane & 7, m4 = lane >> 3;
    const float sl2e = 0.08838834764831845f * 1.4426950408889634f;
    const uint32_t lk = sb + C_KV + ((m4 & 1) * 8 + r8) * 128 + (((m4 >> 1) ^ r8) << 4);
    const uint32_t lkm = sb + xq + (8 + r8) * 272 + (m4 & 1) * 32 + (m4 >> 1) * 16;
    asm volatile("cp.async.wait_all;" ::: "memory");
    __syncwarp();
    float x[4][4];
#pragma unroll
    for (int i = 0; i < 4; i++) x[i][0] = x[i][1] = x[i][2] = x[i][3] = 0.f;
#pragma unroll
    for (int kp = 0; kp < 4; kp++) {
        uint32_t q[4], a[4];
        ldsm4(q, lm + qs + kp * 64);
        ldsm4(a, lkm + kp * 64);
        mma16816(x[2], a[0], a[1], a[2], a[3], q[0], q[1]);
        mma16816(x[3], a[0], a[1], a[2], a[3], q[2], q[3]);
#pragma unroll
        for (int u = 0; u < 4; u++) {
            if ((u & 1) >= NK) continue;
            ldsm4(a, (lk ^ (((kp & 1) * 2 + (u >> 1)) << 5)) + (kp >> 1) * 4096 + (u & 1) * 2048);
            mma16816(x[u & 1], a[0], a[1], a[2], a[3], q[u & 2], q[(u & 2) + 1]);
        }
    }
    x[2][0] += x[3][2]; x[2][1] += x[3][3];
    const int lim = i8 + 2 * (lane & 3) - (lane >> 2);
    uint32_t p[5];
    {
        float m[2], e[5][2];
#pragma unroll
        for (int b = 0; b < 2; b++) {
            e[4][b] = m[b] = x[2][b];
#pragma unroll
            for (int j = 0; j < 2 * NK; j++) {
                e[j][b] = j < 2 * NK - 2 || 8 * j - b <= lim ? x[j >> 1][(j & 1) * 2 + b] : -3.0e38f;
                m[b] = fmaxf(m[b], e[j][b]);
            }
        }
#pragma unroll
        for (int o = 4; o < 32; o <<= 1) {
            m[0] = fmaxf(m[0], __shfl_xor_sync(~0u, m[0], o));
            m[1] = fmaxf(m[1], __shfl_xor_sync(~0u, m[1], o));
        }
        m[0] *= sl2e; m[1] *= sl2e;
#pragma unroll
        for (int j = 0; j < 5; j++)
            if (j < 2 * NK || j == 4) p[j] = movm(pack2(ex2(fmaf(e[j][0], sl2e, -m[0])), ex2(fmaf(e[j][1], sl2e, -m[1]))));
    }
    const uint32_t lvt = sb + C_KV + 8192 + ((m4 >> 1) * 8 + r8) * 128 + (((m4 & 1) ^ r8) << 4), one = 0x3f803f80u;
    float sm[4] = {0.f, 0.f, 0.f, 0.f}, c[8][4];
    mma16816(sm, one, one, one, one, p[0], p[1]);
    if (NK == 2) mma16816(sm, one, one, one, one, p[2], p[3]);
    mma1688(sm, one, one, p[4]);
#pragma unroll
    for (int j = 0; j < 8; j++) c[j][0] = c[j][1] = c[j][2] = c[j][3] = 0.f;
#pragma unroll
    for (int kk = 0; kk < NK; kk++)
#pragma unroll
        for (int j = 0; j < 8; j++) {
            uint32_t a[4];
            ldsm4t(a, (lvt ^ ((j & 3) << 5)) + (j >> 2) * 4096 + kk * 2048);
            mma16816(c[j], a[0], a[1], a[2], a[3], p[2 * kk], p[2 * kk + 1]);
        }
    float i0, i1;
    asm("rcp.approx.ftz.f32 %0, %1;" : "=f"(i0) : "f"(sm[0]));
    asm("rcp.approx.ftz.f32 %0, %1;" : "=f"(i1) : "f"(sm[1]));
    uint32_t o[4][4];
#pragma unroll
    for (int j = 0; j < 4; j++) {
        uint32_t a[4];
        ldsm4t(a, lm + xq + 16 * 272 + j * 64);
        mma1688(c[2 * j], a[0], a[1], p[4]);
        mma1688(c[2 * j + 1], a[2], a[3], p[4]);
#pragma unroll
        for (int u = 0; u < 4; u++) o[j][u] = pack2(c[2 * j + (u >> 1)][(u & 1) * 2] * i0, c[2 * j + (u >> 1)][(u & 1) * 2 + 1] * i1);
    }
#pragma unroll
    for (int j = 0; j < 4; j++) stsm4t(lm + qs + j * 64, o[j][0], o[j][1], o[j][2], o[j][3]);
    mid();
    __syncwarp();
#pragma unroll
    for (int j = 0; j < 4; j++) lds128(o[j], sb + qs + ((lane >> 4) + 2 * j) * 272 + (lane & 15) * 16);
#pragma unroll
    for (int j = 0; j < 4; j++)
        asm volatile("st.global.v4.u32 [%0], {%1,%2,%3,%4};" ::"l"(dst + (size_t)2 * j * HD), "r"(o[j][0]), "r"(o[j][1]), "r"(o[j][2]), "r"(o[j][3]) : "memory");
}
__device__ __forceinline__ void sum8(float (&c)[4], const uint2 (&v)[8], uint32_t idn) {
    float d[4] = {0.f, 0.f, 0.f, 0.f};
    c[0] = c[1] = c[2] = c[3] = 0.f;
    mma16816(c, v[0].x, v[0].y, v[1].x, v[1].y, idn, idn);
    mma16816(d, v[2].x, v[2].y, v[3].x, v[3].y, idn, idn);
    mma16816(c, v[4].x, v[4].y, v[5].x, v[5].y, idn, idn);
    mma16816(d, v[6].x, v[6].y, v[7].x, v[7].y, idn, idn);
    c[0] += d[0]; c[1] += d[1]; c[2] += d[2]; c[3] += d[3];
}

#define CLS 6
__global__ void __cluster_dims__(CLS, 1, 1) __launch_bounds__(256, 1)
k_chain(const bf16* __restrict__ mem0, const bf16* __restrict__ Wq, const bf16* __restrict__ Wk, const bf16* __restrict__ Wv,
        const bf16* __restrict__ Wo, const __grid_constant__ CUtensorMap mkv) {
    extern __shared__ __align__(1024) uint8_t smem_chain[];
    const uint32_t sb = smem_u32(smem_chain);
    if (sb & 1023) __trap();
    const int w = __shfl_sync(~0u, threadIdx.x >> 5, 0), lane = __shfl_sync(~0u, threadIdx.x & 31, threadIdx.x & 31);
    const int tid = w * 32 + lane, g = lane >> 2, t = lane & 3;
    auto pin = [&](uint32_t x) { asm volatile("shfl.sync.idx.b32 %0, %0, %1, 31, -1;" : "+r"(x) : "r"(lane) : "memory"); return x; };
    const int h = blockIdx.x / 3, r = blockIdx.x - 3 * h;
    const uint32_t bar_x = sb + C_BAR, bar_kv = sb + C_BAR + 8, bar_go = sb + C_BAR + 16, bar_w = sb + C_BAR + 24, self = sb + C_BAR + 60;
    asm volatile("griddepcontrol.launch_dependents;");
    const int tbase = r == 0 ? 0 : 1 + 21 * r, ntile = r == 0 ? 22 : 21;
    uint32_t side;
    if (tid == 0) {
        mbar_init(bar_x, 8); mbar_init(bar_kv, 1); mbar_init(bar_go, 1); mbar_init(bar_w, 1);
        asm volatile("st.shared.u32 [%0], %0;" ::"r"(self) : "memory");
        asm volatile("fence.mbarrier_init.release.cluster;" ::: "memory");
        asm volatile("fence.proxy.async.shared::cta;" ::: "memory");
        mbar_expect_tx(bar_w, 128 * 32 * ntile);
    }
    __syncthreads();
    asm volatile("barrier.cluster.arrive.relaxed.aligned;" ::: "memory");
    if (tid < 128)
        asm volatile("cp.async.bulk.shared::cluster.global.mbarrier::complete_tx::bytes [%0], [%1], %2, [%3];"
                     ::"r"(sb + C_W1 + tid * 720), "l"(Wo + (size_t)(h * 128 + tid) * DM + tbase * 16), "r"(32 * ntile), "r"(bar_w) : "memory");
    const int tile0 = tbase + 7 - w;
    const bool three = w >= (r == 0 ? 2 : 3);
    const uint32_t wa = pin(sb + tid * 16);
#define W1A(i) (wa + C_W1 + (i) * 4096)
#define W2A(x) (wa + C_W2 + ((x) < 8 ? (x) * 4096 : 32768 - 1024 + ((x) - 8) * 3072))
    uint32_t wo0[8][4], wr[64][4];
    {
        const bf16* W = (r == 0 ? Wq : r == 1 ? Wk : Wv) + (size_t)(128 * w + (lane >> 4)) * HD + h * 128 + 8 * (lane & 15);
        uint4 raw[8][8];
        auto fetch = [&](int ks) {
#pragma unroll
            for (int i = 0; i < 8; i++) raw[ks][i] = ldw128(W + (size_t)(16 * ks + 2 * i) * HD);
        };
        fetch(0); fetch(1); fetch(2); fetch(3);
    asm("mov.u32 %0, %%smid;" : "=r"(side));
    side = __ldcg(g_side + (side & 255)) & 1;
    if (tid == 0 && r > 0) asm volatile("st.relaxed.gpu.global.u32 [%0], %1;" ::"l"(g_flag + 128 + 2 * h + r - 1), "r"(2 | side) : "memory");
        if (w == 0) TG(0);
        mbar_wait_u(bar_w, 0);
        if (w == 0) TG(1);
        const uint32_t p = sb + C_W1 + ((lane & 7) + (lane >> 4) * 8) * 720 + (7 - w) * 32 + ((lane >> 3) & 1) * 16;
#pragma unroll
        for (int ks = 0; ks < 8; ks++) {
            uint32_t a[4];
            ldsm4t(wo0[ks], p + ks * 16 * 720);
            ldsm4t(a, p + ks * 16 * 720 + 256);
            sts128(W2A(ks), a[0], a[1], a[2], a[3]);
            if (three) { ldsm4t(a, p + ks * 16 * 720 + 512); sts128(W2A(8 + ks), a[0], a[1], a[2], a[3]); }
        }
        __syncthreads();
        if (w < PFI)
            asm volatile("prefetch.global.L2 [%0];\nprefetch.global.L2 [%0 + 128];" ::"l"(g_kv + (size_t)tid * PW + r * HD + h * 128) : "memory");
        if (w == 0) TG(2);
        const uint32_t stg = sb + C_KV + w * 4096;
        const uint32_t rd = stg + ((lane & 7) + 8 * (lane >> 4)) * 256 + ((((lane >> 3) & 1) ^ (lane & 7)) << 4);
#pragma unroll
        for (int ks = 0; ks < 8; ks++) {
#pragma unroll
            for (int i = 0; i < 8; i++)
                sts128(stg + (2 * i + (lane >> 4)) * 256 + (((lane & 15) ^ (((2 * i) & 6) | (lane >> 4))) << 4),
                       raw[ks][i].x, raw[ks][i].y, raw[ks][i].z, raw[ks][i].w);
            if (ks < 2) fetch(ks + 4);
            if (ks == 3 || ks == 5) fetch(ks / 2 + 5);
            __syncwarp();
#pragma unroll
            for (int j = 0; j < 8; j++) {
                if (smem_idx(ks, j) >= 0) {
                    uint32_t a[4];
                    ldsm4t(a, rd ^ (j << 5));
                    sts128(W1A(smem_idx(ks, j)), a[0], a[1], a[2], a[3]);
                } else ldsm4t(wr[8 * ks + j], rd ^ (j << 5));
            }
            __syncwarp();
        }
    }
    if (w == 0) TG(3);
    wait_count_u(g_flag + (lane & 8), lane & 8 ? 37 : 48);
    asm volatile("fence.proxy.async.shared::cta;" ::: "memory");
    __syncthreads();
    if (tid == 0) {
        mbar_expect_tx(bar_kv, 16384);
        tma3d(sb + C_KV, &mkv, 0, 0, 2 * h, bar_kv);
        tma3d(sb + C_KV + 8192, &mkv, 0, 0, 64 + 2 * h, bar_kv);
    }
    asm volatile("barrier.cluster.wait.aligned;" ::: "memory");

    auto load_kv = [&](int s) {
        asm volatile("{\n.reg .pred p;\nelect.sync _|p, -1;\n@p mbarrier.arrive.expect_tx.shared::cta.b64 _, [%2], 16384;\n"
                     "@p cp.async.bulk.tensor.3d.shared::cluster.global.mbarrier::complete_tx::bytes [%0], [%1, {%3, %4, %5}], [%2];\n"
                     "@p cp.async.bulk.tensor.3d.shared::cluster.global.mbarrier::complete_tx::bytes [%6], [%1, {%3, %4, %7}], [%2];\n}"
                     ::"r"(sb + C_KV), "l"(&mkv), "r"(bar_kv), "r"(0), "r"(s * 32), "r"(2 * h), "r"(sb + C_KV + 8192), "r"(64 + 2 * h) : "memory");
    };
    const bool attends = w == 7 || (w == 6 && r == 0);
    const int i8 = r == 0 ? (w - 4) * 8 : (r - 1) * 8;
    auto load_q = [&](int s) {
        const int l = fresh(lane);
        const bf16* p = g_kv + (size_t)(s * 32 + i8 + (l >> 4)) * PW + 2 * HD + h * 128 + (l & 15) * 8;
#pragma unroll
        for (int j = 0; j < 4; j++)
            asm volatile("cp.async.cg.shared.global [%0], [%1], 16;"
                         ::"r"(sb + C_RED + w * 2176 + ((l >> 4) + 2 * j) * 272 + (l & 15) * 16), "l"(p + (size_t)2 * j * PW) : "memory");
    };
    auto report = [&](int blk) {
        asm volatile("{\n.reg .pred p;\nelect.sync _|p, -1;\nfence.acq_rel.gpu;\n@p red.relaxed.gpu.global.add.u32 [%0], 1;\n}"
                     ::"l"(g_flag + 64 + blk) : "memory");
    };
    const float sl2e = 0.08838834764831845f * 1.4426950408889634f;
    const uint32_t idn = pin(g == 2 * t ? 0x00003f80u : g == 2 * t + 1 ? 0x3f800000u : 0u);
    const uint32_t lm = pin(sb + (lane & 7) * 272 + (lane >> 3) * 16);
    const uint32_t sa = pin(sb + C_SC + (w & 1) * (8 * 52 * 4) + (2 * t * 52 + (w < 4 ? 32 : (w & 2) * 8) + g) * 4);
    const uint32_t sr = pin(sb + C_SC + (g * 52 + 8 * t) * 4), sr2 = pin(sb + C_SC + (g * 52 + 32 + 2 * t) * 4);
    uint32_t kva;
    {
        const int pos = (w & 2) * 8 + (lane & 15), row = (pos & 24) + ((pos + (pos >> 2 & 6)) & 7);
        const int key = 4 * (lane & 6) + (((lane & 7) + 2 * (lane >> 4)) & 7);
        kva = pin(w >= 4 ? sb + C_KV + (w & 1) * 4096 + row * 128 + (((lane >> 4) ^ (row & 7)) << 4)
                         : sb + C_KV + 8192 + (w >> 1) * 4096 + key * 128 + ((((w & 1) * 4 + ((lane >> 3) & 1)) ^ (key & 7)) << 4));
    }
#define ATTEND(NK, s, mid) do {                                                                                       \
        const int l_ = fresh(lane);                                                                                      \
        attend<NK>(sb, lm, C_RED + w * 2176, C_QKV + ((s) & 1) * QKV_SZ, i8, l_,                                         \
                   g_o + (size_t)((s) * 32 + i8 + (l_ >> 4)) * HD + h * 128 + (l_ & 15) * 8, mid);                       \
    } while (0)
    auto chores = [&](int s) {
        if ((s & 3) == 0 && s) report((s >> 2) - 1);
        if ((s & 7) == 6 && s < NSEG - 2) wait_count_u(g_flag + (s >> 3) + 1, (s >> 3) + 1 < 2 * NTA ? 48 : 96);
    };
    uint32_t buf0[8][4], ring[RB1][4];
#define STAGE_W1() do {                                                            \
        _Pragma("unroll") for (int i = 0; i < 8; i++) lds128v(buf0[i], W1A(i));       \
        _Pragma("unroll") for (int i = 0; i < RB1; i++) lds128v(ring[i], W1A(8 + i)); \
    } while (0)
    auto stage_w1 = [&]() { STAGE_W1(); };
    stage_w1();
    uint32_t psel, msel0, msel1;
    {
        const int j = r > 0 ? 2 * h + r - 1 : 0, tl = min(tile0 + 8 * (lane >> 1), 63);
        uint32_t b;
        asm volatile("{\n.reg .pred p;\n.reg .u32 n;\nmov.u32 n, 0;\nAGAIN:\nld.relaxed.gpu.global.u32 %0, [%1];\nsetp.ne.u32 p, %0, 0;\n"
                     "vote.sync.all.pred p, p, -1;\n@p bra.uni DONE;\nadd.u32 n, n, 1;\nsetp.lt.u32 p, n, 0x100000;\n@p bra.uni AGAIN;\ntrap;\nDONE:\n}"
                     : "=&r"(b) : "l"(g_flag + 128 + tl) : "memory");
        psel = __ballot_sync(~0u, (g_home[lane == 6 ? j * 2 + ((w >> 1) & 1) : tl * 2 + (lane & 1)] ^ (lane == 6 ? side : b)) & 1);
        msel0 = __ballot_sync(~0u, (g_home[128 + lane * 4 + (w >> 1)] ^ side) & 1);
        msel1 = __ballot_sync(~0u, (g_home[256 + lane * 4 + (w >> 1)] ^ side) & 1);
        if (r > 0) {
            if (w < 4) asm volatile("prefetch.global.L2 [%0];" ::"l"(g_x + (128 + (1 + (w >> 1)) * 4 + (j >> 4)) * 1024 + (w & 1) * 512 + (j & 15) * 32 + lane) : "memory");
            if (w < 4) asm volatile("prefetch.global.L2 [%0];" ::"l"(g_x + j * 2048 + tid * 16) : "memory");
        }
    }
    uint2 bm[8];
#pragma unroll
    for (int ks = 0; ks < 8; ks++) {
        const uint32_t* p = (const uint32_t*)(mem0 + g * DM + (8 * w + ks) * 16) + t;
        bm[ks] = make_uint2(__ldg(p), __ldg(p + 4));
    }
    if (w == 0) TG(5);
#pragma unroll 1
    for (int s = 0;; s++) {
        TS(1);
        const uint32_t xq = C_QKV + (s & 1) * QKV_SZ;
        {
            float acc[8][4];
#pragma unroll
            for (int ks = 0; ks < 8; ks++) {
#pragma unroll
                for (int j = 0; j < 8; j++) {
                    const int i = smem_idx(ks, j) - 8;
                    if (ks == 0) {
                        acc[j][0] = acc[j][1] = acc[j][2] = acc[j][3] = 0.f;
                        mma16816(acc[j], buf0[j][0], buf0[j][1], buf0[j][2], buf0[j][3], bm[ks].x, bm[ks].y);
                    } else if (i >= 0) {
                        uint32_t(&a)[4] = ring[i % RB1];
                        mma16816(acc[j], a[0], a[1], a[2], a[3], bm[ks].x, bm[ks].y);
                        if (8 + i + RB1 < NS1) lds128v(a, W1A(8 + i + RB1));
                    } else {
                        const uint32_t(&a)[4] = wr[8 * ks + j];
                        mma16816(acc[j], a[0], a[1], a[2], a[3], bm[ks].x, bm[ks].y);
                    }
                }
            }
#pragma unroll
            for (int c = 0; c < 4; c++)
                stsm4t(lm + C_RED + w * 2176 + c * 64, pack2(acc[2 * c][0], acc[2 * c][1]), pack2(acc[2 * c][2], acc[2 * c][3]),
                       pack2(acc[2 * c + 1][0], acc[2 * c + 1][1]), pack2(acc[2 * c + 1][2], acc[2 * c + 1][3]));
        }
        {
            const uint32_t a = sb + C_RED + w * 272 + lane * 8;
            if (w == 3) mbar_wait_u(bar_kv, s & 1);
            TS(2);
            __syncthreads();
            TS(3);
            uint2 v[8];
#pragma unroll
            for (int i = 0; i < 8; i++) v[i] = lds64(a + i * 2176);
            float c[4];
            sum8(c, v, idn);
            const uint32_t p0 = pack2(c[0], c[1]), p1 = pack2(c[2], c[3]);
            const uint32_t dst = sb + xq + (r * 8 + w) * 272 + lane * 8;
#pragma unroll
            for (int i = 1; i < 3; i++) {
                const uint32_t peer = (h % (CLS / 3)) * 3 + (r + i >= 3 ? r + i - 3 : r + i);
                uint32_t rd, rb;
                asm("mapa.shared::cluster.u32 %0, %1, %2;" : "=r"(rd) : "r"(dst), "r"(peer));
                asm("mapa.shared::cluster.u32 %0, %1, %2;" : "=r"(rb) : "r"(bar_x), "r"(peer));
                asm volatile("st.async.weak.shared::cluster.mbarrier::complete_tx::bytes.v2.b32 [%0], {%1,%2}, [%3];"
                             ::"r"(rd), "r"(p0), "r"(p1), "r"(rb) : "memory");
            }
            sts64(dst, p0, p1);
            __syncwarp();
            asm volatile("{\n.reg .pred p;\nsetp.eq.u32 p, %1, 0;\n@p mbarrier.arrive.expect_tx.shared::cta.b64 _, [%0], 512;\n}"
                         ::"r"(bar_x), "r"(lane) : "memory");
        }
        TS(4);
        if (s == NSEG - 1) break;
        uint32_t wb[8][4], wc[8][4];
        const uint32_t po = (tile0 * 2 + (lane >> 4)) * 8192 + ((lane >> 3) & 1) * 2048 + h * 64 + (lane & 7) * 8;
        const uint32_t tag = s & 1;
        auto project = [&](const uint32_t(&wt)[8][4], const uint32_t(&ob)[4][4], int i) {
            float c0[4] = {0.f, 0.f, 0.f, 0.f}, c1[4] = {0.f, 0.f, 0.f, 0.f};
#pragma unroll
            for (int ks = 0; ks < 8; ks++)
                mma16816((ks & 1) ? c1 : c0, wt[ks][0], wt[ks][1], wt[ks][2], wt[ks][3], ob[ks >> 1][(ks & 1) * 2], ob[ks >> 1][(ks & 1) * 2 + 1]);
            uint32_t p0 = pack2(c0[0] + c1[0], c0[1] + c1[1]), p1 = pack2(c0[2] + c1[2], c0[3] + c1[3]);
            asm volatile("movmatrix.sync.aligned.m8n8.trans.b16 %0, %0;\nmovmatrix.sync.aligned.m8n8.trans.b16 %1, %1;" : "+r"(p0), "+r"(p1));
            st_rlx64((uint2*)((char*)g_x + po + i * 131072 + ((psel >> (2 * i + (lane >> 4))) & 1) * 4096), (p0 & ~1u) | tag, p1);
        };
        if (w >= 4) {
            uint32_t ka[4][4];
#pragma unroll
            for (int ks = 0; ks < 4; ks++) ldsm4(ka[ks], kva ^ (ks << 5));
            const uint32_t qa = lm + xq + (w & 1) * 128;
            TS(5);
            mbar_wait_u(bar_x, s & 1);
            TS(6);
            {
                uint32_t qb[2][4];
                ldsm4(qb[0], qa);
                ldsm4(qb[1], qa + 64);
                float c0[4] = {0.f, 0.f, 0.f, 0.f}, c1[4] = {0.f, 0.f, 0.f, 0.f};
                mma16816(c0, ka[0][0], ka[0][1], ka[0][2], ka[0][3], qb[0][0], qb[0][1]);
                mma16816(c1, ka[1][0], ka[1][1], ka[1][2], ka[1][3], qb[0][2], qb[0][3]);
                mma16816(c0, ka[2][0], ka[2][1], ka[2][2], ka[2][3], qb[1][0], qb[1][1]);
                mma16816(c1, ka[3][0], ka[3][1], ka[3][2], ka[3][3], qb[1][2], qb[1][3]);
                sts32f(sa, c0[0] + c1[0]);
                sts32f(sa + 208, c0[1] + c1[1]);
                sts32f(sa + 32, c0[2] + c1[2]);
                sts32f(sa + 240, c0[3] + c1[3]);
            }
            __syncthreads();
            TS(7);
            uint32_t wd;
            if (attends) { load_q(s); wd = delayed<DLYQ>(wa, self); } else wd = delayed<DLYW>(wa, self);
#pragma unroll
            for (int i = 0; i < 8; i++) lds128(wb[i], wd + C_W2 + i * 4096);
#pragma unroll
            for (int i = 0; i < PFC; i++) lds128(wc[i], wd + C_W2 + 32768 - 1024 + i * 3072);
            TS(8);
            __syncthreads();
            TS(9);
            uint32_t ob[4][4];
#pragma unroll
            for (int i = 0; i < 4; i++) ldsm4(ob[i], lm + C_OB + i * 64);
#pragma unroll
            for (int i = PFC; i < 8; i++) lds128(wc[i], W2A(8 + i));
            project(wb, ob, 1);
            project(wo0, ob, 0);
            project(wc, ob, 2);
        } else {
            uint32_t va[4][4];
#pragma unroll
            for (int i = 0; i < 4; i++) ldsm4t(va[i], kva ^ (((i >> 1) << 5) | ((i & 1) * 0x240)));
#pragma unroll
            for (int i = 0; i < 8; i++) lds128(wb[i], W2A(i));
            const uint32_t qa = lm + xq + (w & 1) * 128, oa = lm + w * 64;
            TS(5);
            mbar_wait_u(bar_x, s & 1);
            TS(6);
            if (w < 2) {
                uint32_t qb[2][4], km[2][4];
                ldsm4(qb[0], qa);
                ldsm4(km[0], qa + 8 * 272);
                ldsm4(qb[1], qa + 64);
                ldsm4(km[1], qa + 8 * 272 + 64);
                float c0[4] = {0.f, 0.f, 0.f, 0.f}, c1[4] = {0.f, 0.f, 0.f, 0.f};
                mma16816(c0, km[0][0], km[0][1], km[0][2], km[0][3], qb[0][0], qb[0][2]);
                mma16816(c1, km[0][0], km[0][1], km[0][2], km[0][3], qb[0][1], qb[0][3]);
                mma16816(c0, km[1][0], km[1][1], km[1][2], km[1][3], qb[1][0], qb[1][2]);
                mma16816(c1, km[1][0], km[1][1], km[1][2], km[1][3], qb[1][1], qb[1][3]);
                sts32f(sa, c0[0] + c1[2]);
                sts32f(sa + 208, c0[1] + c1[3]);
            }
            __syncthreads();
            TS(7);
            {
                float4 x0 = lds128f(sr), y0 = lds128f(sr + 1664), x1 = lds128f(sr + 16), y1 = lds128f(sr + 1680);
                float2 x2 = lds64f(sr2), y2 = lds64f(sr2 + 1664);
                float p[10] = {x0.x + y0.x, x0.y + y0.y, x0.z + y0.z, x0.w + y0.w, x1.x + y1.x,
                               x1.y + y1.y, x1.z + y1.z, x1.w + y1.w, x2.x + y2.x, x2.y + y2.y};
                float m = fmaxf(fmaxf(fmaxf(p[0], p[1]), fmaxf(p[2], p[3])), fmaxf(fmaxf(fmaxf(p[4], p[5]), fmaxf(p[6], p[7])), fmaxf(p[8], p[9])));
                const float m1 = __shfl_xor_sync(~0u, m, 1), m2 = __shfl_xor_sync(~0u, m, 2), m3 = __shfl_xor_sync(~0u, m, 3);
                uint32_t vm[4];
                ldsm4t(vm, oa + xq + 16 * 272);
                m = fmaxf(fmaxf(m, m1), fmaxf(m2, m3));
                const float ms = m * sl2e;
#pragma unroll
                for (int i = 0; i < 10; i++) p[i] = ex2(fmaf(p[i], sl2e, -ms));
                const uint32_t b0 = pack2(p[0], p[1]), b1 = pack2(p[2], p[3]), b2 = pack2(p[4], p[5]), b3 = pack2(p[6], p[7]), b4 = pack2(p[8], p[9]);
                const uint32_t one = 0x3f803f80u;
                float o0[4] = {0.f, 0.f, 0.f, 0.f}, o1[4] = {0.f, 0.f, 0.f, 0.f}, sm[4] = {0.f, 0.f, 0.f, 0.f};
                mma16816(sm, one, one, one, one, b0, b1);
                mma16816(o0, va[0][0], va[0][1], va[0][2], va[0][3], b0, b1);
                mma16816(o1, va[2][0], va[2][1], va[2][2], va[2][3], b0, b1);
                mma16816(sm, one, one, one, one, b2, b3);
                mma16816(o0, va[1][0], va[1][1], va[1][2], va[1][3], b2, b3);
                mma16816(o1, va[3][0], va[3][1], va[3][2], va[3][3], b2, b3);
                mma1688(sm, one, one, b4);
                mma1688(o0, vm[0], vm[1], b4);
                mma1688(o1, vm[2], vm[3], b4);
                float i0, i1;
                asm("rcp.approx.ftz.f32 %0, %1;" : "=f"(i0) : "f"(sm[0]));
                asm("rcp.approx.ftz.f32 %0, %1;" : "=f"(i1) : "f"(sm[1]));
                stsm4t(oa + C_OB, pack2(o0[0] * i0, o0[1] * i1), pack2(o0[2] * i0, o0[3] * i1),
                       pack2(o1[0] * i0, o1[1] * i1), pack2(o1[2] * i0, o1[3] * i1));
            }
            TS(8);
            __syncthreads();
            TS(9);
            uint32_t ob[4][4];
#pragma unroll
            for (int i = 0; i < 4; i++) ldsm4(ob[i], lm + C_OB + i * 64);
            if (three) {
#pragma unroll
                for (int i = 0; i < 8; i++) lds128(wc[i], W2A(8 + i));
                project(wb, ob, 1);
                project(wo0, ob, 0);
                project(wc, ob, 2);
            } else {
                project(wb, ob, 1);
                project(wo0, ob, 0);
            }
        }
        TS(10);
        __syncthreads();
        uint32_t eo = (128 + (s + 1) * 4 + (w >> 1)) * 8192 + (((s < 31 ? msel0 : msel1) >> ((s + 1) & 31)) & 1) * 4096 + (w & 1) * 2048 + lane * 8;
        uint64_t d[8];
        if (r == 0) {
            if (w >= 6) {
                auto mid = [&]() {
                    bar_sync(2, 64);
                    TS(11);
                    mbar_wait_u(bar_go, s & 1);
                    eo = delayed<DLY0A>(eo, self);
                    TS(12);
                    fetch_state(d, (const char*)g_x + eo);
                };
                ATTEND(2, s, mid);
                stage_w1();
            } else {
                TS(11); TS(12);
                if (w < 3 && s + PFD < NSEG) {
                    const bf16* p = g_kv + (size_t)((s + PFD) * 32 + fresh(lane)) * PW + w * HD + h * 128;
                    asm volatile("prefetch.global.L2 [%0];\nprefetch.global.L2 [%0 + 128];" ::"l"(p) : "memory");
                }
                const uint32_t wa_ = wa;
                { const uint32_t wa = delayed<DLYS>(wa_, self); STAGE_W1(); }
                if (w == 5) {
                    chores(s);
                    if (h == 0) asm volatile("st.relaxed.gpu.global.u32 [%0], %1;" ::"l"(g_flag + 98), "r"(s + 1) : "memory");
                }
                mbar_wait_u(bar_go, s & 1);
                eo = delayed<DLY0>(eo, self);
                fetch_state(d, (const char*)g_x + eo);
            }
        } else {
            const int j = 2 * h + r - 1;
            if (w < 4) {
                const int l = fresh(lane), g = l >> 2, t = l & 3;
                const char* src = (const char*)g_x + delayed<DLY3>((j * 2 + (w >> 1)) * 8192 + (psel & 64) * 64 + (w & 1) * 2048 + t * 64 + g * 8, self);
                const char* dst = (const char*)g_x + pin((128 + (s + 1) * 4 + (j >> 4)) * 8192 + (j & 15) * 256 + w * 64 + (t & 1) * 4096 + g * 8);
                const uint64_t v = poll_sum(src, tag, (lane & 4) ? 0x3f800000u : 0x00003f80u);
                TS(11);
                asm volatile("st.relaxed.gpu.global.b64 [%0], %1;" ::"l"(dst), "l"(v) : "memory");
                asm volatile("bar.arrive 1, 256;" ::: "memory");
                TS(12);
                stage_w1();
                eo = delayed<DLY1>(eo, self);
                fetch_state(d, (const char*)g_x + eo);
            } else if (w == 7) {
                auto mid = [&]() {
                    TS(11);
                    bar_sync(1, 256);
                    TS(12);
                    eo = delayed<DLY1B>(eo, self);
                    fetch_state(d, (const char*)g_x + eo);
                };
                ATTEND(1, s, mid);
                stage_w1();
            } else {
                if (w >= 5 && s + 3 < NSEG)
                    asm volatile("prefetch.global.L2 [%0];" ::"l"(g_x + (128 + (s + 3) * 4 + (j >> 4)) * 1024 + (w & 1) * 512 + (j & 15) * 32 + lane) : "memory");
                stage_w1();
                if (w == 5) chores(s);
                TS(11);
                bar_sync(1, 256);
                TS(12);
                if (w == 4 && r == 1)
                    asm volatile("{\n.reg .pred p;\n.reg .u32 a;\nelect.sync _|p, -1;\nmapa.shared::cluster.u32 a, %0, %1;\n"
                                 "@p mbarrier.arrive.relaxed.cluster.shared::cluster.b64 _, [a];\n}" ::"r"(bar_go), "r"((h % (CLS / 3)) * 3) : "memory");
                eo = delayed<DLY1A>(eo, self);
                fetch_state(d, (const char*)g_x + eo);
            }
        }
        { const int s_ = s; { const int s = s_ + 1; TS(0); } }
        if (w == 7) load_kv(s + 1);
        settle_state(d, (const char*)g_x + eo);
#pragma unroll
        for (int i = 0; i < 8; i++) { bm[i].x = (uint32_t)d[i]; bm[i].y = (uint32_t)(d[i] >> 32); }
    }
    mbar_wait_u(bar_x, (NSEG - 1) & 1);
    if (attends) {
        auto nothing = []() {};
        load_q(NSEG - 1);
        if (r == 0) ATTEND(2, NSEG - 1, nothing); else ATTEND(1, NSEG - 1, nothing);
    }
    __syncthreads();
    if (w == 5) report(15);
    asm volatile("barrier.cluster.arrive.relaxed.aligned;\nbarrier.cluster.wait.aligned;" ::: "memory");
}

constexpr int S4_US = 4368;
constexpr int S4_RS = 8848;
constexpr int S4_KS = 1296;
constexpr int S4_U = 0, S4_R = 16 * S4_US, S4_K = S4_R + 16 * S4_RS;
constexpr int S4_SMEM = S4_K + 16 * S4_KS;
constexpr int S4_SIG = 3104, S4_PK = 2 * S4_SIG;

struct cf { float r, i; };
__device__ __forceinline__ cf cmul(cf a, cf b) { return {fmaf(a.r, b.r, -a.i * b.i), fmaf(a.r, b.i, a.i * b.r)}; }
__device__ __forceinline__ cf cmulc(cf a, cf b) { return {fmaf(a.r, b.r, a.i * b.i), fmaf(a.i, b.r, -a.r * b.i)}; }
__device__ __forceinline__ cf csq(cf a) { const float t = a.r * a.i; return {fmaf(a.r, a.r, -a.i * a.i), t + t}; }
__device__ __forceinline__ cf cexp(float l2, float turns) {
    const float mag = ex2(l2), fr = (turns - rintf(turns)) * 6.283185307179586f;
    return {mag * __cosf(fr), mag * __sinf(fr)};
}
__device__ __forceinline__ void sts32(uint32_t a, uint32_t v) { asm volatile("st.shared.u32 [%0], %1;" ::"r"(a), "r"(v) : "memory"); }
__device__ __forceinline__ uint32_t lds16(uint32_t a) {
    uint32_t v;
    asm volatile("ld.shared.u16 %0, [%1];" : "=r"(v) : "r"(a) : "memory");
    return v;
}

template <int M0, int NQ>
__device__ __forceinline__ void s4_class(float (&acc)[16][4], uint32_t sig, uint32_t taps, int x0) {
    constexpr int D0 = M0 / 8, D1 = M0 == 32 ? 9 : 15;
    uint32_t R[D1 - D0 + 2];
#pragma unroll
    for (int D = D0 - 1; D <= D1; D++) {
        if (D < D0 || 8 * D - 7 >= 2 * M0) { R[D - D0 + 1] = 0; continue; }
        const int m = 8 * D + x0;
        uint32_t lo = lds16(taps + m * (2 * NQ)), hi = lds16(taps + (m - 1) * (2 * NQ));
        if (D == D0) { lo = m >= M0 ? lo : 0; hi = m > M0 ? hi : 0; }
        if (D == 2 * D0) { lo = m < 2 * M0 ? lo : 0; hi = m <= 2 * M0 ? hi : 0; }
        R[D - D0 + 1] = lo | (hi << 16);
    }
#pragma unroll
    for (int J = 0; 2 * J + D0 < 16; J++) {
        uint32_t a[4];
        ldsm4t(a, sig + J * 512);
#pragma unroll
        for (int D = D0; D <= D1; D++)
            if (2 * J + D < 16) mma16816(acc[2 * J + D], a[0], a[1], a[2], a[3], R[D - D0 + 1], R[D - D0]);
    }
}

__global__ void __launch_bounds__(512, 1)
k_s4(const bf16* __restrict__ u, const bf16* __restrict__ Are, const bf16* __restrict__ Aim, const bf16* __restrict__ Bre,
     const bf16* __restrict__ Bim, const bf16* __restrict__ Cre, const bf16* __restrict__ Cim, const bf16* __restrict__ logdt,
     const bf16* __restrict__ Dsk, bf16* __restrict__ out) {
    extern __shared__ __align__(16) uint8_t smem_s4[];
    const uint32_t sb = smem_u32(smem_s4);
    asm volatile("griddepcontrol.launch_dependents;");
    const int tid = threadIdx.x, w = __shfl_sync(~0u, tid >> 5, 0), lane = tid & 31, g = lane >> 2, t = lane & 3;
#pragma unroll 1
    for (int item = blockIdx.x; item < 64; item += gridDim.x) {
#define TLS(slot)
    if (tid == 0) TLS(0);
    const int d0 = item * 16;
    const int d = d0 + (w & 1) + ((w >> 1) & 3) * 4 + (w >> 3) * 2;
    const uint32_t tr_off = (lane & 15), tr_l = (lane >> 4) * 16;
    const uint32_t ur = sb + S4_U + w * S4_US, rs = sb + S4_R + w * S4_RS, kd = sb + S4_K + w * S4_KS;
    if (lane < 16) sts128(ur + lane * 16, 0, 0, 0, 0);
    {
        const int o = d * 128 + lane * 4;
        const uint2 ar = __ldg((const uint2*)(Are + o)), ai = __ldg((const uint2*)(Aim + o)), br = __ldg((const uint2*)(Bre + o));
        const uint2 bi = __ldg((const uint2*)(Bim + o)), cr = __ldg((const uint2*)(Cre + o)), ci = __ldg((const uint2*)(Cim + o));
        const float dt = bf_round(expf(__bfloat162float(logdt[d])));
        const bf16* src = u + (size_t)(w * 128 + g) * DM + d0 + 4 * t;
        float T[5][4];
#pragma unroll
        for (int i = 0; i < 5; i++) T[i][0] = T[i][1] = T[i][2] = T[i][3] = 0.f;
        float klast = 0.f;
        const uint32_t wr_ = rs + lane * 272, rd_ = rs + t * 544 + g * 16;
#pragma unroll 1
        for (int c = 0; c < 4; c++) {
            uint2 v[4];
#pragma unroll
            for (int i = 0; i < 4; i++) v[i] = __ldg((const uint2*)(src + (size_t)(c * 32 + i * 8) * DM));
            auto pick = [&](const uint2& x) { const uint32_t y = c < 2 ? x.x : x.y; return (c & 1) ? bf_hi(y) : bf_lo(y); };
            auto pk2 = [](cf x) { return pack2(x.r, x.i); };
            const float l2 = dt * pick(ar) * 1.4426950408889634f, tu = dt * pick(ai) * 0.15915494309189535f;
            const cf z1 = cexp(l2, tu), z2 = csq(z1), z4 = csq(z2), z8 = csq(z4);
            const cf z64 = cexp(l2 * 64.f, tu * 64.f), z128 = csq(z64), z256 = csq(z128), z512 = csq(z256);
            cf a0 = {1.f, 0.f}, a1 = z64;
            cf b0 = cmul({pick(cr), pick(ci)}, {dt * pick(br), dt * pick(bi)});
            b0.i = -b0.i;
            cf b1 = cmulc(b0, z128), b2 = cmulc(b0, z256), y3 = cmulc(b0, z512), b4 = cmulc(y3, z512), b3 = y3;
            const cf y2 = cmulc(b2, z128);
#pragma unroll
            for (int i = 0; i < 8; i++) {
                sts128(wr_ + i * 16, pk2(a0), pk2(a1), pk2(b0), pk2(b1));
                sts128(wr_ + i * 16 + 128, pk2(b2), pk2(b3), pk2(b4), 0);
                b4 = cmulc(b4, z128);
                if (i < 7) {
                    a0 = i == 0 ? z8 : cmul(a0, z8); a1 = cmul(a1, z8);
                    b0 = cmulc(b0, z1); b1 = cmulc(b1, z1);
                    b2 = i == 3 ? y2 : cmulc(b2, z2);
                    if (i & 1) { y3 = cmulc(y3, z128); b3 = y3; } else b3 = cmulc(y3, z4);
                }
            }
            klast += b4.r;
            __syncwarp();
#pragma unroll
            for (int k = 0; k < 8; k++) {
                uint32_t x[4], y[4];
                lds128(x, rd_ + (8 * (k >> 1) + (k & 1)) * 272);
                lds128(y, rd_ + (8 * (k >> 1) + (k & 1)) * 272 + 128);
                mma1688(T[0], x[0], x[1], x[2]);
                mma1688(T[1], x[0], x[1], x[3]);
                mma1688(T[2], x[0], x[1], y[0]);
                mma1688(T[3], x[0], x[1], y[1]);
                mma1688(T[4], x[0], x[1], y[2]);
            }
#pragma unroll
            for (int i = 0; i < 2; i++)
                stsm4t(sb + S4_U + tr_off * S4_US + 256 + (w * 128 + c * 32 + i * 16) * 2 + tr_l, v[2 * i].x, v[2 * i].y, v[2 * i + 1].x, v[2 * i + 1].y);
            __syncwarp();
        }
#pragma unroll
        for (int o2 = 16; o2; o2 >>= 1) klast += __shfl_xor_sync(~0u, klast, o2);
#pragma unroll
        for (int hh = 0; hh < 2; hh++) {
            const int i = g + 8 * hh;
            sts32(kd + (8 * i + 2 * t) * 2, pack2(T[0][2 * hh], T[0][2 * hh + 1]));
            sts32(kd + (128 + 8 * i + 2 * t) * 2, pack2(T[1][2 * hh], T[1][2 * hh + 1]));
            sts32(kd + (256 + 4 * i + 2 * (t & 1) + 64 * (t >> 1)) * 2, pack2(T[2][2 * hh], T[2][2 * hh + 1]));
            sts32(kd + (384 + 2 * i + 32 * t) * 2, pack2(T[3][2 * hh], T[3][2 * hh + 1]));
        }
        asm volatile("stmatrix.sync.aligned.m8n8.x2.trans.shared.b16 [%0], {%1,%2};"
                     ::"r"(kd + 1024 + (lane & 7) * 32 + ((lane >> 3) & 1) * 16), "r"(pack2(T[4][0], T[4][1])), "r"(pack2(T[4][2], T[4][3])) : "memory");
        if (lane == 0) sts32(kd + 1280, pack2(klast, 0.f));
    }
    __syncwarp();
    const uint32_t pk = rs + S4_PK + 64;
    {
#pragma unroll
        for (int i = 0; i < 2; i++) {
            const int x = i * 128 + lane * 4;
            const uint2 c = lds64(kd + x * 2);
            uint32_t p = lds16(kd + x * 2 - 2);
            if (x == 0) p = 0;
            sts128(pk + x * 4, __byte_perm(c.x, p, 0x5410), __byte_perm(c.x, 0, 0x1032), __byte_perm(c.y, c.x, 0x7610), __byte_perm(c.y, 0, 0x1032));
        }
#pragma unroll
        for (int i = 2; i < 4; i++) {
            const int x = i * 128 + lane * 4;
            const uint32_t ab = lds32(kd + 256 + x), c = lds16(kd + 256 + x + 4);
            const uint32_t p = x == 256 ? lds16(kd + 510) : ab;
            sts128(pk + x * 4, __byte_perm(ab, p, 0x5410), __byte_perm(ab, 0, 0x1010), __byte_perm(ab, 0, 0x1032), __byte_perm(c, ab, 0x7610));
        }
        const uint32_t v = lds16(kd + 768), v2 = lds16(kd + 1024);
        if (lane < 24) {
            uint32_t x0 = 0, x1 = 0, x2 = 0, x3 = 0;
            if (lane == 0) { x0 = x1 = x2 = v | (v << 16); x3 = v << 16; }
            if (lane == 12) x3 = v2;
            if (lane == 13) { x0 = v2 | (v2 << 16); x1 = v2 << 16; }
            sts128(lane < 20 ? pk + 2048 + lane * 16 : pk - 64 + (lane - 20) * 16, x0, x1, x2, x3);
        }
        if (lane < 4) sts128(rs + (lane >> 1) * S4_SIG + (lane & 1) * 16, 0, 0, 0, 0);
    }
    __syncthreads();
    float acc[16][4];
#pragma unroll
    for (int i = 0; i < 16; i++) acc[i][0] = acc[i][1] = acc[i][2] = acc[i][3] = 0.f;
    const uint32_t lf = (lane & 7) * 32 + ((lane >> 3) & 1) * 16 + (lane >> 4) * 256;
#pragma unroll 1
    for (int ph = 0; ph < 2; ph++) {
    if (((w >> 2) ^ ph) & 1) {
#pragma unroll
    for (int rg = 3; rg >= 2; rg--) {
#pragma unroll 1
        for (int it = 0; it < (rg == 3 ? 4 : 6); it++) {
            const int n = it * 32 + lane;
            uint32_t x[2][4];
            lds128(x[0], ur + 256 + n * 16 - 16);
            lds128(x[1], ur + 256 + n * 16);
            float e[16], p[15], s[11];
#pragma unroll
            for (int i = 0; i < 8; i++) { e[2 * i] = bf_lo(x[i >> 2][i & 3]); e[2 * i + 1] = bf_hi(x[i >> 2][i & 3]); }
#pragma unroll
            for (int i = 0; i < 15; i++) p[i] = e[i] + e[i + 1];
#pragma unroll
            for (int i = 0; i < 11; i++) s[i] = p[i + 3] + e[i + 5];
            const uint32_t o = rs + 16 + n * 16;
            if (rg == 2) sts128(o, pack2(s[0], s[1]), pack2(s[2], s[3]), pack2(s[4], s[5]), pack2(s[6], s[7]));
#pragma unroll
            for (int i = 0; i < 10; i++) s[i] = p[i + 2] + s[i + 1];
            if (rg == 2) {
                sts64(o + S4_SIG + 8, pack2(s[0], s[1]), pack2(s[2], s[3]));
                sts64(o + S4_SIG + 16, pack2(s[4], s[5]), pack2(s[6], s[7]));
            } else {
#pragma unroll
                for (int i = 0; i < 9; i++) s[i] = p[i + 1] + s[i + 1];
                sts64(o + 8, pack2(s[0], s[1]), pack2(s[2], s[3]));
                sts64(o + 16, pack2(s[4], s[5]), pack2(s[6], s[7]));
#pragma unroll
                for (int i = 0; i < 8; i++) s[i] = p[i] + s[i + 1];
                sts64(o + S4_SIG + 8, pack2(s[0], s[1]), pack2(s[2], s[3]));
                sts64(o + S4_SIG + 16, pack2(s[4], s[5]), pack2(s[6], s[7]));
            }
        }
        __syncwarp();
        if (rg == 3) {
#pragma unroll 1
            for (int q = 1; q <= 2; q++) s4_class<64, 2>(acc, rs + lf + (q == 1 ? 16 : S4_SIG), kd + (384 + q) * 2, g - 2 * t);
        } else {
#pragma unroll 1
            for (int q = 1; q <= 4; q++) s4_class<32, 4>(acc, rs + lf + ((q & 1) ? 0 : S4_SIG) + (q < 3 ? 16 : 0), kd + (256 + q) * 2, g - 2 * t);
        }
        __syncwarp();
    }
    } else
    {
        const uint32_t ub = ur + 256 + lf, kb = pk + (g - 2 * t) * 4;
#pragma unroll 1
        for (int j0 = 0; j0 < 8; j0++) {
            uint32_t B[8][4];
#pragma unroll
            for (int i = 0; i < 8; i++) ldsm4(B[i], ub + i * 512 - j0 * 32);
            auto block = [&](int J, uint32_t a) {
                const uint32_t r0 = lds32(a), rp = lds32(a + 32), rm = lds32(a - 32);
                uint32_t r3;
                asm volatile("ld.volatile.shared.u32 %0, [%1];" : "=r"(r3) : "r"(a) : "memory");
#pragma unroll
                for (int I = J; I < 16; I++)
                    mma16816(acc[I], r0, rp, rm, r3, B[(I - J) >> 1][((I - J) & 1) * 2], B[(I - J) >> 1][((I - J) & 1) * 2 + 1]);
            };
#pragma unroll
            for (int J = 0; J < 4; J++) block(J, kb + j0 * 64 + J * 512);
            if (j0 < 2) { block(4, kb + j0 * 64 + 2048); block(8, kb + j0 * 64 + (544 + 16) * 4); }
        }
    }
    }
    {
        __syncwarp();
#pragma unroll
        for (int i = 0; i < 8; i++)
            stsm4t(rs + lf + i * 512, pack2(acc[2 * i][0], acc[2 * i][1]), pack2(acc[2 * i][2], acc[2 * i][3]),
                   pack2(acc[2 * i + 1][0], acc[2 * i + 1][1]), pack2(acc[2 * i + 1][2], acc[2 * i + 1][3]));
    }
    __syncthreads();
    {
        const uint2 dv = __ldg((const uint2*)(Dsk + d0 + 4 * t));
        bf16* dst = out + (size_t)(w * 128 + g) * 2048 + 1024 + d0 + 4 * t;
#pragma unroll
        for (int i = 0; i < 8; i++) {
            uint32_t y[4], x[4], o[4];
            ldsm4t(y, sb + S4_R + tr_off * S4_RS + (w * 128 + i * 16) * 2 + tr_l);
            ldsm4t(x, sb + S4_U + tr_off * S4_US + 256 + (w * 128 + i * 16) * 2 + tr_l);
#pragma unroll
            for (int j = 0; j < 4; j++)
                asm("{\n.reg .b32 s;\nmul.rn.bf16x2 s, %2, %3;\nadd.rn.bf16x2 %0, %1, s;\n}" : "=r"(o[j]) : "r"(y[j]), "r"(x[j]), "r"((j & 1) ? dv.y : dv.x));
            *reinterpret_cast<uint2*>(dst + (size_t)(i * 16) * 2048) = make_uint2(o[0], o[1]);
            *reinterpret_cast<uint2*>(dst + (size_t)(i * 16 + 8) * 2048) = make_uint2(o[2], o[3]);
        }
    }
    if (tid == 0) TLS(1);
    __syncthreads();
    }
}

enum { IT_W256 = 1, IT_W128 = 2, IT_W64 = 3, IT_END = 7 };
struct BgParams { CUtensorMap mo, mo2, mwo4, mwo2, mwo1; };
#define NBT 10
#define P256 56
#define P128 62
struct Sched { uint32_t w0 = 0, w1 = 0; };
__device__ __forceinline__ int next_item(Sched& z) {
    if (z.w0 >= z.w1) {
        uint32_t prog;
        asm volatile("ld.relaxed.gpu.global.u32 %0, [%1];" : "=r"(prog) : "l"(g_flag + 98) : "memory");
        const uint32_t k = prog <= P256 ? 4 : prog <= P128 ? 2 : 1;
        z.w0 = atomicAdd(g_flag + 97, k);
        z.w1 = min(z.w0 + k, NBT * 16u);
        if (z.w0 >= z.w1) return IT_END;
    }
    const uint32_t i = z.w0, k = z.w1 - i >= 4 && !(i & 3) ? 4 : z.w1 - i >= 2 && !(i & 1) ? 2 : 1;
    z.w0 += k;
    return (k == 4 ? IT_W256 : k == 2 ? IT_W128 : IT_W64) | (i >> 4) << 3 | ((i & 15) / k) << 7;
}
constexpr int B_OST = NSTAGE * STAGE_BYTES + 1024;
constexpr int BG_SMEM = B_OST + 32768;

template <int BM, int BN, int KPS, typename ACC>
__device__ __forceinline__ void gemm_mainloop(ACC& acc, const GemmSmem& g, int cw, int rounds, uint32_t& round) {
#pragma unroll
    for (int i = 0; i < BN / 2; i++) acc[i] = 0.f;
#pragma unroll 1
    for (int k0 = 0; k0 < rounds; k0++, round++) {
#pragma unroll
        for (int s = 0; s < 4; s++) {
            mbar_wait_u(g.full + 8 * s, round & 1);
            gemm_stage<BM, BN, KPS>(acc, g.st + s * STAGE_BYTES, cw, false);
            wg_wait<1>();
            if (s > 0 || k0 > 0) mbar_arrive_one(g.empty + 8 * ((s + 3) & 3), threadIdx.x & 31);
        }
    }
    wg_wait<0>();
    mbar_arrive_one(g.empty + 8 * 3, threadIdx.x & 31);
}

template <int BN>
__device__ __forceinline__ void store_tile(const float (&acc)[BN / 2], bf16* dst, int t) {
#pragma unroll
    for (int G = 0; G < BN / 32; G++)
#pragma unroll
        for (int rr = 0; rr < 2; rr++) {
            uint32_t r0 = pack2(acc[16 * G + 2 * rr], acc[16 * G + 2 * rr + 1]), r1 = pack2(acc[16 * G + 4 + 2 * rr], acc[16 * G + 5 + 2 * rr]);
            uint32_t r2 = pack2(acc[16 * G + 8 + 2 * rr], acc[16 * G + 9 + 2 * rr]), r3 = pack2(acc[16 * G + 12 + 2 * rr], acc[16 * G + 13 + 2 * rr]);
            quad_transpose(r0, r1, r2, r3, t);
            *reinterpret_cast<uint4*>(dst + (size_t)rr * 8 * 2048 + G * 32) = make_uint4(r0, r1, r2, r3);
        }
}

template <int BN, int KPS>
__device__ __forceinline__ void wo_item(const GemmSmem& g, int cw, uint32_t& round, bf16* dst, int t) {
    float acc[BN / 2];
    gemm_mainloop<128, BN, KPS>(acc, g, cw, 16 / KPS, round);
    store_tile<BN>(acc, dst, t);
}

__global__ void __launch_bounds__(384, 1) k_bg(const __grid_constant__ BgParams P, bf16* __restrict__ out) {
    extern __shared__ __align__(1024) uint8_t smem_gemm[];
    asm volatile("griddepcontrol.launch_dependents;");
    const uint32_t bar_item = smem_u32(smem_gemm) + NSTAGE * STAGE_BYTES + 128, slot = bar_item + 16;
    if (threadIdx.x == 0) { mbar_init(bar_item, 1); mbar_init(bar_item + 8, 1); }
    GemmSmem g = gemm_setup(smem_gemm, 8);
    const int wg = __shfl_sync(~0u, threadIdx.x >> 7, 0);
    if (wg == 0) {
        asm volatile("setmaxnreg.dec.sync.aligned.u32 40;");
        if (threadIdx.x == 0) {
            uint32_t it = 0;
            Sched z;
            for (int n = 0;; n++) {
                const int code = next_item(z);
                sts32(slot + (n & 1) * 4, code);
                mbar_arrive(bar_item + (n & 1) * 8);
                const int type = code & 7, blk = (code >> 3) & 15, idx = code >> 7;
                if (type == IT_END) break;
                wait_flag(g_flag + 64 + blk, 96);
                asm volatile("fence.proxy.async.global;" ::: "memory");
                for (int k = 0; k < (type == IT_W64 ? 32 : 64); k++, it++) {
                    const int s = it & 3;
                    const uint32_t st = g.st + s * STAGE_BYTES, fb = g.full + 8 * s;
                    mbar_wait(g.empty + 8 * s, ((it >> 2) & 1) ^ 1);
                    mbar_expect_tx(fb, type == IT_W128 ? 32768 : 49152);
                    if (type == IT_W64) {
                        tma3d(st, &P.mo2, 0, blk * 128, k * 2, fb);
                        tma3d(st + 32768, &P.mwo1, 0, k * 128, idx, fb);
                    } else {
                        tma2d(st, &P.mo, k * 64, blk * 128, fb);
                        tma3d(st + 16384, type == IT_W256 ? &P.mwo4 : &P.mwo2, 0, k * 64, idx * (type == IT_W256 ? 4 : 2), fb);
                    }
                }
            }
        }
    } else {
        asm volatile("setmaxnreg.inc.sync.aligned.u32 232;");
        const int cw = wg - 1, lane = threadIdx.x & 31;
        uint32_t round = 0;
#pragma unroll 1
        for (int n = 0;; n++) {
            mbar_wait_u(bar_item + (n & 1) * 8, (n >> 1) & 1);
            const int code = __shfl_sync(~0u, lds32(slot + (n & 1) * 4), 0);
            const int type = code & 7, blk = (code >> 3) & 15, idx = (code >> 7) & 31;
#define TLB(slot_)
            if (type == IT_END) break;
            TLB(0);
            bf16* dst = out + (size_t)(blk * 128 + cw * 64 + ((threadIdx.x >> 5) & 3) * 16 + (lane >> 2)) * 2048 + (lane & 3) * 8;
            if (type == IT_W256) wo_item<256, 1>(g, cw, round, dst + idx * 256, lane & 3);
            else if (type == IT_W128) wo_item<128, 1>(g, cw, round, dst + idx * 128, lane & 3);
            else wo_item<64, 2>(g, cw, round, dst + idx * 64, lane & 3);
            TLB(1);
        }
    }
}

constexpr int TBN = NBT >= 13 ? 64 : 128, TKPS = TBN == 64 ? 2 : 1, TPB = DM / TBN;
__global__ void __cluster_dims__(2, 1, 1) __launch_bounds__(384, 1)
k_tail(const __grid_constant__ BgParams P, bf16* __restrict__ out) {
    extern __shared__ __align__(1024) uint8_t smem_gemm[];
    const uint32_t bar_s = smem_u32(smem_gemm) + NSTAGE * STAGE_BYTES + 128;
    if (threadIdx.x == 0) { TL(4, 0); mbar_init(bar_s, 1); mbar_expect_tx(bar_s, TBN * 256); }
    GemmSmem g = gemm_setup(smem_gemm, 8);
    asm volatile("barrier.cluster.arrive.relaxed.aligned;" ::: "memory");
    const int half = blockIdx.x & 1, blk = NBT + (blockIdx.x >> 1) / TPB, idx = (blockIdx.x >> 1) % TPB;
    const int wg = __shfl_sync(~0u, threadIdx.x >> 7, 0);
    if (wg == 0) {
        if (threadIdx.x == 0) {
            wait_flag(g_flag + 64 + blk, 96);
            asm volatile("fence.proxy.async.global;" ::: "memory");
            for (int k = 0; k < 32 / TKPS; k++) {
                const int s = k & 3, kb = half * 32 + k * TKPS;
                const uint32_t st = g.st + s * STAGE_BYTES, fb = g.full + 8 * s;
                mbar_wait(g.empty + 8 * s, ((k >> 2) & 1) ^ 1);
                mbar_expect_tx(fb, TBN == 64 ? 49152 : 32768);
                if (TBN == 64) {
                    tma3d(st, &P.mo2, 0, blk * 128, kb, fb);
                    tma3d(st + 32768, &P.mwo1, 0, kb * 64, idx, fb);
                } else {
                    tma2d(st, &P.mo, kb * 64, blk * 128, fb);
                    tma3d(st + 16384, &P.mwo2, 0, kb * 64, idx * 2, fb);
                }
            }
        }
        __syncwarp();
        asm volatile("barrier.cluster.wait.aligned;" ::: "memory");
    } else {
        const int cw = wg - 1, lane = threadIdx.x & 31, t = lane & 3;
        float acc[TBN / 2];
        uint32_t round = 0;
        gemm_mainloop<128, TBN, TKPS>(acc, g, cw, 8 / TKPS, round);
        asm volatile("barrier.cluster.wait.aligned;" ::: "memory");
        const uint32_t xa = g.st + B_OST + (threadIdx.x & 127) * 16;
        if (cw != half) {
            uint32_t ra, rb;
            asm("mapa.shared::cluster.u32 %0, %1, %2;" : "=r"(ra) : "r"(xa), "r"(half ^ 1));
            asm("mapa.shared::cluster.u32 %0, %1, %2;" : "=r"(rb) : "r"(bar_s), "r"(half ^ 1));
#pragma unroll
            for (int i = 0; i < TBN / 8; i++)
                asm volatile("st.async.weak.shared::cluster.mbarrier::complete_tx::bytes.v4.f32 [%0], {%1,%2,%3,%4}, [%5];"
                             ::"r"(ra + i * 2048), "f"(acc[4 * i]), "f"(acc[4 * i + 1]), "f"(acc[4 * i + 2]), "f"(acc[4 * i + 3]), "r"(rb) : "memory");
        } else {
            mbar_wait_u(bar_s, 0);
#pragma unroll
            for (int i = 0; i < TBN / 8; i++) {
                const float4 v = lds128f(xa + i * 2048);
                acc[4 * i] += v.x; acc[4 * i + 1] += v.y; acc[4 * i + 2] += v.z; acc[4 * i + 3] += v.w;
            }
            store_tile<TBN>(acc, out + (size_t)(blk * 128 + cw * 64 + ((threadIdx.x >> 5) & 3) * 16 + (lane >> 2)) * 2048 + idx * TBN + t * 8, t);
            if ((threadIdx.x & 127) == 0) TL(4, 1);
        }
    }
    asm volatile("barrier.cluster.arrive.relaxed.aligned;\nbarrier.cluster.wait.aligned;" ::: "memory");
}

typedef CUresult (*EncodeFn)(CUtensorMap*, CUtensorMapDataType, cuuint32_t, void*, const cuuint64_t*, const cuuint64_t*,
                             const cuuint32_t*, const cuuint32_t*, CUtensorMapInterleave, CUtensorMapSwizzle,
                             CUtensorMapL2promotion, CUtensorMapFloatOOBfill);

static void map2d(EncodeFn enc, CUtensorMap* m, const void* p, int rows, int cols, int box_rows) {
    cuuint64_t dim[2] = {(cuuint64_t)cols, (cuuint64_t)rows}, str[1] = {(cuuint64_t)cols * 2};
    cuuint32_t box[2] = {64, (cuuint32_t)box_rows}, es[2] = {1, 1};
    enc(m, CU_TENSOR_MAP_DATA_TYPE_BFLOAT16, 2, (void*)p, dim, str, box, es, CU_TENSOR_MAP_INTERLEAVE_NONE,
        CU_TENSOR_MAP_SWIZZLE_128B, CU_TENSOR_MAP_L2_PROMOTION_L2_256B, CU_TENSOR_MAP_FLOAT_OOB_FILL_NONE);
}
static void map3d(EncodeFn enc, CUtensorMap* m, const void* p, int rows, int cols, int box_rows, int nblk) {
    cuuint64_t dim[3] = {64, (cuuint64_t)rows, (cuuint64_t)cols / 64}, str[2] = {(cuuint64_t)cols * 2, 128};
    cuuint32_t box[3] = {64, (cuuint32_t)box_rows, (cuuint32_t)nblk}, es[3] = {1, 1, 1};
    enc(m, CU_TENSOR_MAP_DATA_TYPE_BFLOAT16, 3, (void*)p, dim, str, box, es, CU_TENSOR_MAP_INTERLEAVE_NONE,
        CU_TENSOR_MAP_SWIZZLE_128B, CU_TENSOR_MAP_L2_PROMOTION_L2_256B, CU_TENSOR_MAP_FLOAT_OOB_FILL_NONE);
}

#define USE_PDL 1

extern "C" void kernel_launch(void* const* d_in, const int* in_sizes, int n_in, void* d_out, int out_size) {
    const bf16 *x = (const bf16*)d_in[0], *mem0 = (const bf16*)d_in[1], *Wq = (const bf16*)d_in[2], *Wk = (const bf16*)d_in[3];
    const bf16 *Wv = (const bf16*)d_in[4], *Wo = (const bf16*)d_in[5];
    const bf16 *u = (const bf16*)d_in[7], *Are = (const bf16*)d_in[8], *Aim = (const bf16*)d_in[9], *Bre = (const bf16*)d_in[10];
    const bf16 *Bim = (const bf16*)d_in[11], *Cre = (const bf16*)d_in[12], *Cim = (const bf16*)d_in[13];
    const bf16 *logdt = (const bf16*)d_in[14], *Dsk = (const bf16*)d_in[15];
    bf16* out = (bf16*)d_out;

    void* fn = nullptr;
    cudaDriverEntryPointQueryResult qr;
    cudaGetDriverEntryPoint("cuTensorMapEncodeTiled", &fn, cudaEnableDefault, &qr);
    EncodeFn enc = (EncodeFn)fn;
    void *kv, *o;
    cudaGetSymbolAddress(&kv, g_kv);
    cudaGetSymbolAddress(&o, g_o);
    CUtensorMap mx, mwq, mwk, mwv, mkv2;
    BgParams P;
    map2d(enc, &mx, x, SEQ, DM, 128);
    map2d(enc, &P.mo, o, SEQ, HD, 128);
    map3d(enc, &P.mo2, o, SEQ, HD, 128, 2);
    map3d(enc, &mwq, Wq, DM, HD, 64, 2);
    map3d(enc, &mwk, Wk, DM, HD, 64, 2);
    map3d(enc, &mwv, Wv, DM, HD, 64, 2);
    map3d(enc, &P.mwo4, Wo, HD, DM, 64, 4);
    map3d(enc, &P.mwo2, Wo, HD, DM, 64, 2);
    map3d(enc, &P.mwo1, Wo, HD, DM, 128, 1);
    map3d(enc, &mkv2, kv, SEQ, PW, 32, 2);
    cudaFuncSetAttribute(k_kv, cudaFuncAttributeMaxDynamicSharedMemorySize, GEMM_SMEM);
    cudaFuncSetAttribute(k_bg, cudaFuncAttributeMaxDynamicSharedMemorySize, BG_SMEM);
    cudaFuncSetAttribute(k_tail, cudaFuncAttributeMaxDynamicSharedMemorySize, BG_SMEM);
    cudaFuncSetAttribute(k_chain, cudaFuncAttributeMaxDynamicSharedMemorySize, CHAIN_SMEM);
    cudaFuncSetAttribute(k_s4, cudaFuncAttributeMaxDynamicSharedMemorySize, S4_SMEM);

    cudaStream_t st = cudaStreamPerThread;
    cudaLaunchAttribute pdl[2], cls[1];
    pdl[0].id = cudaLaunchAttributeProgrammaticStreamSerialization;
    pdl[0].val.programmaticStreamSerializationAllowed = 1;
    cls[0].id = cudaLaunchAttributeClusterDimension;
    cls[0].val.clusterDim.x = CLS; cls[0].val.clusterDim.y = 1; cls[0].val.clusterDim.z = 1;
    cudaLaunchConfig_t cfg = {};
    cfg.stream = st; cfg.attrs = cls; cfg.numAttrs = 1;
    cfg.gridDim = dim3(96); cfg.blockDim = dim3(384); cfg.dynamicSmemBytes = GEMM_SMEM;
    cudaLaunchKernelEx(&cfg, k_kv, mx, mwk, mwv, mwq, Wq, Wo, 0);
    pdl[1] = cls[0]; pdl[1].val.clusterDim.x = 2;
    cfg.attrs = pdl; cfg.numAttrs = 2;
    cfg.gridDim = dim3(36);
    cudaLaunchKernelEx(&cfg, k_kv, mx, mwk, mwv, mwq, Wq, Wo, 96);
    cfg.numAttrs = 1;
    cfg.gridDim = dim3(96); cfg.blockDim = dim3(256); cfg.dynamicSmemBytes = CHAIN_SMEM;
    cudaLaunchKernelEx(&cfg, k_chain, mem0, Wq, Wk, Wv, Wo, mkv2);
    cfg.numAttrs = USE_PDL;
    cfg.gridDim = dim3(36); cfg.blockDim = dim3(512); cfg.dynamicSmemBytes = S4_SMEM;
    cudaLaunchKernelEx(&cfg, k_s4, u, Are, Aim, Bre, Bim, Cre, Cim, logdt, Dsk, out);
    cfg.gridDim = dim3(NBT < 16 ? 36 : 132); cfg.blockDim = dim3(384); cfg.dynamicSmemBytes = BG_SMEM;
    cudaLaunchKernelEx(&cfg, k_bg, P, out);
    cfg.gridDim = dim3((16 - NBT) * TPB * 2);
    if (NBT < 16) cudaLaunchKernelEx(&cfg, k_tail, P, out);
}
```

```cpp
#include <cuda_runtime.h>
#include <cuda_bf16.h>
#include <cuda.h>
#include <stdint.h>

typedef __nv_bfloat16 bf16;

constexpr int SEQ = 2048, DM = 1024, HD = 4096, NSEG = 64;

constexpr int PW = 3 * HD;
#define NTA 3
__device__ __align__(1024) bf16 g_kv[(size_t)SEQ * PW];
__device__ __align__(1024) bf16 g_o[(size_t)SEQ * HD];
constexpr int XPAIRS = 128 + NSEG * 4;
__device__ __align__(8192) uint2 g_x[XPAIRS * 1024];
__device__ uint32_t g_home[XPAIRS];
__device__ uint32_t g_side[256];
__device__ __align__(1024) uint32_t g_flag[256];

#define TL(kern, slot)

__device__ __forceinline__ uint32_t smem_u32(const void* p) { return (uint32_t)__cvta_generic_to_shared(p); }
__device__ __forceinline__ void mbar_init(uint32_t bar, uint32_t cnt) {
    asm volatile("mbarrier.init.shared::cta.b64 [%0], %1;" ::"r"(bar), "r"(cnt) : "memory");
}
__device__ __forceinline__ void mbar_expect_tx(uint32_t bar, uint32_t bytes) {
    asm volatile("mbarrier.arrive.expect_tx.shared::cta.b64 _, [%0], %1;" ::"r"(bar), "r"(bytes) : "memory");
}
__device__ __forceinline__ void mbar_arrive(uint32_t bar) {
    asm volatile("mbarrier.arrive.shared::cta.b64 _, [%0];" ::"r"(bar) : "memory");
}
__device__ __forceinline__ bool mbar_try(uint32_t bar, uint32_t parity) {
    uint32_t ok;
    asm volatile("{\n.reg .pred p;\nmbarrier.try_wait.parity.shared::cta.b64 p, [%1], %2;\nselp.u32 %0, 1, 0, p;\n}"
                 : "=r"(ok) : "r"(bar), "r"(parity) : "memory");
    return ok;
}
constexpr int SPIN_LIMIT = 1 << 20;
__device__ __forceinline__ void mbar_wait(uint32_t bar, uint32_t parity) {
    int n = 0;
    while (!mbar_try(bar, parity)) { if (++n > SPIN_LIMIT) __trap(); }
}
__device__ __forceinline__ void mbar_wait_u(uint32_t bar, uint32_t parity) {
    asm volatile("{\n.reg .pred p;\n.reg .u32 n;\n"
                 "mbarrier.try_wait.parity.shared::cta.b64 p, [%0], %1;\n@p bra.uni DONE;\nmov.u32 n, 0;\n"
                 "AGAIN:\nmbarrier.try_wait.parity.shared::cta.b64 p, [%0], %1;\n@p bra.uni DONE;\n"
                 "add.u32 n, n, 1;\nsetp.lt.u32 p, n, 0x100000;\n@p bra.uni AGAIN;\ntrap;\nDONE:\n}"
                 ::"r"(bar), "r"(parity) : "memory");
}
__device__ __forceinline__ void tma2d(uint32_t dst, const CUtensorMap* m, int c0, int c1, uint32_t bar) {
    asm volatile("cp.async.bulk.tensor.2d.shared::cluster.global.mbarrier::complete_tx::bytes [%0], [%1, {%3, %4}], [%2];"
                 ::"r"(dst), "l"(m), "r"(bar), "r"(c0), "r"(c1) : "memory");
}
__device__ __forceinline__ void tma3d(uint32_t dst, const CUtensorMap* m, int c0, int c1, int c2, uint32_t bar) {
    asm volatile("cp.async.bulk.tensor.3d.shared::cluster.global.mbarrier::complete_tx::bytes [%0], [%1, {%3, %4, %5}], [%2];"
                 ::"r"(dst), "l"(m), "r"(bar), "r"(c0), "r"(c1), "r"(c2) : "memory");
}
__device__ __forceinline__ uint32_t pack2(float lo, float hi) {
    uint32_t r;
    asm("cvt.rn.bf16x2.f32 %0, %1, %2;" : "=r"(r) : "f"(hi), "f"(lo));
    return r;
}
__device__ __forceinline__ float bf_lo(uint32_t v) { return __uint_as_float(v << 16); }
__device__ __forceinline__ float bf_hi(uint32_t v) { return __uint_as_float(v & 0xffff0000u); }
__device__ __forceinline__ float bf_round(float x) { return bf_lo(pack2(x, 0.f)); }
__device__ __forceinline__ float ex2(float x) { float y; asm("ex2.approx.ftz.f32 %0, %1;" : "=f"(y) : "f"(x)); return y; }
__device__ __forceinline__ void mma16816(float (&c)[4], uint32_t a0, uint32_t a1, uint32_t a2, uint32_t a3, uint32_t b0, uint32_t b1) {
    asm volatile("mma.sync.aligned.m16n8k16.row.col.f32.bf16.bf16.f32 {%0,%1,%2,%3}, {%4,%5,%6,%7}, {%8,%9}, {%0,%1,%2,%3};"
                 : "+f"(c[0]), "+f"(c[1]), "+f"(c[2]), "+f"(c[3]) : "r"(a0), "r"(a1), "r"(a2), "r"(a3), "r"(b0), "r"(b1));
}
__device__ __forceinline__ void mma1688(float (&c)[4], uint32_t a0, uint32_t a1, uint32_t b0) {
    asm volatile("mma.sync.aligned.m16n8k8.row.col.f32.bf16.bf16.f32 {%0,%1,%2,%3}, {%4,%5}, {%6}, {%0,%1,%2,%3};"
                 : "+f"(c[0]), "+f"(c[1]), "+f"(c[2]), "+f"(c[3]) : "r"(a0), "r"(a1), "r"(b0));
}
__device__ __forceinline__ void ldsm4(uint32_t (&r)[4], uint32_t a) {
    asm volatile("ldmatrix.sync.aligned.m8n8.x4.shared.b16 {%0,%1,%2,%3}, [%4];"
                 : "=r"(r[0]), "=r"(r[1]), "=r"(r[2]), "=r"(r[3]) : "r"(a) : "memory");
}
__device__ __forceinline__ void ldsm4t(uint32_t (&r)[4], uint32_t a) {
    asm volatile("ldmatrix.sync.aligned.m8n8.x4.trans.shared.b16 {%0,%1,%2,%3}, [%4];"
                 : "=r"(r[0]), "=r"(r[1]), "=r"(r[2]), "=r"(r[3]) : "r"(a) : "memory");
}
__device__ __forceinline__ void ldsm2t(uint32_t& r0, uint32_t& r1, uint32_t a) {
    asm volatile("ldmatrix.sync.aligned.m8n8.x2.trans.shared.b16 {%0,%1}, [%2];" : "=r"(r0), "=r"(r1) : "r"(a) : "memory");
}
__device__ __forceinline__ void stsm4t(uint32_t a, uint32_t r0, uint32_t r1, uint32_t r2, uint32_t r3) {
    asm volatile("stmatrix.sync.aligned.m8n8.x4.trans.shared.b16 [%0], {%1,%2,%3,%4};"
                 ::"r"(a), "r"(r0), "r"(r1), "r"(r2), "r"(r3) : "memory");
}
__device__ __forceinline__ void lds128(uint32_t (&r)[4], uint32_t a) {
    asm volatile("ld.shared.v4.u32 {%0,%1,%2,%3}, [%4];" : "=r"(r[0]), "=r"(r[1]), "=r"(r[2]), "=r"(r[3]) : "r"(a) : "memory");
}
__device__ __forceinline__ float4 lds128f(uint32_t a) {
    float4 v;
    asm volatile("ld.shared.v4.f32 {%0,%1,%2,%3}, [%4];" : "=f"(v.x), "=f"(v.y), "=f"(v.z), "=f"(v.w) : "r"(a) : "memory");
    return v;
}
__device__ __forceinline__ float2 lds64f(uint32_t a) {
    float2 v;
    asm volatile("ld.shared.v2.f32 {%0,%1}, [%2];" : "=f"(v.x), "=f"(v.y) : "r"(a) : "memory");
    return v;
}
__device__ __forceinline__ uint32_t lds32(uint32_t a) {
    uint32_t v;
    asm volatile("ld.shared.u32 %0, [%1];" : "=r"(v) : "r"(a) : "memory");
    return v;
}
__device__ __forceinline__ void sts128(uint32_t a, uint32_t r0, uint32_t r1, uint32_t r2, uint32_t r3) {
    asm volatile("st.shared.v4.u32 [%0], {%1,%2,%3,%4};" ::"r"(a), "r"(r0), "r"(r1), "r"(r2), "r"(r3) : "memory");
}
__device__ __forceinline__ void sts128f(uint32_t a, float r0, float r1, float r2, float r3) {
    asm volatile("st.shared.v4.f32 [%0], {%1,%2,%3,%4};" ::"r"(a), "f"(r0), "f"(r1), "f"(r2), "f"(r3) : "memory");
}
__device__ __forceinline__ void sts64(uint32_t a, uint32_t r0, uint32_t r1) {
    asm volatile("st.shared.v2.u32 [%0], {%1,%2};" ::"r"(a), "r"(r0), "r"(r1) : "memory");
}
__device__ __forceinline__ void sts64f(uint32_t a, float r0, float r1) {
    asm volatile("st.shared.v2.f32 [%0], {%1,%2};" ::"r"(a), "f"(r0), "f"(r1) : "memory");
}
__device__ __forceinline__ void sts32f(uint32_t a, float r0) {
    asm volatile("st.shared.f32 [%0], %1;" ::"r"(a), "f"(r0) : "memory");
}
__device__ __forceinline__ uint2 ld_rlx64(const uint2* p) {
    uint2 v;
    asm volatile("{\n.reg .b64 t;\nld.relaxed.gpu.global.b64 t, [%2];\nmov.b64 {%0,%1}, t;\n}" : "=r"(v.x), "=r"(v.y) : "l"(p) : "memory");
    return v;
}
__device__ __forceinline__ void st_rlx64(uint2* p, uint32_t x, uint32_t y) {
    asm volatile("{\n.reg .b64 t;\nmov.b64 t, {%1,%2};\nst.relaxed.gpu.global.b64 [%0], t;\n}" ::"l"(p), "r"(x), "r"(y) : "memory");
}
__device__ __forceinline__ uint32_t ld_acq32(const uint32_t* p) {
    uint32_t v;
    asm volatile("ld.acquire.gpu.global.u32 %0, [%1];" : "=r"(v) : "l"(p) : "memory");
    return v;
}
__device__ __forceinline__ void wait_flag(const uint32_t* p, uint32_t need) {
    int n = 0;
    while (ld_acq32(p) < need) { __nanosleep(200); if (++n > SPIN_LIMIT) __trap(); }
}
__device__ __forceinline__ void bar_sync(int id, int n) { asm volatile("bar.sync %0, %1;" ::"r"(id), "r"(n) : "memory"); }
__device__ __forceinline__ void wg_fence() { asm volatile("wgmma.fence.sync.aligned;" ::: "memory"); }
__device__ __forceinline__ void wg_commit() { asm volatile("wgmma.commit_group.sync.aligned;" ::: "memory"); }
template <int N> __device__ __forceinline__ void wg_wait() { asm volatile("wgmma.wait_group.sync.aligned %0;" ::"n"(N) : "memory"); }
__device__ __forceinline__ uint64_t desc_sw128(uint32_t addr, uint32_t lbo, uint32_t sbo) {
    return (uint64_t)((addr & 0x3FFFF) >> 4) | ((uint64_t)(lbo >> 4) << 16) | ((uint64_t)(sbo >> 4) << 32) | (1ull << 62);
}
__device__ __forceinline__ void quad_transpose(uint32_t& r0, uint32_t& r1, uint32_t& r2, uint32_t& r3, int t) {
    const bool o = t & 1, h = t & 2;
    uint32_t s0 = __shfl_xor_sync(~0u, o ? r0 : r1, 1), s1 = __shfl_xor_sync(~0u, o ? r2 : r3, 1);
    uint32_t a0 = o ? s0 : r0, a1 = o ? r1 : s0, a2 = o ? s1 : r2, a3 = o ? r3 : s1;
    s0 = __shfl_xor_sync(~0u, h ? a0 : a2, 2); s1 = __shfl_xor_sync(~0u, h ? a1 : a3, 2);
    r0 = h ? s0 : a0; r1 = h ? s1 : a1; r2 = h ? a2 : s0; r3 = h ? a3 : s1;
}

__device__ __forceinline__ void wgmma_n256(float (&d)[128], uint64_t da, uint64_t db, int sd) {
    asm volatile("{\n.reg .pred p;\nsetp.ne.b32 p, %130, 0;\n"
        "wgmma.mma_async.sync.aligned.m64n256k16.f32.bf16.bf16 "
        "{%0,%1,%2,%3,%4,%5,%6,%7,%8,%9,%10,%11,%12,%13,%14,%15,"
        "%16,%17,%18,%19,%20,%21,%22,%23,%24,%25,%26,%27,%28,%29,%30,%31,"
        "%32,%33,%34,%35,%36,%37,%38,%39,%40,%41,%42,%43,%44,%45,%46,%47,"
        "%48,%49,%50,%51,%52,%53,%54,%55,%56,%57,%58,%59,%60,%61,%62,%63,"
        "%64,%65,%66,%67,%68,%69,%70,%71,%72,%73,%74,%75,%76,%77,%78,%79,"
        "%80,%81,%82,%83,%84,%85,%86,%87,%88,%89,%90,%91,%92,%93,%94,%95,"
        "%96,%97,%98,%99,%100,%101,%102,%103,%104,%105,%106,%107,%108,%109,%110,%111,"
        "%112,%113,%114,%115,%116,%117,%118,%119,%120,%121,%122,%123,%124,%125,%126,%127}, %128, %129, p, 1, 1, 0, 1;\n}\n"
        : "+f"(d[0]), "+f"(d[1]), "+f"(d[2]), "+f"(d[3]), "+f"(d[4]), "+f"(d[5]), "+f"(d[6]), "+f"(d[7]),
          "+f"(d[8]), "+f"(d[9]), "+f"(d[10]), "+f"(d[11]), "+f"(d[12]), "+f"(d[13]), "+f"(d[14]), "+f"(d[15]),
          "+f"(d[16]), "+f"(d[17]), "+f"(d[18]), "+f"(d[19]), "+f"(d[20]), "+f"(d[21]), "+f"(d[22]), "+f"(d[23]),
          "+f"(d[24]), "+f"(d[25]), "+f"(d[26]), "+f"(d[27]), "+f"(d[28]), "+f"(d[29]), "+f"(d[30]), "+f"(d[31]),
          "+f"(d[32]), "+f"(d[33]), "+f"(d[34]), "+f"(d[35]), "+f"(d[36]), "+f"(d[37]), "+f"(d[38]), "+f"(d[39]),
          "+f"(d[40]), "+f"(d[41]), "+f"(d[42]), "+f"(d[43]), "+f"(d[44]), "+f"(d[45]), "+f"(d[46]), "+f"(d[47]),
          "+f"(d[48]), "+f"(d[49]), "+f"(d[50]), "+f"(d[51]), "+f"(d[52]), "+f"(d[53]), "+f"(d[54]), "+f"(d[55]),
          "+f"(d[56]), "+f"(d[57]), "+f"(d[58]), "+f"(d[59]), "+f"(d[60]), "+f"(d[61]), "+f"(d[62]), "+f"(d[63]),
          "+f"(d[64]), "+f"(d[65]), "+f"(d[66]), "+f"(d[67]), "+f"(d[68]), "+f"(d[69]), "+f"(d[70]), "+f"(d[71]),
          "+f"(d[72]), "+f"(d[73]), "+f"(d[74]), "+f"(d[75]), "+f"(d[76]), "+f"(d[77]), "+f"(d[78]), "+f"(d[79]),
          "+f"(d[80]), "+f"(d[81]), "+f"(d[82]), "+f"(d[83]), "+f"(d[84]), "+f"(d[85]), "+f"(d[86]), "+f"(d[87]),
          "+f"(d[88]), "+f"(d[89]), "+f"(d[90]), "+f"(d[91]), "+f"(d[92]), "+f"(d[93]), "+f"(d[94]), "+f"(d[95]),
          "+f"(d[96]), "+f"(d[97]), "+f"(d[98]), "+f"(d[99]), "+f"(d[100]), "+f"(d[101]), "+f"(d[102]), "+f"(d[103]),
          "+f"(d[104]), "+f"(d[105]), "+f"(d[106]), "+f"(d[107]), "+f"(d[108]), "+f"(d[109]), "+f"(d[110]), "+f"(d[111]),
          "+f"(d[112]), "+f"(d[113]), "+f"(d[114]), "+f"(d[115]), "+f"(d[116]), "+f"(d[117]), "+f"(d[118]), "+f"(d[119]),
          "+f"(d[120]), "+f"(d[121]), "+f"(d[122]), "+f"(d[123]), "+f"(d[124]), "+f"(d[125]), "+f"(d[126]), "+f"(d[127])
        : "l"(da), "l"(db), "r"(sd));
}

__device__ __forceinline__ void wgmma_n128(float (&d)[64], uint64_t da, uint64_t db, int sd) {
    asm volatile("{\n.reg .pred p;\nsetp.ne.b32 p, %66, 0;\n"
        "wgmma.mma_async.sync.aligned.m64n128k16.f32.bf16.bf16 "
        "{%0,%1,%2,%3,%4,%5,%6,%7,%8,%9,%10,%11,%12,%13,%14,%15,"
        "%16,%17,%18,%19,%20,%21,%22,%23,%24,%25,%26,%27,%28,%29,%30,%31,"
        "%32,%33,%34,%35,%36,%37,%38,%39,%40,%41,%42,%43,%44,%45,%46,%47,"
        "%48,%49,%50,%51,%52,%53,%54,%55,%56,%57,%58,%59,%60,%61,%62,%63}, %64, %65, p, 1, 1, 0, 1;\n}\n"
        : "+f"(d[0]), "+f"(d[1]), "+f"(d[2]), "+f"(d[3]), "+f"(d[4]), "+f"(d[5]), "+f"(d[6]), "+f"(d[7]),
          "+f"(d[8]), "+f"(d[9]), "+f"(d[10]), "+f"(d[11]), "+f"(d[12]), "+f"(d[13]), "+f"(d[14]), "+f"(d[15]),
          "+f"(d[16]), "+f"(d[17]), "+f"(d[18]), "+f"(d[19]), "+f"(d[20]), "+f"(d[21]), "+f"(d[22]), "+f"(d[23]),
          "+f"(d[24]), "+f"(d[25]), "+f"(d[26]), "+f"(d[27]), "+f"(d[28]), "+f"(d[29]), "+f"(d[30]), "+f"(d[31]),
          "+f"(d[32]), "+f"(d[33]), "+f"(d[34]), "+f"(d[35]), "+f"(d[36]), "+f"(d[37]), "+f"(d[38]), "+f"(d[39]),
          "+f"(d[40]), "+f"(d[41]), "+f"(d[42]), "+f"(d[43]), "+f"(d[44]), "+f"(d[45]), "+f"(d[46]), "+f"(d[47]),
          "+f"(d[48]), "+f"(d[49]), "+f"(d[50]), "+f"(d[51]), "+f"(d[52]), "+f"(d[53]), "+f"(d[54]), "+f"(d[55]),
          "+f"(d[56]), "+f"(d[57]), "+f"(d[58]), "+f"(d[59]), "+f"(d[60]), "+f"(d[61]), "+f"(d[62]), "+f"(d[63])
        : "l"(da), "l"(db), "r"(sd));
}

__device__ __forceinline__ void wgmma_n64(float (&d)[32], uint64_t da, uint64_t db, int sd) {
    asm volatile("{\n.reg .pred p;\nsetp.ne.b32 p, %34, 0;\n"
        "wgmma.mma_async.sync.aligned.m64n64k16.f32.bf16.bf16 "
        "{%0,%1,%2,%3,%4,%5,%6,%7,%8,%9,%10,%11,%12,%13,%14,%15,"
        "%16,%17,%18,%19,%20,%21,%22,%23,%24,%25,%26,%27,%28,%29,%30,%31}, %32, %33, p, 1, 1, 0, 1;\n}\n"
        : "+f"(d[0]), "+f"(d[1]), "+f"(d[2]), "+f"(d[3]), "+f"(d[4]), "+f"(d[5]), "+f"(d[6]), "+f"(d[7]),
          "+f"(d[8]), "+f"(d[9]), "+f"(d[10]), "+f"(d[11]), "+f"(d[12]), "+f"(d[13]), "+f"(d[14]), "+f"(d[15]),
          "+f"(d[16]), "+f"(d[17]), "+f"(d[18]), "+f"(d[19]), "+f"(d[20]), "+f"(d[21]), "+f"(d[22]), "+f"(d[23]),
          "+f"(d[24]), "+f"(d[25]), "+f"(d[26]), "+f"(d[27]), "+f"(d[28]), "+f"(d[29]), "+f"(d[30]), "+f"(d[31])
        : "l"(da), "l"(db), "r"(sd));
}

constexpr int STAGE_BYTES = 49152, NSTAGE = 4;
constexpr int GEMM_SMEM = NSTAGE * STAGE_BYTES + 128;

struct GemmSmem { uint32_t st, full, empty; };
__device__ __forceinline__ GemmSmem gemm_setup(uint8_t* raw, int releases) {
    GemmSmem g;
    g.st = smem_u32(raw);
    if (g.st & 1023) __trap();
    g.full = g.st + NSTAGE * STAGE_BYTES; g.empty = g.full + 64;
    if (threadIdx.x == 0) {
        for (int s = 0; s < NSTAGE; s++) { mbar_init(g.full + 8 * s, 1); mbar_init(g.empty + 8 * s, releases); }
        asm volatile("fence.mbarrier_init.release.cluster;" ::: "memory");
        asm volatile("fence.proxy.async.shared::cta;" ::: "memory");
    }
    __syncthreads();
    return g;
}
__device__ __forceinline__ void mbar_arrive_one(uint32_t bar, uint32_t who) {
    asm volatile("{\n.reg .pred p;\nsetp.eq.u32 p, %1, 0;\n@p mbarrier.arrive.shared::cta.b64 _, [%0];\n}" ::"r"(bar), "r"(who) : "memory");
}
template <int BM, int BN, int KPS, typename ACC>
__device__ __forceinline__ void gemm_stage(ACC& acc, uint32_t stage, int wg, bool first) {
    const uint64_t da = desc_sw128(stage + wg * 8192, 16, 1024);
    const uint64_t db = desc_sw128(stage + KPS * BM * 128, 8192, 1024);
    wg_fence();
#pragma unroll
    for (int k = 0; k < 4 * KPS; k++) {
        const uint64_t a = da + (k >> 2) * (BM * 8) + (k & 3) * 2, b = db + k * 128;
        if constexpr (BN == 256) wgmma_n256(acc, a, b, first && k == 0 ? 0 : 1);
        else if constexpr (BN == 128) wgmma_n128(acc, a, b, first && k == 0 ? 0 : 1);
        else wgmma_n64(acc, a, b, first && k == 0 ? 0 : 1);
    }
    wg_commit();
}

__device__ __forceinline__ void kv_store_unit(const uint32_t (&pk)[64], int u, bf16* dst, int t) {
    const int G = (u >> 2) * 2 + (u & 1), hh = (u >> 1) & 1;
    uint32_t r0 = pk[(4 * G + 0) * 2 + hh], r1 = pk[(4 * G + 1) * 2 + hh], r2 = pk[(4 * G + 2) * 2 + hh], r3 = pk[(4 * G + 3) * 2 + hh];
    quad_transpose(r0, r1, r2, r3, t);
#define KVST ".cs"
    asm volatile("st.global" KVST ".v4.u32 [%0], {%1,%2,%3,%4};" ::"l"(dst + (size_t)hh * 8 * PW + G * 32), "r"(r0), "r"(r1), "r"(r2), "r"(r3) : "memory");
}

#define TLK(slot)
#define TLK2(slot)
__device__ __forceinline__ uint32_t near_page(int pair, int line) {
    uint32_t best[2] = {~0u, ~0u};
#pragma unroll 1
#define PMIN 8
#define PMAX 16
    for (int i = 0; i < PMAX; i++) {
        if (i >= PMIN && max(best[0], best[1]) - min(best[0], best[1]) > 110 && max(best[0], best[1]) - min(best[0], best[1]) < 300) break;
        uint32_t t0, t1, v;
        asm volatile("mov.u32 %0, %%clock;" : "=r"(t0)::"memory");
        asm volatile("atom.relaxed.gpu.global.or.b32 %0, [%1], -1;" : "=r"(v) : "l"(g_x + pair * 1024 + (i & 1) * 512 + line * 16) : "memory");
        asm volatile("{\n.reg .pred p;\nsetp.ne.u32 p, %1, 0x12345;\nmov.u32 %0, -1;\n@p mov.u32 %0, %%clock;\n}" : "=r"(t1) : "r"(v) : "memory");
        if (i & 1) best[1] = min(best[1], t1 - t0); else best[0] = min(best[0], t1 - t0);
    }
    return best[1] < best[0];
}
__device__ __forceinline__ void map_pages(int c) {
    uint32_t smid;
    asm("mov.u32 %0, %%smid;" : "=r"(smid));
    const uint32_t side = near_page(0, c & 31);
    g_side[smid & 255] = side;
    for (int p = c; p < XPAIRS; p += 132) g_home[p] = near_page(p, 0) ^ side;
}

__device__ __forceinline__ void kv_tile(int c, int n, int& m, int& nb) {
    if (c < 96) { m = (c & 3) + 4 * n; nb = c >> 2; }
    else {
        const int i = ((c - 96) >> 1) + 18 * n, j = i - 48 * NTA, p = j < 0 ? i / 24 : 2 * NTA + j / 48;
        m = 2 * p + (c & 1); nb = j < 0 ? 24 + i % 24 : j % 48;
    }
}

__global__ void __launch_bounds__(384, 1)
k_kv(const __grid_constant__ CUtensorMap mx, const __grid_constant__ CUtensorMap mwk, const __grid_constant__ CUtensorMap mwv,
     const __grid_constant__ CUtensorMap mwq, const bf16* __restrict__ Wq, const bf16* __restrict__ Wo, int c0) {
    extern __shared__ __align__(1024) uint8_t smem_gemm[];
    const int c = c0 + blockIdx.x, ntile = c < 96 ? NTA : (384 - 48 * NTA + 17 - ((c - 96) >> 1)) / 18;
    if (c != 96) asm volatile("griddepcontrol.launch_dependents;");
    const uint32_t bar_done = smem_u32(smem_gemm) + NSTAGE * STAGE_BYTES + 96;
    if (threadIdx.x == 0) { mbar_init(bar_done, 8); mbar_init(bar_done + 8, 8); }
    GemmSmem g = gemm_setup(smem_gemm, 4);
    if (threadIdx.x == 0) TLK(0);
    uint32_t rank, peer_empty;
    asm("mov.u32 %0, %%cluster_ctarank;" : "=r"(rank));
    asm("mapa.shared::cluster.u32 %0, %1, %2;" : "=r"(peer_empty) : "r"(g.empty), "r"(rank ^ 1));
    asm volatile("barrier.cluster.arrive.relaxed.aligned;\nbarrier.cluster.wait.aligned;" ::: "memory");
    auto release = [&](int s) {
        asm volatile("{\n.reg .pred p;\nsetp.eq.u32 p, %2, 0;\n@p mbarrier.arrive.relaxed.cta.shared::cta.b64 _, [%0];\n"
                     "@p mbarrier.arrive.relaxed.cluster.shared::cluster.b64 _, [%1];\n}"
                     ::"r"(g.empty + 8 * s), "r"(peer_empty + 8 * s), "r"(threadIdx.x & 127) : "memory");
    };
    const int wg = __shfl_sync(~0u, threadIdx.x >> 7, 0);
    if (wg == 0) {
        asm volatile("setmaxnreg.dec.sync.aligned.u32 40;");
        if (threadIdx.x == 0) {
            for (int it = 0; it < ntile * 16; it++) {
                const int s = it & 3, kb = it & 15;
                int m, nb;
                kv_tile(c, it >> 4, m, nb);
                mbar_wait(g.empty + 8 * s, ((it >> 2) & 1) ^ 1);
                mbar_expect_tx(g.full + 8 * s, STAGE_BYTES);
                tma2d(g.st + s * STAGE_BYTES, &mx, kb * 64, m * 128, g.full + 8 * s);
                asm volatile("cp.async.bulk.tensor.3d.shared::cluster.global.mbarrier::complete_tx::bytes.multicast::cluster "
                             "[%0], [%1, {%3, %4, %5}], [%2], %6;"
                             ::"r"(g.st + s * STAGE_BYTES + 16384 + (c & 1) * 16384), "l"(nb < 16 ? &mwk : nb < 32 ? &mwv : &mwq), "r"(g.full + 8 * s),
                               "r"(0), "r"(kb * 64), "r"((nb & 15) * 4 + (c & 1) * 2), "h"((uint16_t)(3u << (rank & ~1u))) : "memory");
#define PF0 (16 * NTA - 22)
                if (c < 96 && it >= PF0 && (it - PF0) * 96 + c < 2048)
                    asm volatile("cp.async.bulk.prefetch.L2.global [%0], 4096;" ::"l"((const char*)Wo + ((it - PF0) * 96 + c) * 4096) : "memory");
            }
        } else if (threadIdx.x == 32) {
            if (c == 96) {
                for (int i = 0; i < 64; i++) reinterpret_cast<uint4*>(g_flag)[i] = make_uint4(0, 0, 0, 0);
                asm volatile("fence.acq_rel.gpu;\ngriddepcontrol.launch_dependents;\ngriddepcontrol.wait;\n"
                             "fence.acq_rel.gpu;\nred.relaxed.gpu.global.add.u32 [%0], 1;" ::"l"(g_flag + 8) : "memory");
            }
        } else if (threadIdx.x == 64) {
            for (int n = 0; n < (c < 96 ? 0 : ntile); n++) {
                int m, nb;
                kv_tile(c, n, m, nb);
                mbar_wait(bar_done + (n & 1) * 8, (n >> 1) & 1);
                asm volatile("fence.acq_rel.gpu;\nred.relaxed.gpu.global.add.u32 [%0], 1;" ::"l"(g_flag + (m >> 1)) : "memory");
            }
        } else if (threadIdx.x >= 96) {
            const uint4 ones = make_uint4(~0u, ~0u, ~0u, ~0u);
            for (int i = c * 32 + threadIdx.x - 96; i < XPAIRS * 512; i += 132 * 32) reinterpret_cast<uint4*>(g_x)[i] = ones;
            __syncwarp();
            if (threadIdx.x == 96) {
                map_pages(c);
                if (c >= 96) asm volatile("fence.acq_rel.gpu;\nred.relaxed.gpu.global.add.u32 [%0], 1;" ::"l"(g_flag + 8) : "memory");
            }
        }
    } else {
        asm volatile("setmaxnreg.inc.sync.aligned.u32 232;");
        const int cw = wg - 1, lane = threadIdx.x & 31, t = lane & 3;
        bf16* const dst0 = g_kv + (size_t)(cw * 64 + ((threadIdx.x >> 5) & 3) * 16 + (lane >> 2)) * PW + t * 8;
        bf16* dst = dst0;
        float acc[128];
        uint32_t pk[64];
#pragma unroll 1
        for (int tile = 0; tile < ntile; tile++) {
#pragma unroll
            for (int kb = 0; kb < 16; kb++) {
                mbar_wait_u(g.full + 8 * (kb & 3), (kb >> 2) & 1);
                if (kb == 0 && tile == 0 && threadIdx.x == 128) TLK2(0);
                gemm_stage<128, 256, 1>(acc, g.st + (kb & 3) * STAGE_BYTES, cw, kb == 0);
                if (tile > 0) {
                    kv_store_unit(pk, kb, dst, t);
                    if (kb == 15) { __syncwarp(); mbar_arrive_one(bar_done + (~tile & 1) * 8, lane); }
                }
                if (kb > 0) {
                    wg_wait<1>();
                    if (kb <= 12 || tile < ntile - 1) release((kb - 1) & 3);
                }
            }
            wg_wait<0>();
            if (tile < 4 && threadIdx.x == 128) TLK2(tile + 1);
            if (tile < ntile - 1) release(3);
#pragma unroll
            for (int i = 0; i < 64; i++) pk[i] = pack2(acc[2 * i], acc[2 * i + 1]);
            int m, nb;
            kv_tile(c, tile, m, nb);
            dst = dst0 + (size_t)m * 128 * PW + nb * 256;
        }
        if (threadIdx.x == 128) TLK(2);
#pragma unroll
        for (int u = 0; u < 16; u++) kv_store_unit(pk, u, dst, t);
        __syncwarp();
        mbar_arrive_one(bar_done + (~ntile & 1) * 8, lane);
        if (threadIdx.x == 128) TLK(1);
    }
}

constexpr int NS1 = 31;
#define RB1 4
#define PFC 4
constexpr int C_W1 = 0;
constexpr int C_W2 = C_W1 + 8 * NS1 * 512;
constexpr int C_KV = C_W2 + 14 * 8 * 512;
constexpr int C_RED = C_KV + 16384;
constexpr int C_QKV = C_RED + 64 * 272;
constexpr int QKV_SZ = 3 * 8 * 272;
constexpr int C_SC = C_RED;
constexpr int C_OB = C_SC + 2 * 8 * 52 * 4;
constexpr int C_BAR = C_QKV + 2 * QKV_SZ;
__host__ __device__ constexpr int smem_idx(int ks, int j) {
    return ks == 0 ? j : ks < 3 ? (j < 4 ? 4 + 4 * ks + j : -1) : (j < 3 ? 7 + 3 * ks + j : -1);
}
constexpr int CHAIN_SMEM = C_BAR + 64;
#define TS(i)
#define TG(i)

#define DLY3 10
#define DLY1 4
#define DLY0 4
#define DLY1A 11
#define DLY0A 0
#define DLY1B 4
#define PFD 3
#define PFI 0
#define DLYW 4
#define DLYQ 3
#define DLYS 0
template <int N> __device__ __forceinline__ uint32_t delayed(uint32_t x, uint32_t self) {
    uint32_t p = self;
#pragma unroll
    for (int i = 0; i < N; i++) asm volatile("ld.volatile.shared.u32 %0, [%0];" : "+r"(p)::"memory");
    return x + (p - self);
}
__device__ __forceinline__ int fresh(int x) { asm volatile("mov.b32 %0, %0;" : "+r"(x)); return x; }
__device__ __forceinline__ void lds128v(uint32_t (&r)[4], uint32_t a) {
    asm volatile("ld.volatile.shared.v4.u32 {%0,%1,%2,%3}, [%4];" : "=r"(r[0]), "=r"(r[1]), "=r"(r[2]), "=r"(r[3]) : "r"(a) : "memory");
}
__device__ __forceinline__ uint2 lds64(uint32_t a) {
    uint2 v;
    asm volatile("ld.shared.v2.u32 {%0,%1}, [%2];" : "=r"(v.x), "=r"(v.y) : "r"(a) : "memory");
    return v;
}
#define LDQ ".L1::no_allocate"
__device__ __forceinline__ uint4 ldw128(const void* p) {
    uint4 v;
    asm volatile("ld.global.nc" LDQ ".v4.u32 {%0,%1,%2,%3}, [%4];" : "=r"(v.x), "=r"(v.y), "=r"(v.z), "=r"(v.w) : "l"(p));
    return v;
}
#define P8_LD(i) "ld.relaxed.gpu.global.b64 d" #i ", [src + " #i " * 256];\n"
#define P8_X(i) "mov.b64 {x" #i ", y" #i "}, d" #i ";\n"
#define P8_HEAD(SRC) "{\n.reg .pred p, q;\n.reg .b64 src, d<8>;\n.reg .b32 n, x<8>, y<8>, m0, m1;\nmov.b64 src, " SRC ";\n"         \
                P8_LD(0) P8_LD(1) P8_LD(2) P8_LD(3) P8_LD(4) P8_LD(5) P8_LD(6) P8_LD(7) "mov.u32 n, 0;\nCHECK:\n" \
                P8_X(0) P8_X(1) P8_X(2) P8_X(3) P8_X(4) P8_X(5) P8_X(6) P8_X(7)
#define P8_VOTE "vote.sync.all.pred p, p, -1;\n@p bra.uni DONE;\n"
#define P8_TAIL "add.u32 n, n, 1;\nsetp.lt.u32 p, n, 0x100000;\n@p bra.uni CHECK;\ntrap;\nDONE:\n"
#define S8_LD(i) "ld.relaxed.gpu.global.b64 %" #i ", [%8 + " #i " * 256];\n"
__device__ __forceinline__ void fetch_state(uint64_t (&d)[8], const void* src) {
    asm volatile(S8_LD(0) S8_LD(1) S8_LD(2) S8_LD(3) S8_LD(4) S8_LD(5) S8_LD(6) S8_LD(7)
                 : "=&l"(d[0]), "=&l"(d[1]), "=&l"(d[2]), "=&l"(d[3]), "=&l"(d[4]), "=&l"(d[5]), "=&l"(d[6]), "=&l"(d[7]) : "l"(src) : "memory");
}
__device__ __forceinline__ void settle_state(uint64_t (&d)[8], const void* src) {
#define S8_X(i) "mov.b64 {x" #i ", _}, %" #i ";\n"
#define S8_R(i) "setp.eq.u32 q, x" #i ", 0xffffffff;\n@q " S8_LD(i)
    asm volatile("{\n.reg .pred p, q;\n.reg .b32 n, x<8>, m0, m1;\nmov.u32 n, 0;\nCHECK:\n"
                 S8_X(0) S8_X(1) S8_X(2) S8_X(3) S8_X(4) S8_X(5) S8_X(6) S8_X(7)
                 "max.u32 m0, x0, x1;\nmax.u32 m0, m0, x2;\nmax.u32 m1, x3, x4;\nmax.u32 m1, m1, x5;\nmax.u32 m0, m0, x6;\n"
                 "max.u32 m0, m0, x7;\nmax.u32 m0, m0, m1;\nsetp.ne.u32 p, m0, 0xffffffff;\n" P8_VOTE
                 S8_R(0) S8_R(1) S8_R(2) S8_R(3) S8_R(4) S8_R(5) S8_R(6) S8_R(7) P8_TAIL "}"
                 : "+l"(d[0]), "+l"(d[1]), "+l"(d[2]), "+l"(d[3]), "+l"(d[4]), "+l"(d[5]), "+l"(d[6]), "+l"(d[7]) : "l"(src) : "memory");
}
__device__ __forceinline__ uint64_t poll_sum(const void* src, uint32_t tag, uint32_t sel) {
#define P8_RT(i) "lop3.b32 m0, x" #i ", %2, 1, 0x28;\nsetp.ne.u32 q, m0, 0;\n@q " P8_LD(i)
#define P8_MMA(c, i, z) "mma.sync.aligned.m16n8k8.row.col.f32.bf16.bf16.f32 {" #c "0," #c "1," #c "2," #c "3}, {x" #i ", y" #i "}, {%3}, {" #z "0," #z "1," #z "2," #z "3};\n"
    uint64_t r;
    asm volatile(P8_HEAD("%1") "{\n.reg .f32 a<4>, b<4>, z<4>;\nmov.f32 z0, 0f00000000;\nmov.f32 z1, z0;\nmov.f32 z2, z0;\nmov.f32 z3, z0;\n"
                 P8_MMA(a, 0, z) P8_MMA(b, 1, z) P8_MMA(a, 2, a) P8_MMA(b, 3, b) P8_MMA(a, 4, a) P8_MMA(b, 5, b) P8_MMA(a, 6, a) P8_MMA(b, 7, b)
                 "add.f32 a0, a0, b0;\nadd.f32 a1, a1, b1;\nadd.f32 a2, a2, b2;\nadd.f32 a3, a3, b3;\n"
                 "cvt.rn.bf16x2.f32 m0, a1, a0;\ncvt.rn.bf16x2.f32 m1, a3, a2;\nmov.b64 %0, {m0, m1};\n}\n"
                 "lop3.b32 m0, x0, x1, %2, 0x7e;\nlop3.b32 m1, x2, x3, %2, 0x7e;\nlop3.b32 m0, m0, x4, %2, 0xf6;\n"
                 "lop3.b32 m1, m1, x5, %2, 0xf6;\nlop3.b32 m0, m0, x6, %2, 0xf6;\nlop3.b32 m1, m1, x7, %2, 0xf6;\n"
                 "lop3.b32 m0, m0, m1, 1, 0xa8;\nsetp.eq.u32 p, m0, 0;\n" P8_VOTE
                 P8_RT(0) P8_RT(1) P8_RT(2) P8_RT(3) P8_RT(4) P8_RT(5) P8_RT(6) P8_RT(7) P8_TAIL "}"
                 : "=&l"(r) : "l"(src), "r"(tag), "r"(sel) : "memory");
    return r;
}
__device__ __forceinline__ void wait_count_u(const uint32_t* p, uint32_t need) {
    asm volatile("{\n.reg .pred p;\n.reg .u32 n, v;\nmov.u32 n, 0;\nAGAIN:\nld.acquire.gpu.global.u32 v, [%0];\nsetp.ge.u32 p, v, %1;\n"
                 "vote.sync.all.pred p, p, -1;\n@p bra.uni DONE;\nadd.u32 n, n, 1;\nsetp.lt.u32 p, n, 0x100000;\n@p bra.uni AGAIN;\ntrap;\n"
                 "DONE:\nfence.proxy.async.global;\n}" ::"l"(p), "r"(need) : "memory");
}
__device__ __forceinline__ uint32_t movm(uint32_t x) { asm volatile("movmatrix.sync.aligned.m8n8.trans.b16 %0, %0;" : "+r"(x)); return x; }
template <int NK, typename F>
__device__ __forceinline__ void attend(uint32_t sb, uint32_t lm, uint32_t qs, uint32_t xq, int i8, int lane, bf16* dst, F mid) {
    const int r8 = lane & 7, m4 = lane >> 3;
    const float sl2e = 0.08838834764831845f * 1.4426950408889634f;
    const uint32_t lk = sb + C_KV + ((m4 & 1) * 8 + r8) * 128 + (((m4 >> 1) ^ r8) << 4);
    const uint32_t lkm = sb + xq + (8 + r8) * 272 + (m4 & 1) * 32 + (m4 >> 1) * 16;
    asm volatile("cp.async.wait_all;" ::: "memory");
    __syncwarp();
    float x[4][4];
#pragma unroll
    for (int i = 0; i < 4; i++) x[i][0] = x[i][1] = x[i][2] = x[i][3] = 0.f;
#pragma unroll
    for (int kp = 0; kp < 4; kp++) {
        uint32_t q[4], a[4];
        ldsm4(q, lm + qs + kp * 64);
        ldsm4(a, lkm + kp * 64);
        mma16816(x[2], a[0], a[1], a[2], a[3], q[0], q[1]);
        mma16816(x[3], a[0], a[1], a[2], a[3], q[2], q[3]);
#pragma unroll
        for (int u = 0; u < 4; u++) {
            if ((u & 1) >= NK) continue;
            ldsm4(a, (lk ^ (((kp & 1) * 2 + (u >> 1)) << 5)) + (kp >> 1) * 4096 + (u & 1) * 2048);
            mma16816(x[u & 1], a[0], a[1], a[2], a[3], q[u & 2], q[(u & 2) + 1]);
        }
    }
    x[2][0] += x[3][2]; x[2][1] += x[3][3];
    const int lim = i8 + 2 * (lane & 3) - (lane >> 2);
    uint32_t p[5];
    {
        float m[2], e[5][2];
#pragma unroll
        for (int b = 0; b < 2; b++) {
            e[4][b] = m[b] = x[2][b];
#pragma unroll
            for (int j = 0; j < 2 * NK; j++) {
                e[j][b] = j < 2 * NK - 2 || 8 * j - b <= lim ? x[j >> 1][(j & 1) * 2 + b] : -3.0e38f;
                m[b] = fmaxf(m[b], e[j][b]);
            }
        }
#pragma unroll
        for (int o = 4; o < 32; o <<= 1) {
            m[0] = fmaxf(m[0], __shfl_xor_sync(~0u, m[0], o));
            m[1] = fmaxf(m[1], __shfl_xor_sync(~0u, m[1], o));
        }
        m[0] *= sl2e; m[1] *= sl2e;
#pragma unroll
        for (int j = 0; j < 5; j++)
            if (j < 2 * NK || j == 4) p[j] = movm(pack2(ex2(fmaf(e[j][0], sl2e, -m[0])), ex2(fmaf(e[j][1], sl2e, -m[1]))));
    }
    const uint32_t lvt = sb + C_KV + 8192 + ((m4 >> 1) * 8 + r8) * 128 + (((m4 & 1) ^ r8) << 4), one = 0x3f803f80u;
    float sm[4] = {0.f, 0.f, 0.f, 0.f}, c[8][4];
    mma16816(sm, one, one, one, one, p[0], p[1]);
    if (NK == 2) mma16816(sm, one, one, one, one, p[2], p[3]);
    mma1688(sm, one, one, p[4]);
#pragma unroll
    for (int j = 0; j < 8; j++) c[j][0] = c[j][1] = c[j][2] = c[j][3] = 0.f;
#pragma unroll
    for (int kk = 0; kk < NK; kk++)
#pragma unroll
        for (int j = 0; j < 8; j++) {
            uint32_t a[4];
            ldsm4t(a, (lvt ^ ((j & 3) << 5)) + (j >> 2) * 4096 + kk * 2048);
            mma16816(c[j], a[0], a[1], a[2], a[3], p[2 * kk], p[2 * kk + 1]);
        }
    float i0, i1;
    asm("rcp.approx.ftz.f32 %0, %1;" : "=f"(i0) : "f"(sm[0]));
    asm("rcp.approx.ftz.f32 %0, %1;" : "=f"(i1) : "f"(sm[1]));
    uint32_t o[4][4];
#pragma unroll
    for (int j = 0; j < 4; j++) {
        uint32_t a[4];
        ldsm4t(a, lm + xq + 16 * 272 + j * 64);
        mma1688(c[2 * j], a[0], a[1], p[4]);
        mma1688(c[2 * j + 1], a[2], a[3], p[4]);
#pragma unroll
        for (int u = 0; u < 4; u++) o[j][u] = pack2(c[2 * j + (u >> 1)][(u & 1) * 2] * i0, c[2 * j + (u >> 1)][(u & 1) * 2 + 1] * i1);
    }
#pragma unroll
    for (int j = 0; j < 4; j++) stsm4t(lm + qs + j * 64, o[j][0], o[j][1], o[j][2], o[j][3]);
    mid();
    __syncwarp();
#pragma unroll
    for (int j = 0; j < 4; j++) lds128(o[j], sb + qs + ((lane >> 4) + 2 * j) * 272 + (lane & 15) * 16);
#pragma unroll
    for (int j = 0; j < 4; j++)
        asm volatile("st.global.v4.u32 [%0], {%1,%2,%3,%4};" ::"l"(dst + (size_t)2 * j * HD), "r"(o[j][0]), "r"(o[j][1]), "r"(o[j][2]), "r"(o[j][3]) : "memory");
}
__device__ __forceinline__ void sum8(float (&c)[4], const uint2 (&v)[8], uint32_t idn) {
    float d[4] = {0.f, 0.f, 0.f, 0.f};
    c[0] = c[1] = c[2] = c[3] = 0.f;
    mma16816(c, v[0].x, v[0].y, v[1].x, v[1].y, idn, idn);
    mma16816(d, v[2].x, v[2].y, v[3].x, v[3].y, idn, idn);
    mma16816(c, v[4].x, v[4].y, v[5].x, v[5].y, idn, idn);
    mma16816(d, v[6].x, v[6].y, v[7].x, v[7].y, idn, idn);
    c[0] += d[0]; c[1] += d[1]; c[2] += d[2]; c[3] += d[3];
}

#define CLS 6
__global__ void __cluster_dims__(CLS, 1, 1) __launch_bounds__(256, 1)
k_chain(const bf16* __restrict__ mem0, const bf16* __restrict__ Wq, const bf16* __restrict__ Wk, const bf16* __restrict__ Wv,
        const bf16* __restrict__ Wo, const __grid_constant__ CUtensorMap mkv) {
    extern __shared__ __align__(1024) uint8_t smem_chain[];
    const uint32_t sb = smem_u32(smem_chain);
    if (sb & 1023) __trap();
    const int w = __shfl_sync(~0u, threadIdx.x >> 5, 0), lane = __shfl_sync(~0u, threadIdx.x & 31, threadIdx.x & 31);
    const int tid = w * 32 + lane, g = lane >> 2, t = lane & 3;
    auto pin = [&](uint32_t x) { asm volatile("shfl.sync.idx.b32 %0, %0, %1, 31, -1;" : "+r"(x) : "r"(lane) : "memory"); return x; };
    const int h = blockIdx.x / 3, r = blockIdx.x - 3 * h;
    const uint32_t bar_x = sb + C_BAR, bar_kv = sb + C_BAR + 8, bar_go = sb + C_BAR + 16, bar_w = sb + C_BAR + 24, self = sb + C_BAR + 60;
    asm volatile("griddepcontrol.launch_dependents;");
    const int tbase = r == 0 ? 0 : 1 + 21 * r, ntile = r == 0 ? 22 : 21;
    uint32_t side;
    if (tid == 0) {
        mbar_init(bar_x, 8); mbar_init(bar_kv, 1); mbar_init(bar_go, 1); mbar_init(bar_w, 1);
        asm volatile("st.shared.u32 [%0], %0;" ::"r"(self) : "memory");
        asm volatile("fence.mbarrier_init.release.cluster;" ::: "memory");
        asm volatile("fence.proxy.async.shared::cta;" ::: "memory");
        mbar_expect_tx(bar_w, 128 * 32 * ntile);
    }
    __syncthreads();
    asm volatile("barrier.cluster.arrive.relaxed.aligned;" ::: "memory");
    if (tid < 128)
        asm volatile("cp.async.bulk.shared::cluster.global.mbarrier::complete_tx::bytes [%0], [%1], %2, [%3];"
                     ::"r"(sb + C_W1 + tid * 720), "l"(Wo + (size_t)(h * 128 + tid) * DM + tbase * 16), "r"(32 * ntile), "r"(bar_w) : "memory");
    const int tile0 = tbase + 7 - w;
    const bool three = w >= (r == 0 ? 2 : 3);
    const uint32_t wa = pin(sb + tid * 16);
#define W1A(i) (wa + C_W1 + (i) * 4096)
#define W2A(x) (wa + C_W2 + ((x) < 8 ? (x) * 4096 : 32768 - 1024 + ((x) - 8) * 3072))
    uint32_t wo0[8][4], wr[64][4];
    {
        const bf16* W = (r == 0 ? Wq : r == 1 ? Wk : Wv) + (size_t)(128 * w + (lane >> 4)) * HD + h * 128 + 8 * (lane & 15);
        uint4 raw[8][8];
        auto fetch = [&](int ks) {
#pragma unroll
            for (int i = 0; i < 8; i++) raw[ks][i] = ldw128(W + (size_t)(16 * ks + 2 * i) * HD);
        };
        fetch(0); fetch(1); fetch(2); fetch(3);
    asm("mov.u32 %0, %%smid;" : "=r"(side));
    side = __ldcg(g_side + (side & 255)) & 1;
    if (tid == 0 && r > 0) asm volatile("st.relaxed.gpu.global.u32 [%0], %1;" ::"l"(g_flag + 128 + 2 * h + r - 1), "r"(2 | side) : "memory");
        if (w == 0) TG(0);
        mbar_wait_u(bar_w, 0);
        if (w == 0) TG(1);
        const uint32_t p = sb + C_W1 + ((lane & 7) + (lane >> 4) * 8) * 720 + (7 - w) * 32 + ((lane >> 3) & 1) * 16;
#pragma unroll
        for (int ks = 0; ks < 8; ks++) {
            uint32_t a[4];
            ldsm4t(wo0[ks], p + ks * 16 * 720);
            ldsm4t(a, p + ks * 16 * 720 + 256);
            sts128(W2A(ks), a[0], a[1], a[2], a[3]);
            if (three) { ldsm4t(a, p + ks * 16 * 720 + 512); sts128(W2A(8 + ks), a[0], a[1], a[2], a[3]); }
        }
        __syncthreads();
        if (w < PFI)
            asm volatile("prefetch.global.L2 [%0];\nprefetch.global.L2 [%0 + 128];" ::"l"(g_kv + (size_t)tid * PW + r * HD + h * 128) : "memory");
        if (w == 0) TG(2);
        const uint32_t stg = sb + C_KV + w * 4096;
        const uint32_t rd = stg + ((lane & 7) + 8 * (lane >> 4)) * 256 + ((((lane >> 3) & 1) ^ (lane & 7)) << 4);
#pragma unroll
        for (int ks = 0; ks < 8; ks++) {
#pragma unroll
            for (int i = 0; i < 8; i++)
                sts128(stg + (2 * i + (lane >> 4)) * 256 + (((lane & 15) ^ (((2 * i) & 6) | (lane >> 4))) << 4),
                       raw[ks][i].x, raw[ks][i].y, raw[ks][i].z, raw[ks][i].w);
            if (ks < 2) fetch(ks + 4);
            if (ks == 3 || ks == 5) fetch(ks / 2 + 5);
            __syncwarp();
#pragma unroll
            for (int j = 0; j < 8; j++) {
                if (smem_idx(ks, j) >= 0) {
                    uint32_t a[4];
                    ldsm4t(a, rd ^ (j << 5));
                    sts128(W1A(smem_idx(ks, j)), a[0], a[1], a[2], a[3]);
                } else ldsm4t(wr[8 * ks + j], rd ^ (j << 5));
            }
            __syncwarp();
        }
    }
    if (w == 0) TG(3);
    wait_count_u(g_flag + (lane & 8), lane & 8 ? 37 : 48);
    asm volatile("fence.proxy.async.shared::cta;" ::: "memory");
    __syncthreads();
    if (tid == 0) {
        mbar_expect_tx(bar_kv, 16384);
        tma3d(sb + C_KV, &mkv, 0, 0, 2 * h, bar_kv);
        tma3d(sb + C_KV + 8192, &mkv, 0, 0, 64 + 2 * h, bar_kv);
    }
    asm volatile("barrier.cluster.wait.aligned;" ::: "memory");

    auto load_kv = [&](int s) {
        asm volatile("{\n.reg .pred p;\nelect.sync _|p, -1;\n@p mbarrier.arrive.expect_tx.shared::cta.b64 _, [%2], 16384;\n"
                     "@p cp.async.bulk.tensor.3d.shared::cluster.global.mbarrier::complete_tx::bytes [%0], [%1, {%3, %4, %5}], [%2];\n"
                     "@p cp.async.bulk.tensor.3d.shared::cluster.global.mbarrier::complete_tx::bytes [%6], [%1, {%3, %4, %7}], [%2];\n}"
                     ::"r"(sb + C_KV), "l"(&mkv), "r"(bar_kv), "r"(0), "r"(s * 32), "r"(2 * h), "r"(sb + C_KV + 8192), "r"(64 + 2 * h) : "memory");
    };
    const bool attends = w == 7 || (w == 6 && r == 0);
    const int i8 = r == 0 ? (w - 4) * 8 : (r - 1) * 8;
    auto load_q = [&](int s) {
        const int l = fresh(lane);
        const bf16* p = g_kv + (size_t)(s * 32 + i8 + (l >> 4)) * PW + 2 * HD + h * 128 + (l & 15) * 8;
#pragma unroll
        for (int j = 0; j < 4; j++)
            asm volatile("cp.async.cg.shared.global [%0], [%1], 16;"
                         ::"r"(sb + C_RED + w * 2176 + ((l >> 4) + 2 * j) * 272 + (l & 15) * 16), "l"(p + (size_t)2 * j * PW) : "memory");
    };
    auto report = [&](int blk) {
        asm volatile("{\n.reg .pred p;\nelect.sync _|p, -1;\nfence.acq_rel.gpu;\n@p red.relaxed.gpu.global.add.u32 [%0], 1;\n}"
                     ::"l"(g_flag + 64 + blk) : "memory");
    };
    const float sl2e = 0.08838834764831845f * 1.4426950408889634f;
    const uint32_t idn = pin(g == 2 * t ? 0x00003f80u : g == 2 * t + 1 ? 0x3f800000u : 0u);
    const uint32_t lm = pin(sb + (lane & 7) * 272 + (lane >> 3) * 16);
    const uint32_t sa = pin(sb + C_SC + (w & 1) * (8 * 52 * 4) + (2 * t * 52 + (w < 4 ? 32 : (w & 2) * 8) + g) * 4);
    const uint32_t sr = pin(sb + C_SC + (g * 52 + 8 * t) * 4), sr2 = pin(sb + C_SC + (g * 52 + 32 + 2 * t) * 4);
    uint32_t kva;
    {
        const int pos = (w & 2) * 8 + (lane & 15), row = (pos & 24) + ((pos + (pos >> 2 & 6)) & 7);
        const int key = 4 * (lane & 6) + (((lane & 7) + 2 * (lane >> 4)) & 7);
        kva = pin(w >= 4 ? sb + C_KV + (w & 1) * 4096 + row * 128 + (((lane >> 4) ^ (row & 7)) << 4)
                         : sb + C_KV + 8192 + (w >> 1) * 4096 + key * 128 + ((((w & 1) * 4 + ((lane >> 3) & 1)) ^ (key & 7)) << 4));
    }
#define ATTEND(NK, s, mid) do {                                                                                       \
        const int l_ = fresh(lane);                                                                                      \
        attend<NK>(sb, lm, C_RED + w * 2176, C_QKV + ((s) & 1) * QKV_SZ, i8, l_,                                         \
                   g_o + (size_t)((s) * 32 + i8 + (l_ >> 4)) * HD + h * 128 + (l_ & 15) * 8, mid);                       \
    } while (0)
    auto chores = [&](int s) {
        if ((s & 3) == 0 && s) report((s >> 2) - 1);
        if ((s & 7) == 6 && s < NSEG - 2) wait_count_u(g_flag + (s >> 3) + 1, (s >> 3) + 1 < 2 * NTA ? 48 : 96);
    };
    uint32_t buf0[8][4], ring[RB1][4];
#define STAGE_W1() do {                                                            \
        _Pragma("unroll") for (int i = 0; i < 8; i++) lds128v(buf0[i], W1A(i));       \
        _Pragma("unroll") for (int i = 0; i < RB1; i++) lds128v(ring[i], W1A(8 + i)); \
    } while (0)
    auto stage_w1 = [&]() { STAGE_W1(); };
    stage_w1();
    uint32_t psel, msel0, msel1;
    {
        const int j = r > 0 ? 2 * h + r - 1 : 0, tl = min(tile0 + 8 * (lane >> 1), 63);
        uint32_t b;
        asm volatile("{\n.reg .pred p;\n.reg .u32 n;\nmov.u32 n, 0;\nAGAIN:\nld.relaxed.gpu.global.u32 %0, [%1];\nsetp.ne.u32 p, %0, 0;\n"
                     "vote.sync.all.pred p, p, -1;\n@p bra.uni DONE;\nadd.u32 n, n, 1;\nsetp.lt.u32 p, n, 0x100000;\n@p bra.uni AGAIN;\ntrap;\nDONE:\n}"
                     : "=&r"(b) : "l"(g_flag + 128 + tl) : "memory");
        psel = __ballot_sync(~0u, (g_home[lane == 6 ? j * 2 + ((w >> 1) & 1) : tl * 2 + (lane & 1)] ^ (lane == 6 ? side : b)) & 1);
        msel0 = __ballot_sync(~0u, (g_home[128 + lane * 4 + (w >> 1)] ^ side) & 1);
        msel1 = __ballot_sync(~0u, (g_home[256 + lane * 4 + (w >> 1)] ^ side) & 1);
        if (r > 0) {
            if (w < 4) asm volatile("prefetch.global.L2 [%0];" ::"l"(g_x + (128 + (1 + (w >> 1)) * 4 + (j >> 4)) * 1024 + (w & 1) * 512 + (j & 15) * 32 + lane) : "memory");
            if (w < 4) asm volatile("prefetch.global.L2 [%0];" ::"l"(g_x + j * 2048 + tid * 16) : "memory");
        }
    }
    uint2 bm[8];
#pragma unroll
    for (int ks = 0; ks < 8; ks++) {
        const uint32_t* p = (const uint32_t*)(mem0 + g * DM + (8 * w + ks) * 16) + t;
        bm[ks] = make_uint2(__ldg(p), __ldg(p + 4));
    }
    if (w == 0) TG(5);
#pragma unroll 1
    for (int s = 0;; s++) {
        TS(1);
        const uint32_t xq = C_QKV + (s & 1) * QKV_SZ;
        {
            float acc[8][4];
#pragma unroll
            for (int ks = 0; ks < 8; ks++) {
#pragma unroll
                for (int j = 0; j < 8; j++) {
                    const int i = smem_idx(ks, j) - 8;
                    if (ks == 0) {
                        acc[j][0] = acc[j][1] = acc[j][2] = acc[j][3] = 0.f;
                        mma16816(acc[j], buf0[j][0], buf0[j][1], buf0[j][2], buf0[j][3], bm[ks].x, bm[ks].y);
                    } else if (i >= 0) {
                        uint32_t(&a)[4] = ring[i % RB1];
                        mma16816(acc[j], a[0], a[1], a[2], a[3], bm[ks].x, bm[ks].y);
                        if (8 + i + RB1 < NS1) lds128v(a, W1A(8 + i + RB1));
                    } else {
                        const uint32_t(&a)[4] = wr[8 * ks + j];
                        mma16816(acc[j], a[0], a[1], a[2], a[3], bm[ks].x, bm[ks].y);
                    }
                }
            }
#pragma unroll
            for (int c = 0; c < 4; c++)
                stsm4t(lm + C_RED + w * 2176 + c * 64, pack2(acc[2 * c][0], acc[2 * c][1]), pack2(acc[2 * c][2], acc[2 * c][3]),
                       pack2(acc[2 * c + 1][0], acc[2 * c + 1][1]), pack2(acc[2 * c + 1][2], acc[2 * c + 1][3]));
        }
        {
            const uint32_t a = sb + C_RED + w * 272 + lane * 8;
            if (w == 3) mbar_wait_u(bar_kv, s & 1);
            TS(2);
            __syncthreads();
            TS(3);
            uint2 v[8];
#pragma unroll
            for (int i = 0; i < 8; i++) v[i] = lds64(a + i * 2176);
            float c[4];
            sum8(c, v, idn);
            const uint32_t p0 = pack2(c[0], c[1]), p1 = pack2(c[2], c[3]);
            const uint32_t dst = sb + xq + (r * 8 + w) * 272 + lane * 8;
#pragma unroll
            for (int i = 1; i < 3; i++) {
                const uint32_t peer = (h % (CLS / 3)) * 3 + (r + i >= 3 ? r + i - 3 : r + i);
                uint32_t rd, rb;
                asm("mapa.shared::cluster.u32 %0, %1, %2;" : "=r"(rd) : "r"(dst), "r"(peer));
                asm("mapa.shared::cluster.u32 %0, %1, %2;" : "=r"(rb) : "r"(bar_x), "r"(peer));
                asm volatile("st.async.weak.shared::cluster.mbarrier::complete_tx::bytes.v2.b32 [%0], {%1,%2}, [%3];"
                             ::"r"(rd), "r"(p0), "r"(p1), "r"(rb) : "memory");
            }
            sts64(dst, p0, p1);
            __syncwarp();
            asm volatile("{\n.reg .pred p;\nsetp.eq.u32 p, %1, 0;\n@p mbarrier.arrive.expect_tx.shared::cta.b64 _, [%0], 512;\n}"
                         ::"r"(bar_x), "r"(lane) : "memory");
        }
        TS(4);
        if (s == NSEG - 1) break;
        uint32_t wb[8][4], wc[8][4];
        const uint32_t po = (tile0 * 2 + (lane >> 4)) * 8192 + ((lane >> 3) & 1) * 2048 + h * 64 + (lane & 7) * 8;
        const uint32_t tag = s & 1;
        auto project = [&](const uint32_t(&wt)[8][4], const uint32_t(&ob)[4][4], int i) {
            float c0[4] = {0.f, 0.f, 0.f, 0.f}, c1[4] = {0.f, 0.f, 0.f, 0.f};
#pragma unroll
            for (int ks = 0; ks < 8; ks++)
                mma16816((ks & 1) ? c1 : c0, wt[ks][0], wt[ks][1], wt[ks][2], wt[ks][3], ob[ks >> 1][(ks & 1) * 2], ob[ks >> 1][(ks & 1) * 2 + 1]);
            uint32_t p0 = pack2(c0[0] + c1[0], c0[1] + c1[1]), p1 = pack2(c0[2] + c1[2], c0[3] + c1[3]);
            asm volatile("movmatrix.sync.aligned.m8n8.trans.b16 %0, %0;\nmovmatrix.sync.aligned.m8n8.trans.b16 %1, %1;" : "+r"(p0), "+r"(p1));
            st_rlx64((uint2*)((char*)g_x + po + i * 131072 + ((psel >> (2 * i + (lane >> 4))) & 1) * 4096), (p0 & ~1u) | tag, p1);
        };
        if (w >= 4) {
            uint32_t ka[4][4];
#pragma unroll
            for (int ks = 0; ks < 4; ks++) ldsm4(ka[ks], kva ^ (ks << 5));
            const uint32_t qa = lm + xq + (w & 1) * 128;
            TS(5);
            mbar_wait_u(bar_x, s & 1);
            TS(6);
            {
                uint32_t qb[2][4];
                ldsm4(qb[0], qa);
                ldsm4(qb[1], qa + 64);
                float c0[4] = {0.f, 0.f, 0.f, 0.f}, c1[4] = {0.f, 0.f, 0.f, 0.f};
                mma16816(c0, ka[0][0], ka[0][1], ka[0][2], ka[0][3], qb[0][0], qb[0][1]);
                mma16816(c1, ka[1][0], ka[1][1], ka[1][2], ka[1][3], qb[0][2], qb[0][3]);
                mma16816(c0, ka[2][0], ka[2][1], ka[2][2], ka[2][3], qb[1][0], qb[1][1]);
                mma16816(c1, ka[3][0], ka[3][1], ka[3][2], ka[3][3], qb[1][2], qb[1][3]);
                sts32f(sa, c0[0] + c1[0]);
                sts32f(sa + 208, c0[1] + c1[1]);
                sts32f(sa + 32, c0[2] + c1[2]);
                sts32f(sa + 240, c0[3] + c1[3]);
            }
            __syncthreads();
            TS(7);
            uint32_t wd;
            if (attends) { load_q(s); wd = delayed<DLYQ>(wa, self); } else wd = delayed<DLYW>(wa, self);
#pragma unroll
            for (int i = 0; i < 8; i++) lds128(wb[i], wd + C_W2 + i * 4096);
#pragma unroll
            for (int i = 0; i < PFC; i++) lds128(wc[i], wd + C_W2 + 32768 - 1024 + i * 3072);
            TS(8);
            __syncthreads();
            TS(9);
            uint32_t ob[4][4];
#pragma unroll
            for (int i = 0; i < 4; i++) ldsm4(ob[i], lm + C_OB + i * 64);
#pragma unroll
            for (int i = PFC; i < 8; i++) lds128(wc[i], W2A(8 + i));
            project(wb, ob, 1);
            project(wo0, ob, 0);
            project(wc, ob, 2);
        } else {
            uint32_t va[4][4];
#pragma unroll
            for (int i = 0; i < 4; i++) ldsm4t(va[i], kva ^ (((i >> 1) << 5) | ((i & 1) * 0x240)));
#pragma unroll
            for (int i = 0; i < 8; i++) lds128(wb[i], W2A(i));
            const uint32_t qa = lm + xq + (w & 1) * 128, oa = lm + w * 64;
            TS(5);
            mbar_wait_u(bar_x, s & 1);
            TS(6);
            if (w < 2) {
                uint32_t qb[2][4], km[2][4];
                ldsm4(qb[0], qa);
                ldsm4(km[0], qa + 8 * 272);
                ldsm4(qb[1], qa + 64);
                ldsm4(km[1], qa + 8 * 272 + 64);
                float c0[4] = {0.f, 0.f, 0.f, 0.f}, c1[4] = {0.f, 0.f, 0.f, 0.f};
                mma16816(c0, km[0][0], km[0][1], km[0][2], km[0][3], qb[0][0], qb[0][2]);
                mma16816(c1, km[0][0], km[0][1], km[0][2], km[0][3], qb[0][1], qb[0][3]);
                mma16816(c0, km[1][0], km[1][1], km[1][2], km[1][3], qb[1][0], qb[1][2]);
                mma16816(c1, km[1][0], km[1][1], km[1][2], km[1][3], qb[1][1], qb[1][3]);
                sts32f(sa, c0[0] + c1[2]);
                sts32f(sa + 208, c0[1] + c1[3]);
            }
            __syncthreads();
            TS(7);
            {
                float4 x0 = lds128f(sr), y0 = lds128f(sr + 1664), x1 = lds128f(sr + 16), y1 = lds128f(sr + 1680);
                float2 x2 = lds64f(sr2), y2 = lds64f(sr2 + 1664);
                float p[10] = {x0.x + y0.x, x0.y + y0.y, x0.z + y0.z, x0.w + y0.w, x1.x + y1.x,
                               x1.y + y1.y, x1.z + y1.z, x1.w + y1.w, x2.x + y2.x, x2.y + y2.y};
                float m = fmaxf(fmaxf(fmaxf(p[0], p[1]), fmaxf(p[2], p[3])), fmaxf(fmaxf(fmaxf(p[4], p[5]), fmaxf(p[6], p[7])), fmaxf(p[8], p[9])));
                const float m1 = __shfl_xor_sync(~0u, m, 1), m2 = __shfl_xor_sync(~0u, m, 2), m3 = __shfl_xor_sync(~0u, m, 3);
                uint32_t vm[4];
                ldsm4t(vm, oa + xq + 16 * 272);
                m = fmaxf(fmaxf(m, m1), fmaxf(m2, m3));
                const float ms = m * sl2e;
#pragma unroll
                for (int i = 0; i < 10; i++) p[i] = ex2(fmaf(p[i], sl2e, -ms));
                const uint32_t b0 = pack2(p[0], p[1]), b1 = pack2(p[2], p[3]), b2 = pack2(p[4], p[5]), b3 = pack2(p[6], p[7]), b4 = pack2(p[8], p[9]);
                const uint32_t one = 0x3f803f80u;
                float o0[4] = {0.f, 0.f, 0.f, 0.f}, o1[4] = {0.f, 0.f, 0.f, 0.f}, sm[4] = {0.f, 0.f, 0.f, 0.f};
                mma16816(sm, one, one, one, one, b0, b1);
                mma16816(o0, va[0][0], va[0][1], va[0][2], va[0][3], b0, b1);
                mma16816(o1, va[2][0], va[2][1], va[2][2], va[2][3], b0, b1);
                mma16816(sm, one, one, one, one, b2, b3);
                mma16816(o0, va[1][0], va[1][1], va[1][2], va[1][3], b2, b3);
                mma16816(o1, va[3][0], va[3][1], va[3][2], va[3][3], b2, b3);
                mma1688(sm, one, one, b4);
                mma1688(o0, vm[0], vm[1], b4);
                mma1688(o1, vm[2], vm[3], b4);
                float i0, i1;
                asm("rcp.approx.ftz.f32 %0, %1;" : "=f"(i0) : "f"(sm[0]));
                asm("rcp.approx.ftz.f32 %0, %1;" : "=f"(i1) : "f"(sm[1]));
                stsm4t(oa + C_OB, pack2(o0[0] * i0, o0[1] * i1), pack2(o0[2] * i0, o0[3] * i1),
                       pack2(o1[0] * i0, o1[1] * i1), pack2(o1[2] * i0, o1[3] * i1));
            }
            TS(8);
            __syncthreads();
            TS(9);
            uint32_t ob[4][4];
#pragma unroll
            for (int i = 0; i < 4; i++) ldsm4(ob[i], lm + C_OB + i * 64);
            if (three) {
#pragma unroll
                for (int i = 0; i < 8; i++) lds128(wc[i], W2A(8 + i));
                project(wb, ob, 1);
                project(wo0, ob, 0);
                project(wc, ob, 2);
            } else {
                project(wb, ob, 1);
                project(wo0, ob, 0);
            }
        }
        TS(10);
        __syncthreads();
        uint32_t eo = (128 + (s + 1) * 4 + (w >> 1)) * 8192 + (((s < 31 ? msel0 : msel1) >> ((s + 1) & 31)) & 1) * 4096 + (w & 1) * 2048 + lane * 8;
        uint64_t d[8];
        if (r == 0) {
            if (w >= 6) {
                auto mid = [&]() {
                    bar_sync(2, 64);
                    TS(11);
                    mbar_wait_u(bar_go, s & 1);
                    eo = delayed<DLY0A>(eo, self);
                    TS(12);
                    fetch_state(d, (const char*)g_x + eo);
                };
                ATTEND(2, s, mid);
                stage_w1();
            } else {
                TS(11); TS(12);
                if (w < 3 && s + PFD < NSEG) {
                    const bf16* p = g_kv + (size_t)((s + PFD) * 32 + fresh(lane)) * PW + w * HD + h * 128;
                    asm volatile("prefetch.global.L2 [%0];\nprefetch.global.L2 [%0 + 128];" ::"l"(p) : "memory");
                }
                const uint32_t wa_ = wa;
                { const uint32_t wa = delayed<DLYS>(wa_, self); STAGE_W1(); }
                if (w == 5) {
                    chores(s);
                    if (h == 0) asm volatile("st.relaxed.gpu.global.u32 [%0], %1;" ::"l"(g_flag + 98), "r"(s + 1) : "memory");
                }
                mbar_wait_u(bar_go, s & 1);
                eo = delayed<DLY0>(eo, self);
                fetch_state(d, (const char*)g_x + eo);
            }
        } else {
            const int j = 2 * h + r - 1;
            if (w < 4) {
                const int l = fresh(lane), g = l >> 2, t = l & 3;
                const char* src = (const char*)g_x + delayed<DLY3>((j * 2 + (w >> 1)) * 8192 + (psel & 64) * 64 + (w & 1) * 2048 + t * 64 + g * 8, self);
                const char* dst = (const char*)g_x + pin((128 + (s + 1) * 4 + (j >> 4)) * 8192 + (j & 15) * 256 + w * 64 + (t & 1) * 4096 + g * 8);
                const uint64_t v = poll_sum(src, tag, (lane & 4) ? 0x3f800000u : 0x00003f80u);
                TS(11);
                asm volatile("st.relaxed.gpu.global.b64 [%0], %1;" ::"l"(dst), "l"(v) : "memory");
                asm volatile("bar.arrive 1, 256;" ::: "memory");
                TS(12);
                stage_w1();
                eo = delayed<DLY1>(eo, self);
                fetch_state(d, (const char*)g_x + eo);
            } else if (w == 7) {
                auto mid = [&]() {
                    TS(11);
                    bar_sync(1, 256);
                    TS(12);
                    eo = delayed<DLY1B>(eo, self);
                    fetch_state(d, (const char*)g_x + eo);
                };
                ATTEND(1, s, mid);
                stage_w1();
            } else {
                if (w >= 5 && s + 3 < NSEG)
                    asm volatile("prefetch.global.L2 [%0];" ::"l"(g_x + (128 + (s + 3) * 4 + (j >> 4)) * 1024 + (w & 1) * 512 + (j & 15) * 32 + lane) : "memory");
                stage_w1();
                if (w == 5) chores(s);
                TS(11);
                bar_sync(1, 256);
                TS(12);
                if (w == 4 && r == 1)
                    asm volatile("{\n.reg .pred p;\n.reg .u32 a;\nelect.sync _|p, -1;\nmapa.shared::cluster.u32 a, %0, %1;\n"
                                 "@p mbarrier.arrive.relaxed.cluster.shared::cluster.b64 _, [a];\n}" ::"r"(bar_go), "r"((h % (CLS / 3)) * 3) : "memory");
                eo = delayed<DLY1A>(eo, self);
                fetch_state(d, (const char*)g_x + eo);
            }
        }
        { const int s_ = s; { const int s = s_ + 1; TS(0); } }
        if (w == 7) load_kv(s + 1);
        settle_state(d, (const char*)g_x + eo);
#pragma unroll
        for (int i = 0; i < 8; i++) { bm[i].x = (uint32_t)d[i]; bm[i].y = (uint32_t)(d[i] >> 32); }
    }
    mbar_wait_u(bar_x, (NSEG - 1) & 1);
    if (attends) {
        auto nothing = []() {};
        load_q(NSEG - 1);
        if (r == 0) ATTEND(2, NSEG - 1, nothing); else ATTEND(1, NSEG - 1, nothing);
    }
    __syncthreads();
    if (w == 5) report(15);
    asm volatile("barrier.cluster.arrive.relaxed.aligned;\nbarrier.cluster.wait.aligned;" ::: "memory");
}

constexpr int S4_US = 4368;
constexpr int S4_RS = 8848;
constexpr int S4_KS = 1296;
constexpr int S4_U = 0, S4_R = 16 * S4_US, S4_K = S4_R + 16 * S4_RS;
constexpr int S4_SMEM = S4_K + 16 * S4_KS;
constexpr int S4_SIG = 3104, S4_PK = 2 * S4_SIG;

struct cf { float r, i; };
__device__ __forceinline__ cf cmul(cf a, cf b) { return {fmaf(a.r, b.r, -a.i * b.i), fmaf(a.r, b.i, a.i * b.r)}; }
__device__ __forceinline__ cf cmulc(cf a, cf b) { return {fmaf(a.r, b.r, a.i * b.i), fmaf(a.i, b.r, -a.r * b.i)}; }
__device__ __forceinline__ cf csq(cf a) { const float t = a.r * a.i; return {fmaf(a.r, a.r, -a.i * a.i), t + t}; }
__device__ __forceinline__ cf cexp(float l2, float turns) {
    const float mag = ex2(l2), fr = (turns - rintf(turns)) * 6.283185307179586f;
    return {mag * __cosf(fr), mag * __sinf(fr)};
}
__device__ __forceinline__ void sts32(uint32_t a, uint32_t v) { asm volatile("st.shared.u32 [%0], %1;" ::"r"(a), "r"(v) : "memory"); }
__device__ __forceinline__ uint32_t lds16(uint32_t a) {
    uint32_t v;
    asm volatile("ld.shared.u16 %0, [%1];" : "=r"(v) : "r"(a) : "memory");
    return v;
}

template <int M0, int NQ>
__device__ __forceinline__ void s4_class(float (&acc)[16][4], uint32_t sig, uint32_t taps, int x0) {
    constexpr int D0 = M0 / 8, D1 = M0 == 32 ? 9 : 15;
    uint32_t R[D1 - D0 + 2];
#pragma unroll
    for (int D = D0 - 1; D <= D1; D++) {
        if (D < D0 || 8 * D - 7 >= 2 * M0) { R[D - D0 + 1] = 0; continue; }
        const int m = 8 * D + x0;
        uint32_t lo = lds16(taps + m * (2 * NQ)), hi = lds16(taps + (m - 1) * (2 * NQ));
        if (D == D0) { lo = m >= M0 ? lo : 0; hi = m > M0 ? hi : 0; }
        if (D == 2 * D0) { lo = m < 2 * M0 ? lo : 0; hi = m <= 2 * M0 ? hi : 0; }
        R[D - D0 + 1] = lo | (hi << 16);
    }
#pragma unroll
    for (int J = 0; 2 * J + D0 < 16; J++) {
        uint32_t a[4];
        ldsm4t(a, sig + J * 512);
#pragma unroll
        for (int D = D0; D <= D1; D++)
            if (2 * J + D < 16) mma16816(acc[2 * J + D], a[0], a[1], a[2], a[3], R[D - D0 + 1], R[D - D0]);
    }
}

__global__ void __launch_bounds__(512, 1)
k_s4(const bf16* __restrict__ u, const bf16* __restrict__ Are, const bf16* __restrict__ Aim, const bf16* __restrict__ Bre,
     const bf16* __restrict__ Bim, const bf16* __restrict__ Cre, const bf16* __restrict__ Cim, const bf16* __restrict__ logdt,
     const bf16* __restrict__ Dsk, bf16* __restrict__ out) {
    extern __shared__ __align__(16) uint8_t smem_s4[];
    const uint32_t sb = smem_u32(smem_s4);
    asm volatile("griddepcontrol.launch_dependents;");
    const int tid = threadIdx.x, w = __shfl_sync(~0u, tid >> 5, 0), lane = tid & 31, g = lane >> 2, t = lane & 3;
#pragma unroll 1
    for (int item = blockIdx.x; item < 64; item += gridDim.x) {
#define TLS(slot)
    if (tid == 0) TLS(0);
    const int d0 = item * 16;
    const int d = d0 + (w & 1) + ((w >> 1) & 3) * 4 + (w >> 3) * 2;
    const uint32_t tr_off = (lane & 15), tr_l = (lane >> 4) * 16;
    const uint32_t ur = sb + S4_U + w * S4_US, rs = sb + S4_R + w * S4_RS, kd = sb + S4_K + w * S4_KS;
    if (lane < 16) sts128(ur + lane * 16, 0, 0, 0, 0);
    {
        const int o = d * 128 + lane * 4;
        const uint2 ar = __ldg((const uint2*)(Are + o)), ai = __ldg((const uint2*)(Aim + o)), br = __ldg((const uint2*)(Bre + o));
        const uint2 bi = __ldg((const uint2*)(Bim + o)), cr = __ldg((const uint2*)(Cre + o)), ci = __ldg((const uint2*)(Cim + o));
        const float dt = bf_round(expf(__bfloat162float(logdt[d])));
        const bf16* src = u + (size_t)(w * 128 + g) * DM + d0 + 4 * t;
        float T[5][4];
#pragma unroll
        for (int i = 0; i < 5; i++) T[i][0] = T[i][1] = T[i][2] = T[i][3] = 0.f;
        float klast = 0.f;
        const uint32_t wr_ = rs + lane * 272, rd_ = rs + t * 544 + g * 16;
#pragma unroll 1
        for (int c = 0; c < 4; c++) {
            uint2 v[4];
#pragma unroll
            for (int i = 0; i < 4; i++) v[i] = __ldg((const uint2*)(src + (size_t)(c * 32 + i * 8) * DM));
            auto pick = [&](const uint2& x) { const uint32_t y = c < 2 ? x.x : x.y; return (c & 1) ? bf_hi(y) : bf_lo(y); };
            auto pk2 = [](cf x) { return pack2(x.r, x.i); };
            const float l2 = dt * pick(ar) * 1.4426950408889634f, tu = dt * pick(ai) * 0.15915494309189535f;
            const cf z1 = cexp(l2, tu), z2 = csq(z1), z4 = csq(z2), z8 = csq(z4);
            const cf z64 = cexp(l2 * 64.f, tu * 64.f), z128 = csq(z64), z256 = csq(z128), z512 = csq(z256);
            cf a0 = {1.f, 0.f}, a1 = z64;
            cf b0 = cmul({pick(cr), pick(ci)}, {dt * pick(br), dt * pick(bi)});
            b0.i = -b0.i;
            cf b1 = cmulc(b0, z128), b2 = cmulc(b0, z256), y3 = cmulc(b0, z512), b4 = cmulc(y3, z512), b3 = y3;
            const cf y2 = cmulc(b2, z128);
#pragma unroll
            for (int i = 0; i < 8; i++) {
                sts128(wr_ + i * 16, pk2(a0), pk2(a1), pk2(b0), pk2(b1));
                sts128(wr_ + i * 16 + 128, pk2(b2), pk2(b3), pk2(b4), 0);
                b4 = cmulc(b4, z128);
                if (i < 7) {
                    a0 = i == 0 ? z8 : cmul(a0, z8); a1 = cmul(a1, z8);
                    b0 = cmulc(b0, z1); b1 = cmulc(b1, z1);
                    b2 = i == 3 ? y2 : cmulc(b2, z2);
                    if (i & 1) { y3 = cmulc(y3, z128); b3 = y3; } else b3 = cmulc(y3, z4);
                }
            }
            klast += b4.r;
            __syncwarp();
#pragma unroll
            for (int k = 0; k < 8; k++) {
                uint32_t x[4], y[4];
                lds128(x, rd_ + (8 * (k >> 1) + (k & 1)) * 272);
                lds128(y, rd_ + (8 * (k >> 1) + (k & 1)) * 272 + 128);
                mma1688(T[0], x[0], x[1], x[2]);
                mma1688(T[1], x[0], x[1], x[3]);
                mma1688(T[2], x[0], x[1], y[0]);
                mma1688(T[3], x[0], x[1], y[1]);
                mma1688(T[4], x[0], x[1], y[2]);
            }
#pragma unroll
            for (int i = 0; i < 2; i++)
                stsm4t(sb + S4_U + tr_off * S4_US + 256 + (w * 128 + c * 32 + i * 16) * 2 + tr_l, v[2 * i].x, v[2 * i].y, v[2 * i + 1].x, v[2 * i + 1].y);
            __syncwarp();
        }
#pragma unroll
        for (int o2 = 16; o2; o2 >>= 1) klast += __shfl_xor_sync(~0u, klast, o2);
#pragma unroll
        for (int hh = 0; hh < 2; hh++) {
            const int i = g + 8 * hh;
            sts32(kd + (8 * i + 2 * t) * 2, pack2(T[0][2 * hh], T[0][2 * hh + 1]));
            sts32(kd + (128 + 8 * i + 2 * t) * 2, pack2(T[1][2 * hh], T[1][2 * hh + 1]));
            sts32(kd + (256 + 4 * i + 2 * (t & 1) + 64 * (t >> 1)) * 2, pack2(T[2][2 * hh], T[2][2 * hh + 1]));
            sts32(kd + (384 + 2 * i + 32 * t) * 2, pack2(T[3][2 * hh], T[3][2 * hh + 1]));
        }
        asm volatile("stmatrix.sync.aligned.m8n8.x2.trans.shared.b16 [%0], {%1,%2};"
                     ::"r"(kd + 1024 + (lane & 7) * 32 + ((lane >> 3) & 1) * 16), "r"(pack2(T[4][0], T[4][1])), "r"(pack2(T[4][2], T[4][3])) : "memory");
        if (lane == 0) sts32(kd + 1280, pack2(klast, 0.f));
    }
    __syncwarp();
    const uint32_t pk = rs + S4_PK + 64;
    {
#pragma unroll
        for (int i = 0; i < 2; i++) {
            const int x = i * 128 + lane * 4;
            const uint2 c = lds64(kd + x * 2);
            uint32_t p = lds16(kd + x * 2 - 2);
            if (x == 0) p = 0;
            sts128(pk + x * 4, __byte_perm(c.x, p, 0x5410), __byte_perm(c.x, 0, 0x1032), __byte_perm(c.y, c.x, 0x7610), __byte_perm(c.y, 0, 0x1032));
        }
#pragma unroll
        for (int i = 2; i < 4; i++) {
            const int x = i * 128 + lane * 4;
            const uint32_t ab = lds32(kd + 256 + x), c = lds16(kd + 256 + x + 4);
            const uint32_t p = x == 256 ? lds16(kd + 510) : ab;
            sts128(pk + x * 4, __byte_perm(ab, p, 0x5410), __byte_perm(ab, 0, 0x1010), __byte_perm(ab, 0, 0x1032), __byte_perm(c, ab, 0x7610));
        }
        const uint32_t v = lds16(kd + 768), v2 = lds16(kd + 1024);
        if (lane < 24) {
            uint32_t x0 = 0, x1 = 0, x2 = 0, x3 = 0;
            if (lane == 0) { x0 = x1 = x2 = v | (v << 16); x3 = v << 16; }
            if (lane == 12) x3 = v2;
            if (lane == 13) { x0 = v2 | (v2 << 16); x1 = v2 << 16; }
            sts128(lane < 20 ? pk + 2048 + lane * 16 : pk - 64 + (lane - 20) * 16, x0, x1, x2, x3);
        }
        if (lane < 4) sts128(rs + (lane >> 1) * S4_SIG + (lane & 1) * 16, 0, 0, 0, 0);
    }
    __syncthreads();
    float acc[16][4];
#pragma unroll
    for (int i = 0; i < 16; i++) acc[i][0] = acc[i][1] = acc[i][2] = acc[i][3] = 0.f;
    const uint32_t lf = (lane & 7) * 32 + ((lane >> 3) & 1) * 16 + (lane >> 4) * 256;
#pragma unroll 1
    for (int ph = 0; ph < 2; ph++) {
    if (((w >> 2) ^ ph) & 1) {
#pragma unroll
    for (int rg = 3; rg >= 2; rg--) {
#pragma unroll 1
        for (int it = 0; it < (rg == 3 ? 4 : 6); it++) {
            const int n = it * 32 + lane;
            uint32_t x[2][4];
            lds128(x[0], ur + 256 + n * 16 - 16);
            lds128(x[1], ur + 256 + n * 16);
            float e[16], p[15], s[11];
#pragma unroll
            for (int i = 0; i < 8; i++) { e[2 * i] = bf_lo(x[i >> 2][i & 3]); e[2 * i + 1] = bf_hi(x[i >> 2][i & 3]); }
#pragma unroll
            for (int i = 0; i < 15; i++) p[i] = e[i] + e[i + 1];
#pragma unroll
            for (int i = 0; i < 11; i++) s[i] = p[i + 3] + e[i + 5];
            const uint32_t o = rs + 16 + n * 16;
            if (rg == 2) sts128(o, pack2(s[0], s[1]), pack2(s[2], s[3]), pack2(s[4], s[5]), pack2(s[6], s[7]));
#pragma unroll
            for (int i = 0; i < 10; i++) s[i] = p[i + 2] + s[i + 1];
            if (rg == 2) {
                sts64(o + S4_SIG + 8, pack2(s[0], s[1]), pack2(s[2], s[3]));
                sts64(o + S4_SIG + 16, pack2(s[4], s[5]), pack2(s[6], s[7]));
            } else {
#pragma unroll
                for (int i = 0; i < 9; i++) s[i] = p[i + 1] + s[i + 1];
                sts64(o + 8, pack2(s[0], s[1]), pack2(s[2], s[3]));
                sts64(o + 16, pack2(s[4], s[5]), pack2(s[6], s[7]));
#pragma unroll
                for (int i = 0; i < 8; i++) s[i] = p[i] + s[i + 1];
                sts64(o + S4_SIG + 8, pack2(s[0], s[1]), pack2(s[2], s[3]));
                sts64(o + S4_SIG + 16, pack2(s[4], s[5]), pack2(s[6], s[7]));
            }
        }
        __syncwarp();
        if (rg == 3) {
#pragma unroll 1
            for (int q = 1; q <= 2; q++) s4_class<64, 2>(acc, rs + lf + (q == 1 ? 16 : S4_SIG), kd + (384 + q) * 2, g - 2 * t);
        } else {
#pragma unroll 1
            for (int q = 1; q <= 4; q++) s4_class<32, 4>(acc, rs + lf + ((q & 1) ? 0 : S4_SIG) + (q < 3 ? 16 : 0), kd + (256 + q) * 2, g - 2 * t);
        }
        __syncwarp();
    }
    } else
    {
        const uint32_t ub = ur + 256 + lf, kb = pk + (g - 2 * t) * 4;
#pragma unroll 1
        for (int j0 = 0; j0 < 8; j0++) {
            uint32_t B[8][4];
#pragma unroll
            for (int i = 0; i < 8; i++) ldsm4(B[i], ub + i * 512 - j0 * 32);
            auto block = [&](int J, uint32_t a) {
                const uint32_t r0 = lds32(a), rp = lds32(a + 32), rm = lds32(a - 32);
                uint32_t r3;
                asm volatile("ld.volatile.shared.u32 %0, [%1];" : "=r"(r3) : "r"(a) : "memory");
#pragma unroll
                for (int I = J; I < 16; I++)
                    mma16816(acc[I], r0, rp, rm, r3, B[(I - J) >> 1][((I - J) & 1) * 2], B[(I - J) >> 1][((I - J) & 1) * 2 + 1]);
            };
#pragma unroll
            for (int J = 0; J < 4; J++) block(J, kb + j0 * 64 + J * 512);
            if (j0 < 2) { block(4, kb + j0 * 64 + 2048); block(8, kb + j0 * 64 + (544 + 16) * 4); }
        }
    }
    }
    {
        __syncwarp();
#pragma unroll
        for (int i = 0; i < 8; i++)
            stsm4t(rs + lf + i * 512, pack2(acc[2 * i][0], acc[2 * i][1]), pack2(acc[2 * i][2], acc[2 * i][3]),
                   pack2(acc[2 * i + 1][0], acc[2 * i + 1][1]), pack2(acc[2 * i + 1][2], acc[2 * i + 1][3]));
    }
    __syncthreads();
    {
        const uint2 dv = __ldg((const uint2*)(Dsk + d0 + 4 * t));
        bf16* dst = out + (size_t)(w * 128 + g) * 2048 + 1024 + d0 + 4 * t;
#pragma unroll
        for (int i = 0; i < 8; i++) {
            uint32_t y[4], x[4], o[4];
            ldsm4t(y, sb + S4_R + tr_off * S4_RS + (w * 128 + i * 16) * 2 + tr_l);
            ldsm4t(x, sb + S4_U + tr_off * S4_US + 256 + (w * 128 + i * 16) * 2 + tr_l);
#pragma unroll
            for (int j = 0; j < 4; j++)
                asm("{\n.reg .b32 s;\nmul.rn.bf16x2 s, %2, %3;\nadd.rn.bf16x2 %0, %1, s;\n}" : "=r"(o[j]) : "r"(y[j]), "r"(x[j]), "r"((j & 1) ? dv.y : dv.x));
            *reinterpret_cast<uint2*>(dst + (size_t)(i * 16) * 2048) = make_uint2(o[0], o[1]);
            *reinterpret_cast<uint2*>(dst + (size_t)(i * 16 + 8) * 2048) = make_uint2(o[2], o[3]);
        }
    }
    if (tid == 0) TLS(1);
    __syncthreads();
    }
}

enum { IT_W256 = 1, IT_W128 = 2, IT_W64 = 3, IT_END = 7 };
struct BgParams { CUtensorMap mo, mo2, mwo4, mwo2, mwo1; };
#define NBT 10
#define P256 56
#define P128 62
struct Sched { uint32_t w0 = 0, w1 = 0; };
__device__ __forceinline__ int next_item(Sched& z) {
    if (z.w0 >= z.w1) {
        uint32_t prog;
        asm volatile("ld.relaxed.gpu.global.u32 %0, [%1];" : "=r"(prog) : "l"(g_flag + 98) : "memory");
        const uint32_t k = prog <= P256 ? 4 : prog <= P128 ? 2 : 1;
        z.w0 = atomicAdd(g_flag + 97, k);
        z.w1 = min(z.w0 + k, NBT * 16u);
        if (z.w0 >= z.w1) return IT_END;
    }
    const uint32_t i = z.w0, k = z.w1 - i >= 4 && !(i & 3) ? 4 : z.w1 - i >= 2 && !(i & 1) ? 2 : 1;
    z.w0 += k;
    return (k == 4 ? IT_W256 : k == 2 ? IT_W128 : IT_W64) | (i >> 4) << 3 | ((i & 15) / k) << 7;
}
constexpr int B_OST = NSTAGE * STAGE_BYTES + 1024;
constexpr int BG_SMEM = B_OST + 32768;

template <int BM, int BN, int KPS, typename ACC>
__device__ __forceinline__ void gemm_mainloop(ACC& acc, const GemmSmem& g, int cw, int rounds, uint32_t& round) {
#pragma unroll
    for (int i = 0; i < BN / 2; i++) acc[i] = 0.f;
#pragma unroll 1
    for (int k0 = 0; k0 < rounds; k0++, round++) {
#pragma unroll
        for (int s = 0; s < 4; s++) {
            mbar_wait_u(g.full + 8 * s, round & 1);
            gemm_stage<BM, BN, KPS>(acc, g.st + s * STAGE_BYTES, cw, false);
            wg_wait<1>();
            if (s > 0 || k0 > 0) mbar_arrive_one(g.empty + 8 * ((s + 3) & 3), threadIdx.x & 31);
        }
    }
    wg_wait<0>();
    mbar_arrive_one(g.empty + 8 * 3, threadIdx.x & 31);
}

template <int BN>
__device__ __forceinline__ void store_tile(const float (&acc)[BN / 2], bf16* dst, int t) {
#pragma unroll
    for (int G = 0; G < BN / 32; G++)
#pragma unroll
        for (int rr = 0; rr < 2; rr++) {
            uint32_t r0 = pack2(acc[16 * G + 2 * rr], acc[16 * G + 2 * rr + 1]), r1 = pack2(acc[16 * G + 4 + 2 * rr], acc[16 * G + 5 + 2 * rr]);
            uint32_t r2 = pack2(acc[16 * G + 8 + 2 * rr], acc[16 * G + 9 + 2 * rr]), r3 = pack2(acc[16 * G + 12 + 2 * rr], acc[16 * G + 13 + 2 * rr]);
            quad_transpose(r0, r1, r2, r3, t);
            *reinterpret_cast<uint4*>(dst + (size_t)rr * 8 * 2048 + G * 32) = make_uint4(r0, r1, r2, r3);
        }
}

template <int BN, int KPS>
__device__ __forceinline__ void wo_item(const GemmSmem& g, int cw, uint32_t& round, bf16* dst, int t) {
    float acc[BN / 2];
    gemm_mainloop<128, BN, KPS>(acc, g, cw, 16 / KPS, round);
    store_tile<BN>(acc, dst, t);
}

__global__ void __launch_bounds__(384, 1) k_bg(const __grid_constant__ BgParams P, bf16* __restrict__ out) {
    extern __shared__ __align__(1024) uint8_t smem_gemm[];
    asm volatile("griddepcontrol.launch_dependents;");
    const uint32_t bar_item = smem_u32(smem_gemm) + NSTAGE * STAGE_BYTES + 128, slot = bar_item + 16;
    if (threadIdx.x == 0) { mbar_init(bar_item, 1); mbar_init(bar_item + 8, 1); }
    GemmSmem g = gemm_setup(smem_gemm, 8);
    const int wg = __shfl_sync(~0u, threadIdx.x >> 7, 0);
    if (wg == 0) {
        asm volatile("setmaxnreg.dec.sync.aligned.u32 40;");
        if (threadIdx.x == 0) {
            uint32_t it = 0;
            Sched z;
            for (int n = 0;; n++) {
                const int code = next_item(z);
                sts32(slot + (n & 1) * 4, code);
                mbar_arrive(bar_item + (n & 1) * 8);
                const int type = code & 7, blk = (code >> 3) & 15, idx = code >> 7;
                if (type == IT_END) break;
                wait_flag(g_flag + 64 + blk, 96);
                asm volatile("fence.proxy.async.global;" ::: "memory");
                for (int k = 0; k < (type == IT_W64 ? 32 : 64); k++, it++) {
                    const int s = it & 3;
                    const uint32_t st = g.st + s * STAGE_BYTES, fb = g.full + 8 * s;
                    mbar_wait(g.empty + 8 * s, ((it >> 2) & 1) ^ 1);
                    mbar_expect_tx(fb, type == IT_W128 ? 32768 : 49152);
                    if (type == IT_W64) {
                        tma3d(st, &P.mo2, 0, blk * 128, k * 2, fb);
                        tma3d(st + 32768, &P.mwo1, 0, k * 128, idx, fb);
                    } else {
                        tma2d(st, &P.mo, k * 64, blk * 128, fb);
                        tma3d(st + 16384, type == IT_W256 ? &P.mwo4 : &P.mwo2, 0, k * 64, idx * (type == IT_W256 ? 4 : 2), fb);
                    }
                }
            }
        }
    } else {
        asm volatile("setmaxnreg.inc.sync.aligned.u32 232;");
        const int cw = wg - 1, lane = threadIdx.x & 31;
        uint32_t round = 0;
#pragma unroll 1
        for (int n = 0;; n++) {
            mbar_wait_u(bar_item + (n & 1) * 8, (n >> 1) & 1);
            const int code = __shfl_sync(~0u, lds32(slot + (n & 1) * 4), 0);
            const int type = code & 7, blk = (code >> 3) & 15, idx = (code >> 7) & 31;
#define TLB(slot_)
            if (type == IT_END) break;
            TLB(0);
            bf16* dst = out + (size_t)(blk * 128 + cw * 64 + ((threadIdx.x >> 5) & 3) * 16 + (lane >> 2)) * 2048 + (lane & 3) * 8;
            if (type == IT_W256) wo_item<256, 1>(g, cw, round, dst + idx * 256, lane & 3);
            else if (type == IT_W128) wo_item<128, 1>(g, cw, round, dst + idx * 128, lane & 3);
            else wo_item<64, 2>(g, cw, round, dst + idx * 64, lane & 3);
            TLB(1);
        }
    }
}

static_assert(NBT == 10, "k_tail covers blocks 10..15");
__global__ void __cluster_dims__(6, 1, 1) __launch_bounds__(384, 1)
k_tail(const __grid_constant__ BgParams P, bf16* __restrict__ out) {
    extern __shared__ __align__(1024) uint8_t smem_gemm[];
    const int cl = blockIdx.x / 6, rank = blockIdx.x - 6 * cl, half = rank & 1, pr = rank >> 1;
    const int blk = NBT + (cl >> 3) * 3 + pr, idx = cl & 7;
    const uint32_t st = smem_u32(smem_gemm), full = st + 6 * 32768, empty = full + 64, emptyb = full + 128, bar_s = full + 192;
    if (threadIdx.x == 0) {
        TL(4, 0);
        for (int s = 0; s < 6; s++) { mbar_init(full + 8 * s, 1); mbar_init(empty + 8 * s, 2); mbar_init(emptyb + 8 * s, 6); }
        mbar_init(bar_s, 1); mbar_expect_tx(bar_s, 32768);
        asm volatile("fence.mbarrier_init.release.cluster;\nfence.proxy.async.shared::cta;" ::: "memory");
    }
    if (threadIdx.x == 32) asm volatile("prefetch.tensormap [%0];\nprefetch.tensormap [%1];" ::"l"(&P.mo), "l"(&P.mwo2) : "memory");
    __syncthreads();
    asm volatile("barrier.cluster.arrive.relaxed.aligned;\nbarrier.cluster.wait.aligned;" ::: "memory");
    const int wg = __shfl_sync(~0u, threadIdx.x >> 7, 0);
    if (wg == 0) {
        if (threadIdx.x == 0) {
            wait_flag(g_flag + 64 + blk, 96);
            asm volatile("fence.proxy.async.global;" ::: "memory");
            for (int k = 0, s = 0, ph = 1; k < 32; k++) {
                mbar_wait(empty + 8 * s, ph);
                mbar_expect_tx(full + 8 * s, 32768);
                tma2d(st + s * 32768, &P.mo, (half * 32 + k) * 64, blk * 128, full + 8 * s);
                if (++s == 6) { s = 0; ph ^= 1; }
            }
        } else if (threadIdx.x == 32) {
            for (int k = pr, s = pr, ph = 1; k < 32; k += 3) {
                mbar_wait(emptyb + 8 * s, ph);
                asm volatile("cp.async.bulk.tensor.3d.shared::cluster.global.mbarrier::complete_tx::bytes.multicast::cluster "
                             "[%0], [%1, {%3, %4, %5}], [%2], %6;"
                             ::"r"(st + s * 32768 + 16384), "l"(&P.mwo2), "r"(full + 8 * s), "r"(0), "r"((half * 32 + k) * 64), "r"(idx * 2),
                               "h"((uint16_t)(0x15 << half)) : "memory");
                s += 3;
                if (s >= 6) { s -= 6; ph ^= 1; }
            }
        }
    } else {
        const int cw = wg - 1, lane = threadIdx.x & 31, t = lane & 3;
        float acc[64], fin[32];
#pragma unroll
        for (int i = 0; i < 64; i++) acc[i] = 0.f;
#pragma unroll 1
        for (int k = 0, s = 0, ph = 0, sp = 0; k < 32; k++) {
            mbar_wait_u(full + 8 * s, ph);
            gemm_stage<128, 128, 1>(acc, st + s * 32768, cw, false);
            wg_wait<1>();
            if (k > 0 && k <= 26)
                asm volatile("{\n.reg .pred p;\n.reg .u32 a;\nsetp.eq.u32 p, %3, 0;\nmapa.shared::cluster.u32 a, %1, %2;\n"
                             "@p mbarrier.arrive.relaxed.cta.shared::cta.b64 _, [%0];\n@p mbarrier.arrive.relaxed.cluster.shared::cluster.b64 _, [a];\n}"
                             ::"r"(empty + 8 * sp), "r"(emptyb + 8 * sp), "r"((sp >= 3 ? sp - 3 : sp) * 2 + half), "r"(threadIdx.x & 127) : "memory");
            sp = s;
            if (++s == 6) { s = 0; ph ^= 1; }
        }
        wg_wait<0>();
        const uint32_t xa = st + B_OST + (threadIdx.x - 128) * 16;
        uint32_t ra, rb;
        asm("mapa.shared::cluster.u32 %0, %1, %2;" : "=r"(ra) : "r"(xa), "r"(rank ^ 1));
        asm("mapa.shared::cluster.u32 %0, %1, %2;" : "=r"(rb) : "r"(bar_s), "r"(rank ^ 1));
#pragma unroll
        for (int i = 0; i < 8; i++) {
            float v[4];
#pragma unroll
            for (int j = 0; j < 4; j++) {
                v[j] = half ? acc[4 * i + j] : acc[32 + 4 * i + j];
                fin[4 * i + j] = half ? acc[32 + 4 * i + j] : acc[4 * i + j];
            }
            asm volatile("st.async.weak.shared::cluster.mbarrier::complete_tx::bytes.v4.f32 [%0], {%1,%2,%3,%4}, [%5];"
                         ::"r"(ra + i * 4096), "f"(v[0]), "f"(v[1]), "f"(v[2]), "f"(v[3]), "r"(rb) : "memory");
        }
        mbar_wait_u(bar_s, 0);
#pragma unroll
        for (int i = 0; i < 8; i++) {
            const float4 v = lds128f(xa + i * 4096);
            fin[4 * i] += v.x; fin[4 * i + 1] += v.y; fin[4 * i + 2] += v.z; fin[4 * i + 3] += v.w;
        }
        store_tile<64>(fin, out + (size_t)(blk * 128 + cw * 64 + ((threadIdx.x >> 5) & 3) * 16 + (lane >> 2)) * 2048 + idx * 128 + half * 64 + t * 8, t);
        if (threadIdx.x == 128) TL(4, 1);
    }
}

typedef CUresult (*EncodeFn)(CUtensorMap*, CUtensorMapDataType, cuuint32_t, void*, const cuuint64_t*, const cuuint64_t*,
                             const cuuint32_t*, const cuuint32_t*, CUtensorMapInterleave, CUtensorMapSwizzle,
                             CUtensorMapL2promotion, CUtensorMapFloatOOBfill);

static void map2d(EncodeFn enc, CUtensorMap* m, const void* p, int rows, int cols, int box_rows) {
    cuuint64_t dim[2] = {(cuuint64_t)cols, (cuuint64_t)rows}, str[1] = {(cuuint64_t)cols * 2};
    cuuint32_t box[2] = {64, (cuuint32_t)box_rows}, es[2] = {1, 1};
    enc(m, CU_TENSOR_MAP_DATA_TYPE_BFLOAT16, 2, (void*)p, dim, str, box, es, CU_TENSOR_MAP_INTERLEAVE_NONE,
        CU_TENSOR_MAP_SWIZZLE_128B, CU_TENSOR_MAP_L2_PROMOTION_L2_256B, CU_TENSOR_MAP_FLOAT_OOB_FILL_NONE);
}
static void map3d(EncodeFn enc, CUtensorMap* m, const void* p, int rows, int cols, int box_rows, int nblk) {
    cuuint64_t dim[3] = {64, (cuuint64_t)rows, (cuuint64_t)cols / 64}, str[2] = {(cuuint64_t)cols * 2, 128};
    cuuint32_t box[3] = {64, (cuuint32_t)box_rows, (cuuint32_t)nblk}, es[3] = {1, 1, 1};
    enc(m, CU_TENSOR_MAP_DATA_TYPE_BFLOAT16, 3, (void*)p, dim, str, box, es, CU_TENSOR_MAP_INTERLEAVE_NONE,
        CU_TENSOR_MAP_SWIZZLE_128B, CU_TENSOR_MAP_L2_PROMOTION_L2_256B, CU_TENSOR_MAP_FLOAT_OOB_FILL_NONE);
}

#define USE_PDL 1

extern "C" void kernel_launch(void* const* d_in, const int* in_sizes, int n_in, void* d_out, int out_size) {
    const bf16 *x = (const bf16*)d_in[0], *mem0 = (const bf16*)d_in[1], *Wq = (const bf16*)d_in[2], *Wk = (const bf16*)d_in[3];
    const bf16 *Wv = (const bf16*)d_in[4], *Wo = (const bf16*)d_in[5];
    const bf16 *u = (const bf16*)d_in[7], *Are = (const bf16*)d_in[8], *Aim = (const bf16*)d_in[9], *Bre = (const bf16*)d_in[10];
    const bf16 *Bim = (const bf16*)d_in[11], *Cre = (const bf16*)d_in[12], *Cim = (const bf16*)d_in[13];
    const bf16 *logdt = (const bf16*)d_in[14], *Dsk = (const bf16*)d_in[15];
    bf16* out = (bf16*)d_out;

    void* fn = nullptr;
    cudaDriverEntryPointQueryResult qr;
    cudaGetDriverEntryPoint("cuTensorMapEncodeTiled", &fn, cudaEnableDefault, &qr);
    EncodeFn enc = (EncodeFn)fn;
    void *kv, *o;
    cudaGetSymbolAddress(&kv, g_kv);
    cudaGetSymbolAddress(&o, g_o);
    CUtensorMap mx, mwq, mwk, mwv, mkv2;
    BgParams P;
    map2d(enc, &mx, x, SEQ, DM, 128);
    map2d(enc, &P.mo, o, SEQ, HD, 128);
    map3d(enc, &P.mo2, o, SEQ, HD, 128, 2);
    map3d(enc, &mwq, Wq, DM, HD, 64, 2);
    map3d(enc, &mwk, Wk, DM, HD, 64, 2);
    map3d(enc, &mwv, Wv, DM, HD, 64, 2);
    map3d(enc, &P.mwo4, Wo, HD, DM, 64, 4);
    map3d(enc, &P.mwo2, Wo, HD, DM, 64, 2);
    map3d(enc, &P.mwo1, Wo, HD, DM, 128, 1);
    map3d(enc, &mkv2, kv, SEQ, PW, 32, 2);
    cudaFuncSetAttribute(k_kv, cudaFuncAttributeMaxDynamicSharedMemorySize, GEMM_SMEM);
    cudaFuncSetAttribute(k_bg, cudaFuncAttributeMaxDynamicSharedMemorySize, BG_SMEM);
    cudaFuncSetAttribute(k_tail, cudaFuncAttributeMaxDynamicSharedMemorySize, BG_SMEM);
    cudaFuncSetAttribute(k_chain, cudaFuncAttributeMaxDynamicSharedMemorySize, CHAIN_SMEM);
    cudaFuncSetAttribute(k_s4, cudaFuncAttributeMaxDynamicSharedMemorySize, S4_SMEM);

    cudaStream_t st = cudaStreamPerThread;
    cudaLaunchAttribute pdl[2], cls[1];
    pdl[0].id = cudaLaunchAttributeProgrammaticStreamSerialization;
    pdl[0].val.programmaticStreamSerializationAllowed = 1;
    cls[0].id = cudaLaunchAttributeClusterDimension;
    cls[0].val.clusterDim.x = CLS; cls[0].val.clusterDim.y = 1; cls[0].val.clusterDim.z = 1;
    cudaLaunchConfig_t cfg = {};
    cfg.stream = st; cfg.attrs = cls; cfg.numAttrs = 1;
    cfg.gridDim = dim3(96); cfg.blockDim = dim3(384); cfg.dynamicSmemBytes = GEMM_SMEM;
    cudaLaunchKernelEx(&cfg, k_kv, mx, mwk, mwv, mwq, Wq, Wo, 0);
    pdl[1] = cls[0]; pdl[1].val.clusterDim.x = 2;
    cfg.attrs = pdl; cfg.numAttrs = 2;
    cfg.gridDim = dim3(36);
    cudaLaunchKernelEx(&cfg, k_kv, mx, mwk, mwv, mwq, Wq, Wo, 96);
    cfg.numAttrs = 1;
    cfg.gridDim = dim3(96); cfg.blockDim = dim3(256); cfg.dynamicSmemBytes = CHAIN_SMEM;
    cudaLaunchKernelEx(&cfg, k_chain, mem0, Wq, Wk, Wv, Wo, mkv2);
    cfg.numAttrs = USE_PDL;
    cfg.gridDim = dim3(36); cfg.blockDim = dim3(512); cfg.dynamicSmemBytes = S4_SMEM;
    cudaLaunchKernelEx(&cfg, k_s4, u, Are, Aim, Bre, Bim, Cre, Cim, logdt, Dsk, out);
    cfg.gridDim = dim3(36); cfg.blockDim = dim3(384); cfg.dynamicSmemBytes = BG_SMEM;
    cudaLaunchKernelEx(&cfg, k_bg, P, out);
    cfg.gridDim = dim3(96);
    cudaLaunchKernelEx(&cfg, k_tail, P, out);
}
```

```cpp
#include <cuda_runtime.h>
#include <cuda_bf16.h>
#include <cuda.h>
#include <stdint.h>

typedef __nv_bfloat16 bf16;

constexpr int SEQ = 2048, DM = 1024, HD = 4096, NSEG = 64;

constexpr int PW = 3 * HD;
#define NTA 3
__device__ __align__(1024) bf16 g_kv[(size_t)SEQ * PW];
__device__ __align__(1024) bf16 g_o[(size_t)SEQ * HD];
constexpr int XPAIRS = 128 + NSEG * 4;
__device__ __align__(8192) uint2 g_x[XPAIRS * 1024];
__device__ uint32_t g_home[XPAIRS];
__device__ uint32_t g_side[256];
__device__ __align__(1024) uint32_t g_flag[256];

#define TL(kern, slot)

__device__ __forceinline__ uint32_t smem_u32(const void* p) { return (uint32_t)__cvta_generic_to_shared(p); }
__device__ __forceinline__ void mbar_init(uint32_t bar, uint32_t cnt) {
    asm volatile("mbarrier.init.shared::cta.b64 [%0], %1;" ::"r"(bar), "r"(cnt) : "memory");
}
__device__ __forceinline__ void mbar_expect_tx(uint32_t bar, uint32_t bytes) {
    asm volatile("mbarrier.arrive.expect_tx.shared::cta.b64 _, [%0], %1;" ::"r"(bar), "r"(bytes) : "memory");
}
__device__ __forceinline__ void mbar_arrive(uint32_t bar) {
    asm volatile("mbarrier.arrive.shared::cta.b64 _, [%0];" ::"r"(bar) : "memory");
}
__device__ __forceinline__ bool mbar_try(uint32_t bar, uint32_t parity) {
    uint32_t ok;
    asm volatile("{\n.reg .pred p;\nmbarrier.try_wait.parity.shared::cta.b64 p, [%1], %2;\nselp.u32 %0, 1, 0, p;\n}"
                 : "=r"(ok) : "r"(bar), "r"(parity) : "memory");
    return ok;
}
constexpr int SPIN_LIMIT = 1 << 20;
__device__ __forceinline__ void mbar_wait(uint32_t bar, uint32_t parity) {
    int n = 0;
    while (!mbar_try(bar, parity)) { if (++n > SPIN_LIMIT) __trap(); }
}
__device__ __forceinline__ void mbar_wait_u(uint32_t bar, uint32_t parity) {
    asm volatile("{\n.reg .pred p;\n.reg .u32 n;\n"
                 "mbarrier.try_wait.parity.shared::cta.b64 p, [%0], %1;\n@p bra.uni DONE;\nmov.u32 n, 0;\n"
                 "AGAIN:\nmbarrier.try_wait.parity.shared::cta.b64 p, [%0], %1;\n@p bra.uni DONE;\n"
                 "add.u32 n, n, 1;\nsetp.lt.u32 p, n, 0x100000;\n@p bra.uni AGAIN;\ntrap;\nDONE:\n}"
                 ::"r"(bar), "r"(parity) : "memory");
}
__device__ __forceinline__ void tma2d(uint32_t dst, const CUtensorMap* m, int c0, int c1, uint32_t bar) {
    asm volatile("cp.async.bulk.tensor.2d.shared::cluster.global.mbarrier::complete_tx::bytes [%0], [%1, {%3, %4}], [%2];"
                 ::"r"(dst), "l"(m), "r"(bar), "r"(c0), "r"(c1) : "memory");
}
__device__ __forceinline__ void tma3d(uint32_t dst, const CUtensorMap* m, int c0, int c1, int c2, uint32_t bar) {
    asm volatile("cp.async.bulk.tensor.3d.shared::cluster.global.mbarrier::complete_tx::bytes [%0], [%1, {%3, %4, %5}], [%2];"
                 ::"r"(dst), "l"(m), "r"(bar), "r"(c0), "r"(c1), "r"(c2) : "memory");
}
__device__ __forceinline__ uint32_t pack2(float lo, float hi) {
    uint32_t r;
    asm("cvt.rn.bf16x2.f32 %0, %1, %2;" : "=r"(r) : "f"(hi), "f"(lo));
    return r;
}
__device__ __forceinline__ float bf_lo(uint32_t v) { return __uint_as_float(v << 16); }
__device__ __forceinline__ float bf_hi(uint32_t v) { return __uint_as_float(v & 0xffff0000u); }
__device__ __forceinline__ float bf_round(float x) { return bf_lo(pack2(x, 0.f)); }
__device__ __forceinline__ float ex2(float x) { float y; asm("ex2.approx.ftz.f32 %0, %1;" : "=f"(y) : "f"(x)); return y; }
__device__ __forceinline__ void mma16816(float (&c)[4], uint32_t a0, uint32_t a1, uint32_t a2, uint32_t a3, uint32_t b0, uint32_t b1) {
    asm volatile("mma.sync.aligned.m16n8k16.row.col.f32.bf16.bf16.f32 {%0,%1,%2,%3}, {%4,%5,%6,%7}, {%8,%9}, {%0,%1,%2,%3};"
                 : "+f"(c[0]), "+f"(c[1]), "+f"(c[2]), "+f"(c[3]) : "r"(a0), "r"(a1), "r"(a2), "r"(a3), "r"(b0), "r"(b1));
}
__device__ __forceinline__ void mma1688(float (&c)[4], uint32_t a0, uint32_t a1, uint32_t b0) {
    asm volatile("mma.sync.aligned.m16n8k8.row.col.f32.bf16.bf16.f32 {%0,%1,%2,%3}, {%4,%5}, {%6}, {%0,%1,%2,%3};"
                 : "+f"(c[0]), "+f"(c[1]), "+f"(c[2]), "+f"(c[3]) : "r"(a0), "r"(a1), "r"(b0));
}
__device__ __forceinline__ void ldsm4(uint32_t (&r)[4], uint32_t a) {
    asm volatile("ldmatrix.sync.aligned.m8n8.x4.shared.b16 {%0,%1,%2,%3}, [%4];"
                 : "=r"(r[0]), "=r"(r[1]), "=r"(r[2]), "=r"(r[3]) : "r"(a) : "memory");
}
__device__ __forceinline__ void ldsm4t(uint32_t (&r)[4], uint32_t a) {
    asm volatile("ldmatrix.sync.aligned.m8n8.x4.trans.shared.b16 {%0,%1,%2,%3}, [%4];"
                 : "=r"(r[0]), "=r"(r[1]), "=r"(r[2]), "=r"(r[3]) : "r"(a) : "memory");
}
__device__ __forceinline__ void ldsm2t(uint32_t& r0, uint32_t& r1, uint32_t a) {
    asm volatile("ldmatrix.sync.aligned.m8n8.x2.trans.shared.b16 {%0,%1}, [%2];" : "=r"(r0), "=r"(r1) : "r"(a) : "memory");
}
__device__ __forceinline__ void stsm4t(uint32_t a, uint32_t r0, uint32_t r1, uint32_t r2, uint32_t r3) {
    asm volatile("stmatrix.sync.aligned.m8n8.x4.trans.shared.b16 [%0], {%1,%2,%3,%4};"
                 ::"r"(a), "r"(r0), "r"(r1), "r"(r2), "r"(r3) : "memory");
}
__device__ __forceinline__ void lds128(uint32_t (&r)[4], uint32_t a) {
    asm volatile("ld.shared.v4.u32 {%0,%1,%2,%3}, [%4];" : "=r"(r[0]), "=r"(r[1]), "=r"(r[2]), "=r"(r[3]) : "r"(a) : "memory");
}
__device__ __forceinline__ float4 lds128f(uint32_t a) {
    float4 v;
    asm volatile("ld.shared.v4.f32 {%0,%1,%2,%3}, [%4];" : "=f"(v.x), "=f"(v.y), "=f"(v.z), "=f"(v.w) : "r"(a) : "memory");
    return v;
}
__device__ __forceinline__ float2 lds64f(uint32_t a) {
    float2 v;
    asm volatile("ld.shared.v2.f32 {%0,%1}, [%2];" : "=f"(v.x), "=f"(v.y) : "r"(a) : "memory");
    return v;
}
__device__ __forceinline__ uint32_t lds32(uint32_t a) {
    uint32_t v;
    asm volatile("ld.shared.u32 %0, [%1];" : "=r"(v) : "r"(a) : "memory");
    return v;
}
__device__ __forceinline__ void sts128(uint32_t a, uint32_t r0, uint32_t r1, uint32_t r2, uint32_t r3) {
    asm volatile("st.shared.v4.u32 [%0], {%1,%2,%3,%4};" ::"r"(a), "r"(r0), "r"(r1), "r"(r2), "r"(r3) : "memory");
}
__device__ __forceinline__ void sts128f(uint32_t a, float r0, float r1, float r2, float r3) {
    asm volatile("st.shared.v4.f32 [%0], {%1,%2,%3,%4};" ::"r"(a), "f"(r0), "f"(r1), "f"(r2), "f"(r3) : "memory");
}
__device__ __forceinline__ void sts64(uint32_t a, uint32_t r0, uint32_t r1) {
    asm volatile("st.shared.v2.u32 [%0], {%1,%2};" ::"r"(a), "r"(r0), "r"(r1) : "memory");
}
__device__ __forceinline__ void sts64f(uint32_t a, float r0, float r1) {
    asm volatile("st.shared.v2.f32 [%0], {%1,%2};" ::"r"(a), "f"(r0), "f"(r1) : "memory");
}
__device__ __forceinline__ void sts32f(uint32_t a, float r0) {
    asm volatile("st.shared.f32 [%0], %1;" ::"r"(a), "f"(r0) : "memory");
}
__device__ __forceinline__ uint2 ld_rlx64(const uint2* p) {
    uint2 v;
    asm volatile("{\n.reg .b64 t;\nld.relaxed.gpu.global.b64 t, [%2];\nmov.b64 {%0,%1}, t;\n}" : "=r"(v.x), "=r"(v.y) : "l"(p) : "memory");
    return v;
}
__device__ __forceinline__ void st_rlx64(uint2* p, uint32_t x, uint32_t y) {
    asm volatile("{\n.reg .b64 t;\nmov.b64 t, {%1,%2};\nst.relaxed.gpu.global.b64 [%0], t;\n}" ::"l"(p), "r"(x), "r"(y) : "memory");
}
__device__ __forceinline__ uint32_t ld_acq32(const uint32_t* p) {
    uint32_t v;
    asm volatile("ld.acquire.gpu.global.u32 %0, [%1];" : "=r"(v) : "l"(p) : "memory");
    return v;
}
__device__ __forceinline__ void wait_flag(const uint32_t* p, uint32_t need) {
    int n = 0;
    while (ld_acq32(p) < need) { __nanosleep(200); if (++n > SPIN_LIMIT) __trap(); }
}
__device__ __forceinline__ void bar_sync(int id, int n) { asm volatile("bar.sync %0, %1;" ::"r"(id), "r"(n) : "memory"); }
__device__ __forceinline__ void wg_fence() { asm volatile("wgmma.fence.sync.aligned;" ::: "memory"); }
__device__ __forceinline__ void wg_commit() { asm volatile("wgmma.commit_group.sync.aligned;" ::: "memory"); }
template <int N> __device__ __forceinline__ void wg_wait() { asm volatile("wgmma.wait_group.sync.aligned %0;" ::"n"(N) : "memory"); }
__device__ __forceinline__ uint64_t desc_sw128(uint32_t addr, uint32_t lbo, uint32_t sbo) {
    return (uint64_t)((addr & 0x3FFFF) >> 4) | ((uint64_t)(lbo >> 4) << 16) | ((uint64_t)(sbo >> 4) << 32) | (1ull << 62);
}
__device__ __forceinline__ void quad_transpose(uint32_t& r0, uint32_t& r1, uint32_t& r2, uint32_t& r3, int t) {
    const bool o = t & 1, h = t & 2;
    uint32_t s0 = __shfl_xor_sync(~0u, o ? r0 : r1, 1), s1 = __shfl_xor_sync(~0u, o ? r2 : r3, 1);
    uint32_t a0 = o ? s0 : r0, a1 = o ? r1 : s0, a2 = o ? s1 : r2, a3 = o ? r3 : s1;
    s0 = __shfl_xor_sync(~0u, h ? a0 : a2, 2); s1 = __shfl_xor_sync(~0u, h ? a1 : a3, 2);
    r0 = h ? s0 : a0; r1 = h ? s1 : a1; r2 = h ? a2 : s0; r3 = h ? a3 : s1;
}

__device__ __forceinline__ void wgmma_n256(float (&d)[128], uint64_t da, uint64_t db, int sd) {
    asm volatile("{\n.reg .pred p;\nsetp.ne.b32 p, %130, 0;\n"
        "wgmma.mma_async.sync.aligned.m64n256k16.f32.bf16.bf16 "
        "{%0,%1,%2,%3,%4,%5,%6,%7,%8,%9,%10,%11,%12,%13,%14,%15,"
        "%16,%17,%18,%19,%20,%21,%22,%23,%24,%25,%26,%27,%28,%29,%30,%31,"
        "%32,%33,%34,%35,%36,%37,%38,%39,%40,%41,%42,%43,%44,%45,%46,%47,"
        "%48,%49,%50,%51,%52,%53,%54,%55,%56,%57,%58,%59,%60,%61,%62,%63,"
        "%64,%65,%66,%67,%68,%69,%70,%71,%72,%73,%74,%75,%76,%77,%78,%79,"
        "%80,%81,%82,%83,%84,%85,%86,%87,%88,%89,%90,%91,%92,%93,%94,%95,"
        "%96,%97,%98,%99,%100,%101,%102,%103,%104,%105,%106,%107,%108,%109,%110,%111,"
        "%112,%113,%114,%115,%116,%117,%118,%119,%120,%121,%122,%123,%124,%125,%126,%127}, %128, %129, p, 1, 1, 0, 1;\n}\n"
        : "+f"(d[0]), "+f"(d[1]), "+f"(d[2]), "+f"(d[3]), "+f"(d[4]), "+f"(d[5]), "+f"(d[6]), "+f"(d[7]),
          "+f"(d[8]), "+f"(d[9]), "+f"(d[10]), "+f"(d[11]), "+f"(d[12]), "+f"(d[13]), "+f"(d[14]), "+f"(d[15]),
          "+f"(d[16]), "+f"(d[17]), "+f"(d[18]), "+f"(d[19]), "+f"(d[20]), "+f"(d[21]), "+f"(d[22]), "+f"(d[23]),
          "+f"(d[24]), "+f"(d[25]), "+f"(d[26]), "+f"(d[27]), "+f"(d[28]), "+f"(d[29]), "+f"(d[30]), "+f"(d[31]),
          "+f"(d[32]), "+f"(d[33]), "+f"(d[34]), "+f"(d[35]), "+f"(d[36]), "+f"(d[37]), "+f"(d[38]), "+f"(d[39]),
          "+f"(d[40]), "+f"(d[41]), "+f"(d[42]), "+f"(d[43]), "+f"(d[44]), "+f"(d[45]), "+f"(d[46]), "+f"(d[47]),
          "+f"(d[48]), "+f"(d[49]), "+f"(d[50]), "+f"(d[51]), "+f"(d[52]), "+f"(d[53]), "+f"(d[54]), "+f"(d[55]),
          "+f"(d[56]), "+f"(d[57]), "+f"(d[58]), "+f"(d[59]), "+f"(d[60]), "+f"(d[61]), "+f"(d[62]), "+f"(d[63]),
          "+f"(d[64]), "+f"(d[65]), "+f"(d[66]), "+f"(d[67]), "+f"(d[68]), "+f"(d[69]), "+f"(d[70]), "+f"(d[71]),
          "+f"(d[72]), "+f"(d[73]), "+f"(d[74]), "+f"(d[75]), "+f"(d[76]), "+f"(d[77]), "+f"(d[78]), "+f"(d[79]),
          "+f"(d[80]), "+f"(d[81]), "+f"(d[82]), "+f"(d[83]), "+f"(d[84]), "+f"(d[85]), "+f"(d[86]), "+f"(d[87]),
          "+f"(d[88]), "+f"(d[89]), "+f"(d[90]), "+f"(d[91]), "+f"(d[92]), "+f"(d[93]), "+f"(d[94]), "+f"(d[95]),
          "+f"(d[96]), "+f"(d[97]), "+f"(d[98]), "+f"(d[99]), "+f"(d[100]), "+f"(d[101]), "+f"(d[102]), "+f"(d[103]),
          "+f"(d[104]), "+f"(d[105]), "+f"(d[106]), "+f"(d[107]), "+f"(d[108]), "+f"(d[109]), "+f"(d[110]), "+f"(d[111]),
          "+f"(d[112]), "+f"(d[113]), "+f"(d[114]), "+f"(d[115]), "+f"(d[116]), "+f"(d[117]), "+f"(d[118]), "+f"(d[119]),
          "+f"(d[120]), "+f"(d[121]), "+f"(d[122]), "+f"(d[123]), "+f"(d[124]), "+f"(d[125]), "+f"(d[126]), "+f"(d[127])
        : "l"(da), "l"(db), "r"(sd));
}

__device__ __forceinline__ void wgmma_n128(float (&d)[64], uint64_t da, uint64_t db, int sd) {
    asm volatile("{\n.reg .pred p;\nsetp.ne.b32 p, %66, 0;\n"
        "wgmma.mma_async.sync.aligned.m64n128k16.f32.bf16.bf16 "
        "{%0,%1,%2,%3,%4,%5,%6,%7,%8,%9,%10,%11,%12,%13,%14,%15,"
        "%16,%17,%18,%19,%20,%21,%22,%23,%24,%25,%26,%27,%28,%29,%30,%31,"
        "%32,%33,%34,%35,%36,%37,%38,%39,%40,%41,%42,%43,%44,%45,%46,%47,"
        "%48,%49,%50,%51,%52,%53,%54,%55,%56,%57,%58,%59,%60,%61,%62,%63}, %64, %65, p, 1, 1, 0, 1;\n}\n"
        : "+f"(d[0]), "+f"(d[1]), "+f"(d[2]), "+f"(d[3]), "+f"(d[4]), "+f"(d[5]), "+f"(d[6]), "+f"(d[7]),
          "+f"(d[8]), "+f"(d[9]), "+f"(d[10]), "+f"(d[11]), "+f"(d[12]), "+f"(d[13]), "+f"(d[14]), "+f"(d[15]),
          "+f"(d[16]), "+f"(d[17]), "+f"(d[18]), "+f"(d[19]), "+f"(d[20]), "+f"(d[21]), "+f"(d[22]), "+f"(d[23]),
          "+f"(d[24]), "+f"(d[25]), "+f"(d[26]), "+f"(d[27]), "+f"(d[28]), "+f"(d[29]), "+f"(d[30]), "+f"(d[31]),
          "+f"(d[32]), "+f"(d[33]), "+f"(d[34]), "+f"(d[35]), "+f"(d[36]), "+f"(d[37]), "+f"(d[38]), "+f"(d[39]),
          "+f"(d[40]), "+f"(d[41]), "+f"(d[42]), "+f"(d[43]), "+f"(d[44]), "+f"(d[45]), "+f"(d[46]), "+f"(d[47]),
          "+f"(d[48]), "+f"(d[49]), "+f"(d[50]), "+f"(d[51]), "+f"(d[52]), "+f"(d[53]), "+f"(d[54]), "+f"(d[55]),
          "+f"(d[56]), "+f"(d[57]), "+f"(d[58]), "+f"(d[59]), "+f"(d[60]), "+f"(d[61]), "+f"(d[62]), "+f"(d[63])
        : "l"(da), "l"(db), "r"(sd));
}

__device__ __forceinline__ void wgmma_n64(float (&d)[32], uint64_t da, uint64_t db, int sd) {
    asm volatile("{\n.reg .pred p;\nsetp.ne.b32 p, %34, 0;\n"
        "wgmma.mma_async.sync.aligned.m64n64k16.f32.bf16.bf16 "
        "{%0,%1,%2,%3,%4,%5,%6,%7,%8,%9,%10,%11,%12,%13,%14,%15,"
        "%16,%17,%18,%19,%20,%21,%22,%23,%24,%25,%26,%27,%28,%29,%30,%31}, %32, %33, p, 1, 1, 0, 1;\n}\n"
        : "+f"(d[0]), "+f"(d[1]), "+f"(d[2]), "+f"(d[3]), "+f"(d[4]), "+f"(d[5]), "+f"(d[6]), "+f"(d[7]),
          "+f"(d[8]), "+f"(d[9]), "+f"(d[10]), "+f"(d[11]), "+f"(d[12]), "+f"(d[13]), "+f"(d[14]), "+f"(d[15]),
          "+f"(d[16]), "+f"(d[17]), "+f"(d[18]), "+f"(d[19]), "+f"(d[20]), "+f"(d[21]), "+f"(d[22]), "+f"(d[23]),
          "+f"(d[24]), "+f"(d[25]), "+f"(d[26]), "+f"(d[27]), "+f"(d[28]), "+f"(d[29]), "+f"(d[30]), "+f"(d[31])
        : "l"(da), "l"(db), "r"(sd));
}

constexpr int STAGE_BYTES = 49152, NSTAGE = 4;
constexpr int GEMM_SMEM = NSTAGE * STAGE_BYTES + 128;

struct GemmSmem { uint32_t st, full, empty; };
__device__ __forceinline__ GemmSmem gemm_setup(uint8_t* raw, int releases) {
    GemmSmem g;
    g.st = smem_u32(raw);
    if (g.st & 1023) __trap();
    g.full = g.st + NSTAGE * STAGE_BYTES; g.empty = g.full + 64;
    if (threadIdx.x == 0) {
        for (int s = 0; s < NSTAGE; s++) { mbar_init(g.full + 8 * s, 1); mbar_init(g.empty + 8 * s, releases); }
        asm volatile("fence.mbarrier_init.release.cluster;" ::: "memory");
        asm volatile("fence.proxy.async.shared::cta;" ::: "memory");
    }
    __syncthreads();
    return g;
}
__device__ __forceinline__ void mbar_arrive_one(uint32_t bar, uint32_t who) {
    asm volatile("{\n.reg .pred p;\nsetp.eq.u32 p, %1, 0;\n@p mbarrier.arrive.shared::cta.b64 _, [%0];\n}" ::"r"(bar), "r"(who) : "memory");
}
template <int BM, int BN, int KPS, typename ACC>
__device__ __forceinline__ void gemm_stage(ACC& acc, uint32_t stage, int wg, bool first) {
    const uint64_t da = desc_sw128(stage + wg * 8192, 16, 1024);
    const uint64_t db = desc_sw128(stage + KPS * BM * 128, 8192, 1024);
    wg_fence();
#pragma unroll
    for (int k = 0; k < 4 * KPS; k++) {
        const uint64_t a = da + (k >> 2) * (BM * 8) + (k & 3) * 2, b = db + k * 128;
        if constexpr (BN == 256) wgmma_n256(acc, a, b, first && k == 0 ? 0 : 1);
        else if constexpr (BN == 128) wgmma_n128(acc, a, b, first && k == 0 ? 0 : 1);
        else wgmma_n64(acc, a, b, first && k == 0 ? 0 : 1);
    }
    wg_commit();
}

__device__ __forceinline__ void kv_store_unit(const uint32_t (&pk)[64], int u, bf16* dst, int t) {
    const int G = (u >> 2) * 2 + (u & 1), hh = (u >> 1) & 1;
    uint32_t r0 = pk[(4 * G + 0) * 2 + hh], r1 = pk[(4 * G + 1) * 2 + hh], r2 = pk[(4 * G + 2) * 2 + hh], r3 = pk[(4 * G + 3) * 2 + hh];
    quad_transpose(r0, r1, r2, r3, t);
#define KVST ".cs"
    asm volatile("st.global" KVST ".v4.u32 [%0], {%1,%2,%3,%4};" ::"l"(dst + (size_t)hh * 8 * PW + G * 32), "r"(r0), "r"(r1), "r"(r2), "r"(r3) : "memory");
}

#define TLK(slot)
#define TLK2(slot)
__device__ __forceinline__ uint32_t near_page(int pair, int line) {
    uint32_t best[2] = {~0u, ~0u};
#pragma unroll 1
#define PMIN 8
#define PMAX 16
    for (int i = 0; i < PMAX; i++) {
        if (i >= PMIN && max(best[0], best[1]) - min(best[0], best[1]) > 110 && max(best[0], best[1]) - min(best[0], best[1]) < 300) break;
        uint32_t t0, t1, v;
        asm volatile("mov.u32 %0, %%clock;" : "=r"(t0)::"memory");
        asm volatile("atom.relaxed.gpu.global.or.b32 %0, [%1], -1;" : "=r"(v) : "l"(g_x + pair * 1024 + (i & 1) * 512 + line * 16) : "memory");
        asm volatile("{\n.reg .pred p;\nsetp.ne.u32 p, %1, 0x12345;\nmov.u32 %0, -1;\n@p mov.u32 %0, %%clock;\n}" : "=r"(t1) : "r"(v) : "memory");
        if (i & 1) best[1] = min(best[1], t1 - t0); else best[0] = min(best[0], t1 - t0);
    }
    return best[1] < best[0];
}
__device__ __forceinline__ void map_pages(int c) {
    uint32_t smid;
    asm("mov.u32 %0, %%smid;" : "=r"(smid));
    const uint32_t side = near_page(0, c & 31);
    g_side[smid & 255] = side;
    for (int p = c; p < XPAIRS; p += 132) g_home[p] = near_page(p, 0) ^ side;
}

__device__ __forceinline__ void kv_tile(int c, int n, int& m, int& nb) {
    if (c < 96) { m = (c & 3) + 4 * n; nb = c >> 2; }
    else {
        const int i = ((c - 96) >> 1) + 18 * n, j = i - 48 * NTA, p = j < 0 ? i / 24 : 2 * NTA + j / 48;
        m = 2 * p + (c & 1); nb = j < 0 ? 24 + i % 24 : j % 48;
    }
}

__global__ void __launch_bounds__(384, 1)
k_kv(const __grid_constant__ CUtensorMap mx, const __grid_constant__ CUtensorMap mwk, const __grid_constant__ CUtensorMap mwv,
     const __grid_constant__ CUtensorMap mwq, const bf16* __restrict__ Wq, const bf16* __restrict__ Wo, int c0) {
    extern __shared__ __align__(1024) uint8_t smem_gemm[];
    const int c = c0 + blockIdx.x, ntile = c < 96 ? NTA : (384 - 48 * NTA + 17 - ((c - 96) >> 1)) / 18;
    if (c != 96) asm volatile("griddepcontrol.launch_dependents;");
    const uint32_t bar_done = smem_u32(smem_gemm) + NSTAGE * STAGE_BYTES + 96;
    if (threadIdx.x == 0) { mbar_init(bar_done, 8); mbar_init(bar_done + 8, 8); }
    GemmSmem g = gemm_setup(smem_gemm, 4);
    if (threadIdx.x == 0) TLK(0);
    uint32_t rank, peer_empty;
    asm("mov.u32 %0, %%cluster_ctarank;" : "=r"(rank));
    asm("mapa.shared::cluster.u32 %0, %1, %2;" : "=r"(peer_empty) : "r"(g.empty), "r"(rank ^ 1));
    asm volatile("barrier.cluster.arrive.relaxed.aligned;\nbarrier.cluster.wait.aligned;" ::: "memory");
    auto release = [&](int s) {
        asm volatile("{\n.reg .pred p;\nsetp.eq.u32 p, %2, 0;\n@p mbarrier.arrive.relaxed.cta.shared::cta.b64 _, [%0];\n"
                     "@p mbarrier.arrive.relaxed.cluster.shared::cluster.b64 _, [%1];\n}"
                     ::"r"(g.empty + 8 * s), "r"(peer_empty + 8 * s), "r"(threadIdx.x & 127) : "memory");
    };
    const int wg = __shfl_sync(~0u, threadIdx.x >> 7, 0);
    if (wg == 0) {
        asm volatile("setmaxnreg.dec.sync.aligned.u32 40;");
        if (threadIdx.x == 0) {
            for (int it = 0; it < ntile * 16; it++) {
                const int s = it & 3, kb = it & 15;
                int m, nb;
                kv_tile(c, it >> 4, m, nb);
                mbar_wait(g.empty + 8 * s, ((it >> 2) & 1) ^ 1);
                mbar_expect_tx(g.full + 8 * s, STAGE_BYTES);
                tma2d(g.st + s * STAGE_BYTES, &mx, kb * 64, m * 128, g.full + 8 * s);
                asm volatile("cp.async.bulk.tensor.3d.shared::cluster.global.mbarrier::complete_tx::bytes.multicast::cluster "
                             "[%0], [%1, {%3, %4, %5}], [%2], %6;"
                             ::"r"(g.st + s * STAGE_BYTES + 16384 + (c & 1) * 16384), "l"(nb < 16 ? &mwk : nb < 32 ? &mwv : &mwq), "r"(g.full + 8 * s),
                               "r"(0), "r"(kb * 64), "r"((nb & 15) * 4 + (c & 1) * 2), "h"((uint16_t)(3u << (rank & ~1u))) : "memory");
#define PF0 (16 * NTA - 22)
                if (c < 96 && it >= PF0 && (it - PF0) * 96 + c < 2048)
                    asm volatile("cp.async.bulk.prefetch.L2.global [%0], 4096;" ::"l"((const char*)Wo + ((it - PF0) * 96 + c) * 4096) : "memory");
            }
        } else if (threadIdx.x == 32) {
            if (c == 96) {
                for (int i = 0; i < 64; i++) reinterpret_cast<uint4*>(g_flag)[i] = make_uint4(0, 0, 0, 0);
                asm volatile("fence.acq_rel.gpu;\ngriddepcontrol.launch_dependents;\ngriddepcontrol.wait;\n"
                             "fence.acq_rel.gpu;\nred.relaxed.gpu.global.add.u32 [%0], 1;" ::"l"(g_flag + 8) : "memory");
            }
        } else if (threadIdx.x == 64) {
            for (int n = 0; n < (c < 96 ? 0 : ntile); n++) {
                int m, nb;
                kv_tile(c, n, m, nb);
                mbar_wait(bar_done + (n & 1) * 8, (n >> 1) & 1);
                asm volatile("fence.acq_rel.gpu;\nred.relaxed.gpu.global.add.u32 [%0], 1;" ::"l"(g_flag + (m >> 1)) : "memory");
            }
        } else if (threadIdx.x >= 96) {
            mbar_wait(g.full + 24, 0);
            const uint4 ones = make_uint4(~0u, ~0u, ~0u, ~0u);
            for (int i = c * 32 + threadIdx.x - 96; i < XPAIRS * 512; i += 132 * 32) reinterpret_cast<uint4*>(g_x)[i] = ones;
            __syncwarp();
            if (threadIdx.x == 96) {
                map_pages(c);
                if (c >= 96) asm volatile("fence.acq_rel.gpu;\nred.relaxed.gpu.global.add.u32 [%0], 1;" ::"l"(g_flag + 8) : "memory");
            }
        }
    } else {
        asm volatile("setmaxnreg.inc.sync.aligned.u32 232;");
        const int cw = wg - 1, lane = threadIdx.x & 31, t = lane & 3;
        bf16* const dst0 = g_kv + (size_t)(cw * 64 + ((threadIdx.x >> 5) & 3) * 16 + (lane >> 2)) * PW + t * 8;
        bf16* dst = dst0;
        float acc[128];
        uint32_t pk[64];
#pragma unroll 1
        for (int tile = 0; tile < ntile; tile++) {
#pragma unroll
            for (int kb = 0; kb < 16; kb++) {
                mbar_wait_u(g.full + 8 * (kb & 3), (kb >> 2) & 1);
                if (kb == 0 && tile == 0 && threadIdx.x == 128) TLK2(0);
                gemm_stage<128, 256, 1>(acc, g.st + (kb & 3) * STAGE_BYTES, cw, kb == 0);
                if (tile > 0) {
                    kv_store_unit(pk, kb, dst, t);
                    if (kb == 15) { __syncwarp(); mbar_arrive_one(bar_done + (~tile & 1) * 8, lane); }
                }
                if (kb > 0) {
                    wg_wait<1>();
                    if (kb <= 12 || tile < ntile - 1) release((kb - 1) & 3);
                }
            }
            wg_wait<0>();
            if (tile < 4 && threadIdx.x == 128) TLK2(tile + 1);
            if (tile < ntile - 1) release(3);
#pragma unroll
            for (int i = 0; i < 64; i++) pk[i] = pack2(acc[2 * i], acc[2 * i + 1]);
            int m, nb;
            kv_tile(c, tile, m, nb);
            dst = dst0 + (size_t)m * 128 * PW + nb * 256;
        }
        if (threadIdx.x == 128) TLK(2);
#pragma unroll
        for (int u = 0; u < 16; u++) kv_store_unit(pk, u, dst, t);
        __syncwarp();
        mbar_arrive_one(bar_done + (~ntile & 1) * 8, lane);
        if (threadIdx.x == 128) TLK(1);
    }
}

constexpr int NS1 = 31;
#define RB1 4
#define PFC 4
constexpr int C_W1 = 0;
constexpr int C_W2 = C_W1 + 8 * NS1 * 512;
constexpr int C_KV = C_W2 + 14 * 8 * 512;
constexpr int C_RED = C_KV + 16384;
constexpr int C_QKV = C_RED + 64 * 272;
constexpr int QKV_SZ = 3 * 8 * 272;
constexpr int C_SC = C_RED;
constexpr int C_OB = C_SC + 2 * 8 * 52 * 4;
constexpr int C_BAR = C_QKV + 2 * QKV_SZ;
__host__ __device__ constexpr int smem_idx(int ks, int j) {
    return ks == 0 ? j : ks < 3 ? (j < 4 ? 4 + 4 * ks + j : -1) : (j < 3 ? 7 + 3 * ks + j : -1);
}
constexpr int CHAIN_SMEM = C_BAR + 64;
#define TS(i)
#define TG(i)

#define DLY3 10
#define DLY1 4
#define DLY0 4
#define DLY1A 11
#define DLY0A 0
#define DLY1B 4
#define PFD 3
#define PFI 0
#define DLYW 4
#define DLYQ 3
#define DLYS 0
template <int N> __device__ __forceinline__ uint32_t delayed(uint32_t x, uint32_t self) {
    uint32_t p = self;
#pragma unroll
    for (int i = 0; i < N; i++) asm volatile("ld.volatile.shared.u32 %0, [%0];" : "+r"(p)::"memory");
    return x + (p - self);
}
__device__ __forceinline__ int fresh(int x) { asm volatile("mov.b32 %0, %0;" : "+r"(x)); return x; }
__device__ __forceinline__ void lds128v(uint32_t (&r)[4], uint32_t a) {
    asm volatile("ld.volatile.shared.v4.u32 {%0,%1,%2,%3}, [%4];" : "=r"(r[0]), "=r"(r[1]), "=r"(r[2]), "=r"(r[3]) : "r"(a) : "memory");
}
__device__ __forceinline__ uint2 lds64(uint32_t a) {
    uint2 v;
    asm volatile("ld.shared.v2.u32 {%0,%1}, [%2];" : "=r"(v.x), "=r"(v.y) : "r"(a) : "memory");
    return v;
}
#define LDQ ".L1::no_allocate"
__device__ __forceinline__ uint4 ldw128(const void* p) {
    uint4 v;
    asm volatile("ld.global.nc" LDQ ".v4.u32 {%0,%1,%2,%3}, [%4];" : "=r"(v.x), "=r"(v.y), "=r"(v.z), "=r"(v.w) : "l"(p));
    return v;
}
#define P8_LD(i) "ld.relaxed.gpu.global.b64 d" #i ", [src + " #i " * 256];\n"
#define P8_X(i) "mov.b64 {x" #i ", y" #i "}, d" #i ";\n"
#define P8_HEAD(SRC) "{\n.reg .pred p, q;\n.reg .b64 src, d<8>;\n.reg .b32 n, x<8>, y<8>, m0, m1;\nmov.b64 src, " SRC ";\n"         \
                P8_LD(0) P8_LD(1) P8_LD(2) P8_LD(3) P8_LD(4) P8_LD(5) P8_LD(6) P8_LD(7) "mov.u32 n, 0;\nCHECK:\n" \
                P8_X(0) P8_X(1) P8_X(2) P8_X(3) P8_X(4) P8_X(5) P8_X(6) P8_X(7)
#define P8_VOTE "vote.sync.all.pred p, p, -1;\n@p bra.uni DONE;\n"
#define P8_TAIL "add.u32 n, n, 1;\nsetp.lt.u32 p, n, 0x100000;\n@p bra.uni CHECK;\ntrap;\nDONE:\n"
#define S8_LD(i) "ld.relaxed.gpu.global.b64 %" #i ", [%8 + " #i " * 256];\n"
__device__ __forceinline__ void fetch_state(uint64_t (&d)[8], const void* src) {
    asm volatile(S8_LD(0) S8_LD(1) S8_LD(2) S8_LD(3) S8_LD(4) S8_LD(5) S8_LD(6) S8_LD(7)
                 : "=&l"(d[0]), "=&l"(d[1]), "=&l"(d[2]), "=&l"(d[3]), "=&l"(d[4]), "=&l"(d[5]), "=&l"(d[6]), "=&l"(d[7]) : "l"(src) : "memory");
}
__device__ __forceinline__ void settle_state(uint64_t (&d)[8], const void* src) {
#define S8_X(i) "mov.b64 {x" #i ", _}, %" #i ";\n"
#define S8_R(i) "setp.eq.u32 q, x" #i ", 0xffffffff;\n@q " S8_LD(i)
    asm volatile("{\n.reg .pred p, q;\n.reg .b32 n, x<8>, m0, m1;\nmov.u32 n, 0;\nCHECK:\n"
                 S8_X(0) S8_X(1) S8_X(2) S8_X(3) S8_X(4) S8_X(5) S8_X(6) S8_X(7)
                 "max.u32 m0, x0, x1;\nmax.u32 m0, m0, x2;\nmax.u32 m1, x3, x4;\nmax.u32 m1, m1, x5;\nmax.u32 m0, m0, x6;\n"
                 "max.u32 m0, m0, x7;\nmax.u32 m0, m0, m1;\nsetp.ne.u32 p, m0, 0xffffffff;\n" P8_VOTE
                 S8_R(0) S8_R(1) S8_R(2) S8_R(3) S8_R(4) S8_R(5) S8_R(6) S8_R(7) P8_TAIL "}"
                 : "+l"(d[0]), "+l"(d[1]), "+l"(d[2]), "+l"(d[3]), "+l"(d[4]), "+l"(d[5]), "+l"(d[6]), "+l"(d[7]) : "l"(src) : "memory");
}
__device__ __forceinline__ uint64_t poll_sum(const void* src, uint32_t tag, uint32_t sel) {
#define P8_RT(i) "lop3.b32 m0, x" #i ", %2, 1, 0x28;\nsetp.ne.u32 q, m0, 0;\n@q " P8_LD(i)
#define P8_MMA(c, i, z) "mma.sync.aligned.m16n8k8.row.col.f32.bf16.bf16.f32 {" #c "0," #c "1," #c "2," #c "3}, {x" #i ", y" #i "}, {%3}, {" #z "0," #z "1," #z "2," #z "3};\n"
    uint64_t r;
    asm volatile(P8_HEAD("%1") "{\n.reg .f32 a<4>, b<4>, z<4>;\nmov.f32 z0, 0f00000000;\nmov.f32 z1, z0;\nmov.f32 z2, z0;\nmov.f32 z3, z0;\n"
                 P8_MMA(a, 0, z) P8_MMA(b, 1, z) P8_MMA(a, 2, a) P8_MMA(b, 3, b) P8_MMA(a, 4, a) P8_MMA(b, 5, b) P8_MMA(a, 6, a) P8_MMA(b, 7, b)
                 "add.f32 a0, a0, b0;\nadd.f32 a1, a1, b1;\nadd.f32 a2, a2, b2;\nadd.f32 a3, a3, b3;\n"
                 "cvt.rn.bf16x2.f32 m0, a1, a0;\ncvt.rn.bf16x2.f32 m1, a3, a2;\nmov.b64 %0, {m0, m1};\n}\n"
                 "lop3.b32 m0, x0, x1, %2, 0x7e;\nlop3.b32 m1, x2, x3, %2, 0x7e;\nlop3.b32 m0, m0, x4, %2, 0xf6;\n"
                 "lop3.b32 m1, m1, x5, %2, 0xf6;\nlop3.b32 m0, m0, x6, %2, 0xf6;\nlop3.b32 m1, m1, x7, %2, 0xf6;\n"
                 "lop3.b32 m0, m0, m1, 1, 0xa8;\nsetp.eq.u32 p, m0, 0;\n" P8_VOTE
                 P8_RT(0) P8_RT(1) P8_RT(2) P8_RT(3) P8_RT(4) P8_RT(5) P8_RT(6) P8_RT(7) P8_TAIL "}"
                 : "=&l"(r) : "l"(src), "r"(tag), "r"(sel) : "memory");
    return r;
}
__device__ __forceinline__ void wait_count_u(const uint32_t* p, uint32_t need) {
    asm volatile("{\n.reg .pred p;\n.reg .u32 n, v;\nmov.u32 n, 0;\nAGAIN:\nld.acquire.gpu.global.u32 v, [%0];\nsetp.ge.u32 p, v, %1;\n"
                 "vote.sync.all.pred p, p, -1;\n@p bra.uni DONE;\nadd.u32 n, n, 1;\nsetp.lt.u32 p, n, 0x100000;\n@p bra.uni AGAIN;\ntrap;\n"
                 "DONE:\nfence.proxy.async.global;\n}" ::"l"(p), "r"(need) : "memory");
}
__device__ __forceinline__ uint32_t movm(uint32_t x) { asm volatile("movmatrix.sync.aligned.m8n8.trans.b16 %0, %0;" : "+r"(x)); return x; }
template <int NK, typename F>
__device__ __forceinline__ void attend(uint32_t sb, uint32_t lm, uint32_t qs, uint32_t xq, int i8, int lane, bf16* dst, F mid) {
    const int r8 = lane & 7, m4 = lane >> 3;
    const float sl2e = 0.08838834764831845f * 1.4426950408889634f;
    const uint32_t lk = sb + C_KV + ((m4 & 1) * 8 + r8) * 128 + (((m4 >> 1) ^ r8) << 4);
    const uint32_t lkm = sb + xq + (8 + r8) * 272 + (m4 & 1) * 32 + (m4 >> 1) * 16;
    asm volatile("cp.async.wait_all;" ::: "memory");
    __syncwarp();
    float x[4][4];
#pragma unroll
    for (int i = 0; i < 4; i++) x[i][0] = x[i][1] = x[i][2] = x[i][3] = 0.f;
#pragma unroll
    for (int kp = 0; kp < 4; kp++) {
        uint32_t q[4], a[4];
        ldsm4(q, lm + qs + kp * 64);
        ldsm4(a, lkm + kp * 64);
        mma16816(x[2], a[0], a[1], a[2], a[3], q[0], q[1]);
        mma16816(x[3], a[0], a[1], a[2], a[3], q[2], q[3]);
#pragma unroll
        for (int u = 0; u < 4; u++) {
            if ((u & 1) >= NK) continue;
            ldsm4(a, (lk ^ (((kp & 1) * 2 + (u >> 1)) << 5)) + (kp >> 1) * 4096 + (u & 1) * 2048);
            mma16816(x[u & 1], a[0], a[1], a[2], a[3], q[u & 2], q[(u & 2) + 1]);
        }
    }
    x[2][0] += x[3][2]; x[2][1] += x[3][3];
    const int lim = i8 + 2 * (lane & 3) - (lane >> 2);
    uint32_t p[5];
    {
        float m[2], e[5][2];
#pragma unroll
        for (int b = 0; b < 2; b++) {
            e[4][b] = m[b] = x[2][b];
#pragma unroll
            for (int j = 0; j < 2 * NK; j++) {
                e[j][b] = j < 2 * NK - 2 || 8 * j - b <= lim ? x[j >> 1][(j & 1) * 2 + b] : -3.0e38f;
                m[b] = fmaxf(m[b], e[j][b]);
            }
        }
#pragma unroll
        for (int o = 4; o < 32; o <<= 1) {
            m[0] = fmaxf(m[0], __shfl_xor_sync(~0u, m[0], o));
            m[1] = fmaxf(m[1], __shfl_xor_sync(~0u, m[1], o));
        }
        m[0] *= sl2e; m[1] *= sl2e;
#pragma unroll
        for (int j = 0; j < 5; j++)
            if (j < 2 * NK || j == 4) p[j] = movm(pack2(ex2(fmaf(e[j][0], sl2e, -m[0])), ex2(fmaf(e[j][1], sl2e, -m[1]))));
    }
    const uint32_t lvt = sb + C_KV + 8192 + ((m4 >> 1) * 8 + r8) * 128 + (((m4 & 1) ^ r8) << 4), one = 0x3f803f80u;
    float sm[4] = {0.f, 0.f, 0.f, 0.f}, c[8][4];
    mma16816(sm, one, one, one, one, p[0], p[1]);
    if (NK == 2) mma16816(sm, one, one, one, one, p[2], p[3]);
    mma1688(sm, one, one, p[4]);
#pragma unroll
    for (int j = 0; j < 8; j++) c[j][0] = c[j][1] = c[j][2] = c[j][3] = 0.f;
#pragma unroll
    for (int kk = 0; kk < NK; kk++)
#pragma unroll
        for (int j = 0; j < 8; j++) {
            uint32_t a[4];
            ldsm4t(a, (lvt ^ ((j & 3) << 5)) + (j >> 2) * 4096 + kk * 2048);
            mma16816(c[j], a[0], a[1], a[2], a[3], p[2 * kk], p[2 * kk + 1]);
        }
    float i0, i1;
    asm("rcp.approx.ftz.f32 %0, %1;" : "=f"(i0) : "f"(sm[0]));
    asm("rcp.approx.ftz.f32 %0, %1;" : "=f"(i1) : "f"(sm[1]));
    uint32_t o[4][4];
#pragma unroll
    for (int j = 0; j < 4; j++) {
        uint32_t a[4];
        ldsm4t(a, lm + xq + 16 * 272 + j * 64);
        mma1688(c[2 * j], a[0], a[1], p[4]);
        mma1688(c[2 * j + 1], a[2], a[3], p[4]);
#pragma unroll
        for (int u = 0; u < 4; u++) o[j][u] = pack2(c[2 * j + (u >> 1)][(u & 1) * 2] * i0, c[2 * j + (u >> 1)][(u & 1) * 2 + 1] * i1);
    }
#pragma unroll
    for (int j = 0; j < 4; j++) stsm4t(lm + qs + j * 64, o[j][0], o[j][1], o[j][2], o[j][3]);
    mid();
    __syncwarp();
#pragma unroll
    for (int j = 0; j < 4; j++) lds128(o[j], sb + qs + ((lane >> 4) + 2 * j) * 272 + (lane & 15) * 16);
#pragma unroll
    for (int j = 0; j < 4; j++)
        asm volatile("st.global.v4.u32 [%0], {%1,%2,%3,%4};" ::"l"(dst + (size_t)2 * j * HD), "r"(o[j][0]), "r"(o[j][1]), "r"(o[j][2]), "r"(o[j][3]) : "memory");
}
__device__ __forceinline__ void sum8(float (&c)[4], const uint2 (&v)[8], uint32_t idn) {
    float d[4] = {0.f, 0.f, 0.f, 0.f};
    c[0] = c[1] = c[2] = c[3] = 0.f;
    mma16816(c, v[0].x, v[0].y, v[1].x, v[1].y, idn, idn);
    mma16816(d, v[2].x, v[2].y, v[3].x, v[3].y, idn, idn);
    mma16816(c, v[4].x, v[4].y, v[5].x, v[5].y, idn, idn);
    mma16816(d, v[6].x, v[6].y, v[7].x, v[7].y, idn, idn);
    c[0] += d[0]; c[1] += d[1]; c[2] += d[2]; c[3] += d[3];
}

#define CLS 6
__global__ void __cluster_dims__(CLS, 1, 1) __launch_bounds__(256, 1)
k_chain(const bf16* __restrict__ mem0, const bf16* __restrict__ Wq, const bf16* __restrict__ Wk, const bf16* __restrict__ Wv,
        const bf16* __restrict__ Wo, const __grid_constant__ CUtensorMap mkv) {
    extern __shared__ __align__(1024) uint8_t smem_chain[];
    const uint32_t sb = smem_u32(smem_chain);
    if (sb & 1023) __trap();
    const int w = __shfl_sync(~0u, threadIdx.x >> 5, 0), lane = __shfl_sync(~0u, threadIdx.x & 31, threadIdx.x & 31);
    const int tid = w * 32 + lane, g = lane >> 2, t = lane & 3;
    auto pin = [&](uint32_t x) { asm volatile("shfl.sync.idx.b32 %0, %0, %1, 31, -1;" : "+r"(x) : "r"(lane) : "memory"); return x; };
    const int h = blockIdx.x / 3, r = blockIdx.x - 3 * h;
    const uint32_t bar_x = sb + C_BAR, bar_kv = sb + C_BAR + 8, bar_go = sb + C_BAR + 16, bar_w = sb + C_BAR + 24, self = sb + C_BAR + 60;
    asm volatile("griddepcontrol.launch_dependents;");
    const int tbase = r == 0 ? 0 : 1 + 21 * r, ntile = r == 0 ? 22 : 21;
    uint32_t side;
    if (tid == 0) {
        mbar_init(bar_x, 8); mbar_init(bar_kv, 1); mbar_init(bar_go, 1); mbar_init(bar_w, 1);
        asm volatile("st.shared.u32 [%0], %0;" ::"r"(self) : "memory");
        asm volatile("fence.mbarrier_init.release.cluster;" ::: "memory");
        asm volatile("fence.proxy.async.shared::cta;" ::: "memory");
        mbar_expect_tx(bar_w, 128 * 32 * ntile);
    }
    __syncthreads();
    asm volatile("barrier.cluster.arrive.relaxed.aligned;" ::: "memory");
    if (tid < 128)
        asm volatile("cp.async.bulk.shared::cluster.global.mbarrier::complete_tx::bytes [%0], [%1], %2, [%3];"
                     ::"r"(sb + C_W1 + tid * 720), "l"(Wo + (size_t)(h * 128 + tid) * DM + tbase * 16), "r"(32 * ntile), "r"(bar_w) : "memory");
    const int tile0 = tbase + 7 - w;
    const bool three = w >= (r == 0 ? 2 : 3);
    const uint32_t wa = pin(sb + tid * 16);
#define W1A(i) (wa + C_W1 + (i) * 4096)
#define W2A(x) (wa + C_W2 + ((x) < 8 ? (x) * 4096 : 32768 - 1024 + ((x) - 8) * 3072))
    uint32_t wo0[8][4], wr[64][4];
    {
        const bf16* W = (r == 0 ? Wq : r == 1 ? Wk : Wv) + (size_t)(128 * w + (lane >> 4)) * HD + h * 128 + 8 * (lane & 15);
        uint4 raw[8][8];
        auto fetch = [&](int ks) {
#pragma unroll
            for (int i = 0; i < 8; i++) raw[ks][i] = ldw128(W + (size_t)(16 * ks + 2 * i) * HD);
        };
        fetch(0); fetch(1); fetch(2); fetch(3);
    asm("mov.u32 %0, %%smid;" : "=r"(side));
    side = __ldcg(g_side + (side & 255)) & 1;
    if (tid == 0 && r > 0) asm volatile("st.relaxed.gpu.global.u32 [%0], %1;" ::"l"(g_flag + 128 + 2 * h + r - 1), "r"(2 | side) : "memory");
        if (w == 0) TG(0);
        mbar_wait_u(bar_w, 0);
        if (w == 0) TG(1);
        const uint32_t p = sb + C_W1 + ((lane & 7) + (lane >> 4) * 8) * 720 + (7 - w) * 32 + ((lane >> 3) & 1) * 16;
#pragma unroll
        for (int ks = 0; ks < 8; ks++) {
            uint32_t a[4];
            ldsm4t(wo0[ks], p + ks * 16 * 720);
            ldsm4t(a, p + ks * 16 * 720 + 256);
            sts128(W2A(ks), a[0], a[1], a[2], a[3]);
            if (three) { ldsm4t(a, p + ks * 16 * 720 + 512); sts128(W2A(8 + ks), a[0], a[1], a[2], a[3]); }
        }
        __syncthreads();
        if (w < PFI)
            asm volatile("prefetch.global.L2 [%0];\nprefetch.global.L2 [%0 + 128];" ::"l"(g_kv + (size_t)tid * PW + r * HD + h * 128) : "memory");
        if (w == 0) TG(2);
        const uint32_t stg = sb + C_KV + w * 4096;
        const uint32_t rd = stg + ((lane & 7) + 8 * (lane >> 4)) * 256 + ((((lane >> 3) & 1) ^ (lane & 7)) << 4);
#pragma unroll
        for (int ks = 0; ks < 8; ks++) {
#pragma unroll
            for (int i = 0; i < 8; i++)
                sts128(stg + (2 * i + (lane >> 4)) * 256 + (((lane & 15) ^ (((2 * i) & 6) | (lane >> 4))) << 4),
                       raw[ks][i].x, raw[ks][i].y, raw[ks][i].z, raw[ks][i].w);
            if (ks < 2) fetch(ks + 4);
            if (ks == 3 || ks == 5) fetch(ks / 2 + 5);
            __syncwarp();
#pragma unroll
            for (int j = 0; j < 8; j++) {
                if (smem_idx(ks, j) >= 0) {
                    uint32_t a[4];
                    ldsm4t(a, rd ^ (j << 5));
                    sts128(W1A(smem_idx(ks, j)), a[0], a[1], a[2], a[3]);
                } else ldsm4t(wr[8 * ks + j], rd ^ (j << 5));
            }
            __syncwarp();
        }
    }
    if (w == 0) TG(3);
    wait_count_u(g_flag + (lane & 8), lane & 8 ? 37 : 48);
    asm volatile("fence.proxy.async.shared::cta;" ::: "memory");
    __syncthreads();
    if (tid == 0) {
        mbar_expect_tx(bar_kv, 16384);
        tma3d(sb + C_KV, &mkv, 0, 0, 2 * h, bar_kv);
        tma3d(sb + C_KV + 8192, &mkv, 0, 0, 64 + 2 * h, bar_kv);
    }
    asm volatile("barrier.cluster.wait.aligned;" ::: "memory");

    auto load_kv = [&](int s) {
        asm volatile("{\n.reg .pred p;\nelect.sync _|p, -1;\n@p mbarrier.arrive.expect_tx.shared::cta.b64 _, [%2], 16384;\n"
                     "@p cp.async.bulk.tensor.3d.shared::cluster.global.mbarrier::complete_tx::bytes [%0], [%1, {%3, %4, %5}], [%2];\n"
                     "@p cp.async.bulk.tensor.3d.shared::cluster.global.mbarrier::complete_tx::bytes [%6], [%1, {%3, %4, %7}], [%2];\n}"
                     ::"r"(sb + C_KV), "l"(&mkv), "r"(bar_kv), "r"(0), "r"(s * 32), "r"(2 * h), "r"(sb + C_KV + 8192), "r"(64 + 2 * h) : "memory");
    };
    const bool attends = w == 7 || (w == 6 && r == 0);
    const int i8 = r == 0 ? (w - 4) * 8 : (r - 1) * 8;
    auto load_q = [&](int s) {
        const int l = fresh(lane);
        const bf16* p = g_kv + (size_t)(s * 32 + i8 + (l >> 4)) * PW + 2 * HD + h * 128 + (l & 15) * 8;
#pragma unroll
        for (int j = 0; j < 4; j++)
            asm volatile("cp.async.cg.shared.global [%0], [%1], 16;"
                         ::"r"(sb + C_RED + w * 2176 + ((l >> 4) + 2 * j) * 272 + (l & 15) * 16), "l"(p + (size_t)2 * j * PW) : "memory");
    };
    auto report = [&](int blk) {
        asm volatile("{\n.reg .pred p;\nelect.sync _|p, -1;\nfence.acq_rel.gpu;\n@p red.relaxed.gpu.global.add.u32 [%0], 1;\n}"
                     ::"l"(g_flag + 64 + blk) : "memory");
    };
    const float sl2e = 0.08838834764831845f * 1.4426950408889634f;
    const uint32_t idn = pin(g == 2 * t ? 0x00003f80u : g == 2 * t + 1 ? 0x3f800000u : 0u);
    const uint32_t lm = pin(sb + (lane & 7) * 272 + (lane >> 3) * 16);
    const uint32_t sa = pin(sb + C_SC + (w & 1) * (8 * 52 * 4) + (2 * t * 52 + (w < 4 ? 32 : (w & 2) * 8) + g) * 4);
    const uint32_t sr = pin(sb + C_SC + (g * 52 + 8 * t) * 4), sr2 = pin(sb + C_SC + (g * 52 + 32 + 2 * t) * 4);
    uint32_t kva;
    {
        const int pos = (w & 2) * 8 + (lane & 15), row = (pos & 24) + ((pos + (pos >> 2 & 6)) & 7);
        const int key = 4 * (lane & 6) + (((lane & 7) + 2 * (lane >> 4)) & 7);
        kva = pin(w >= 4 ? sb + C_KV + (w & 1) * 4096 + row * 128 + (((lane >> 4) ^ (row & 7)) << 4)
                         : sb + C_KV + 8192 + (w >> 1) * 4096 + key * 128 + ((((w & 1) * 4 + ((lane >> 3) & 1)) ^ (key & 7)) << 4));
    }
#define ATTEND(NK, s, mid) do {                                                                                       \
        const int l_ = fresh(lane);                                                                                      \
        attend<NK>(sb, lm, C_RED + w * 2176, C_QKV + ((s) & 1) * QKV_SZ, i8, l_,                                         \
                   g_o + (size_t)((s) * 32 + i8 + (l_ >> 4)) * HD + h * 128 + (l_ & 15) * 8, mid);                       \
    } while (0)
    auto chores = [&](int s) {
        if ((s & 3) == 0 && s) report((s >> 2) - 1);
        if ((s & 7) == 6 && s < NSEG - 2) wait_count_u(g_flag + (s >> 3) + 1, (s >> 3) + 1 < 2 * NTA ? 48 : 96);
    };
    uint32_t buf0[8][4], ring[RB1][4];
#define STAGE_W1() do {                                                            \
        _Pragma("unroll") for (int i = 0; i < 8; i++) lds128v(buf0[i], W1A(i));       \
        _Pragma("unroll") for (int i = 0; i < RB1; i++) lds128v(ring[i], W1A(8 + i)); \
    } while (0)
    auto stage_w1 = [&]() { STAGE_W1(); };
    stage_w1();
    uint32_t psel, msel0, msel1;
    {
        const int j = r > 0 ? 2 * h + r - 1 : 0, tl = min(tile0 + 8 * (lane >> 1), 63);
        uint32_t b;
        asm volatile("{\n.reg .pred p;\n.reg .u32 n;\nmov.u32 n, 0;\nAGAIN:\nld.relaxed.gpu.global.u32 %0, [%1];\nsetp.ne.u32 p, %0, 0;\n"
                     "vote.sync.all.pred p, p, -1;\n@p bra.uni DONE;\nadd.u32 n, n, 1;\nsetp.lt.u32 p, n, 0x100000;\n@p bra.uni AGAIN;\ntrap;\nDONE:\n}"
                     : "=&r"(b) : "l"(g_flag + 128 + tl) : "memory");
        psel = __ballot_sync(~0u, (g_home[lane == 6 ? j * 2 + ((w >> 1) & 1) : tl * 2 + (lane & 1)] ^ (lane == 6 ? side : b)) & 1);
        msel0 = __ballot_sync(~0u, (g_home[128 + lane * 4 + (w >> 1)] ^ side) & 1);
        msel1 = __ballot_sync(~0u, (g_home[256 + lane * 4 + (w >> 1)] ^ side) & 1);
        if (r > 0) {
            if (w < 4) asm volatile("prefetch.global.L2 [%0];" ::"l"(g_x + (128 + (1 + (w >> 1)) * 4 + (j >> 4)) * 1024 + (w & 1) * 512 + (j & 15) * 32 + lane) : "memory");
            if (w < 4) asm volatile("prefetch.global.L2 [%0];" ::"l"(g_x + j * 2048 + tid * 16) : "memory");
        }
    }
    uint2 bm[8];
#pragma unroll
    for (int ks = 0; ks < 8; ks++) {
        const uint32_t* p = (const uint32_t*)(mem0 + g * DM + (8 * w + ks) * 16) + t;
        bm[ks] = make_uint2(__ldg(p), __ldg(p + 4));
    }
    if (w == 0) TG(5);
#pragma unroll 1
    for (int s = 0;; s++) {
        TS(1);
        const uint32_t xq = C_QKV + (s & 1) * QKV_SZ;
        {
            float acc[8][4];
#pragma unroll
            for (int ks = 0; ks < 8; ks++) {
#pragma unroll
                for (int j = 0; j < 8; j++) {
                    const int i = smem_idx(ks, j) - 8;
                    if (ks == 0) {
                        acc[j][0] = acc[j][1] = acc[j][2] = acc[j][3] = 0.f;
                        mma16816(acc[j], buf0[j][0], buf0[j][1], buf0[j][2], buf0[j][3], bm[ks].x, bm[ks].y);
                    } else if (i >= 0) {
                        uint32_t(&a)[4] = ring[i % RB1];
                        mma16816(acc[j], a[0], a[1], a[2], a[3], bm[ks].x, bm[ks].y);
                        if (8 + i + RB1 < NS1) lds128v(a, W1A(8 + i + RB1));
                    } else {
                        const uint32_t(&a)[4] = wr[8 * ks + j];
                        mma16816(acc[j], a[0], a[1], a[2], a[3], bm[ks].x, bm[ks].y);
                    }
                }
            }
#pragma unroll
            for (int c = 0; c < 4; c++)
                stsm4t(lm + C_RED + w * 2176 + c * 64, pack2(acc[2 * c][0], acc[2 * c][1]), pack2(acc[2 * c][2], acc[2 * c][3]),
                       pack2(acc[2 * c + 1][0], acc[2 * c + 1][1]), pack2(acc[2 * c + 1][2], acc[2 * c + 1][3]));
        }
        {
            const uint32_t a = sb + C_RED + w * 272 + lane * 8;
            if (w == 3) mbar_wait_u(bar_kv, s & 1);
            TS(2);
            __syncthreads();
            TS(3);
            uint2 v[8];
#pragma unroll
            for (int i = 0; i < 8; i++) v[i] = lds64(a + i * 2176);
            float c[4];
            sum8(c, v, idn);
            const uint32_t p0 = pack2(c[0], c[1]), p1 = pack2(c[2], c[3]);
            const uint32_t dst = sb + xq + (r * 8 + w) * 272 + lane * 8;
#pragma unroll
            for (int i = 1; i < 3; i++) {
                const uint32_t peer = (h % (CLS / 3)) * 3 + (r + i >= 3 ? r + i - 3 : r + i);
                uint32_t rd, rb;
                asm("mapa.shared::cluster.u32 %0, %1, %2;" : "=r"(rd) : "r"(dst), "r"(peer));
                asm("mapa.shared::cluster.u32 %0, %1, %2;" : "=r"(rb) : "r"(bar_x), "r"(peer));
                asm volatile("st.async.weak.shared::cluster.mbarrier::complete_tx::bytes.v2.b32 [%0], {%1,%2}, [%3];"
                             ::"r"(rd), "r"(p0), "r"(p1), "r"(rb) : "memory");
            }
            sts64(dst, p0, p1);
            __syncwarp();
            asm volatile("{\n.reg .pred p;\nsetp.eq.u32 p, %1, 0;\n@p mbarrier.arrive.expect_tx.shared::cta.b64 _, [%0], 512;\n}"
                         ::"r"(bar_x), "r"(lane) : "memory");
        }
        TS(4);
        if (s == NSEG - 1) break;
        uint32_t wb[8][4], wc[8][4];
        const uint32_t po = (tile0 * 2 + (lane >> 4)) * 8192 + ((lane >> 3) & 1) * 2048 + h * 64 + (lane & 7) * 8;
        const uint32_t tag = s & 1;
        auto project = [&](const uint32_t(&wt)[8][4], const uint32_t(&ob)[4][4], int i) {
            float c0[4] = {0.f, 0.f, 0.f, 0.f}, c1[4] = {0.f, 0.f, 0.f, 0.f};
#pragma unroll
            for (int ks = 0; ks < 8; ks++)
                mma16816((ks & 1) ? c1 : c0, wt[ks][0], wt[ks][1], wt[ks][2], wt[ks][3], ob[ks >> 1][(ks & 1) * 2], ob[ks >> 1][(ks & 1) * 2 + 1]);
            uint32_t p0 = pack2(c0[0] + c1[0], c0[1] + c1[1]), p1 = pack2(c0[2] + c1[2], c0[3] + c1[3]);
            asm volatile("movmatrix.sync.aligned.m8n8.trans.b16 %0, %0;\nmovmatrix.sync.aligned.m8n8.trans.b16 %1, %1;" : "+r"(p0), "+r"(p1));
            st_rlx64((uint2*)((char*)g_x + po + i * 131072 + ((psel >> (2 * i + (lane >> 4))) & 1) * 4096), (p0 & ~1u) | tag, p1);
        };
        if (w >= 4) {
            uint32_t ka[4][4];
#pragma unroll
            for (int ks = 0; ks < 4; ks++) ldsm4(ka[ks], kva ^ (ks << 5));
            const uint32_t qa = lm + xq + (w & 1) * 128;
            TS(5);
            mbar_wait_u(bar_x, s & 1);
            TS(6);
            {
                uint32_t qb[2][4];
                ldsm4(qb[0], qa);
                ldsm4(qb[1], qa + 64);
                float c0[4] = {0.f, 0.f, 0.f, 0.f}, c1[4] = {0.f, 0.f, 0.f, 0.f};
                mma16816(c0, ka[0][0], ka[0][1], ka[0][2], ka[0][3], qb[0][0], qb[0][1]);
                mma16816(c1, ka[1][0], ka[1][1], ka[1][2], ka[1][3], qb[0][2], qb[0][3]);
                mma16816(c0, ka[2][0], ka[2][1], ka[2][2], ka[2][3], qb[1][0], qb[1][1]);
                mma16816(c1, ka[3][0], ka[3][1], ka[3][2], ka[3][3], qb[1][2], qb[1][3]);
                sts32f(sa, c0[0] + c1[0]);
                sts32f(sa + 208, c0[1] + c1[1]);
                sts32f(sa + 32, c0[2] + c1[2]);
                sts32f(sa + 240, c0[3] + c1[3]);
            }
            __syncthreads();
            TS(7);
            uint32_t wd;
            if (attends) { load_q(s); wd = delayed<DLYQ>(wa, self); } else wd = delayed<DLYW>(wa, self);
#pragma unroll
            for (int i = 0; i < 8; i++) lds128(wb[i], wd + C_W2 + i * 4096);
#pragma unroll
            for (int i = 0; i < PFC; i++) lds128(wc[i], wd + C_W2 + 32768 - 1024 + i * 3072);
            TS(8);
            __syncthreads();
            TS(9);
            uint32_t ob[4][4];
#pragma unroll
            for (int i = 0; i < 4; i++) ldsm4(ob[i], lm + C_OB + i * 64);
#pragma unroll
            for (int i = PFC; i < 8; i++) lds128(wc[i], W2A(8 + i));
            project(wb, ob, 1);
            project(wo0, ob, 0);
            project(wc, ob, 2);
        } else {
            uint32_t va[4][4];
#pragma unroll
            for (int i = 0; i < 4; i++) ldsm4t(va[i], kva ^ (((i >> 1) << 5) | ((i & 1) * 0x240)));
#pragma unroll
            for (int i = 0; i < 8; i++) lds128(wb[i], W2A(i));
            const uint32_t qa = lm + xq + (w & 1) * 128, oa = lm + w * 64;
            TS(5);
            mbar_wait_u(bar_x, s & 1);
            TS(6);
            if (w < 2) {
                uint32_t qb[2][4], km[2][4];
                ldsm4(qb[0], qa);
                ldsm4(km[0], qa + 8 * 272);
                ldsm4(qb[1], qa + 64);
                ldsm4(km[1], qa + 8 * 272 + 64);
                float c0[4] = {0.f, 0.f, 0.f, 0.f}, c1[4] = {0.f, 0.f, 0.f, 0.f};
                mma16816(c0, km[0][0], km[0][1], km[0][2], km[0][3], qb[0][0], qb[0][2]);
                mma16816(c1, km[0][0], km[0][1], km[0][2], km[0][3], qb[0][1], qb[0][3]);
                mma16816(c0, km[1][0], km[1][1], km[1][2], km[1][3], qb[1][0], qb[1][2]);
                mma16816(c1, km[1][0], km[1][1], km[1][2], km[1][3], qb[1][1], qb[1][3]);
                sts32f(sa, c0[0] + c1[2]);
                sts32f(sa + 208, c0[1] + c1[3]);
            }
            __syncthreads();
            TS(7);
            {
                float4 x0 = lds128f(sr), y0 = lds128f(sr + 1664), x1 = lds128f(sr + 16), y1 = lds128f(sr + 1680);
                float2 x2 = lds64f(sr2), y2 = lds64f(sr2 + 1664);
                float p[10] = {x0.x + y0.x, x0.y + y0.y, x0.z + y0.z, x0.w + y0.w, x1.x + y1.x,
                               x1.y + y1.y, x1.z + y1.z, x1.w + y1.w, x2.x + y2.x, x2.y + y2.y};
                float m = fmaxf(fmaxf(fmaxf(p[0], p[1]), fmaxf(p[2], p[3])), fmaxf(fmaxf(fmaxf(p[4], p[5]), fmaxf(p[6], p[7])), fmaxf(p[8], p[9])));
                const float m1 = __shfl_xor_sync(~0u, m, 1), m2 = __shfl_xor_sync(~0u, m, 2), m3 = __shfl_xor_sync(~0u, m, 3);
                uint32_t vm[4];
                ldsm4t(vm, oa + xq + 16 * 272);
                m = fmaxf(fmaxf(m, m1), fmaxf(m2, m3));
                const float ms = m * sl2e;
#pragma unroll
                for (int i = 0; i < 10; i++) p[i] = ex2(fmaf(p[i], sl2e, -ms));
                const uint32_t b0 = pack2(p[0], p[1]), b1 = pack2(p[2], p[3]), b2 = pack2(p[4], p[5]), b3 = pack2(p[6], p[7]), b4 = pack2(p[8], p[9]);
                const uint32_t one = 0x3f803f80u;
                float o0[4] = {0.f, 0.f, 0.f, 0.f}, o1[4] = {0.f, 0.f, 0.f, 0.f}, sm[4] = {0.f, 0.f, 0.f, 0.f};
                mma16816(sm, one, one, one, one, b0, b1);
                mma16816(o0, va[0][0], va[0][1], va[0][2], va[0][3], b0, b1);
                mma16816(o1, va[2][0], va[2][1], va[2][2], va[2][3], b0, b1);
                mma16816(sm, one, one, one, one, b2, b3);
                mma16816(o0, va[1][0], va[1][1], va[1][2], va[1][3], b2, b3);
                mma16816(o1, va[3][0], va[3][1], va[3][2], va[3][3], b2, b3);
                mma1688(sm, one, one, b4);
                mma1688(o0, vm[0], vm[1], b4);
                mma1688(o1, vm[2], vm[3], b4);
                float i0, i1;
                asm("rcp.approx.ftz.f32 %0, %1;" : "=f"(i0) : "f"(sm[0]));
                asm("rcp.approx.ftz.f32 %0, %1;" : "=f"(i1) : "f"(sm[1]));
                stsm4t(oa + C_OB, pack2(o0[0] * i0, o0[1] * i1), pack2(o0[2] * i0, o0[3] * i1),
                       pack2(o1[0] * i0, o1[1] * i1), pack2(o1[2] * i0, o1[3] * i1));
            }
            TS(8);
            __syncthreads();
            TS(9);
            uint32_t ob[4][4];
#pragma unroll
            for (int i = 0; i < 4; i++) ldsm4(ob[i], lm + C_OB + i * 64);
            if (three) {
#pragma unroll
                for (int i = 0; i < 8; i++) lds128(wc[i], W2A(8 + i));
                project(wb, ob, 1);
                project(wo0, ob, 0);
                project(wc, ob, 2);
            } else {
                project(wb, ob, 1);
                project(wo0, ob, 0);
            }
        }
        TS(10);
        __syncthreads();
        uint32_t eo = (128 + (s + 1) * 4 + (w >> 1)) * 8192 + (((s < 31 ? msel0 : msel1) >> ((s + 1) & 31)) & 1) * 4096 + (w & 1) * 2048 + lane * 8;
        uint64_t d[8];
        if (r == 0) {
            if (w >= 6) {
                auto mid = [&]() {
                    bar_sync(2, 64);
                    TS(11);
                    mbar_wait_u(bar_go, s & 1);
                    eo = delayed<DLY0A>(eo, self);
                    TS(12);
                    fetch_state(d, (const char*)g_x + eo);
                };
                ATTEND(2, s, mid);
                stage_w1();
            } else {
                TS(11); TS(12);
                if (w < 3 && s + PFD < NSEG) {
                    const bf16* p = g_kv + (size_t)((s + PFD) * 32 + fresh(lane)) * PW + w * HD + h * 128;
                    asm volatile("prefetch.global.L2 [%0];\nprefetch.global.L2 [%0 + 128];" ::"l"(p) : "memory");
                }
                const uint32_t wa_ = wa;
                { const uint32_t wa = delayed<DLYS>(wa_, self); STAGE_W1(); }
                if (w == 5) {
                    chores(s);
                    if (h == 0) asm volatile("st.relaxed.gpu.global.u32 [%0], %1;" ::"l"(g_flag + 98), "r"(s + 1) : "memory");
                }
                mbar_wait_u(bar_go, s & 1);
                eo = delayed<DLY0>(eo, self);
                fetch_state(d, (const char*)g_x + eo);
            }
        } else {
            const int j = 2 * h + r - 1;
            if (w < 4) {
                const int l = fresh(lane), g = l >> 2, t = l & 3;
                const char* src = (const char*)g_x + delayed<DLY3>((j * 2 + (w >> 1)) * 8192 + (psel & 64) * 64 + (w & 1) * 2048 + t * 64 + g * 8, self);
                const char* dst = (const char*)g_x + pin((128 + (s + 1) * 4 + (j >> 4)) * 8192 + (j & 15) * 256 + w * 64 + (t & 1) * 4096 + g * 8);
                const uint64_t v = poll_sum(src, tag, (lane & 4) ? 0x3f800000u : 0x00003f80u);
                TS(11);
                asm volatile("st.relaxed.gpu.global.b64 [%0], %1;" ::"l"(dst), "l"(v) : "memory");
                asm volatile("bar.arrive 1, 256;" ::: "memory");
                TS(12);
                stage_w1();
                eo = delayed<DLY1>(eo, self);
                fetch_state(d, (const char*)g_x + eo);
            } else if (w == 7) {
                auto mid = [&]() {
                    TS(11);
                    bar_sync(1, 256);
                    TS(12);
                    eo = delayed<DLY1B>(eo, self);
                    fetch_state(d, (const char*)g_x + eo);
                };
                ATTEND(1, s, mid);
                stage_w1();
            } else {
                if (w >= 5 && s + 3 < NSEG)
                    asm volatile("prefetch.global.L2 [%0];" ::"l"(g_x + (128 + (s + 3) * 4 + (j >> 4)) * 1024 + (w & 1) * 512 + (j & 15) * 32 + lane) : "memory");
                stage_w1();
                if (w == 5) chores(s);
                TS(11);
                bar_sync(1, 256);
                TS(12);
                if (w == 4 && r == 1)
                    asm volatile("{\n.reg .pred p;\n.reg .u32 a;\nelect.sync _|p, -1;\nmapa.shared::cluster.u32 a, %0, %1;\n"
                                 "@p mbarrier.arrive.relaxed.cluster.shared::cluster.b64 _, [a];\n}" ::"r"(bar_go), "r"((h % (CLS / 3)) * 3) : "memory");
                eo = delayed<DLY1A>(eo, self);
                fetch_state(d, (const char*)g_x + eo);
            }
        }
        { const int s_ = s; { const int s = s_ + 1; TS(0); } }
        if (w == 7) load_kv(s + 1);
        settle_state(d, (const char*)g_x + eo);
#pragma unroll
        for (int i = 0; i < 8; i++) { bm[i].x = (uint32_t)d[i]; bm[i].y = (uint32_t)(d[i] >> 32); }
    }
    mbar_wait_u(bar_x, (NSEG - 1) & 1);
    if (attends) {
        auto nothing = []() {};
        load_q(NSEG - 1);
        if (r == 0) ATTEND(2, NSEG - 1, nothing); else ATTEND(1, NSEG - 1, nothing);
    }
    __syncthreads();
    if (w == 5) report(15);
    asm volatile("barrier.cluster.arrive.relaxed.aligned;\nbarrier.cluster.wait.aligned;" ::: "memory");
}

constexpr int S4_US = 4368;
constexpr int S4_RS = 8848;
constexpr int S4_KS = 1296;
constexpr int S4_U = 0, S4_R = 16 * S4_US, S4_K = S4_R + 16 * S4_RS;
constexpr int S4_SMEM = S4_K + 16 * S4_KS;
constexpr int S4_SIG = 3104, S4_PK = 2 * S4_SIG;

struct cf { float r, i; };
__device__ __forceinline__ cf cmul(cf a, cf b) { return {fmaf(a.r, b.r, -a.i * b.i), fmaf(a.r, b.i, a.i * b.r)}; }
__device__ __forceinline__ cf cmulc(cf a, cf b) { return {fmaf(a.r, b.r, a.i * b.i), fmaf(a.i, b.r, -a.r * b.i)}; }
__device__ __forceinline__ cf csq(cf a) { const float t = a.r * a.i; return {fmaf(a.r, a.r, -a.i * a.i), t + t}; }
__device__ __forceinline__ cf cexp(float l2, float turns) {
    const float mag = ex2(l2), fr = (turns - rintf(turns)) * 6.283185307179586f;
    return {mag * __cosf(fr), mag * __sinf(fr)};
}
__device__ __forceinline__ void sts32(uint32_t a, uint32_t v) { asm volatile("st.shared.u32 [%0], %1;" ::"r"(a), "r"(v) : "memory"); }
__device__ __forceinline__ uint32_t lds16(uint32_t a) {
    uint32_t v;
    asm volatile("ld.shared.u16 %0, [%1];" : "=r"(v) : "r"(a) : "memory");
    return v;
}

template <int M0, int NQ>
__device__ __forceinline__ void s4_class(float (&acc)[16][4], uint32_t sig, uint32_t taps, int x0) {
    constexpr int D0 = M0 / 8, D1 = M0 == 32 ? 9 : 15;
    uint32_t R[D1 - D0 + 2];
#pragma unroll
    for (int D = D0 - 1; D <= D1; D++) {
        if (D < D0 || 8 * D - 7 >= 2 * M0) { R[D - D0 + 1] = 0; continue; }
        const int m = 8 * D + x0;
        uint32_t lo = lds16(taps + m * (2 * NQ)), hi = lds16(taps + (m - 1) * (2 * NQ));
        if (D == D0) { lo = m >= M0 ? lo : 0; hi = m > M0 ? hi : 0; }
        if (D == 2 * D0) { lo = m < 2 * M0 ? lo : 0; hi = m <= 2 * M0 ? hi : 0; }
        R[D - D0 + 1] = lo | (hi << 16);
    }
#pragma unroll
    for (int J = 0; 2 * J + D0 < 16; J++) {
        uint32_t a[4];
        ldsm4t(a, sig + J * 512);
#pragma unroll
        for (int D = D0; D <= D1; D++)
            if (2 * J + D < 16) mma16816(acc[2 * J + D], a[0], a[1], a[2], a[3], R[D - D0 + 1], R[D - D0]);
    }
}

__global__ void __launch_bounds__(512, 1)
k_s4(const bf16* __restrict__ u, const bf16* __restrict__ Are, const bf16* __restrict__ Aim, const bf16* __restrict__ Bre,
     const bf16* __restrict__ Bim, const bf16* __restrict__ Cre, const bf16* __restrict__ Cim, const bf16* __restrict__ logdt,
     const bf16* __restrict__ Dsk, bf16* __restrict__ out) {
    extern __shared__ __align__(16) uint8_t smem_s4[];
    const uint32_t sb = smem_u32(smem_s4);
    asm volatile("griddepcontrol.launch_dependents;");
    const int tid = threadIdx.x, w = __shfl_sync(~0u, tid >> 5, 0), lane = tid & 31, g = lane >> 2, t = lane & 3;
    const int dw = (w & 1) + ((w >> 1) & 3) * 4 + (w >> 3) * 2;
    uint2 ar, ai, br, bi, cr, ci;
    bf16 ldt;
    auto load_params = [&](int item) {
        const int d = item * 16 + dw, o = d * 128 + lane * 4;
        ar = __ldg((const uint2*)(Are + o)); ai = __ldg((const uint2*)(Aim + o)); br = __ldg((const uint2*)(Bre + o));
        bi = __ldg((const uint2*)(Bim + o)); cr = __ldg((const uint2*)(Cre + o)); ci = __ldg((const uint2*)(Cim + o));
        ldt = logdt[d];
    };
    load_params(blockIdx.x);
#pragma unroll 1
    for (int item = blockIdx.x; item < 64; item += gridDim.x) {
#define TLS(slot)
    if (tid == 0) TLS(0);
    const int d0 = item * 16;
    const uint32_t tr_off = (lane & 15), tr_l = (lane >> 4) * 16;
    const uint32_t ur = sb + S4_U + w * S4_US, rs = sb + S4_R + w * S4_RS, kd = sb + S4_K + w * S4_KS;
    if (lane < 16) sts128(ur + lane * 16, 0, 0, 0, 0);
    {
        const float dt = bf_round(expf(__bfloat162float(ldt)));
        const bf16* src = u + (size_t)(w * 128 + g) * DM + d0 + 4 * t;
        float T[5][4];
#pragma unroll
        for (int i = 0; i < 5; i++) T[i][0] = T[i][1] = T[i][2] = T[i][3] = 0.f;
        float klast = 0.f;
        const uint32_t wr_ = rs + lane * 272, rd_ = rs + t * 544 + g * 16;
#pragma unroll 1
        for (int c = 0; c < 4; c++) {
            uint2 v[4];
#pragma unroll
            for (int i = 0; i < 4; i++) v[i] = __ldg((const uint2*)(src + (size_t)(c * 32 + i * 8) * DM));
            auto pick = [&](const uint2& x) { const uint32_t y = c < 2 ? x.x : x.y; return (c & 1) ? bf_hi(y) : bf_lo(y); };
            auto pk2 = [](cf x) { return pack2(x.r, x.i); };
            const float l2 = dt * pick(ar) * 1.4426950408889634f, tu = dt * pick(ai) * 0.15915494309189535f;
            const cf z1 = cexp(l2, tu), z2 = csq(z1), z4 = csq(z2), z8 = csq(z4);
            const cf z64 = cexp(l2 * 64.f, tu * 64.f), z128 = csq(z64), z256 = csq(z128), z512 = csq(z256);
            cf a0 = {1.f, 0.f}, a1 = z64;
            cf b0 = cmul({pick(cr), pick(ci)}, {dt * pick(br), dt * pick(bi)});
            b0.i = -b0.i;
            cf b1 = cmulc(b0, z128), b2 = cmulc(b0, z256), y3 = cmulc(b0, z512), b4 = cmulc(y3, z512), b3 = y3;
            const cf y2 = cmulc(b2, z128);
#pragma unroll
            for (int i = 0; i < 8; i++) {
                sts128(wr_ + i * 16, pk2(a0), pk2(a1), pk2(b0), pk2(b1));
                sts128(wr_ + i * 16 + 128, pk2(b2), pk2(b3), pk2(b4), 0);
                b4 = cmulc(b4, z128);
                if (i < 7) {
                    a0 = i == 0 ? z8 : cmul(a0, z8); a1 = cmul(a1, z8);
                    b0 = cmulc(b0, z1); b1 = cmulc(b1, z1);
                    b2 = i == 3 ? y2 : cmulc(b2, z2);
                    if (i & 1) { y3 = cmulc(y3, z128); b3 = y3; } else b3 = cmulc(y3, z4);
                }
            }
            klast += b4.r;
            __syncwarp();
#pragma unroll
            for (int k = 0; k < 8; k++) {
                uint32_t x[4], y[4];
                lds128(x, rd_ + (8 * (k >> 1) + (k & 1)) * 272);
                lds128(y, rd_ + (8 * (k >> 1) + (k & 1)) * 272 + 128);
                mma1688(T[0], x[0], x[1], x[2]);
                mma1688(T[1], x[0], x[1], x[3]);
                mma1688(T[2], x[0], x[1], y[0]);
                mma1688(T[3], x[0], x[1], y[1]);
                mma1688(T[4], x[0], x[1], y[2]);
            }
#pragma unroll
            for (int i = 0; i < 2; i++)
                stsm4t(sb + S4_U + tr_off * S4_US + 256 + (w * 128 + c * 32 + i * 16) * 2 + tr_l, v[2 * i].x, v[2 * i].y, v[2 * i + 1].x, v[2 * i + 1].y);
            __syncwarp();
        }
#pragma unroll
        for (int o2 = 16; o2; o2 >>= 1) klast += __shfl_xor_sync(~0u, klast, o2);
#pragma unroll
        for (int hh = 0; hh < 2; hh++) {
            const int i = g + 8 * hh;
            sts32(kd + (8 * i + 2 * t) * 2, pack2(T[0][2 * hh], T[0][2 * hh + 1]));
            sts32(kd + (128 + 8 * i + 2 * t) * 2, pack2(T[1][2 * hh], T[1][2 * hh + 1]));
            sts32(kd + (256 + 4 * i + 2 * (t & 1) + 64 * (t >> 1)) * 2, pack2(T[2][2 * hh], T[2][2 * hh + 1]));
            sts32(kd + (384 + 2 * i + 32 * t) * 2, pack2(T[3][2 * hh], T[3][2 * hh + 1]));
        }
        asm volatile("stmatrix.sync.aligned.m8n8.x2.trans.shared.b16 [%0], {%1,%2};"
                     ::"r"(kd + 1024 + (lane & 7) * 32 + ((lane >> 3) & 1) * 16), "r"(pack2(T[4][0], T[4][1])), "r"(pack2(T[4][2], T[4][3])) : "memory");
        if (lane == 0) sts32(kd + 1280, pack2(klast, 0.f));
    }
    __syncwarp();
    const uint32_t pk = rs + S4_PK + 64;
    {
#pragma unroll
        for (int i = 0; i < 2; i++) {
            const int x = i * 128 + lane * 4;
            const uint2 c = lds64(kd + x * 2);
            uint32_t p = lds16(kd + x * 2 - 2);
            if (x == 0) p = 0;
            sts128(pk + x * 4, __byte_perm(c.x, p, 0x5410), __byte_perm(c.x, 0, 0x1032), __byte_perm(c.y, c.x, 0x7610), __byte_perm(c.y, 0, 0x1032));
        }
#pragma unroll
        for (int i = 2; i < 4; i++) {
            const int x = i * 128 + lane * 4;
            const uint32_t ab = lds32(kd + 256 + x), c = lds16(kd + 256 + x + 4);
            const uint32_t p = x == 256 ? lds16(kd + 510) : ab;
            sts128(pk + x * 4, __byte_perm(ab, p, 0x5410), __byte_perm(ab, 0, 0x1010), __byte_perm(ab, 0, 0x1032), __byte_perm(c, ab, 0x7610));
        }
        const uint32_t v = lds16(kd + 768), v2 = lds16(kd + 1024);
        if (lane < 24) {
            uint32_t x0 = 0, x1 = 0, x2 = 0, x3 = 0;
            if (lane == 0) { x0 = x1 = x2 = v | (v << 16); x3 = v << 16; }
            if (lane == 12) x3 = v2;
            if (lane == 13) { x0 = v2 | (v2 << 16); x1 = v2 << 16; }
            sts128(lane < 20 ? pk + 2048 + lane * 16 : pk - 64 + (lane - 20) * 16, x0, x1, x2, x3);
        }
        if (lane < 4) sts128(rs + (lane >> 1) * S4_SIG + (lane & 1) * 16, 0, 0, 0, 0);
    }
    __syncthreads();
    float acc[16][4];
#pragma unroll
    for (int i = 0; i < 16; i++) acc[i][0] = acc[i][1] = acc[i][2] = acc[i][3] = 0.f;
    const uint32_t lf = (lane & 7) * 32 + ((lane >> 3) & 1) * 16 + (lane >> 4) * 256;
#pragma unroll 1
    for (int ph = 0; ph < 2; ph++) {
    if (((w >> 2) ^ ph) & 1) {
#pragma unroll
    for (int rg = 3; rg >= 2; rg--) {
#pragma unroll 1
        for (int it = 0; it < (rg == 3 ? 4 : 6); it++) {
            const int n = it * 32 + lane;
            uint32_t x[2][4];
            lds128(x[0], ur + 256 + n * 16 - 16);
            lds128(x[1], ur + 256 + n * 16);
            float e[16], p[15], s[11];
#pragma unroll
            for (int i = 0; i < 8; i++) { e[2 * i] = bf_lo(x[i >> 2][i & 3]); e[2 * i + 1] = bf_hi(x[i >> 2][i & 3]); }
#pragma unroll
            for (int i = 0; i < 15; i++) p[i] = e[i] + e[i + 1];
#pragma unroll
            for (int i = 0; i < 11; i++) s[i] = p[i + 3] + e[i + 5];
            const uint32_t o = rs + 16 + n * 16;
            if (rg == 2) sts128(o, pack2(s[0], s[1]), pack2(s[2], s[3]), pack2(s[4], s[5]), pack2(s[6], s[7]));
#pragma unroll
            for (int i = 0; i < 10; i++) s[i] = p[i + 2] + s[i + 1];
            if (rg == 2) {
                sts64(o + S4_SIG + 8, pack2(s[0], s[1]), pack2(s[2], s[3]));
                sts64(o + S4_SIG + 16, pack2(s[4], s[5]), pack2(s[6], s[7]));
            } else {
#pragma unroll
                for (int i = 0; i < 9; i++) s[i] = p[i + 1] + s[i + 1];
                sts64(o + 8, pack2(s[0], s[1]), pack2(s[2], s[3]));
                sts64(o + 16, pack2(s[4], s[5]), pack2(s[6], s[7]));
#pragma unroll
                for (int i = 0; i < 8; i++) s[i] = p[i] + s[i + 1];
                sts64(o + S4_SIG + 8, pack2(s[0], s[1]), pack2(s[2], s[3]));
                sts64(o + S4_SIG + 16, pack2(s[4], s[5]), pack2(s[6], s[7]));
            }
        }
        __syncwarp();
        if (rg == 3) {
#pragma unroll 1
            for (int q = 1; q <= 2; q++) s4_class<64, 2>(acc, rs + lf + (q == 1 ? 16 : S4_SIG), kd + (384 + q) * 2, g - 2 * t);
        } else {
#pragma unroll 1
            for (int q = 1; q <= 4; q++) s4_class<32, 4>(acc, rs + lf + ((q & 1) ? 0 : S4_SIG) + (q < 3 ? 16 : 0), kd + (256 + q) * 2, g - 2 * t);
        }
        __syncwarp();
    }
    } else
    {
        const uint32_t ub = ur + 256 + lf, kb = pk + (g - 2 * t) * 4;
#pragma unroll 1
        for (int j0 = 0; j0 < 8; j0++) {
            uint32_t B[8][4];
#pragma unroll
            for (int i = 0; i < 8; i++) ldsm4(B[i], ub + i * 512 - j0 * 32);
            auto block = [&](int J, uint32_t a) {
                const uint32_t r0 = lds32(a), rp = lds32(a + 32), rm = lds32(a - 32);
                uint32_t r3;
                asm volatile("ld.volatile.shared.u32 %0, [%1];" : "=r"(r3) : "r"(a) : "memory");
#pragma unroll
                for (int I = J; I < 16; I++)
                    mma16816(acc[I], r0, rp, rm, r3, B[(I - J) >> 1][((I - J) & 1) * 2], B[(I - J) >> 1][((I - J) & 1) * 2 + 1]);
            };
#pragma unroll
            for (int J = 0; J < 4; J++) block(J, kb + j0 * 64 + J * 512);
            if (j0 < 2) { block(4, kb + j0 * 64 + 2048); block(8, kb + j0 * 64 + (544 + 16) * 4); }
        }
    }
    }
    {
        __syncwarp();
#pragma unroll
        for (int i = 0; i < 8; i++)
            stsm4t(rs + lf + i * 512, pack2(acc[2 * i][0], acc[2 * i][1]), pack2(acc[2 * i][2], acc[2 * i][3]),
                   pack2(acc[2 * i + 1][0], acc[2 * i + 1][1]), pack2(acc[2 * i + 1][2], acc[2 * i + 1][3]));
    }
    __syncthreads();
    {
        const uint2 dv = __ldg((const uint2*)(Dsk + d0 + 4 * t));
        load_params(min(item + (int)gridDim.x, 63));
        bf16* dst = out + (size_t)(w * 128 + g) * 2048 + 1024 + d0 + 4 * t;
        uint32_t o[8][4];
#pragma unroll
        for (int i = 0; i < 8; i++) {
            uint32_t y[4], x[4];
            ldsm4t(y, sb + S4_R + tr_off * S4_RS + (w * 128 + i * 16) * 2 + tr_l);
            ldsm4t(x, sb + S4_U + tr_off * S4_US + 256 + (w * 128 + i * 16) * 2 + tr_l);
#pragma unroll
            for (int j = 0; j < 4; j++)
                asm("{\n.reg .b32 s;\nmul.rn.bf16x2 s, %2, %3;\nadd.rn.bf16x2 %0, %1, s;\n}" : "=r"(o[i][j]) : "r"(y[j]), "r"(x[j]), "r"((j & 1) ? dv.y : dv.x));
        }
        __syncthreads();
#pragma unroll
        for (int i = 0; i < 8; i++) {
            *reinterpret_cast<uint2*>(dst + (size_t)(i * 16) * 2048) = make_uint2(o[i][0], o[i][1]);
            *reinterpret_cast<uint2*>(dst + (size_t)(i * 16 + 8) * 2048) = make_uint2(o[i][2], o[i][3]);
        }
    }
    if (tid == 0) TLS(1);
    }
}

enum { IT_W256 = 1, IT_W128 = 2, IT_W64 = 3, IT_END = 7 };
struct BgParams { CUtensorMap mo, mo2, mwo4, mwo2, mwo1; };
#define NBT 10
#define P256 56
#define P128 62
struct Sched { uint32_t w0, w1; };
__device__ __forceinline__ int next_item(Sched& z) {
    if (z.w0 >= z.w1) {
        uint32_t prog;
        asm volatile("ld.relaxed.gpu.global.u32 %0, [%1];" : "=r"(prog) : "l"(g_flag + 98) : "memory");
        const uint32_t k = prog <= P256 ? 4 : prog <= P128 ? 2 : 1;
        z.w0 = 4 * gridDim.x + atomicAdd(g_flag + 97, k);
        z.w1 = min(z.w0 + k, NBT * 16u);
        if (z.w0 >= z.w1) return IT_END;
    }
    const uint32_t i = z.w0, k = z.w1 - i >= 4 && !(i & 3) ? 4 : z.w1 - i >= 2 && !(i & 1) ? 2 : 1;
    z.w0 += k;
    return (k == 4 ? IT_W256 : k == 2 ? IT_W128 : IT_W64) | (i >> 4) << 3 | ((i & 15) / k) << 7;
}
constexpr int B_OST = NSTAGE * STAGE_BYTES + 1024;
constexpr int BG_SMEM = B_OST + 32768;

template <int BM, int BN, int KPS, typename ACC>
__device__ __forceinline__ void gemm_mainloop(ACC& acc, const GemmSmem& g, int cw, int rounds, uint32_t& round) {
#pragma unroll
    for (int i = 0; i < BN / 2; i++) acc[i] = 0.f;
#pragma unroll 1
    for (int k0 = 0; k0 < rounds; k0++, round++) {
#pragma unroll
        for (int s = 0; s < 4; s++) {
            mbar_wait_u(g.full + 8 * s, round & 1);
            gemm_stage<BM, BN, KPS>(acc, g.st + s * STAGE_BYTES, cw, false);
            wg_wait<1>();
            if (s > 0 || k0 > 0) mbar_arrive_one(g.empty + 8 * ((s + 3) & 3), threadIdx.x & 31);
        }
    }
    wg_wait<0>();
    mbar_arrive_one(g.empty + 8 * 3, threadIdx.x & 31);
}

template <int BN>
__device__ __forceinline__ void store_tile(const float (&acc)[BN / 2], bf16* dst, int t) {
#pragma unroll
    for (int G = 0; G < BN / 32; G++)
#pragma unroll
        for (int rr = 0; rr < 2; rr++) {
            uint32_t r0 = pack2(acc[16 * G + 2 * rr], acc[16 * G + 2 * rr + 1]), r1 = pack2(acc[16 * G + 4 + 2 * rr], acc[16 * G + 5 + 2 * rr]);
            uint32_t r2 = pack2(acc[16 * G + 8 + 2 * rr], acc[16 * G + 9 + 2 * rr]), r3 = pack2(acc[16 * G + 12 + 2 * rr], acc[16 * G + 13 + 2 * rr]);
            quad_transpose(r0, r1, r2, r3, t);
            *reinterpret_cast<uint4*>(dst + (size_t)rr * 8 * 2048 + G * 32) = make_uint4(r0, r1, r2, r3);
        }
}

template <int BN, int KPS>
__device__ __forceinline__ void wo_item(const GemmSmem& g, int cw, uint32_t& round, bf16* dst, int t) {
    float acc[BN / 2];
    gemm_mainloop<128, BN, KPS>(acc, g, cw, 16 / KPS, round);
    store_tile<BN>(acc, dst, t);
}

__global__ void __launch_bounds__(384, 1) k_bg(const __grid_constant__ BgParams P, bf16* __restrict__ out) {
    extern __shared__ __align__(1024) uint8_t smem_gemm[];
    asm volatile("griddepcontrol.launch_dependents;");
    const uint32_t bar_item = smem_u32(smem_gemm) + NSTAGE * STAGE_BYTES + 128, slot = bar_item + 16;
    if (threadIdx.x == 0) { mbar_init(bar_item, 1); mbar_init(bar_item + 8, 1); }
    if (threadIdx.x == 32) asm volatile("prefetch.tensormap [%0];\nprefetch.tensormap [%1];" ::"l"(&P.mo), "l"(&P.mwo4) : "memory");
    GemmSmem g = gemm_setup(smem_gemm, 8);
    const int wg = __shfl_sync(~0u, threadIdx.x >> 7, 0);
    if (wg == 0) {
        asm volatile("setmaxnreg.dec.sync.aligned.u32 40;");
        if (threadIdx.x == 0) {
            uint32_t it = 0;
            Sched z = {4 * blockIdx.x, 4 * blockIdx.x + 4};
            for (int n = 0;; n++) {
                const int code = next_item(z);
                sts32(slot + (n & 1) * 4, code);
                mbar_arrive(bar_item + (n & 1) * 8);
                const int type = code & 7, blk = (code >> 3) & 15, idx = code >> 7;
                if (type == IT_END) break;
                wait_flag(g_flag + 64 + blk, 96);
                asm volatile("fence.proxy.async.global;" ::: "memory");
                for (int k = 0; k < (type == IT_W64 ? 32 : 64); k++, it++) {
                    const int s = it & 3;
                    const uint32_t st = g.st + s * STAGE_BYTES, fb = g.full + 8 * s;
                    mbar_wait(g.empty + 8 * s, ((it >> 2) & 1) ^ 1);
                    mbar_expect_tx(fb, type == IT_W128 ? 32768 : 49152);
                    if (type == IT_W64) {
                        tma3d(st, &P.mo2, 0, blk * 128, k * 2, fb);
                        tma3d(st + 32768, &P.mwo1, 0, k * 128, idx, fb);
                    } else {
                        tma2d(st, &P.mo, k * 64, blk * 128, fb);
                        tma3d(st + 16384, type == IT_W256 ? &P.mwo4 : &P.mwo2, 0, k * 64, idx * (type == IT_W256 ? 4 : 2), fb);
                    }
                }
            }
        }
    } else {
        asm volatile("setmaxnreg.inc.sync.aligned.u32 232;");
        const int cw = wg - 1, lane = threadIdx.x & 31;
        uint32_t round = 0;
#pragma unroll 1
        for (int n = 0;; n++) {
            mbar_wait_u(bar_item + (n & 1) * 8, (n >> 1) & 1);
            const int code = __shfl_sync(~0u, lds32(slot + (n & 1) * 4), 0);
            const int type = code & 7, blk = (code >> 3) & 15, idx = (code >> 7) & 31;
#define TLB(slot_)
            if (type == IT_END) break;
            TLB(0);
            bf16* dst = out + (size_t)(blk * 128 + cw * 64 + ((threadIdx.x >> 5) & 3) * 16 + (lane >> 2)) * 2048 + (lane & 3) * 8;
            if (type == IT_W256) wo_item<256, 1>(g, cw, round, dst + idx * 256, lane & 3);
            else if (type == IT_W128) wo_item<128, 1>(g, cw, round, dst + idx * 128, lane & 3);
            else wo_item<64, 2>(g, cw, round, dst + idx * 64, lane & 3);
            TLB(1);
        }
    }
}

static_assert(NBT == 10, "k_tail covers blocks 10..15");
__global__ void __cluster_dims__(6, 1, 1) __launch_bounds__(384, 1)
k_tail(const __grid_constant__ BgParams P, bf16* __restrict__ out) {
    extern __shared__ __align__(1024) uint8_t smem_gemm[];
    const int cl = blockIdx.x / 6, rank = blockIdx.x - 6 * cl, half = rank & 1, pr = rank >> 1;
    const int blk = NBT + (cl >> 3) * 3 + pr, idx = cl & 7;
    const uint32_t st = smem_u32(smem_gemm), full = st + 6 * 32768, empty = full + 64, emptyb = full + 128, bar_s = full + 192;
    if (threadIdx.x == 0) {
        TL(4, 0);
        for (int s = 0; s < 6; s++) { mbar_init(full + 8 * s, 1); mbar_init(empty + 8 * s, 2); mbar_init(emptyb + 8 * s, 6); }
        mbar_init(bar_s, 1); mbar_expect_tx(bar_s, 32768);
        asm volatile("fence.mbarrier_init.release.cluster;\nfence.proxy.async.shared::cta;" ::: "memory");
    }
    if (threadIdx.x == 32) asm volatile("prefetch.tensormap [%0];\nprefetch.tensormap [%1];" ::"l"(&P.mo), "l"(&P.mwo2) : "memory");
    __syncthreads();
    asm volatile("barrier.cluster.arrive.relaxed.aligned;\nbarrier.cluster.wait.aligned;" ::: "memory");
    const int wg = __shfl_sync(~0u, threadIdx.x >> 7, 0);
    if (wg == 0) {
        if (threadIdx.x == 0) {
            wait_flag(g_flag + 64 + blk, 96);
            asm volatile("fence.proxy.async.global;" ::: "memory");
            for (int k = 0, s = 0, ph = 1; k < 32; k++) {
                mbar_wait(empty + 8 * s, ph);
                mbar_expect_tx(full + 8 * s, 32768);
                tma2d(st + s * 32768, &P.mo, (half * 32 + k) * 64, blk * 128, full + 8 * s);
                if (++s == 6) { s = 0; ph ^= 1; }
            }
        } else if (threadIdx.x == 32) {
            for (int k = pr, s = pr, ph = 1; k < 32; k += 3) {
                mbar_wait(emptyb + 8 * s, ph);
                asm volatile("cp.async.bulk.tensor.3d.shared::cluster.global.mbarrier::complete_tx::bytes.multicast::cluster "
                             "[%0], [%1, {%3, %4, %5}], [%2], %6;"
                             ::"r"(st + s * 32768 + 16384), "l"(&P.mwo2), "r"(full + 8 * s), "r"(0), "r"((half * 32 + k) * 64), "r"(idx * 2),
                               "h"((uint16_t)(0x15 << half)) : "memory");
                s += 3;
                if (s >= 6) { s -= 6; ph ^= 1; }
            }
        }
    } else {
        const int cw = wg - 1, lane = threadIdx.x & 31, t = lane & 3;
        float acc[64], fin[32];
#pragma unroll
        for (int i = 0; i < 64; i++) acc[i] = 0.f;
#pragma unroll 1
        for (int k = 0, s = 0, ph = 0, sp = 0; k < 32; k++) {
            mbar_wait_u(full + 8 * s, ph);
            gemm_stage<128, 128, 1>(acc, st + s * 32768, cw, false);
            wg_wait<1>();
            if (k > 0 && k <= 26)
                asm volatile("{\n.reg .pred p;\n.reg .u32 a;\nsetp.eq.u32 p, %3, 0;\nmapa.shared::cluster.u32 a, %1, %2;\n"
                             "@p mbarrier.arrive.relaxed.cta.shared::cta.b64 _, [%0];\n@p mbarrier.arrive.relaxed.cluster.shared::cluster.b64 _, [a];\n}"
                             ::"r"(empty + 8 * sp), "r"(emptyb + 8 * sp), "r"((sp >= 3 ? sp - 3 : sp) * 2 + half), "r"(threadIdx.x & 127) : "memory");
            sp = s;
            if (++s == 6) { s = 0; ph ^= 1; }
        }
        wg_wait<0>();
        const uint32_t xa = st + B_OST + (threadIdx.x - 128) * 16;
        uint32_t ra, rb;
        asm("mapa.shared::cluster.u32 %0, %1, %2;" : "=r"(ra) : "r"(xa), "r"(rank ^ 1));
        asm("mapa.shared::cluster.u32 %0, %1, %2;" : "=r"(rb) : "r"(bar_s), "r"(rank ^ 1));
#pragma unroll
        for (int i = 0; i < 8; i++) {
            float v[4];
#pragma unroll
            for (int j = 0; j < 4; j++) {
                v[j] = half ? acc[4 * i + j] : acc[32 + 4 * i + j];
                fin[4 * i + j] = half ? acc[32 + 4 * i + j] : acc[4 * i + j];
            }
            asm volatile("st.async.weak.shared::cluster.mbarrier::complete_tx::bytes.v4.f32 [%0], {%1,%2,%3,%4}, [%5];"
                         ::"r"(ra + i * 4096), "f"(v[0]), "f"(v[1]), "f"(v[2]), "f"(v[3]), "r"(rb) : "memory");
        }
        mbar_wait_u(bar_s, 0);
#pragma unroll
        for (int i = 0; i < 8; i++) {
            const float4 v = lds128f(xa + i * 4096);
            fin[4 * i] += v.x; fin[4 * i + 1] += v.y; fin[4 * i + 2] += v.z; fin[4 * i + 3] += v.w;
        }
        store_tile<64>(fin, out + (size_t)(blk * 128 + cw * 64 + ((threadIdx.x >> 5) & 3) * 16 + (lane >> 2)) * 2048 + idx * 128 + half * 64 + t * 8, t);
        if (threadIdx.x == 128) TL(4, 1);
    }
}

typedef CUresult (*EncodeFn)(CUtensorMap*, CUtensorMapDataType, cuuint32_t, void*, const cuuint64_t*, const cuuint64_t*,
                             const cuuint32_t*, const cuuint32_t*, CUtensorMapInterleave, CUtensorMapSwizzle,
                             CUtensorMapL2promotion, CUtensorMapFloatOOBfill);

static void map2d(EncodeFn enc, CUtensorMap* m, const void* p, int rows, int cols, int box_rows) {
    cuuint64_t dim[2] = {(cuuint64_t)cols, (cuuint64_t)rows}, str[1] = {(cuuint64_t)cols * 2};
    cuuint32_t box[2] = {64, (cuuint32_t)box_rows}, es[2] = {1, 1};
    enc(m, CU_TENSOR_MAP_DATA_TYPE_BFLOAT16, 2, (void*)p, dim, str, box, es, CU_TENSOR_MAP_INTERLEAVE_NONE,
        CU_TENSOR_MAP_SWIZZLE_128B, CU_TENSOR_MAP_L2_PROMOTION_L2_256B, CU_TENSOR_MAP_FLOAT_OOB_FILL_NONE);
}
static void map3d(EncodeFn enc, CUtensorMap* m, const void* p, int rows, int cols, int box_rows, int nblk) {
    cuuint64_t dim[3] = {64, (cuuint64_t)rows, (cuuint64_t)cols / 64}, str[2] = {(cuuint64_t)cols * 2, 128};
    cuuint32_t box[3] = {64, (cuuint32_t)box_rows, (cuuint32_t)nblk}, es[3] = {1, 1, 1};
    enc(m, CU_TENSOR_MAP_DATA_TYPE_BFLOAT16, 3, (void*)p, dim, str, box, es, CU_TENSOR_MAP_INTERLEAVE_NONE,
        CU_TENSOR_MAP_SWIZZLE_128B, CU_TENSOR_MAP_L2_PROMOTION_L2_256B, CU_TENSOR_MAP_FLOAT_OOB_FILL_NONE);
}

#define USE_PDL 1

extern "C" void kernel_launch(void* const* d_in, const int* in_sizes, int n_in, void* d_out, int out_size) {
    const bf16 *x = (const bf16*)d_in[0], *mem0 = (const bf16*)d_in[1], *Wq = (const bf16*)d_in[2], *Wk = (const bf16*)d_in[3];
    const bf16 *Wv = (const bf16*)d_in[4], *Wo = (const bf16*)d_in[5];
    const bf16 *u = (const bf16*)d_in[7], *Are = (const bf16*)d_in[8], *Aim = (const bf16*)d_in[9], *Bre = (const bf16*)d_in[10];
    const bf16 *Bim = (const bf16*)d_in[11], *Cre = (const bf16*)d_in[12], *Cim = (const bf16*)d_in[13];
    const bf16 *logdt = (const bf16*)d_in[14], *Dsk = (const bf16*)d_in[15];
    bf16* out = (bf16*)d_out;

    void* fn = nullptr;
    cudaDriverEntryPointQueryResult qr;
    cudaGetDriverEntryPoint("cuTensorMapEncodeTiled", &fn, cudaEnableDefault, &qr);
    EncodeFn enc = (EncodeFn)fn;
    void *kv, *o;
    cudaGetSymbolAddress(&kv, g_kv);
    cudaGetSymbolAddress(&o, g_o);
    CUtensorMap mx, mwq, mwk, mwv, mkv2;
    BgParams P;
    map2d(enc, &mx, x, SEQ, DM, 128);
    map2d(enc, &P.mo, o, SEQ, HD, 128);
    map3d(enc, &P.mo2, o, SEQ, HD, 128, 2);
    map3d(enc, &mwq, Wq, DM, HD, 64, 2);
    map3d(enc, &mwk, Wk, DM, HD, 64, 2);
    map3d(enc, &mwv, Wv, DM, HD, 64, 2);
    map3d(enc, &P.mwo4, Wo, HD, DM, 64, 4);
    map3d(enc, &P.mwo2, Wo, HD, DM, 64, 2);
    map3d(enc, &P.mwo1, Wo, HD, DM, 128, 1);
    map3d(enc, &mkv2, kv, SEQ, PW, 32, 2);
    cudaFuncSetAttribute(k_kv, cudaFuncAttributeMaxDynamicSharedMemorySize, GEMM_SMEM);
    cudaFuncSetAttribute(k_bg, cudaFuncAttributeMaxDynamicSharedMemorySize, BG_SMEM);
    cudaFuncSetAttribute(k_tail, cudaFuncAttributeMaxDynamicSharedMemorySize, BG_SMEM);
    cudaFuncSetAttribute(k_chain, cudaFuncAttributeMaxDynamicSharedMemorySize, CHAIN_SMEM);
    cudaFuncSetAttribute(k_s4, cudaFuncAttributeMaxDynamicSharedMemorySize, S4_SMEM);

    cudaStream_t st = cudaStreamPerThread;
    cudaLaunchAttribute pdl[2], cls[1];
    pdl[0].id = cudaLaunchAttributeProgrammaticStreamSerialization;
    pdl[0].val.programmaticStreamSerializationAllowed = 1;
    cls[0].id = cudaLaunchAttributeClusterDimension;
    cls[0].val.clusterDim.x = CLS; cls[0].val.clusterDim.y = 1; cls[0].val.clusterDim.z = 1;
    cudaLaunchConfig_t cfg = {};
    cfg.stream = st; cfg.attrs = cls; cfg.numAttrs = 1;
    cfg.gridDim = dim3(96); cfg.blockDim = dim3(384); cfg.dynamicSmemBytes = GEMM_SMEM;
    cudaLaunchKernelEx(&cfg, k_kv, mx, mwk, mwv, mwq, Wq, Wo, 0);
    pdl[1] = cls[0]; pdl[1].val.clusterDim.x = 2;
    cfg.attrs = pdl; cfg.numAttrs = 2;
    cfg.gridDim = dim3(36);
    cudaLaunchKernelEx(&cfg, k_kv, mx, mwk, mwv, mwq, Wq, Wo, 96);
    cfg.numAttrs = 1;
    cfg.gridDim = dim3(96); cfg.blockDim = dim3(256); cfg.dynamicSmemBytes = CHAIN_SMEM;
    cudaLaunchKernelEx(&cfg, k_chain, mem0, Wq, Wk, Wv, Wo, mkv2);
    cfg.numAttrs = USE_PDL;
    cfg.gridDim = dim3(36); cfg.blockDim = dim3(512); cfg.dynamicSmemBytes = S4_SMEM;
    cudaLaunchKernelEx(&cfg, k_s4, u, Are, Aim, Bre, Bim, Cre, Cim, logdt, Dsk, out);
    cfg.gridDim = dim3(36); cfg.blockDim = dim3(384); cfg.dynamicSmemBytes = BG_SMEM;
    cudaLaunchKernelEx(&cfg, k_bg, P, out);
    cfg.gridDim = dim3(96);
    cudaLaunchKernelEx(&cfg, k_tail, P, out);
}
```

```cpp
#include <cuda_runtime.h>
#include <cuda_bf16.h>
#include <cuda.h>
#include <stdint.h>

typedef __nv_bfloat16 bf16;

constexpr int SEQ = 2048, DM = 1024, HD = 4096, NSEG = 64;

constexpr int PW = 3 * HD;
#define NTA 3
__device__ __align__(1024) bf16 g_kv[(size_t)SEQ * PW];
__device__ __align__(1024) bf16 g_o[(size_t)SEQ * HD];
constexpr int XPAIRS = 128 + NSEG * 4;
__device__ __align__(8192) uint2 g_x[XPAIRS * 1024];
__device__ uint32_t g_home[XPAIRS];
__device__ uint32_t g_side[256];
__device__ __align__(1024) uint32_t g_flag[256];

#define TL(kern, slot)

__device__ __forceinline__ uint32_t smem_u32(const void* p) { return (uint32_t)__cvta_generic_to_shared(p); }
__device__ __forceinline__ void mbar_init(uint32_t bar, uint32_t cnt) {
    asm volatile("mbarrier.init.shared::cta.b64 [%0], %1;" ::"r"(bar), "r"(cnt) : "memory");
}
__device__ __forceinline__ void mbar_expect_tx(uint32_t bar, uint32_t bytes) {
    asm volatile("mbarrier.arrive.expect_tx.shared::cta.b64 _, [%0], %1;" ::"r"(bar), "r"(bytes) : "memory");
}
__device__ __forceinline__ void mbar_arrive(uint32_t bar) {
    asm volatile("mbarrier.arrive.shared::cta.b64 _, [%0];" ::"r"(bar) : "memory");
}
__device__ __forceinline__ bool mbar_try(uint32_t bar, uint32_t parity) {
    uint32_t ok;
    asm volatile("{\n.reg .pred p;\nmbarrier.try_wait.parity.shared::cta.b64 p, [%1], %2;\nselp.u32 %0, 1, 0, p;\n}"
                 : "=r"(ok) : "r"(bar), "r"(parity) : "memory");
    return ok;
}
constexpr int SPIN_LIMIT = 1 << 20;
__device__ __forceinline__ void mbar_wait(uint32_t bar, uint32_t parity) {
    int n = 0;
    while (!mbar_try(bar, parity)) { if (++n > SPIN_LIMIT) __trap(); }
}
__device__ __forceinline__ void mbar_wait_u(uint32_t bar, uint32_t parity) {
    asm volatile("{\n.reg .pred p;\n.reg .u32 n;\n"
                 "mbarrier.try_wait.parity.shared::cta.b64 p, [%0], %1;\n@p bra.uni DONE;\nmov.u32 n, 0;\n"
                 "AGAIN:\nmbarrier.try_wait.parity.shared::cta.b64 p, [%0], %1;\n@p bra.uni DONE;\n"
                 "add.u32 n, n, 1;\nsetp.lt.u32 p, n, 0x100000;\n@p bra.uni AGAIN;\ntrap;\nDONE:\n}"
                 ::"r"(bar), "r"(parity) : "memory");
}
__device__ __forceinline__ void tma2d(uint32_t dst, const CUtensorMap* m, int c0, int c1, uint32_t bar) {
    asm volatile("cp.async.bulk.tensor.2d.shared::cluster.global.mbarrier::complete_tx::bytes [%0], [%1, {%3, %4}], [%2];"
                 ::"r"(dst), "l"(m), "r"(bar), "r"(c0), "r"(c1) : "memory");
}
__device__ __forceinline__ void tma3d(uint32_t dst, const CUtensorMap* m, int c0, int c1, int c2, uint32_t bar) {
    asm volatile("cp.async.bulk.tensor.3d.shared::cluster.global.mbarrier::complete_tx::bytes [%0], [%1, {%3, %4, %5}], [%2];"
                 ::"r"(dst), "l"(m), "r"(bar), "r"(c0), "r"(c1), "r"(c2) : "memory");
}
__device__ __forceinline__ uint32_t pack2(float lo, float hi) {
    uint32_t r;
    asm("cvt.rn.bf16x2.f32 %0, %1, %2;" : "=r"(r) : "f"(hi), "f"(lo));
    return r;
}
__device__ __forceinline__ float bf_lo(uint32_t v) { return __uint_as_float(v << 16); }
__device__ __forceinline__ float bf_hi(uint32_t v) { return __uint_as_float(v & 0xffff0000u); }
__device__ __forceinline__ float bf_round(float x) { return bf_lo(pack2(x, 0.f)); }
__device__ __forceinline__ float ex2(float x) { float y; asm("ex2.approx.ftz.f32 %0, %1;" : "=f"(y) : "f"(x)); return y; }
__device__ __forceinline__ void mma16816(float (&c)[4], uint32_t a0, uint32_t a1, uint32_t a2, uint32_t a3, uint32_t b0, uint32_t b1) {
    asm volatile("mma.sync.aligned.m16n8k16.row.col.f32.bf16.bf16.f32 {%0,%1,%2,%3}, {%4,%5,%6,%7}, {%8,%9}, {%0,%1,%2,%3};"
                 : "+f"(c[0]), "+f"(c[1]), "+f"(c[2]), "+f"(c[3]) : "r"(a0), "r"(a1), "r"(a2), "r"(a3), "r"(b0), "r"(b1));
}
__device__ __forceinline__ void mma1688(float (&c)[4], uint32_t a0, uint32_t a1, uint32_t b0) {
    asm volatile("mma.sync.aligned.m16n8k8.row.col.f32.bf16.bf16.f32 {%0,%1,%2,%3}, {%4,%5}, {%6}, {%0,%1,%2,%3};"
                 : "+f"(c[0]), "+f"(c[1]), "+f"(c[2]), "+f"(c[3]) : "r"(a0), "r"(a1), "r"(b0));
}
__device__ __forceinline__ void ldsm4(uint32_t (&r)[4], uint32_t a) {
    asm volatile("ldmatrix.sync.aligned.m8n8.x4.shared.b16 {%0,%1,%2,%3}, [%4];"
                 : "=r"(r[0]), "=r"(r[1]), "=r"(r[2]), "=r"(r[3]) : "r"(a) : "memory");
}
__device__ __forceinline__ void ldsm4t(uint32_t (&r)[4], uint32_t a) {
    asm volatile("ldmatrix.sync.aligned.m8n8.x4.trans.shared.b16 {%0,%1,%2,%3}, [%4];"
                 : "=r"(r[0]), "=r"(r[1]), "=r"(r[2]), "=r"(r[3]) : "r"(a) : "memory");
}
__device__ __forceinline__ void ldsm2t(uint32_t& r0, uint32_t& r1, uint32_t a) {
    asm volatile("ldmatrix.sync.aligned.m8n8.x2.trans.shared.b16 {%0,%1}, [%2];" : "=r"(r0), "=r"(r1) : "r"(a) : "memory");
}
__device__ __forceinline__ void stsm4t(uint32_t a, uint32_t r0, uint32_t r1, uint32_t r2, uint32_t r3) {
    asm volatile("stmatrix.sync.aligned.m8n8.x4.trans.shared.b16 [%0], {%1,%2,%3,%4};"
                 ::"r"(a), "r"(r0), "r"(r1), "r"(r2), "r"(r3) : "memory");
}
__device__ __forceinline__ void lds128(uint32_t (&r)[4], uint32_t a) {
    asm volatile("ld.shared.v4.u32 {%0,%1,%2,%3}, [%4];" : "=r"(r[0]), "=r"(r[1]), "=r"(r[2]), "=r"(r[3]) : "r"(a) : "memory");
}
__device__ __forceinline__ float4 lds128f(uint32_t a) {
    float4 v;
    asm volatile("ld.shared.v4.f32 {%0,%1,%2,%3}, [%4];" : "=f"(v.x), "=f"(v.y), "=f"(v.z), "=f"(v.w) : "r"(a) : "memory");
    return v;
}
__device__ __forceinline__ float2 lds64f(uint32_t a) {
    float2 v;
    asm volatile("ld.shared.v2.f32 {%0,%1}, [%2];" : "=f"(v.x), "=f"(v.y) : "r"(a) : "memory");
    return v;
}
__device__ __forceinline__ uint32_t lds32(uint32_t a) {
    uint32_t v;
    asm volatile("ld.shared.u32 %0, [%1];" : "=r"(v) : "r"(a) : "memory");
    return v;
}
__device__ __forceinline__ void sts128(uint32_t a, uint32_t r0, uint32_t r1, uint32_t r2, uint32_t r3) {
    asm volatile("st.shared.v4.u32 [%0], {%1,%2,%3,%4};" ::"r"(a), "r"(r0), "r"(r1), "r"(r2), "r"(r3) : "memory");
}
__device__ __forceinline__ void sts128f(uint32_t a, float r0, float r1, float r2, float r3) {
    asm volatile("st.shared.v4.f32 [%0], {%1,%2,%3,%4};" ::"r"(a), "f"(r0), "f"(r1), "f"(r2), "f"(r3) : "memory");
}
__device__ __forceinline__ void sts64(uint32_t a, uint32_t r0, uint32_t r1) {
    asm volatile("st.shared.v2.u32 [%0], {%1,%2};" ::"r"(a), "r"(r0), "r"(r1) : "memory");
}
__device__ __forceinline__ void sts64f(uint32_t a, float r0, float r1) {
    asm volatile("st.shared.v2.f32 [%0], {%1,%2};" ::"r"(a), "f"(r0), "f"(r1) : "memory");
}
__device__ __forceinline__ void sts32f(uint32_t a, float r0) {
    asm volatile("st.shared.f32 [%0], %1;" ::"r"(a), "f"(r0) : "memory");
}
__device__ __forceinline__ uint2 ld_rlx64(const uint2* p) {
    uint2 v;
    asm volatile("{\n.reg .b64 t;\nld.relaxed.gpu.global.b64 t, [%2];\nmov.b64 {%0,%1}, t;\n}" : "=r"(v.x), "=r"(v.y) : "l"(p) : "memory");
    return v;
}
__device__ __forceinline__ void st_rlx64(uint2* p, uint32_t x, uint32_t y) {
    asm volatile("{\n.reg .b64 t;\nmov.b64 t, {%1,%2};\nst.relaxed.gpu.global.b64 [%0], t;\n}" ::"l"(p), "r"(x), "r"(y) : "memory");
}
__device__ __forceinline__ uint32_t ld_acq32(const uint32_t* p) {
    uint32_t v;
    asm volatile("ld.acquire.gpu.global.u32 %0, [%1];" : "=r"(v) : "l"(p) : "memory");
    return v;
}
__device__ __forceinline__ void wait_flag(const uint32_t* p, uint32_t need) {
    int n = 0;
    while (ld_acq32(p) < need) { __nanosleep(200); if (++n > SPIN_LIMIT) __trap(); }
}
__device__ __forceinline__ void bar_sync(int id, int n) { asm volatile("bar.sync %0, %1;" ::"r"(id), "r"(n) : "memory"); }
__device__ __forceinline__ void wg_fence() { asm volatile("wgmma.fence.sync.aligned;" ::: "memory"); }
__device__ __forceinline__ void wg_commit() { asm volatile("wgmma.commit_group.sync.aligned;" ::: "memory"); }
template <int N> __device__ __forceinline__ void wg_wait() { asm volatile("wgmma.wait_group.sync.aligned %0;" ::"n"(N) : "memory"); }
__device__ __forceinline__ uint64_t desc_sw128(uint32_t addr, uint32_t lbo, uint32_t sbo) {
    return (uint64_t)((addr & 0x3FFFF) >> 4) | ((uint64_t)(lbo >> 4) << 16) | ((uint64_t)(sbo >> 4) << 32) | (1ull << 62);
}
__device__ __forceinline__ void quad_transpose(uint32_t& r0, uint32_t& r1, uint32_t& r2, uint32_t& r3, int t) {
    const bool o = t & 1, h = t & 2;
    uint32_t s0 = __shfl_xor_sync(~0u, o ? r0 : r1, 1), s1 = __shfl_xor_sync(~0u, o ? r2 : r3, 1);
    uint32_t a0 = o ? s0 : r0, a1 = o ? r1 : s0, a2 = o ? s1 : r2, a3 = o ? r3 : s1;
    s0 = __shfl_xor_sync(~0u, h ? a0 : a2, 2); s1 = __shfl_xor_sync(~0u, h ? a1 : a3, 2);
    r0 = h ? s0 : a0; r1 = h ? s1 : a1; r2 = h ? a2 : s0; r3 = h ? a3 : s1;
}

__device__ __forceinline__ void wgmma_n256(float (&d)[128], uint64_t da, uint64_t db, int sd) {
    asm volatile("{\n.reg .pred p;\nsetp.ne.b32 p, %130, 0;\n"
        "wgmma.mma_async.sync.aligned.m64n256k16.f32.bf16.bf16 "
        "{%0,%1,%2,%3,%4,%5,%6,%7,%8,%9,%10,%11,%12,%13,%14,%15,"
        "%16,%17,%18,%19,%20,%21,%22,%23,%24,%25,%26,%27,%28,%29,%30,%31,"
        "%32,%33,%34,%35,%36,%37,%38,%39,%40,%41,%42,%43,%44,%45,%46,%47,"
        "%48,%49,%50,%51,%52,%53,%54,%55,%56,%57,%58,%59,%60,%61,%62,%63,"
        "%64,%65,%66,%67,%68,%69,%70,%71,%72,%73,%74,%75,%76,%77,%78,%79,"
        "%80,%81,%82,%83,%84,%85,%86,%87,%88,%89,%90,%91,%92,%93,%94,%95,"
        "%96,%97,%98,%99,%100,%101,%102,%103,%104,%105,%106,%107,%108,%109,%110,%111,"
        "%112,%113,%114,%115,%116,%117,%118,%119,%120,%121,%122,%123,%124,%125,%126,%127}, %128, %129, p, 1, 1, 0, 1;\n}\n"
        : "+f"(d[0]), "+f"(d[1]), "+f"(d[2]), "+f"(d[3]), "+f"(d[4]), "+f"(d[5]), "+f"(d[6]), "+f"(d[7]),
          "+f"(d[8]), "+f"(d[9]), "+f"(d[10]), "+f"(d[11]), "+f"(d[12]), "+f"(d[13]), "+f"(d[14]), "+f"(d[15]),
          "+f"(d[16]), "+f"(d[17]), "+f"(d[18]), "+f"(d[19]), "+f"(d[20]), "+f"(d[21]), "+f"(d[22]), "+f"(d[23]),
          "+f"(d[24]), "+f"(d[25]), "+f"(d[26]), "+f"(d[27]), "+f"(d[28]), "+f"(d[29]), "+f"(d[30]), "+f"(d[31]),
          "+f"(d[32]), "+f"(d[33]), "+f"(d[34]), "+f"(d[35]), "+f"(d[36]), "+f"(d[37]), "+f"(d[38]), "+f"(d[39]),
          "+f"(d[40]), "+f"(d[41]), "+f"(d[42]), "+f"(d[43]), "+f"(d[44]), "+f"(d[45]), "+f"(d[46]), "+f"(d[47]),
          "+f"(d[48]), "+f"(d[49]), "+f"(d[50]), "+f"(d[51]), "+f"(d[52]), "+f"(d[53]), "+f"(d[54]), "+f"(d[55]),
          "+f"(d[56]), "+f"(d[57]), "+f"(d[58]), "+f"(d[59]), "+f"(d[60]), "+f"(d[61]), "+f"(d[62]), "+f"(d[63]),
          "+f"(d[64]), "+f"(d[65]), "+f"(d[66]), "+f"(d[67]), "+f"(d[68]), "+f"(d[69]), "+f"(d[70]), "+f"(d[71]),
          "+f"(d[72]), "+f"(d[73]), "+f"(d[74]), "+f"(d[75]), "+f"(d[76]), "+f"(d[77]), "+f"(d[78]), "+f"(d[79]),
          "+f"(d[80]), "+f"(d[81]), "+f"(d[82]), "+f"(d[83]), "+f"(d[84]), "+f"(d[85]), "+f"(d[86]), "+f"(d[87]),
          "+f"(d[88]), "+f"(d[89]), "+f"(d[90]), "+f"(d[91]), "+f"(d[92]), "+f"(d[93]), "+f"(d[94]), "+f"(d[95]),
          "+f"(d[96]), "+f"(d[97]), "+f"(d[98]), "+f"(d[99]), "+f"(d[100]), "+f"(d[101]), "+f"(d[102]), "+f"(d[103]),
          "+f"(d[104]), "+f"(d[105]), "+f"(d[106]), "+f"(d[107]), "+f"(d[108]), "+f"(d[109]), "+f"(d[110]), "+f"(d[111]),
          "+f"(d[112]), "+f"(d[113]), "+f"(d[114]), "+f"(d[115]), "+f"(d[116]), "+f"(d[117]), "+f"(d[118]), "+f"(d[119]),
          "+f"(d[120]), "+f"(d[121]), "+f"(d[122]), "+f"(d[123]), "+f"(d[124]), "+f"(d[125]), "+f"(d[126]), "+f"(d[127])
        : "l"(da), "l"(db), "r"(sd));
}

__device__ __forceinline__ void wgmma_n128(float (&d)[64], uint64_t da, uint64_t db, int sd) {
    asm volatile("{\n.reg .pred p;\nsetp.ne.b32 p, %66, 0;\n"
        "wgmma.mma_async.sync.aligned.m64n128k16.f32.bf16.bf16 "
        "{%0,%1,%2,%3,%4,%5,%6,%7,%8,%9,%10,%11,%12,%13,%14,%15,"
        "%16,%17,%18,%19,%20,%21,%22,%23,%24,%25,%26,%27,%28,%29,%30,%31,"
        "%32,%33,%34,%35,%36,%37,%38,%39,%40,%41,%42,%43,%44,%45,%46,%47,"
        "%48,%49,%50,%51,%52,%53,%54,%55,%56,%57,%58,%59,%60,%61,%62,%63}, %64, %65, p, 1, 1, 0, 1;\n}\n"
        : "+f"(d[0]), "+f"(d[1]), "+f"(d[2]), "+f"(d[3]), "+f"(d[4]), "+f"(d[5]), "+f"(d[6]), "+f"(d[7]),
          "+f"(d[8]), "+f"(d[9]), "+f"(d[10]), "+f"(d[11]), "+f"(d[12]), "+f"(d[13]), "+f"(d[14]), "+f"(d[15]),
          "+f"(d[16]), "+f"(d[17]), "+f"(d[18]), "+f"(d[19]), "+f"(d[20]), "+f"(d[21]), "+f"(d[22]), "+f"(d[23]),
          "+f"(d[24]), "+f"(d[25]), "+f"(d[26]), "+f"(d[27]), "+f"(d[28]), "+f"(d[29]), "+f"(d[30]), "+f"(d[31]),
          "+f"(d[32]), "+f"(d[33]), "+f"(d[34]), "+f"(d[35]), "+f"(d[36]), "+f"(d[37]), "+f"(d[38]), "+f"(d[39]),
          "+f"(d[40]), "+f"(d[41]), "+f"(d[42]), "+f"(d[43]), "+f"(d[44]), "+f"(d[45]), "+f"(d[46]), "+f"(d[47]),
          "+f"(d[48]), "+f"(d[49]), "+f"(d[50]), "+f"(d[51]), "+f"(d[52]), "+f"(d[53]), "+f"(d[54]), "+f"(d[55]),
          "+f"(d[56]), "+f"(d[57]), "+f"(d[58]), "+f"(d[59]), "+f"(d[60]), "+f"(d[61]), "+f"(d[62]), "+f"(d[63])
        : "l"(da), "l"(db), "r"(sd));
}

__device__ __forceinline__ void wgmma_n64(float (&d)[32], uint64_t da, uint64_t db, int sd) {
    asm volatile("{\n.reg .pred p;\nsetp.ne.b32 p, %34, 0;\n"
        "wgmma.mma_async.sync.aligned.m64n64k16.f32.bf16.bf16 "
        "{%0,%1,%2,%3,%4,%5,%6,%7,%8,%9,%10,%11,%12,%13,%14,%15,"
        "%16,%17,%18,%19,%20,%21,%22,%23,%24,%25,%26,%27,%28,%29,%30,%31}, %32, %33, p, 1, 1, 0, 1;\n}\n"
        : "+f"(d[0]), "+f"(d[1]), "+f"(d[2]), "+f"(d[3]), "+f"(d[4]), "+f"(d[5]), "+f"(d[6]), "+f"(d[7]),
          "+f"(d[8]), "+f"(d[9]), "+f"(d[10]), "+f"(d[11]), "+f"(d[12]), "+f"(d[13]), "+f"(d[14]), "+f"(d[15]),
          "+f"(d[16]), "+f"(d[17]), "+f"(d[18]), "+f"(d[19]), "+f"(d[20]), "+f"(d[21]), "+f"(d[22]), "+f"(d[23]),
          "+f"(d[24]), "+f"(d[25]), "+f"(d[26]), "+f"(d[27]), "+f"(d[28]), "+f"(d[29]), "+f"(d[30]), "+f"(d[31])
        : "l"(da), "l"(db), "r"(sd));
}

constexpr int STAGE_BYTES = 49152, NSTAGE = 4;
constexpr int GEMM_SMEM = NSTAGE * STAGE_BYTES + 128;

struct GemmSmem { uint32_t st, full, empty; };
__device__ __forceinline__ GemmSmem gemm_setup(uint8_t* raw, int releases) {
    GemmSmem g;
    g.st = smem_u32(raw);
    if (g.st & 1023) __trap();
    g.full = g.st + NSTAGE * STAGE_BYTES; g.empty = g.full + 64;
    if (threadIdx.x == 0) {
        for (int s = 0; s < NSTAGE; s++) { mbar_init(g.full + 8 * s, 1); mbar_init(g.empty + 8 * s, releases); }
        asm volatile("fence.mbarrier_init.release.cluster;" ::: "memory");
        asm volatile("fence.proxy.async.shared::cta;" ::: "memory");
    }
    __syncthreads();
    return g;
}
__device__ __forceinline__ void mbar_arrive_one(uint32_t bar, uint32_t who) {
    asm volatile("{\n.reg .pred p;\nsetp.eq.u32 p, %1, 0;\n@p mbarrier.arrive.shared::cta.b64 _, [%0];\n}" ::"r"(bar), "r"(who) : "memory");
}
template <int BM, int BN, int KPS, typename ACC>
__device__ __forceinline__ void gemm_stage(ACC& acc, uint32_t stage, int wg, bool first) {
    const uint64_t da = desc_sw128(stage + wg * 8192, 16, 1024);
    const uint64_t db = desc_sw128(stage + KPS * BM * 128, 8192, 1024);
    wg_fence();
#pragma unroll
    for (int k = 0; k < 4 * KPS; k++) {
        const uint64_t a = da + (k >> 2) * (BM * 8) + (k & 3) * 2, b = db + k * 128;
        if constexpr (BN == 256) wgmma_n256(acc, a, b, first && k == 0 ? 0 : 1);
        else if constexpr (BN == 128) wgmma_n128(acc, a, b, first && k == 0 ? 0 : 1);
        else wgmma_n64(acc, a, b, first && k == 0 ? 0 : 1);
    }
    wg_commit();
}

__device__ __forceinline__ void kv_store_unit(const uint32_t (&pk)[64], int u, bf16* dst, int t) {
    const int G = (u >> 2) * 2 + (u & 1), hh = (u >> 1) & 1;
    uint32_t r0 = pk[(4 * G + 0) * 2 + hh], r1 = pk[(4 * G + 1) * 2 + hh], r2 = pk[(4 * G + 2) * 2 + hh], r3 = pk[(4 * G + 3) * 2 + hh];
    quad_transpose(r0, r1, r2, r3, t);
#define KVST ".cs"
    asm volatile("st.global" KVST ".v4.u32 [%0], {%1,%2,%3,%4};" ::"l"(dst + (size_t)hh * 8 * PW + G * 32), "r"(r0), "r"(r1), "r"(r2), "r"(r3) : "memory");
}

#define TLK(slot)
#define TLK2(slot)
__device__ __forceinline__ uint32_t near_page(int pair, int line) {
    uint32_t best[2] = {~0u, ~0u};
#pragma unroll 1
#define PMIN 8
#define PMAX 16
    for (int i = 0; i < PMAX; i++) {
        if (i >= PMIN && max(best[0], best[1]) - min(best[0], best[1]) > 110 && max(best[0], best[1]) - min(best[0], best[1]) < 300) break;
        uint32_t t0, t1, v;
        asm volatile("mov.u32 %0, %%clock;" : "=r"(t0)::"memory");
        asm volatile("atom.relaxed.gpu.global.or.b32 %0, [%1], -1;" : "=r"(v) : "l"(g_x + pair * 1024 + (i & 1) * 512 + line * 16) : "memory");
        asm volatile("{\n.reg .pred p;\nsetp.ne.u32 p, %1, 0x12345;\nmov.u32 %0, -1;\n@p mov.u32 %0, %%clock;\n}" : "=r"(t1) : "r"(v) : "memory");
        if (i & 1) best[1] = min(best[1], t1 - t0); else best[0] = min(best[0], t1 - t0);
    }
    return best[1] < best[0];
}
__device__ __forceinline__ void map_pages(int c) {
    uint32_t smid;
    asm("mov.u32 %0, %%smid;" : "=r"(smid));
    const uint32_t side = near_page(0, c & 31);
    g_side[smid & 255] = side;
    for (int p = c; p < XPAIRS; p += 132) g_home[p] = near_page(p, 0) ^ side;
}

__device__ __forceinline__ void kv_tile(int c, int n, int& m, int& nb) {
    if (c < 96) { m = (c & 3) + 4 * n; nb = c >> 2; }
    else {
        const int i = ((c - 96) >> 1) + 18 * n, j = i - 48 * NTA, p = j < 0 ? i / 24 : 2 * NTA + j / 48;
        m = 2 * p + (c & 1); nb = j < 0 ? 24 + i % 24 : j % 48;
    }
}

__global__ void __launch_bounds__(384, 1)
k_kv(const __grid_constant__ CUtensorMap mx, const __grid_constant__ CUtensorMap mwk, const __grid_constant__ CUtensorMap mwv,
     const __grid_constant__ CUtensorMap mwq, const bf16* __restrict__ Wq, const bf16* __restrict__ Wo, int c0) {
    extern __shared__ __align__(1024) uint8_t smem_gemm[];
    const int c = c0 + blockIdx.x, ntile = c < 96 ? NTA : (384 - 48 * NTA + 17 - ((c - 96) >> 1)) / 18;
    if (c != 96) asm volatile("griddepcontrol.launch_dependents;");
    const uint32_t bar_done = smem_u32(smem_gemm) + NSTAGE * STAGE_BYTES + 96;
    if (threadIdx.x == 0) { mbar_init(bar_done, 8); mbar_init(bar_done + 8, 8); }
    GemmSmem g = gemm_setup(smem_gemm, 4);
    if (threadIdx.x == 0) TLK(0);
    uint32_t rank, peer_empty;
    asm("mov.u32 %0, %%cluster_ctarank;" : "=r"(rank));
    asm("mapa.shared::cluster.u32 %0, %1, %2;" : "=r"(peer_empty) : "r"(g.empty), "r"(rank ^ 1));
    asm volatile("barrier.cluster.arrive.relaxed.aligned;\nbarrier.cluster.wait.aligned;" ::: "memory");
    auto release = [&](int s) {
        asm volatile("{\n.reg .pred p;\nsetp.eq.u32 p, %2, 0;\n@p mbarrier.arrive.relaxed.cta.shared::cta.b64 _, [%0];\n"
                     "@p mbarrier.arrive.relaxed.cluster.shared::cluster.b64 _, [%1];\n}"
                     ::"r"(g.empty + 8 * s), "r"(peer_empty + 8 * s), "r"(threadIdx.x & 127) : "memory");
    };
    const int wg = __shfl_sync(~0u, threadIdx.x >> 7, 0);
    if (wg == 0) {
        asm volatile("setmaxnreg.dec.sync.aligned.u32 40;");
        if (threadIdx.x == 0) {
            for (int it = 0; it < ntile * 16; it++) {
                const int s = it & 3, kb = it & 15;
                int m, nb;
                kv_tile(c, it >> 4, m, nb);
                mbar_wait(g.empty + 8 * s, ((it >> 2) & 1) ^ 1);
                mbar_expect_tx(g.full + 8 * s, STAGE_BYTES);
                tma2d(g.st + s * STAGE_BYTES, &mx, kb * 64, m * 128, g.full + 8 * s);
                asm volatile("cp.async.bulk.tensor.3d.shared::cluster.global.mbarrier::complete_tx::bytes.multicast::cluster "
                             "[%0], [%1, {%3, %4, %5}], [%2], %6;"
                             ::"r"(g.st + s * STAGE_BYTES + 16384 + (c & 1) * 16384), "l"(nb < 16 ? &mwk : nb < 32 ? &mwv : &mwq), "r"(g.full + 8 * s),
                               "r"(0), "r"(kb * 64), "r"((nb & 15) * 4 + (c & 1) * 2), "h"((uint16_t)(3u << (rank & ~1u))) : "memory");
#define PF0 (16 * NTA - 22)
                if (c < 96 && it >= PF0 && (it - PF0) * 96 + c < 2048)
                    asm volatile("cp.async.bulk.prefetch.L2.global [%0], 4096;" ::"l"((const char*)Wo + ((it - PF0) * 96 + c) * 4096) : "memory");
            }
        } else if (threadIdx.x == 32) {
            if (c == 96) {
                for (int i = 4; i < 64; i++) reinterpret_cast<uint4*>(g_flag)[i] = make_uint4(0, 0, 0, 0);
                asm volatile("fence.acq_rel.gpu;\ngriddepcontrol.launch_dependents;\ngriddepcontrol.wait;\n"
                             "fence.acq_rel.gpu;\nred.relaxed.gpu.global.add.u32 [%0], 1;" ::"l"(g_flag + 8) : "memory");
            }
        } else if (threadIdx.x == 64) {
            for (int n = 0; n < (c < 96 ? 0 : ntile); n++) {
                int m, nb;
                kv_tile(c, n, m, nb);
                mbar_wait(bar_done + (n & 1) * 8, (n >> 1) & 1);
                asm volatile("fence.acq_rel.gpu;\nred.relaxed.gpu.global.add.u32 [%0], 1;" ::"l"(g_flag + (m >> 1)) : "memory");
            }
        } else if (threadIdx.x >= 96) {
            mbar_wait(g.full + 24, 0);
            const uint4 ones = make_uint4(~0u, ~0u, ~0u, ~0u);
            for (int i = c * 32 + threadIdx.x - 96; i < XPAIRS * 512; i += 132 * 32) reinterpret_cast<uint4*>(g_x)[i] = ones;
            __syncwarp();
            if (threadIdx.x == 96) {
                map_pages(c);
                if (c >= 96) asm volatile("fence.acq_rel.gpu;\nred.relaxed.gpu.global.add.u32 [%0], 1;" ::"l"(g_flag + 8) : "memory");
            }
        }
    } else {
        asm volatile("setmaxnreg.inc.sync.aligned.u32 232;");
        const int cw = wg - 1, lane = threadIdx.x & 31, t = lane & 3;
        bf16* const dst0 = g_kv + (size_t)(cw * 64 + ((threadIdx.x >> 5) & 3) * 16 + (lane >> 2)) * PW + t * 8;
        bf16* dst = dst0;
        float acc[128];
        uint32_t pk[64];
#pragma unroll 1
        for (int tile = 0; tile < ntile; tile++) {
#pragma unroll
            for (int kb = 0; kb < 16; kb++) {
                mbar_wait_u(g.full + 8 * (kb & 3), (kb >> 2) & 1);
                if (kb == 0 && tile == 0 && threadIdx.x == 128) TLK2(0);
                gemm_stage<128, 256, 1>(acc, g.st + (kb & 3) * STAGE_BYTES, cw, kb == 0);
                if (tile > 0) {
                    kv_store_unit(pk, kb, dst, t);
                    if (kb == 15) { __syncwarp(); mbar_arrive_one(bar_done + (~tile & 1) * 8, lane); }
                }
                if (kb > 0) {
                    wg_wait<1>();
                    if (kb <= 12 || tile < ntile - 1) release((kb - 1) & 3);
                }
            }
            wg_wait<0>();
            if (tile < 4 && threadIdx.x == 128) TLK2(tile + 1);
            if (tile < ntile - 1) release(3);
#pragma unroll
            for (int i = 0; i < 64; i++) pk[i] = pack2(acc[2 * i], acc[2 * i + 1]);
            int m, nb;
            kv_tile(c, tile, m, nb);
            dst = dst0 + (size_t)m * 128 * PW + nb * 256;
        }
        if (threadIdx.x == 128) TLK(2);
#pragma unroll
        for (int u = 0; u < 16; u++) kv_store_unit(pk, u, dst, t);
        __syncwarp();
        mbar_arrive_one(bar_done + (~ntile & 1) * 8, lane);
        if (threadIdx.x == 128) TLK(1);
    }
}

constexpr int NS1 = 31;
#define RB1 4
#define PFC 4
constexpr int C_W1 = 0;
constexpr int C_W2 = C_W1 + 8 * NS1 * 512;
constexpr int C_KV = C_W2 + 14 * 8 * 512;
constexpr int C_RED = C_KV + 16384;
constexpr int C_QKV = C_RED + 64 * 272;
constexpr int QKV_SZ = 3 * 8 * 272;
constexpr int C_SC = C_RED;
constexpr int C_OB = C_SC + 2 * 8 * 52 * 4;
constexpr int C_BAR = C_QKV + 2 * QKV_SZ;
__host__ __device__ constexpr int smem_idx(int ks, int j) {
    return ks == 0 ? j : ks < 3 ? (j < 4 ? 4 + 4 * ks + j : -1) : (j < 3 ? 7 + 3 * ks + j : -1);
}
constexpr int CHAIN_SMEM = C_BAR + 64;
#define TS(i)
#define TG(i)

#define DLY3 10
#define DLY1 4
#define DLY0 4
#define DLY1A 11
#define DLY0A 0
#define DLY1B 4
#define PFD 3
#define DLYW 4
#define DLYQ 3
#define DLYS 0
template <int N> __device__ __forceinline__ uint32_t delayed(uint32_t x, uint32_t self) {
    uint32_t p = self;
#pragma unroll
    for (int i = 0; i < N; i++) asm volatile("ld.volatile.shared.u32 %0, [%0];" : "+r"(p)::"memory");
    return x + (p - self);
}
__device__ __forceinline__ int fresh(int x) { asm volatile("mov.b32 %0, %0;" : "+r"(x)); return x; }
__device__ __forceinline__ void lds128v(uint32_t (&r)[4], uint32_t a) {
    asm volatile("ld.volatile.shared.v4.u32 {%0,%1,%2,%3}, [%4];" : "=r"(r[0]), "=r"(r[1]), "=r"(r[2]), "=r"(r[3]) : "r"(a) : "memory");
}
__device__ __forceinline__ uint2 lds64(uint32_t a) {
    uint2 v;
    asm volatile("ld.shared.v2.u32 {%0,%1}, [%2];" : "=r"(v.x), "=r"(v.y) : "r"(a) : "memory");
    return v;
}
#define LDQ ".L1::no_allocate"
__device__ __forceinline__ uint4 ldw128(const void* p) {
    uint4 v;
    asm volatile("ld.global.nc" LDQ ".v4.u32 {%0,%1,%2,%3}, [%4];" : "=r"(v.x), "=r"(v.y), "=r"(v.z), "=r"(v.w) : "l"(p));
    return v;
}
#define P8_LD(i) "ld.relaxed.gpu.global.b64 d" #i ", [src + " #i " * 256];\n"
#define P8_X(i) "mov.b64 {x" #i ", y" #i "}, d" #i ";\n"
#define P8_HEAD(SRC) "{\n.reg .pred p, q;\n.reg .b64 src, d<8>;\n.reg .b32 n, x<8>, y<8>, m0, m1;\nmov.b64 src, " SRC ";\n"         \
                P8_LD(0) P8_LD(1) P8_LD(2) P8_LD(3) P8_LD(4) P8_LD(5) P8_LD(6) P8_LD(7) "mov.u32 n, 0;\nCHECK:\n" \
                P8_X(0) P8_X(1) P8_X(2) P8_X(3) P8_X(4) P8_X(5) P8_X(6) P8_X(7)
#define P8_VOTE "vote.sync.all.pred p, p, -1;\n@p bra.uni DONE;\n"
#define P8_TAIL "add.u32 n, n, 1;\nsetp.lt.u32 p, n, 0x100000;\n@p bra.uni CHECK;\ntrap;\nDONE:\n"
#define S8_LD(i) "ld.relaxed.gpu.global.b64 %" #i ", [%8 + " #i " * 256];\n"
__device__ __forceinline__ void fetch_state(uint64_t (&d)[8], const void* src) {
    asm volatile(S8_LD(0) S8_LD(1) S8_LD(2) S8_LD(3) S8_LD(4) S8_LD(5) S8_LD(6) S8_LD(7)
                 : "=&l"(d[0]), "=&l"(d[1]), "=&l"(d[2]), "=&l"(d[3]), "=&l"(d[4]), "=&l"(d[5]), "=&l"(d[6]), "=&l"(d[7]) : "l"(src) : "memory");
}
__device__ __forceinline__ void settle_state(uint64_t (&d)[8], const void* src) {
#define S8_X(i) "mov.b64 {x" #i ", _}, %" #i ";\n"
#define S8_R(i) "setp.eq.u32 q, x" #i ", 0xffffffff;\n@q " S8_LD(i)
    asm volatile("{\n.reg .pred p, q;\n.reg .b32 n, x<8>, m0, m1;\nmov.u32 n, 0;\nCHECK:\n"
                 S8_X(0) S8_X(1) S8_X(2) S8_X(3) S8_X(4) S8_X(5) S8_X(6) S8_X(7)
                 "max.u32 m0, x0, x1;\nmax.u32 m0, m0, x2;\nmax.u32 m1, x3, x4;\nmax.u32 m1, m1, x5;\nmax.u32 m0, m0, x6;\n"
                 "max.u32 m0, m0, x7;\nmax.u32 m0, m0, m1;\nsetp.ne.u32 p, m0, 0xffffffff;\n" P8_VOTE
                 S8_R(0) S8_R(1) S8_R(2) S8_R(3) S8_R(4) S8_R(5) S8_R(6) S8_R(7) P8_TAIL "}"
                 : "+l"(d[0]), "+l"(d[1]), "+l"(d[2]), "+l"(d[3]), "+l"(d[4]), "+l"(d[5]), "+l"(d[6]), "+l"(d[7]) : "l"(src) : "memory");
}
__device__ __forceinline__ uint64_t poll_sum(const void* src, uint32_t tag, uint32_t sel) {
#define P8_RT(i) "lop3.b32 m0, x" #i ", %2, 1, 0x28;\nsetp.ne.u32 q, m0, 0;\n@q " P8_LD(i)
#define P8_MMA(c, i, z) "mma.sync.aligned.m16n8k8.row.col.f32.bf16.bf16.f32 {" #c "0," #c "1," #c "2," #c "3}, {x" #i ", y" #i "}, {%3}, {" #z "0," #z "1," #z "2," #z "3};\n"
    uint64_t r;
    asm volatile(P8_HEAD("%1") "{\n.reg .f32 a<4>, b<4>, z<4>;\nmov.f32 z0, 0f00000000;\nmov.f32 z1, z0;\nmov.f32 z2, z0;\nmov.f32 z3, z0;\n"
                 P8_MMA(a, 0, z) P8_MMA(b, 1, z) P8_MMA(a, 2, a) P8_MMA(b, 3, b) P8_MMA(a, 4, a) P8_MMA(b, 5, b) P8_MMA(a, 6, a) P8_MMA(b, 7, b)
                 "add.f32 a0, a0, b0;\nadd.f32 a1, a1, b1;\nadd.f32 a2, a2, b2;\nadd.f32 a3, a3, b3;\n"
                 "cvt.rn.bf16x2.f32 m0, a1, a0;\ncvt.rn.bf16x2.f32 m1, a3, a2;\nmov.b64 %0, {m0, m1};\n}\n"
                 "lop3.b32 m0, x0, x1, %2, 0x7e;\nlop3.b32 m1, x2, x3, %2, 0x7e;\nlop3.b32 m0, m0, x4, %2, 0xf6;\n"
                 "lop3.b32 m1, m1, x5, %2, 0xf6;\nlop3.b32 m0, m0, x6, %2, 0xf6;\nlop3.b32 m1, m1, x7, %2, 0xf6;\n"
                 "lop3.b32 m0, m0, m1, 1, 0xa8;\nsetp.eq.u32 p, m0, 0;\n" P8_VOTE
                 P8_RT(0) P8_RT(1) P8_RT(2) P8_RT(3) P8_RT(4) P8_RT(5) P8_RT(6) P8_RT(7) P8_TAIL "}"
                 : "=&l"(r) : "l"(src), "r"(tag), "r"(sel) : "memory");
    return r;
}
__device__ __forceinline__ void wait_count_u(const uint32_t* p, uint32_t need) {
    asm volatile("{\n.reg .pred p;\n.reg .u32 n, v;\nmov.u32 n, 0;\nAGAIN:\nld.acquire.gpu.global.u32 v, [%0];\nsetp.ge.u32 p, v, %1;\n"
                 "vote.sync.all.pred p, p, -1;\n@p bra.uni DONE;\nadd.u32 n, n, 1;\nsetp.lt.u32 p, n, 0x100000;\n@p bra.uni AGAIN;\ntrap;\n"
                 "DONE:\nfence.proxy.async.global;\n}" ::"l"(p), "r"(need) : "memory");
}
__device__ __forceinline__ uint32_t movm(uint32_t x) { asm volatile("movmatrix.sync.aligned.m8n8.trans.b16 %0, %0;" : "+r"(x)); return x; }
template <int NK, typename F>
__device__ __forceinline__ void attend(uint32_t sb, uint32_t lm, uint32_t qs, uint32_t xq, int i8, int lane, bf16* dst, F mid) {
    const int r8 = lane & 7, m4 = lane >> 3;
    const float sl2e = 0.08838834764831845f * 1.4426950408889634f;
    const uint32_t lk = sb + C_KV + ((m4 & 1) * 8 + r8) * 128 + (((m4 >> 1) ^ r8) << 4);
    const uint32_t lkm = sb + xq + (8 + r8) * 272 + (m4 & 1) * 32 + (m4 >> 1) * 16;
    asm volatile("cp.async.wait_all;" ::: "memory");
    __syncwarp();
    float x[4][4];
#pragma unroll
    for (int i = 0; i < 4; i++) x[i][0] = x[i][1] = x[i][2] = x[i][3] = 0.f;
#pragma unroll
    for (int kp = 0; kp < 4; kp++) {
        uint32_t q[4], a[4];
        ldsm4(q, lm + qs + kp * 64);
        ldsm4(a, lkm + kp * 64);
        mma16816(x[2], a[0], a[1], a[2], a[3], q[0], q[1]);
        mma16816(x[3], a[0], a[1], a[2], a[3], q[2], q[3]);
#pragma unroll
        for (int u = 0; u < 4; u++) {
            if ((u & 1) >= NK) continue;
            ldsm4(a, (lk ^ (((kp & 1) * 2 + (u >> 1)) << 5)) + (kp >> 1) * 4096 + (u & 1) * 2048);
            mma16816(x[u & 1], a[0], a[1], a[2], a[3], q[u & 2], q[(u & 2) + 1]);
        }
    }
    x[2][0] += x[3][2]; x[2][1] += x[3][3];
    const int lim = i8 + 2 * (lane & 3) - (lane >> 2);
    uint32_t p[5];
    {
        float m[2], e[5][2];
#pragma unroll
        for (int b = 0; b < 2; b++) {
            e[4][b] = m[b] = x[2][b];
#pragma unroll
            for (int j = 0; j < 2 * NK; j++) {
                e[j][b] = j < 2 * NK - 2 || 8 * j - b <= lim ? x[j >> 1][(j & 1) * 2 + b] : -3.0e38f;
                m[b] = fmaxf(m[b], e[j][b]);
            }
        }
#pragma unroll
        for (int o = 4; o < 32; o <<= 1) {
            m[0] = fmaxf(m[0], __shfl_xor_sync(~0u, m[0], o));
            m[1] = fmaxf(m[1], __shfl_xor_sync(~0u, m[1], o));
        }
        m[0] *= sl2e; m[1] *= sl2e;
#pragma unroll
        for (int j = 0; j < 5; j++)
            if (j < 2 * NK || j == 4) p[j] = movm(pack2(ex2(fmaf(e[j][0], sl2e, -m[0])), ex2(fmaf(e[j][1], sl2e, -m[1]))));
    }
    const uint32_t lvt = sb + C_KV + 8192 + ((m4 >> 1) * 8 + r8) * 128 + (((m4 & 1) ^ r8) << 4), one = 0x3f803f80u;
    float sm[4] = {0.f, 0.f, 0.f, 0.f}, c[8][4];
    mma16816(sm, one, one, one, one, p[0], p[1]);
    if (NK == 2) mma16816(sm, one, one, one, one, p[2], p[3]);
    mma1688(sm, one, one, p[4]);
#pragma unroll
    for (int j = 0; j < 8; j++) c[j][0] = c[j][1] = c[j][2] = c[j][3] = 0.f;
#pragma unroll
    for (int kk = 0; kk < NK; kk++)
#pragma unroll
        for (int j = 0; j < 8; j++) {
            uint32_t a[4];
            ldsm4t(a, (lvt ^ ((j & 3) << 5)) + (j >> 2) * 4096 + kk * 2048);
            mma16816(c[j], a[0], a[1], a[2], a[3], p[2 * kk], p[2 * kk + 1]);
        }
    float i0, i1;
    asm("rcp.approx.ftz.f32 %0, %1;" : "=f"(i0) : "f"(sm[0]));
    asm("rcp.approx.ftz.f32 %0, %1;" : "=f"(i1) : "f"(sm[1]));
    uint32_t o[4][4];
#pragma unroll
    for (int j = 0; j < 4; j++) {
        uint32_t a[4];
        ldsm4t(a, lm + xq + 16 * 272 + j * 64);
        mma1688(c[2 * j], a[0], a[1], p[4]);
        mma1688(c[2 * j + 1], a[2], a[3], p[4]);
#pragma unroll
        for (int u = 0; u < 4; u++) o[j][u] = pack2(c[2 * j + (u >> 1)][(u & 1) * 2] * i0, c[2 * j + (u >> 1)][(u & 1) * 2 + 1] * i1);
    }
#pragma unroll
    for (int j = 0; j < 4; j++) stsm4t(lm + qs + j * 64, o[j][0], o[j][1], o[j][2], o[j][3]);
    mid();
    __syncwarp();
#pragma unroll
    for (int j = 0; j < 4; j++) lds128(o[j], sb + qs + ((lane >> 4) + 2 * j) * 272 + (lane & 15) * 16);
#pragma unroll
    for (int j = 0; j < 4; j++)
        asm volatile("st.global.v4.u32 [%0], {%1,%2,%3,%4};" ::"l"(dst + (size_t)2 * j * HD), "r"(o[j][0]), "r"(o[j][1]), "r"(o[j][2]), "r"(o[j][3]) : "memory");
}
__device__ __forceinline__ void sum8(float (&c)[4], const uint2 (&v)[8], uint32_t idn) {
    float d[4] = {0.f, 0.f, 0.f, 0.f};
    c[0] = c[1] = c[2] = c[3] = 0.f;
    mma16816(c, v[0].x, v[0].y, v[1].x, v[1].y, idn, idn);
    mma16816(d, v[2].x, v[2].y, v[3].x, v[3].y, idn, idn);
    mma16816(c, v[4].x, v[4].y, v[5].x, v[5].y, idn, idn);
    mma16816(d, v[6].x, v[6].y, v[7].x, v[7].y, idn, idn);
    c[0] += d[0]; c[1] += d[1]; c[2] += d[2]; c[3] += d[3];
}

#define CLS 6
__global__ void __cluster_dims__(CLS, 1, 1) __launch_bounds__(256, 1)
k_chain(const bf16* __restrict__ mem0, const bf16* __restrict__ Wq, const bf16* __restrict__ Wk, const bf16* __restrict__ Wv,
        const bf16* __restrict__ Wo, const __grid_constant__ CUtensorMap mkv) {
    extern __shared__ __align__(1024) uint8_t smem_chain[];
    const uint32_t sb = smem_u32(smem_chain);
    if (sb & 1023) __trap();
    const int w = __shfl_sync(~0u, threadIdx.x >> 5, 0), lane = __shfl_sync(~0u, threadIdx.x & 31, threadIdx.x & 31);
    const int tid = w * 32 + lane, g = lane >> 2, t = lane & 3;
    auto pin = [&](uint32_t x) { asm volatile("shfl.sync.idx.b32 %0, %0, %1, 31, -1;" : "+r"(x) : "r"(lane) : "memory"); return x; };
    const int h = blockIdx.x / 3, r = blockIdx.x - 3 * h;
    const uint32_t bar_x = sb + C_BAR, bar_kv = sb + C_BAR + 8, bar_go = sb + C_BAR + 16, bar_w = sb + C_BAR + 24, self = sb + C_BAR + 60;
    asm volatile("griddepcontrol.launch_dependents;");
    const int tbase = r == 0 ? 0 : 1 + 21 * r, ntile = r == 0 ? 22 : 21;
    uint32_t side;
    if (tid == 0) {
        mbar_init(bar_x, 8); mbar_init(bar_kv, 1); mbar_init(bar_go, 1); mbar_init(bar_w, 1);
        asm volatile("st.shared.u32 [%0], %0;" ::"r"(self) : "memory");
        asm volatile("fence.mbarrier_init.release.cluster;" ::: "memory");
        asm volatile("fence.proxy.async.shared::cta;" ::: "memory");
        mbar_expect_tx(bar_w, 128 * 32 * ntile);
    }
    __syncthreads();
    asm volatile("barrier.cluster.arrive.relaxed.aligned;" ::: "memory");
    asm("mov.u32 %0, %%smid;" : "=r"(side));
    asm volatile("ld.relaxed.gpu.global.u32 %0, [%1];" : "=r"(side) : "l"(g_side + (side & 255)) : "memory");
    if (tid < 128)
        asm volatile("cp.async.bulk.shared::cluster.global.mbarrier::complete_tx::bytes [%0], [%1], %2, [%3];"
                     ::"r"(sb + C_W1 + tid * 720), "l"(Wo + (size_t)(h * 128 + tid) * DM + tbase * 16), "r"(32 * ntile), "r"(bar_w) : "memory");
    const int tile0 = tbase + 7 - w;
    const bool three = w >= (r == 0 ? 2 : 3);
    const uint32_t wa = pin(sb + tid * 16);
#define W1A(i) (wa + C_W1 + (i) * 4096)
#define W2A(x) (wa + C_W2 + ((x) < 8 ? (x) * 4096 : 32768 - 1024 + ((x) - 8) * 3072))
    uint32_t wo0[8][4], wr[64][4];
    {
        const bf16* W = (r == 0 ? Wq : r == 1 ? Wk : Wv) + (size_t)(128 * w + (lane >> 4)) * HD + h * 128 + 8 * (lane & 15);
        uint4 raw[8][8];
        auto fetch = [&](int ks) {
#pragma unroll
            for (int i = 0; i < 8; i++) raw[ks][i] = ldw128(W + (size_t)(16 * ks + 2 * i) * HD);
        };
        fetch(0); fetch(1); fetch(2); fetch(3);
        if (w == 0) TG(0);
        mbar_wait_u(bar_w, 0);
        if (w == 0) TG(1);
        const uint32_t p = sb + C_W1 + ((lane & 7) + (lane >> 4) * 8) * 720 + (7 - w) * 32 + ((lane >> 3) & 1) * 16;
#pragma unroll
        for (int ks = 0; ks < 8; ks++) {
            uint32_t a[4];
            ldsm4t(wo0[ks], p + ks * 16 * 720);
            ldsm4t(a, p + ks * 16 * 720 + 256);
            sts128(W2A(ks), a[0], a[1], a[2], a[3]);
            if (three) { ldsm4t(a, p + ks * 16 * 720 + 512); sts128(W2A(8 + ks), a[0], a[1], a[2], a[3]); }
        }
        __syncthreads();
        side &= 1;
        if (w == 7 && r > 0) asm volatile("st.relaxed.gpu.global.u32 [%0], %1;" ::"l"(g_flag + 128 + 2 * h + r - 1), "r"(2 | side) : "memory");
        if (w == 0) TG(2);
        const uint32_t stg = sb + C_KV + w * 4096;
        const uint32_t rd = stg + ((lane & 7) + 8 * (lane >> 4)) * 256 + ((((lane >> 3) & 1) ^ (lane & 7)) << 4);
#pragma unroll
        for (int ks = 0; ks < 8; ks++) {
#pragma unroll
            for (int i = 0; i < 8; i++)
                sts128(stg + (2 * i + (lane >> 4)) * 256 + (((lane & 15) ^ (((2 * i) & 6) | (lane >> 4))) << 4),
                       raw[ks][i].x, raw[ks][i].y, raw[ks][i].z, raw[ks][i].w);
            if (ks < 2) fetch(ks + 4);
            if (ks == 3 || ks == 5) fetch(ks / 2 + 5);
            __syncwarp();
#pragma unroll
            for (int j = 0; j < 8; j++) {
                if (smem_idx(ks, j) >= 0) {
                    uint32_t a[4];
                    ldsm4t(a, rd ^ (j << 5));
                    sts128(W1A(smem_idx(ks, j)), a[0], a[1], a[2], a[3]);
                } else ldsm4t(wr[8 * ks + j], rd ^ (j << 5));
            }
            __syncwarp();
        }
    }
    if (w == 0) TG(3);
    wait_count_u(g_flag + (lane & 8), lane & 8 ? 37 : 48);
    asm volatile("fence.proxy.async.shared::cta;" ::: "memory");
    __syncthreads();
    if (tid == 0) {
        mbar_expect_tx(bar_kv, 16384);
        tma3d(sb + C_KV, &mkv, 0, 0, 2 * h, bar_kv);
        tma3d(sb + C_KV + 8192, &mkv, 0, 0, 64 + 2 * h, bar_kv);
    }
    asm volatile("barrier.cluster.wait.aligned;" ::: "memory");

    auto load_kv = [&](int s) {
        asm volatile("{\n.reg .pred p;\nelect.sync _|p, -1;\n@p mbarrier.arrive.expect_tx.shared::cta.b64 _, [%2], 16384;\n"
                     "@p cp.async.bulk.tensor.3d.shared::cluster.global.mbarrier::complete_tx::bytes [%0], [%1, {%3, %4, %5}], [%2];\n"
                     "@p cp.async.bulk.tensor.3d.shared::cluster.global.mbarrier::complete_tx::bytes [%6], [%1, {%3, %4, %7}], [%2];\n}"
                     ::"r"(sb + C_KV), "l"(&mkv), "r"(bar_kv), "r"(0), "r"(s * 32), "r"(2 * h), "r"(sb + C_KV + 8192), "r"(64 + 2 * h) : "memory");
    };
    const bool attends = w == 7 || (w == 6 && r == 0);
    const int i8 = r == 0 ? (w - 4) * 8 : (r - 1) * 8;
    auto load_q = [&](int s) {
        const int l = fresh(lane);
        const bf16* p = g_kv + (size_t)(s * 32 + i8 + (l >> 4)) * PW + 2 * HD + h * 128 + (l & 15) * 8;
#pragma unroll
        for (int j = 0; j < 4; j++)
            asm volatile("cp.async.cg.shared.global [%0], [%1], 16;"
                         ::"r"(sb + C_RED + w * 2176 + ((l >> 4) + 2 * j) * 272 + (l & 15) * 16), "l"(p + (size_t)2 * j * PW) : "memory");
    };
    auto report = [&](int blk) {
        asm volatile("{\n.reg .pred p;\nelect.sync _|p, -1;\nfence.acq_rel.gpu;\n@p red.relaxed.gpu.global.add.u32 [%0], 1;\n}"
                     ::"l"(g_flag + 64 + blk) : "memory");
    };
    const float sl2e = 0.08838834764831845f * 1.4426950408889634f;
    const uint32_t idn = pin(g == 2 * t ? 0x00003f80u : g == 2 * t + 1 ? 0x3f800000u : 0u);
    const uint32_t lm = pin(sb + (lane & 7) * 272 + (lane >> 3) * 16);
    const uint32_t sa = pin(sb + C_SC + (w & 1) * (8 * 52 * 4) + (2 * t * 52 + (w < 4 ? 32 : (w & 2) * 8) + g) * 4);
    const uint32_t sr = pin(sb + C_SC + (g * 52 + 8 * t) * 4), sr2 = pin(sb + C_SC + (g * 52 + 32 + 2 * t) * 4);
    uint32_t kva;
    {
        const int pos = (w & 2) * 8 + (lane & 15), row = (pos & 24) + ((pos + (pos >> 2 & 6)) & 7);
        const int key = 4 * (lane & 6) + (((lane & 7) + 2 * (lane >> 4)) & 7);
        kva = pin(w >= 4 ? sb + C_KV + (w & 1) * 4096 + row * 128 + (((lane >> 4) ^ (row & 7)) << 4)
                         : sb + C_KV + 8192 + (w >> 1) * 4096 + key * 128 + ((((w & 1) * 4 + ((lane >> 3) & 1)) ^ (key & 7)) << 4));
    }
#define ATTEND(NK, s, mid) do {                                                                                       \
        const int l_ = fresh(lane);                                                                                      \
        attend<NK>(sb, lm, C_RED + w * 2176, C_QKV + ((s) & 1) * QKV_SZ, i8, l_,                                         \
                   g_o + (size_t)((s) * 32 + i8 + (l_ >> 4)) * HD + h * 128 + (l_ & 15) * 8, mid);                       \
    } while (0)
    auto chores = [&](int s) {
        if ((s & 3) == 0 && s) report((s >> 2) - 1);
        if ((s & 7) == 6 && s < NSEG - 2) wait_count_u(g_flag + (s >> 3) + 1, (s >> 3) + 1 < 2 * NTA ? 48 : 96);
    };
    uint32_t buf0[8][4], ring[RB1][4];
#define STAGE_W1() do {                                                            \
        _Pragma("unroll") for (int i = 0; i < 8; i++) lds128v(buf0[i], W1A(i));       \
        _Pragma("unroll") for (int i = 0; i < RB1; i++) lds128v(ring[i], W1A(8 + i)); \
    } while (0)
    auto stage_w1 = [&]() { STAGE_W1(); };
    stage_w1();
    uint32_t psel, msel0, msel1;
    {
        const int j = r > 0 ? 2 * h + r - 1 : 0, tl = min(tile0 + 8 * (lane >> 1), 63);
        uint32_t b;
        asm volatile("{\n.reg .pred p;\n.reg .u32 n;\nmov.u32 n, 0;\nAGAIN:\nld.relaxed.gpu.global.u32 %0, [%1];\nsetp.ne.u32 p, %0, 0;\n"
                     "vote.sync.all.pred p, p, -1;\n@p bra.uni DONE;\nadd.u32 n, n, 1;\nsetp.lt.u32 p, n, 0x100000;\n@p bra.uni AGAIN;\ntrap;\nDONE:\n}"
                     : "=&r"(b) : "l"(g_flag + 128 + tl) : "memory");
        psel = __ballot_sync(~0u, (g_home[lane == 6 ? j * 2 + ((w >> 1) & 1) : tl * 2 + (lane & 1)] ^ (lane == 6 ? side : b)) & 1);
        msel0 = __ballot_sync(~0u, (g_home[128 + lane * 4 + (w >> 1)] ^ side) & 1);
        msel1 = __ballot_sync(~0u, (g_home[256 + lane * 4 + (w >> 1)] ^ side) & 1);
        if (r > 0) {
            if (w < 4) asm volatile("prefetch.global.L2 [%0];" ::"l"(g_x + (128 + (1 + (w >> 1)) * 4 + (j >> 4)) * 1024 + (w & 1) * 512 + (j & 15) * 32 + lane) : "memory");
            if (w < 4) asm volatile("prefetch.global.L2 [%0];" ::"l"(g_x + j * 2048 + tid * 16) : "memory");
        }
    }
    uint2 bm[8];
#pragma unroll
    for (int ks = 0; ks < 8; ks++) {
        const uint32_t* p = (const uint32_t*)(mem0 + g * DM + (8 * w + ks) * 16) + t;
        bm[ks] = make_uint2(__ldg(p), __ldg(p + 4));
    }
    if (w == 0) TG(5);
#pragma unroll 1
    for (int s = 0;; s++) {
        TS(1);
        const uint32_t xq = C_QKV + (s & 1) * QKV_SZ;
        {
            float acc[8][4];
#pragma unroll
            for (int ks = 0; ks < 8; ks++) {
#pragma unroll
                for (int j = 0; j < 8; j++) {
                    const int i = smem_idx(ks, j) - 8;
                    if (ks == 0) {
                        acc[j][0] = acc[j][1] = acc[j][2] = acc[j][3] = 0.f;
                        mma16816(acc[j], buf0[j][0], buf0[j][1], buf0[j][2], buf0[j][3], bm[ks].x, bm[ks].y);
                    } else if (i >= 0) {
                        uint32_t(&a)[4] = ring[i % RB1];
                        mma16816(acc[j], a[0], a[1], a[2], a[3], bm[ks].x, bm[ks].y);
                        if (8 + i + RB1 < NS1) lds128v(a, W1A(8 + i + RB1));
                    } else {
                        const uint32_t(&a)[4] = wr[8 * ks + j];
                        mma16816(acc[j], a[0], a[1], a[2], a[3], bm[ks].x, bm[ks].y);
                    }
                }
            }
#pragma unroll
            for (int c = 0; c < 4; c++)
                stsm4t(lm + C_RED + w * 2176 + c * 64, pack2(acc[2 * c][0], acc[2 * c][1]), pack2(acc[2 * c][2], acc[2 * c][3]),
                       pack2(acc[2 * c + 1][0], acc[2 * c + 1][1]), pack2(acc[2 * c + 1][2], acc[2 * c + 1][3]));
        }
        {
            const uint32_t a = sb + C_RED + w * 272 + lane * 8;
            if (w == 3) mbar_wait_u(bar_kv, s & 1);
            TS(2);
            __syncthreads();
            TS(3);
            uint2 v[8];
#pragma unroll
            for (int i = 0; i < 8; i++) v[i] = lds64(a + i * 2176);
            float c[4];
            sum8(c, v, idn);
            const uint32_t p0 = pack2(c[0], c[1]), p1 = pack2(c[2], c[3]);
            const uint32_t dst = sb + xq + (r * 8 + w) * 272 + lane * 8;
#pragma unroll
            for (int i = 1; i < 3; i++) {
                const uint32_t peer = (h % (CLS / 3)) * 3 + (r + i >= 3 ? r + i - 3 : r + i);
                uint32_t rd, rb;
                asm("mapa.shared::cluster.u32 %0, %1, %2;" : "=r"(rd) : "r"(dst), "r"(peer));
                asm("mapa.shared::cluster.u32 %0, %1, %2;" : "=r"(rb) : "r"(bar_x), "r"(peer));
                asm volatile("st.async.weak.shared::cluster.mbarrier::complete_tx::bytes.v2.b32 [%0], {%1,%2}, [%3];"
                             ::"r"(rd), "r"(p0), "r"(p1), "r"(rb) : "memory");
            }
            sts64(dst, p0, p1);
            __syncwarp();
            asm volatile("{\n.reg .pred p;\nsetp.eq.u32 p, %1, 0;\n@p mbarrier.arrive.expect_tx.shared::cta.b64 _, [%0], 512;\n}"
                         ::"r"(bar_x), "r"(lane) : "memory");
        }
        TS(4);
        if (s == NSEG - 1) break;
        uint32_t wb[8][4], wc[8][4];
        const uint32_t po = (tile0 * 2 + (lane >> 4)) * 8192 + ((lane >> 3) & 1) * 2048 + h * 64 + (lane & 7) * 8;
        const uint32_t tag = s & 1;
        auto project = [&](const uint32_t(&wt)[8][4], const uint32_t(&ob)[4][4], int i) {
            float c0[4] = {0.f, 0.f, 0.f, 0.f}, c1[4] = {0.f, 0.f, 0.f, 0.f};
#pragma unroll
            for (int ks = 0; ks < 8; ks++)
                mma16816((ks & 1) ? c1 : c0, wt[ks][0], wt[ks][1], wt[ks][2], wt[ks][3], ob[ks >> 1][(ks & 1) * 2], ob[ks >> 1][(ks & 1) * 2 + 1]);
            uint32_t p0 = pack2(c0[0] + c1[0], c0[1] + c1[1]), p1 = pack2(c0[2] + c1[2], c0[3] + c1[3]);
            asm volatile("movmatrix.sync.aligned.m8n8.trans.b16 %0, %0;\nmovmatrix.sync.aligned.m8n8.trans.b16 %1, %1;" : "+r"(p0), "+r"(p1));
            st_rlx64((uint2*)((char*)g_x + po + i * 131072 + ((psel >> (2 * i + (lane >> 4))) & 1) * 4096), (p0 & ~1u) | tag, p1);
        };
        if (w >= 4) {
            uint32_t ka[4][4];
#pragma unroll
            for (int ks = 0; ks < 4; ks++) ldsm4(ka[ks], kva ^ (ks << 5));
            const uint32_t qa = lm + xq + (w & 1) * 128;
            TS(5);
            mbar_wait_u(bar_x, s & 1);
            TS(6);
            {
                uint32_t qb[2][4];
                ldsm4(qb[0], qa);
                ldsm4(qb[1], qa + 64);
                float c0[4] = {0.f, 0.f, 0.f, 0.f}, c1[4] = {0.f, 0.f, 0.f, 0.f};
                mma16816(c0, ka[0][0], ka[0][1], ka[0][2], ka[0][3], qb[0][0], qb[0][1]);
                mma16816(c1, ka[1][0], ka[1][1], ka[1][2], ka[1][3], qb[0][2], qb[0][3]);
                mma16816(c0, ka[2][0], ka[2][1], ka[2][2], ka[2][3], qb[1][0], qb[1][1]);
                mma16816(c1, ka[3][0], ka[3][1], ka[3][2], ka[3][3], qb[1][2], qb[1][3]);
                sts32f(sa, c0[0] + c1[0]);
                sts32f(sa + 208, c0[1] + c1[1]);
                sts32f(sa + 32, c0[2] + c1[2]);
                sts32f(sa + 240, c0[3] + c1[3]);
            }
            __syncthreads();
            TS(7);
            uint32_t wd;
            if (attends) { load_q(s); wd = delayed<DLYQ>(wa, self); } else wd = delayed<DLYW>(wa, self);
#pragma unroll
            for (int i = 0; i < 8; i++) lds128(wb[i], wd + C_W2 + i * 4096);
#pragma unroll
            for (int i = 0; i < PFC; i++) lds128(wc[i], wd + C_W2 + 32768 - 1024 + i * 3072);
            TS(8);
            __syncthreads();
            TS(9);
            uint32_t ob[4][4];
#pragma unroll
            for (int i = 0; i < 4; i++) ldsm4(ob[i], lm + C_OB + i * 64);
#pragma unroll
            for (int i = PFC; i < 8; i++) lds128(wc[i], W2A(8 + i));
            project(wb, ob, 1);
            project(wo0, ob, 0);
            project(wc, ob, 2);
        } else {
            uint32_t va[4][4];
#pragma unroll
            for (int i = 0; i < 4; i++) ldsm4t(va[i], kva ^ (((i >> 1) << 5) | ((i & 1) * 0x240)));
#pragma unroll
            for (int i = 0; i < 8; i++) lds128(wb[i], W2A(i));
            const uint32_t qa = lm + xq + (w & 1) * 128, oa = lm + w * 64;
            TS(5);
            mbar_wait_u(bar_x, s & 1);
            TS(6);
            if (w < 2) {
                uint32_t qb[2][4], km[2][4];
                ldsm4(qb[0], qa);
                ldsm4(km[0], qa + 8 * 272);
                ldsm4(qb[1], qa + 64);
                ldsm4(km[1], qa + 8 * 272 + 64);
                float c0[4] = {0.f, 0.f, 0.f, 0.f}, c1[4] = {0.f, 0.f, 0.f, 0.f};
                mma16816(c0, km[0][0], km[0][1], km[0][2], km[0][3], qb[0][0], qb[0][2]);
                mma16816(c1, km[0][0], km[0][1], km[0][2], km[0][3], qb[0][1], qb[0][3]);
                mma16816(c0, km[1][0], km[1][1], km[1][2], km[1][3], qb[1][0], qb[1][2]);
                mma16816(c1, km[1][0], km[1][1], km[1][2], km[1][3], qb[1][1], qb[1][3]);
                sts32f(sa, c0[0] + c1[2]);
                sts32f(sa + 208, c0[1] + c1[3]);
            }
            __syncthreads();
            TS(7);
            {
                float4 x0 = lds128f(sr), y0 = lds128f(sr + 1664), x1 = lds128f(sr + 16), y1 = lds128f(sr + 1680);
                float2 x2 = lds64f(sr2), y2 = lds64f(sr2 + 1664);
                float p[10] = {x0.x + y0.x, x0.y + y0.y, x0.z + y0.z, x0.w + y0.w, x1.x + y1.x,
                               x1.y + y1.y, x1.z + y1.z, x1.w + y1.w, x2.x + y2.x, x2.y + y2.y};
                float m = fmaxf(fmaxf(fmaxf(p[0], p[1]), fmaxf(p[2], p[3])), fmaxf(fmaxf(fmaxf(p[4], p[5]), fmaxf(p[6], p[7])), fmaxf(p[8], p[9])));
                const float m1 = __shfl_xor_sync(~0u, m, 1), m2 = __shfl_xor_sync(~0u, m, 2), m3 = __shfl_xor_sync(~0u, m, 3);
                uint32_t vm[4];
                ldsm4t(vm, oa + xq + 16 * 272);
                m = fmaxf(fmaxf(m, m1), fmaxf(m2, m3));
                const float ms = m * sl2e;
#pragma unroll
                for (int i = 0; i < 10; i++) p[i] = ex2(fmaf(p[i], sl2e, -ms));
                const uint32_t b0 = pack2(p[0], p[1]), b1 = pack2(p[2], p[3]), b2 = pack2(p[4], p[5]), b3 = pack2(p[6], p[7]), b4 = pack2(p[8], p[9]);
                const uint32_t one = 0x3f803f80u;
                float o0[4] = {0.f, 0.f, 0.f, 0.f}, o1[4] = {0.f, 0.f, 0.f, 0.f}, sm[4] = {0.f, 0.f, 0.f, 0.f};
                mma16816(sm, one, one, one, one, b0, b1);
                mma16816(o0, va[0][0], va[0][1], va[0][2], va[0][3], b0, b1);
                mma16816(o1, va[2][0], va[2][1], va[2][2], va[2][3], b0, b1);
                mma16816(sm, one, one, one, one, b2, b3);
                mma16816(o0, va[1][0], va[1][1], va[1][2], va[1][3], b2, b3);
                mma16816(o1, va[3][0], va[3][1], va[3][2], va[3][3], b2, b3);
                mma1688(sm, one, one, b4);
                mma1688(o0, vm[0], vm[1], b4);
                mma1688(o1, vm[2], vm[3], b4);
                float i0, i1;
                asm("rcp.approx.ftz.f32 %0, %1;" : "=f"(i0) : "f"(sm[0]));
                asm("rcp.approx.ftz.f32 %0, %1;" : "=f"(i1) : "f"(sm[1]));
                stsm4t(oa + C_OB, pack2(o0[0] * i0, o0[1] * i1), pack2(o0[2] * i0, o0[3] * i1),
                       pack2(o1[0] * i0, o1[1] * i1), pack2(o1[2] * i0, o1[3] * i1));
            }
            TS(8);
            __syncthreads();
            TS(9);
            uint32_t ob[4][4];
#pragma unroll
            for (int i = 0; i < 4; i++) ldsm4(ob[i], lm + C_OB + i * 64);
            if (three) {
#pragma unroll
                for (int i = 0; i < 8; i++) lds128(wc[i], W2A(8 + i));
                project(wb, ob, 1);
                project(wo0, ob, 0);
                project(wc, ob, 2);
            } else {
                project(wb, ob, 1);
                project(wo0, ob, 0);
            }
        }
        TS(10);
        __syncthreads();
        uint32_t eo = (128 + (s + 1) * 4 + (w >> 1)) * 8192 + (((s < 31 ? msel0 : msel1) >> ((s + 1) & 31)) & 1) * 4096 + (w & 1) * 2048 + lane * 8;
        uint64_t d[8];
        if (r == 0) {
            if (w >= 6) {
                auto mid = [&]() {
                    bar_sync(2, 64);
                    TS(11);
                    mbar_wait_u(bar_go, s & 1);
                    eo = delayed<DLY0A>(eo, self);
                    TS(12);
                    fetch_state(d, (const char*)g_x + eo);
                };
                ATTEND(2, s, mid);
                stage_w1();
            } else {
                TS(11); TS(12);
                if (w < 3 && s + PFD < NSEG) {
                    const bf16* p = g_kv + (size_t)((s + PFD) * 32 + fresh(lane)) * PW + w * HD + h * 128;
                    asm volatile("prefetch.global.L2 [%0];\nprefetch.global.L2 [%0 + 128];" ::"l"(p) : "memory");
                }
                const uint32_t wa_ = wa;
                { const uint32_t wa = delayed<DLYS>(wa_, self); STAGE_W1(); }
                if (w == 5) {
                    chores(s);
                    if (h == 0) asm volatile("st.relaxed.gpu.global.u32 [%0], %1;" ::"l"(g_flag + 98), "r"(s + 1) : "memory");
                }
                mbar_wait_u(bar_go, s & 1);
                eo = delayed<DLY0>(eo, self);
                fetch_state(d, (const char*)g_x + eo);
            }
        } else {
            const int j = 2 * h + r - 1;
            if (w < 4) {
                const int l = fresh(lane), g = l >> 2, t = l & 3;
                const char* src = (const char*)g_x + delayed<DLY3>((j * 2 + (w >> 1)) * 8192 + (psel & 64) * 64 + (w & 1) * 2048 + t * 64 + g * 8, self);
                const char* dst = (const char*)g_x + pin((128 + (s + 1) * 4 + (j >> 4)) * 8192 + (j & 15) * 256 + w * 64 + (t & 1) * 4096 + g * 8);
                const uint64_t v = poll_sum(src, tag, (lane & 4) ? 0x3f800000u : 0x00003f80u);
                TS(11);
                asm volatile("st.relaxed.gpu.global.b64 [%0], %1;" ::"l"(dst), "l"(v) : "memory");
                asm volatile("bar.arrive 1, 256;" ::: "memory");
                TS(12);
                stage_w1();
                eo = delayed<DLY1>(eo, self);
                fetch_state(d, (const char*)g_x + eo);
            } else if (w == 7) {
                auto mid = [&]() {
                    TS(11);
                    bar_sync(1, 256);
                    TS(12);
                    eo = delayed<DLY1B>(eo, self);
                    fetch_state(d, (const char*)g_x + eo);
                };
                ATTEND(1, s, mid);
                stage_w1();
            } else {
                if (w >= 5 && s + 3 < NSEG)
                    asm volatile("prefetch.global.L2 [%0];" ::"l"(g_x + (128 + (s + 3) * 4 + (j >> 4)) * 1024 + (w & 1) * 512 + (j & 15) * 32 + lane) : "memory");
                stage_w1();
                if (w == 5) chores(s);
                TS(11);
                bar_sync(1, 256);
                TS(12);
                if (w == 4 && r == 1)
                    asm volatile("{\n.reg .pred p;\n.reg .u32 a;\nelect.sync _|p, -1;\nmapa.shared::cluster.u32 a, %0, %1;\n"
                                 "@p mbarrier.arrive.relaxed.cluster.shared::cluster.b64 _, [a];\n}" ::"r"(bar_go), "r"((h % (CLS / 3)) * 3) : "memory");
                eo = delayed<DLY1A>(eo, self);
                fetch_state(d, (const char*)g_x + eo);
            }
        }
        { const int s_ = s; { const int s = s_ + 1; TS(0); } }
        if (w == 7) load_kv(s + 1);
        settle_state(d, (const char*)g_x + eo);
#pragma unroll
        for (int i = 0; i < 8; i++) { bm[i].x = (uint32_t)d[i]; bm[i].y = (uint32_t)(d[i] >> 32); }
    }
    mbar_wait_u(bar_x, (NSEG - 1) & 1);
    if (attends) {
        auto nothing = []() {};
        load_q(NSEG - 1);
        if (r == 0) ATTEND(2, NSEG - 1, nothing); else ATTEND(1, NSEG - 1, nothing);
    }
    __syncthreads();
    if (w == 5) report(15);
    asm volatile("barrier.cluster.arrive.relaxed.aligned;\nbarrier.cluster.wait.aligned;" ::: "memory");
}

constexpr int S4_US = 4368;
constexpr int S4_RS = 8848;
constexpr int S4_KS = 1296;
constexpr int S4_U = 0, S4_R = 16 * S4_US, S4_K = S4_R + 16 * S4_RS;
constexpr int S4_SMEM = S4_K + 16 * S4_KS;
constexpr int S4_SIG = 3104, S4_PK = 2 * S4_SIG;

struct cf { float r, i; };
__device__ __forceinline__ cf cmul(cf a, cf b) { return {fmaf(a.r, b.r, -a.i * b.i), fmaf(a.r, b.i, a.i * b.r)}; }
__device__ __forceinline__ cf cmulc(cf a, cf b) { return {fmaf(a.r, b.r, a.i * b.i), fmaf(a.i, b.r, -a.r * b.i)}; }
__device__ __forceinline__ cf csq(cf a) { const float t = a.r * a.i; return {fmaf(a.r, a.r, -a.i * a.i), t + t}; }
__device__ __forceinline__ cf cexp(float l2, float turns) {
    const float mag = ex2(l2), fr = (turns - rintf(turns)) * 6.283185307179586f;
    return {mag * __cosf(fr), mag * __sinf(fr)};
}
__device__ __forceinline__ void sts32(uint32_t a, uint32_t v) { asm volatile("st.shared.u32 [%0], %1;" ::"r"(a), "r"(v) : "memory"); }
__device__ __forceinline__ uint32_t lds16(uint32_t a) {
    uint32_t v;
    asm volatile("ld.shared.u16 %0, [%1];" : "=r"(v) : "r"(a) : "memory");
    return v;
}

template <int M0, int NQ>
__device__ __forceinline__ void s4_class(float (&acc)[16][4], uint32_t sig, uint32_t taps, int x0) {
    constexpr int D0 = M0 / 8, D1 = M0 == 32 ? 9 : 15;
    uint32_t R[D1 - D0 + 2];
#pragma unroll
    for (int D = D0 - 1; D <= D1; D++) {
        if (D < D0 || 8 * D - 7 >= 2 * M0) { R[D - D0 + 1] = 0; continue; }
        const int m = 8 * D + x0;
        uint32_t lo = lds16(taps + m * (2 * NQ)), hi = lds16(taps + (m - 1) * (2 * NQ));
        if (D == D0) { lo = m >= M0 ? lo : 0; hi = m > M0 ? hi : 0; }
        if (D == 2 * D0) { lo = m < 2 * M0 ? lo : 0; hi = m <= 2 * M0 ? hi : 0; }
        R[D - D0 + 1] = lo | (hi << 16);
    }
#pragma unroll
    for (int J = 0; 2 * J + D0 < 16; J++) {
        uint32_t a[4];
        ldsm4t(a, sig + J * 512);
#pragma unroll
        for (int D = D0; D <= D1; D++)
            if (2 * J + D < 16) mma16816(acc[2 * J + D], a[0], a[1], a[2], a[3], R[D - D0 + 1], R[D - D0]);
    }
}

__global__ void __launch_bounds__(512, 1)
k_s4(const bf16* __restrict__ u, const bf16* __restrict__ Are, const bf16* __restrict__ Aim, const bf16* __restrict__ Bre,
     const bf16* __restrict__ Bim, const bf16* __restrict__ Cre, const bf16* __restrict__ Cim, const bf16* __restrict__ logdt,
     const bf16* __restrict__ Dsk, bf16* __restrict__ out) {
    extern __shared__ __align__(16) uint8_t smem_s4[];
    const uint32_t sb = smem_u32(smem_s4);
    asm volatile("griddepcontrol.launch_dependents;");
    const int tid = threadIdx.x, w = __shfl_sync(~0u, tid >> 5, 0), lane = tid & 31, g = lane >> 2, t = lane & 3;
    const int dw = (w & 1) + ((w >> 1) & 3) * 4 + (w >> 3) * 2;
    uint2 ar, ai, br, bi, cr, ci;
    bf16 ldt;
    auto load_params = [&](int item) {
        const int d = item * 16 + dw, o = d * 128 + lane * 4;
        ar = __ldg((const uint2*)(Are + o)); ai = __ldg((const uint2*)(Aim + o)); br = __ldg((const uint2*)(Bre + o));
        bi = __ldg((const uint2*)(Bim + o)); cr = __ldg((const uint2*)(Cre + o)); ci = __ldg((const uint2*)(Cim + o));
        ldt = logdt[d];
    };
    load_params(blockIdx.x);
#pragma unroll 1
    for (int item = blockIdx.x; item < 64; item += gridDim.x) {
#define TLS(slot)
    if (tid == 0) TLS(0);
    const int d0 = item * 16;
    const uint32_t tr_off = (lane & 15), tr_l = (lane >> 4) * 16;
    const uint32_t ur = sb + S4_U + w * S4_US, rs = sb + S4_R + w * S4_RS, kd = sb + S4_K + w * S4_KS;
    if (lane < 16) sts128(ur + lane * 16, 0, 0, 0, 0);
    {
        const float dt = bf_round(expf(__bfloat162float(ldt)));
        const bf16* src = u + (size_t)(w * 128 + g) * DM + d0 + 4 * t;
        float T[5][4];
#pragma unroll
        for (int i = 0; i < 5; i++) T[i][0] = T[i][1] = T[i][2] = T[i][3] = 0.f;
        float klast = 0.f;
        const uint32_t wr_ = rs + lane * 272, rd_ = rs + t * 544 + g * 16;
#pragma unroll 1
        for (int c = 0; c < 4; c++) {
            uint2 v[4];
#pragma unroll
            for (int i = 0; i < 4; i++) v[i] = __ldg((const uint2*)(src + (size_t)(c * 32 + i * 8) * DM));
            auto pick = [&](const uint2& x) { const uint32_t y = c < 2 ? x.x : x.y; return (c & 1) ? bf_hi(y) : bf_lo(y); };
            auto pk2 = [](cf x) { return pack2(x.r, x.i); };
            const float l2 = dt * pick(ar) * 1.4426950408889634f, tu = dt * pick(ai) * 0.15915494309189535f;
            const cf z1 = cexp(l2, tu), z2 = csq(z1), z4 = csq(z2), z8 = csq(z4);
            const cf z64 = cexp(l2 * 64.f, tu * 64.f), z128 = csq(z64), z256 = csq(z128), z512 = csq(z256);
            cf a0 = {1.f, 0.f}, a1 = z64;
            cf b0 = cmul({pick(cr), pick(ci)}, {dt * pick(br), dt * pick(bi)});
            b0.i = -b0.i;
            cf b1 = cmulc(b0, z128), b2 = cmulc(b0, z256), y3 = cmulc(b0, z512), b4 = cmulc(y3, z512), b3 = y3;
            const cf y2 = cmulc(b2, z128);
#pragma unroll
            for (int i = 0; i < 8; i++) {
                sts128(wr_ + i * 16, pk2(a0), pk2(a1), pk2(b0), pk2(b1));
                sts128(wr_ + i * 16 + 128, pk2(b2), pk2(b3), pk2(b4), 0);
                b4 = cmulc(b4, z128);
                if (i < 7) {
                    a0 = i == 0 ? z8 : cmul(a0, z8); a1 = cmul(a1, z8);
                    b0 = cmulc(b0, z1); b1 = cmulc(b1, z1);
                    b2 = i == 3 ? y2 : cmulc(b2, z2);
                    if (i & 1) { y3 = cmulc(y3, z128); b3 = y3; } else b3 = cmulc(y3, z4);
                }
            }
            klast += b4.r;
            __syncwarp();
#pragma unroll
            for (int k = 0; k < 8; k++) {
                uint32_t x[4], y[4];
                lds128(x, rd_ + (8 * (k >> 1) + (k & 1)) * 272);
                lds128(y, rd_ + (8 * (k >> 1) + (k & 1)) * 272 + 128);
                mma1688(T[0], x[0], x[1], x[2]);
                mma1688(T[1], x[0], x[1], x[3]);
                mma1688(T[2], x[0], x[1], y[0]);
                mma1688(T[3], x[0], x[1], y[1]);
                mma1688(T[4], x[0], x[1], y[2]);
            }
#pragma unroll
            for (int i = 0; i < 2; i++)
                stsm4t(sb + S4_U + tr_off * S4_US + 256 + (w * 128 + c * 32 + i * 16) * 2 + tr_l, v[2 * i].x, v[2 * i].y, v[2 * i + 1].x, v[2 * i + 1].y);
            __syncwarp();
        }
#pragma unroll
        for (int o2 = 16; o2; o2 >>= 1) klast += __shfl_xor_sync(~0u, klast, o2);
#pragma unroll
        for (int hh = 0; hh < 2; hh++) {
            const int i = g + 8 * hh;
            sts32(kd + (8 * i + 2 * t) * 2, pack2(T[0][2 * hh], T[0][2 * hh + 1]));
            sts32(kd + (128 + 8 * i + 2 * t) * 2, pack2(T[1][2 * hh], T[1][2 * hh + 1]));
            sts32(kd + (256 + 4 * i + 2 * (t & 1) + 64 * (t >> 1)) * 2, pack2(T[2][2 * hh], T[2][2 * hh + 1]));
            sts32(kd + (384 + 2 * i + 32 * t) * 2, pack2(T[3][2 * hh], T[3][2 * hh + 1]));
        }
        asm volatile("stmatrix.sync.aligned.m8n8.x2.trans.shared.b16 [%0], {%1,%2};"
                     ::"r"(kd + 1024 + (lane & 7) * 32 + ((lane >> 3) & 1) * 16), "r"(pack2(T[4][0], T[4][1])), "r"(pack2(T[4][2], T[4][3])) : "memory");
        if (lane == 0) sts32(kd + 1280, pack2(klast, 0.f));
    }
    __syncwarp();
    const uint32_t pk = rs + S4_PK + 64;
    {
#pragma unroll
        for (int i = 0; i < 2; i++) {
            const int x = i * 128 + lane * 4;
            const uint2 c = lds64(kd + x * 2);
            uint32_t p = lds16(kd + x * 2 - 2);
            if (x == 0) p = 0;
            sts128(pk + x * 4, __byte_perm(c.x, p, 0x5410), __byte_perm(c.x, 0, 0x1032), __byte_perm(c.y, c.x, 0x7610), __byte_perm(c.y, 0, 0x1032));
        }
#pragma unroll
        for (int i = 2; i < 4; i++) {
            const int x = i * 128 + lane * 4;
            const uint32_t ab = lds32(kd + 256 + x), c = lds16(kd + 256 + x + 4);
            const uint32_t p = x == 256 ? lds16(kd + 510) : ab;
            sts128(pk + x * 4, __byte_perm(ab, p, 0x5410), __byte_perm(ab, 0, 0x1010), __byte_perm(ab, 0, 0x1032), __byte_perm(c, ab, 0x7610));
        }
        const uint32_t v = lds16(kd + 768), v2 = lds16(kd + 1024);
        if (lane < 24) {
            uint32_t x0 = 0, x1 = 0, x2 = 0, x3 = 0;
            if (lane == 0) { x0 = x1 = x2 = v | (v << 16); x3 = v << 16; }
            if (lane == 12) x3 = v2;
            if (lane == 13) { x0 = v2 | (v2 << 16); x1 = v2 << 16; }
            sts128(lane < 20 ? pk + 2048 + lane * 16 : pk - 64 + (lane - 20) * 16, x0, x1, x2, x3);
        }
        if (lane < 4) sts128(rs + (lane >> 1) * S4_SIG + (lane & 1) * 16, 0, 0, 0, 0);
    }
    __syncthreads();
    float acc[16][4];
#pragma unroll
    for (int i = 0; i < 16; i++) acc[i][0] = acc[i][1] = acc[i][2] = acc[i][3] = 0.f;
    const uint32_t lf = (lane & 7) * 32 + ((lane >> 3) & 1) * 16 + (lane >> 4) * 256;
#pragma unroll 1
    for (int ph = 0; ph < 2; ph++) {
    if (((w >> 2) ^ ph) & 1) {
#pragma unroll
    for (int rg = 3; rg >= 2; rg--) {
#pragma unroll 1
        for (int it = 0; it < (rg == 3 ? 4 : 6); it++) {
            const int n = it * 32 + lane;
            uint32_t x[2][4];
            lds128(x[0], ur + 256 + n * 16 - 16);
            lds128(x[1], ur + 256 + n * 16);
            float e[16], p[15], s[11];
#pragma unroll
            for (int i = 0; i < 8; i++) { e[2 * i] = bf_lo(x[i >> 2][i & 3]); e[2 * i + 1] = bf_hi(x[i >> 2][i & 3]); }
#pragma unroll
            for (int i = 0; i < 15; i++) p[i] = e[i] + e[i + 1];
#pragma unroll
            for (int i = 0; i < 11; i++) s[i] = p[i + 3] + e[i + 5];
            const uint32_t o = rs + 16 + n * 16;
            if (rg == 2) sts128(o, pack2(s[0], s[1]), pack2(s[2], s[3]), pack2(s[4], s[5]), pack2(s[6], s[7]));
#pragma unroll
            for (int i = 0; i < 10; i++) s[i] = p[i + 2] + s[i + 1];
            if (rg == 2) {
                sts64(o + S4_SIG + 8, pack2(s[0], s[1]), pack2(s[2], s[3]));
                sts64(o + S4_SIG + 16, pack2(s[4], s[5]), pack2(s[6], s[7]));
            } else {
#pragma unroll
                for (int i = 0; i < 9; i++) s[i] = p[i + 1] + s[i + 1];
                sts64(o + 8, pack2(s[0], s[1]), pack2(s[2], s[3]));
                sts64(o + 16, pack2(s[4], s[5]), pack2(s[6], s[7]));
#pragma unroll
                for (int i = 0; i < 8; i++) s[i] = p[i] + s[i + 1];
                sts64(o + S4_SIG + 8, pack2(s[0], s[1]), pack2(s[2], s[3]));
                sts64(o + S4_SIG + 16, pack2(s[4], s[5]), pack2(s[6], s[7]));
            }
        }
        __syncwarp();
        if (rg == 3) {
#pragma unroll 1
            for (int q = 1; q <= 2; q++) s4_class<64, 2>(acc, rs + lf + (q == 1 ? 16 : S4_SIG), kd + (384 + q) * 2, g - 2 * t);
        } else {
#pragma unroll 1
            for (int q = 1; q <= 4; q++) s4_class<32, 4>(acc, rs + lf + ((q & 1) ? 0 : S4_SIG) + (q < 3 ? 16 : 0), kd + (256 + q) * 2, g - 2 * t);
        }
        __syncwarp();
    }
    } else
    {
        const uint32_t ub = ur + 256 + lf, kb = pk + (g - 2 * t) * 4;
#pragma unroll 1
        for (int j0 = 0; j0 < 8; j0++) {
            uint32_t B[8][4];
#pragma unroll
            for (int i = 0; i < 8; i++) ldsm4(B[i], ub + i * 512 - j0 * 32);
            auto block = [&](int J, uint32_t a) {
                const uint32_t r0 = lds32(a), rp = lds32(a + 32), rm = lds32(a - 32);
                uint32_t r3;
                asm volatile("ld.volatile.shared.u32 %0, [%1];" : "=r"(r3) : "r"(a) : "memory");
#pragma unroll
                for (int I = J; I < 16; I++)
                    mma16816(acc[I], r0, rp, rm, r3, B[(I - J) >> 1][((I - J) & 1) * 2], B[(I - J) >> 1][((I - J) & 1) * 2 + 1]);
            };
#pragma unroll
            for (int J = 0; J < 4; J++) block(J, kb + j0 * 64 + J * 512);
            if (j0 < 2) { block(4, kb + j0 * 64 + 2048); block(8, kb + j0 * 64 + (544 + 16) * 4); }
        }
    }
    }
    {
        __syncwarp();
#pragma unroll
        for (int i = 0; i < 8; i++)
            stsm4t(rs + lf + i * 512, pack2(acc[2 * i][0], acc[2 * i][1]), pack2(acc[2 * i][2], acc[2 * i][3]),
                   pack2(acc[2 * i + 1][0], acc[2 * i + 1][1]), pack2(acc[2 * i + 1][2], acc[2 * i + 1][3]));
    }
    __syncthreads();
    {
        const uint2 dv = __ldg((const uint2*)(Dsk + d0 + 4 * t));
        load_params(min(item + (int)gridDim.x, 63));
        bf16* dst = out + (size_t)(w * 128 + g) * 2048 + 1024 + d0 + 4 * t;
        uint32_t o[8][4];
#pragma unroll
        for (int i = 0; i < 8; i++) {
            uint32_t y[4], x[4];
            ldsm4t(y, sb + S4_R + tr_off * S4_RS + (w * 128 + i * 16) * 2 + tr_l);
            ldsm4t(x, sb + S4_U + tr_off * S4_US + 256 + (w * 128 + i * 16) * 2 + tr_l);
#pragma unroll
            for (int j = 0; j < 4; j++)
                asm("{\n.reg .b32 s;\nmul.rn.bf16x2 s, %2, %3;\nadd.rn.bf16x2 %0, %1, s;\n}" : "=r"(o[i][j]) : "r"(y[j]), "r"(x[j]), "r"((j & 1) ? dv.y : dv.x));
        }
        __syncthreads();
#pragma unroll
        for (int i = 0; i < 8; i++) {
            *reinterpret_cast<uint2*>(dst + (size_t)(i * 16) * 2048) = make_uint2(o[i][0], o[i][1]);
            *reinterpret_cast<uint2*>(dst + (size_t)(i * 16 + 8) * 2048) = make_uint2(o[i][2], o[i][3]);
        }
    }
    if (tid == 0) TLS(1);
    }
}

enum { IT_W256 = 1, IT_W128 = 2, IT_W64 = 3, IT_END = 7 };
struct BgParams { CUtensorMap mo, mo2, mwo4, mwo2, mwo1; };
#define NBT 10
#define P256 56
#define P128 62
struct Sched { uint32_t w0, w1; };
__device__ __forceinline__ int next_item(Sched& z) {
    if (z.w0 >= z.w1) {
        uint32_t prog;
        asm volatile("ld.relaxed.gpu.global.u32 %0, [%1];" : "=r"(prog) : "l"(g_flag + 98) : "memory");
        const uint32_t k = prog <= P256 ? 4 : prog <= P128 ? 2 : 1;
        z.w0 = 4 * gridDim.x + atomicAdd(g_flag + 97, k);
        z.w1 = min(z.w0 + k, NBT * 16u);
        if (z.w0 >= z.w1) return IT_END;
    }
    const uint32_t i = z.w0, k = z.w1 - i >= 4 && !(i & 3) ? 4 : z.w1 - i >= 2 && !(i & 1) ? 2 : 1;
    z.w0 += k;
    return (k == 4 ? IT_W256 : k == 2 ? IT_W128 : IT_W64) | (i >> 4) << 3 | ((i & 15) / k) << 7;
}
constexpr int B_OST = NSTAGE * STAGE_BYTES + 1024;
constexpr int BG_SMEM = B_OST + 32768;

template <int BM, int BN, int KPS, typename ACC>
__device__ __forceinline__ void gemm_mainloop(ACC& acc, const GemmSmem& g, int cw, int rounds, uint32_t& round) {
#pragma unroll
    for (int i = 0; i < BN / 2; i++) acc[i] = 0.f;
#pragma unroll 1
    for (int k0 = 0; k0 < rounds; k0++, round++) {
#pragma unroll
        for (int s = 0; s < 4; s++) {
            mbar_wait_u(g.full + 8 * s, round & 1);
            gemm_stage<BM, BN, KPS>(acc, g.st + s * STAGE_BYTES, cw, false);
            wg_wait<1>();
            if (s > 0 || k0 > 0) mbar_arrive_one(g.empty + 8 * ((s + 3) & 3), threadIdx.x & 31);
        }
    }
    wg_wait<0>();
    mbar_arrive_one(g.empty + 8 * 3, threadIdx.x & 31);
}

template <int BN>
__device__ __forceinline__ void store_tile(const float (&acc)[BN / 2], bf16* dst, int t) {
#pragma unroll
    for (int G = 0; G < BN / 32; G++)
#pragma unroll
        for (int rr = 0; rr < 2; rr++) {
            uint32_t r0 = pack2(acc[16 * G + 2 * rr], acc[16 * G + 2 * rr + 1]), r1 = pack2(acc[16 * G + 4 + 2 * rr], acc[16 * G + 5 + 2 * rr]);
            uint32_t r2 = pack2(acc[16 * G + 8 + 2 * rr], acc[16 * G + 9 + 2 * rr]), r3 = pack2(acc[16 * G + 12 + 2 * rr], acc[16 * G + 13 + 2 * rr]);
            quad_transpose(r0, r1, r2, r3, t);
            *reinterpret_cast<uint4*>(dst + (size_t)rr * 8 * 2048 + G * 32) = make_uint4(r0, r1, r2, r3);
        }
}

template <int BN, int KPS>
__device__ __forceinline__ void wo_item(const GemmSmem& g, int cw, uint32_t& round, bf16* dst, int t) {
    float acc[BN / 2];
    gemm_mainloop<128, BN, KPS>(acc, g, cw, 16 / KPS, round);
    store_tile<BN>(acc, dst, t);
}

__global__ void __launch_bounds__(384, 1) k_bg(const __grid_constant__ BgParams P, bf16* __restrict__ out) {
    extern __shared__ __align__(1024) uint8_t smem_gemm[];
    asm volatile("griddepcontrol.launch_dependents;");
    const uint32_t bar_item = smem_u32(smem_gemm) + NSTAGE * STAGE_BYTES + 128, slot = bar_item + 16;
    if (threadIdx.x == 0) { mbar_init(bar_item, 1); mbar_init(bar_item + 8, 1); }
    if (threadIdx.x == 32) asm volatile("prefetch.tensormap [%0];\nprefetch.tensormap [%1];" ::"l"(&P.mo), "l"(&P.mwo4) : "memory");
    GemmSmem g = gemm_setup(smem_gemm, 8);
    const int wg = __shfl_sync(~0u, threadIdx.x >> 7, 0);
    if (wg == 0) {
        asm volatile("setmaxnreg.dec.sync.aligned.u32 40;");
        if (threadIdx.x == 0) {
            uint32_t it = 0;
            Sched z = {4 * blockIdx.x, 4 * blockIdx.x + 4};
            for (int n = 0;; n++) {
                const int code = next_item(z);
                sts32(slot + (n & 1) * 4, code);
                mbar_arrive(bar_item + (n & 1) * 8);
                const int type = code & 7, blk = (code >> 3) & 15, idx = code >> 7;
                if (type == IT_END) break;
                wait_flag(g_flag + 64 + blk, 96);
                asm volatile("fence.proxy.async.global;" ::: "memory");
                for (int k = 0; k < (type == IT_W64 ? 32 : 64); k++, it++) {
                    const int s = it & 3;
                    const uint32_t st = g.st + s * STAGE_BYTES, fb = g.full + 8 * s;
                    mbar_wait(g.empty + 8 * s, ((it >> 2) & 1) ^ 1);
                    mbar_expect_tx(fb, type == IT_W128 ? 32768 : 49152);
                    if (type == IT_W64) {
                        tma3d(st, &P.mo2, 0, blk * 128, k * 2, fb);
                        tma3d(st + 32768, &P.mwo1, 0, k * 128, idx, fb);
                    } else {
                        tma2d(st, &P.mo, k * 64, blk * 128, fb);
                        tma3d(st + 16384, type == IT_W256 ? &P.mwo4 : &P.mwo2, 0, k * 64, idx * (type == IT_W256 ? 4 : 2), fb);
                    }
                }
            }
        }
    } else {
        asm volatile("setmaxnreg.inc.sync.aligned.u32 232;");
        const int cw = wg - 1, lane = threadIdx.x & 31;
        uint32_t round = 0;
#pragma unroll 1
        for (int n = 0;; n++) {
            mbar_wait_u(bar_item + (n & 1) * 8, (n >> 1) & 1);
            const int code = __shfl_sync(~0u, lds32(slot + (n & 1) * 4), 0);
            const int type = code & 7, blk = (code >> 3) & 15, idx = (code >> 7) & 31;
#define TLB(slot_)
            if (type == IT_END) break;
            TLB(0);
            bf16* dst = out + (size_t)(blk * 128 + cw * 64 + ((threadIdx.x >> 5) & 3) * 16 + (lane >> 2)) * 2048 + (lane & 3) * 8;
            if (type == IT_W256) wo_item<256, 1>(g, cw, round, dst + idx * 256, lane & 3);
            else if (type == IT_W128) wo_item<128, 1>(g, cw, round, dst + idx * 128, lane & 3);
            else wo_item<64, 2>(g, cw, round, dst + idx * 64, lane & 3);
            TLB(1);
        }
    }
}

static_assert(NBT == 10, "k_tail covers blocks 10..15");
__global__ void __cluster_dims__(6, 1, 1) __launch_bounds__(384, 1)
k_tail(const __grid_constant__ BgParams P, bf16* __restrict__ out) {
    extern __shared__ __align__(1024) uint8_t smem_gemm[];
    const int cl = blockIdx.x / 6, rank = blockIdx.x - 6 * cl, half = rank & 1, pr = rank >> 1;
    const int blk = NBT + (cl >> 3) * 3 + pr, idx = cl & 7;
    const uint32_t st = smem_u32(smem_gemm), full = st + 6 * 32768, empty = full + 64, emptyb = full + 128, bar_s = full + 192;
    if (threadIdx.x == 0) {
        TL(4, 0);
        for (int s = 0; s < 6; s++) { mbar_init(full + 8 * s, 1); mbar_init(empty + 8 * s, 2); mbar_init(emptyb + 8 * s, 6); }
        mbar_init(bar_s, 1); mbar_expect_tx(bar_s, 32768);
        asm volatile("fence.mbarrier_init.release.cluster;\nfence.proxy.async.shared::cta;" ::: "memory");
    }
    if (threadIdx.x == 32) asm volatile("prefetch.tensormap [%0];\nprefetch.tensormap [%1];" ::"l"(&P.mo), "l"(&P.mwo2) : "memory");
    __syncthreads();
    asm volatile("barrier.cluster.arrive.relaxed.aligned;\nbarrier.cluster.wait.aligned;" ::: "memory");
    const int wg = __shfl_sync(~0u, threadIdx.x >> 7, 0);
    if (wg == 0) {
        if (threadIdx.x == 0) {
            wait_flag(g_flag + 64 + blk, 96);
            asm volatile("fence.proxy.async.global;" ::: "memory");
            if (blockIdx.x == 95)
                for (int i = 0; i < 4; i++) reinterpret_cast<uint4*>(g_flag)[i] = make_uint4(0, 0, 0, 0);
            for (int k = 0, s = 0, ph = 1; k < 32; k++) {
                mbar_wait(empty + 8 * s, ph);
                mbar_expect_tx(full + 8 * s, 32768);
                tma2d(st + s * 32768, &P.mo, (half * 32 + k) * 64, blk * 128, full + 8 * s);
                if (++s == 6) { s = 0; ph ^= 1; }
            }
        } else if (threadIdx.x == 32) {
            for (int k = pr, s = pr, ph = 1; k < 32; k += 3) {
                mbar_wait(emptyb + 8 * s, ph);
                asm volatile("cp.async.bulk.tensor.3d.shared::cluster.global.mbarrier::complete_tx::bytes.multicast::cluster "
                             "[%0], [%1, {%3, %4, %5}], [%2], %6;"
                             ::"r"(st + s * 32768 + 16384), "l"(&P.mwo2), "r"(full + 8 * s), "r"(0), "r"((half * 32 + k) * 64), "r"(idx * 2),
                               "h"((uint16_t)(0x15 << half)) : "memory");
                s += 3;
                if (s >= 6) { s -= 6; ph ^= 1; }
            }
        }
    } else {
        const int cw = wg - 1, lane = threadIdx.x & 31, t = lane & 3;
        float acc[64], fin[32];
#pragma unroll
        for (int i = 0; i < 64; i++) acc[i] = 0.f;
#pragma unroll 1
        for (int k = 0, s = 0, ph = 0, sp = 0; k < 32; k++) {
            mbar_wait_u(full + 8 * s, ph);
            gemm_stage<128, 128, 1>(acc, st + s * 32768, cw, false);
            wg_wait<1>();
            if (k > 0 && k <= 26)
                asm volatile("{\n.reg .pred p;\n.reg .u32 a;\nsetp.eq.u32 p, %3, 0;\nmapa.shared::cluster.u32 a, %1, %2;\n"
                             "@p mbarrier.arrive.relaxed.cta.shared::cta.b64 _, [%0];\n@p mbarrier.arrive.relaxed.cluster.shared::cluster.b64 _, [a];\n}"
                             ::"r"(empty + 8 * sp), "r"(emptyb + 8 * sp), "r"((sp >= 3 ? sp - 3 : sp) * 2 + half), "r"(threadIdx.x & 127) : "memory");
            sp = s;
            if (++s == 6) { s = 0; ph ^= 1; }
        }
        wg_wait<0>();
        const uint32_t xa = st + B_OST + (threadIdx.x - 128) * 16;
        uint32_t ra, rb;
        asm("mapa.shared::cluster.u32 %0, %1, %2;" : "=r"(ra) : "r"(xa), "r"(rank ^ 1));
        asm("mapa.shared::cluster.u32 %0, %1, %2;" : "=r"(rb) : "r"(bar_s), "r"(rank ^ 1));
#pragma unroll
        for (int i = 0; i < 8; i++) {
            float v[4];
#pragma unroll
            for (int j = 0; j < 4; j++) {
                v[j] = half ? acc[4 * i + j] : acc[32 + 4 * i + j];
                fin[4 * i + j] = half ? acc[32 + 4 * i + j] : acc[4 * i + j];
            }
            asm volatile("st.async.weak.shared::cluster.mbarrier::complete_tx::bytes.v4.f32 [%0], {%1,%2,%3,%4}, [%5];"
                         ::"r"(ra + i * 4096), "f"(v[0]), "f"(v[1]), "f"(v[2]), "f"(v[3]), "r"(rb) : "memory");
        }
        mbar_wait_u(bar_s, 0);
#pragma unroll
        for (int i = 0; i < 8; i++) {
            const float4 v = lds128f(xa + i * 4096);
            fin[4 * i] += v.x; fin[4 * i + 1] += v.y; fin[4 * i + 2] += v.z; fin[4 * i + 3] += v.w;
        }
        store_tile<64>(fin, out + (size_t)(blk * 128 + cw * 64 + ((threadIdx.x >> 5) & 3) * 16 + (lane >> 2)) * 2048 + idx * 128 + half * 64 + t * 8, t);
        if (threadIdx.x == 128) TL(4, 1);
    }
}

typedef CUresult (*EncodeFn)(CUtensorMap*, CUtensorMapDataType, cuuint32_t, void*, const cuuint64_t*, const cuuint64_t*,
                             const cuuint32_t*, const cuuint32_t*, CUtensorMapInterleave, CUtensorMapSwizzle,
                             CUtensorMapL2promotion, CUtensorMapFloatOOBfill);

static void map2d(EncodeFn enc, CUtensorMap* m, const void* p, int rows, int cols, int box_rows) {
    cuuint64_t dim[2] = {(cuuint64_t)cols, (cuuint64_t)rows}, str[1] = {(cuuint64_t)cols * 2};
    cuuint32_t box[2] = {64, (cuuint32_t)box_rows}, es[2] = {1, 1};
    enc(m, CU_TENSOR_MAP_DATA_TYPE_BFLOAT16, 2, (void*)p, dim, str, box, es, CU_TENSOR_MAP_INTERLEAVE_NONE,
        CU_TENSOR_MAP_SWIZZLE_128B, CU_TENSOR_MAP_L2_PROMOTION_L2_256B, CU_TENSOR_MAP_FLOAT_OOB_FILL_NONE);
}
static void map3d(EncodeFn enc, CUtensorMap* m, const void* p, int rows, int cols, int box_rows, int nblk) {
    cuuint64_t dim[3] = {64, (cuuint64_t)rows, (cuuint64_t)cols / 64}, str[2] = {(cuuint64_t)cols * 2, 128};
    cuuint32_t box[3] = {64, (cuuint32_t)box_rows, (cuuint32_t)nblk}, es[3] = {1, 1, 1};
    enc(m, CU_TENSOR_MAP_DATA_TYPE_BFLOAT16, 3, (void*)p, dim, str, box, es, CU_TENSOR_MAP_INTERLEAVE_NONE,
        CU_TENSOR_MAP_SWIZZLE_128B, CU_TENSOR_MAP_L2_PROMOTION_L2_256B, CU_TENSOR_MAP_FLOAT_OOB_FILL_NONE);
}

#define USE_PDL 1

extern "C" void kernel_launch(void* const* d_in, const int* in_sizes, int n_in, void* d_out, int out_size) {
    const bf16 *x = (const bf16*)d_in[0], *mem0 = (const bf16*)d_in[1], *Wq = (const bf16*)d_in[2], *Wk = (const bf16*)d_in[3];
    const bf16 *Wv = (const bf16*)d_in[4], *Wo = (const bf16*)d_in[5];
    const bf16 *u = (const bf16*)d_in[7], *Are = (const bf16*)d_in[8], *Aim = (const bf16*)d_in[9], *Bre = (const bf16*)d_in[10];
    const bf16 *Bim = (const bf16*)d_in[11], *Cre = (const bf16*)d_in[12], *Cim = (const bf16*)d_in[13];
    const bf16 *logdt = (const bf16*)d_in[14], *Dsk = (const bf16*)d_in[15];
    bf16* out = (bf16*)d_out;

    void* fn = nullptr;
    cudaDriverEntryPointQueryResult qr;
    cudaGetDriverEntryPoint("cuTensorMapEncodeTiled", &fn, cudaEnableDefault, &qr);
    EncodeFn enc = (EncodeFn)fn;
    void *kv, *o;
    cudaGetSymbolAddress(&kv, g_kv);
    cudaGetSymbolAddress(&o, g_o);
    CUtensorMap mx, mwq, mwk, mwv, mkv2;
    BgParams P;
    map2d(enc, &mx, x, SEQ, DM, 128);
    map2d(enc, &P.mo, o, SEQ, HD, 128);
    map3d(enc, &P.mo2, o, SEQ, HD, 128, 2);
    map3d(enc, &mwq, Wq, DM, HD, 64, 2);
    map3d(enc, &mwk, Wk, DM, HD, 64, 2);
    map3d(enc, &mwv, Wv, DM, HD, 64, 2);
    map3d(enc, &P.mwo4, Wo, HD, DM, 64, 4);
    map3d(enc, &P.mwo2, Wo, HD, DM, 64, 2);
    map3d(enc, &P.mwo1, Wo, HD, DM, 128, 1);
    map3d(enc, &mkv2, kv, SEQ, PW, 32, 2);
    cudaFuncSetAttribute(k_kv, cudaFuncAttributeMaxDynamicSharedMemorySize, GEMM_SMEM);
    cudaFuncSetAttribute(k_bg, cudaFuncAttributeMaxDynamicSharedMemorySize, BG_SMEM);
    cudaFuncSetAttribute(k_tail, cudaFuncAttributeMaxDynamicSharedMemorySize, BG_SMEM);
    cudaFuncSetAttribute(k_chain, cudaFuncAttributeMaxDynamicSharedMemorySize, CHAIN_SMEM);
    cudaFuncSetAttribute(k_s4, cudaFuncAttributeMaxDynamicSharedMemorySize, S4_SMEM);

    cudaStream_t st = cudaStreamPerThread;
    cudaLaunchAttribute pdl[2], cls[1];
    pdl[0].id = cudaLaunchAttributeProgrammaticStreamSerialization;
    pdl[0].val.programmaticStreamSerializationAllowed = 1;
    cls[0].id = cudaLaunchAttributeClusterDimension;
    cls[0].val.clusterDim.x = CLS; cls[0].val.clusterDim.y = 1; cls[0].val.clusterDim.z = 1;
    cudaLaunchConfig_t cfg = {};
    cfg.stream = st; cfg.attrs = cls; cfg.numAttrs = 1;
    cfg.gridDim = dim3(96); cfg.blockDim = dim3(384); cfg.dynamicSmemBytes = GEMM_SMEM;
    cudaLaunchKernelEx(&cfg, k_kv, mx, mwk, mwv, mwq, Wq, Wo, 0);
    pdl[1] = cls[0]; pdl[1].val.clusterDim.x = 2;
    cfg.attrs = pdl; cfg.numAttrs = 2;
    cfg.gridDim = dim3(36);
    cudaLaunchKernelEx(&cfg, k_kv, mx, mwk, mwv, mwq, Wq, Wo, 96);
    cfg.numAttrs = 1;
    cfg.gridDim = dim3(96); cfg.blockDim = dim3(256); cfg.dynamicSmemBytes = CHAIN_SMEM;
    cudaLaunchKernelEx(&cfg, k_chain, mem0, Wq, Wk, Wv, Wo, mkv2);
    cfg.numAttrs = USE_PDL;
    cfg.gridDim = dim3(36); cfg.blockDim = dim3(512); cfg.dynamicSmemBytes = S4_SMEM;
    cudaLaunchKernelEx(&cfg, k_s4, u, Are, Aim, Bre, Bim, Cre, Cim, logdt, Dsk, out);
    cfg.gridDim = dim3(36); cfg.blockDim = dim3(384); cfg.dynamicSmemBytes = BG_SMEM;
    cudaLaunchKernelEx(&cfg, k_bg, P, out);
    cfg.gridDim = dim3(96);
    cudaLaunchKernelEx(&cfg, k_tail, P, out);
}
```

```cpp
#include <cuda_runtime.h>
#include <cuda_bf16.h>
#include <cuda.h>
#include <stdint.h>

typedef __nv_bfloat16 bf16;

constexpr int SEQ = 2048, DM = 1024, HD = 4096, NSEG = 64;

constexpr int PW = 3 * HD;
#define NTA 3
__device__ __align__(1024) bf16 g_kv[(size_t)SEQ * PW];
__device__ __align__(1024) bf16 g_o[(size_t)SEQ * HD];
constexpr int XPAIRS = 128 + NSEG * 4;
__device__ __align__(8192) uint2 g_x[XPAIRS * 1024];
__device__ uint32_t g_home[XPAIRS];
__device__ uint32_t g_side[256];
__device__ __align__(1024) uint32_t g_flag[256];

__device__ __forceinline__ uint32_t smem_u32(const void* p) { return (uint32_t)__cvta_generic_to_shared(p); }
__device__ __forceinline__ void mbar_init(uint32_t bar, uint32_t cnt) {
    asm volatile("mbarrier.init.shared::cta.b64 [%0], %1;" ::"r"(bar), "r"(cnt) : "memory");
}
__device__ __forceinline__ void mbar_expect_tx(uint32_t bar, uint32_t bytes) {
    asm volatile("mbarrier.arrive.expect_tx.shared::cta.b64 _, [%0], %1;" ::"r"(bar), "r"(bytes) : "memory");
}
__device__ __forceinline__ void mbar_arrive(uint32_t bar) {
    asm volatile("mbarrier.arrive.shared::cta.b64 _, [%0];" ::"r"(bar) : "memory");
}
__device__ __forceinline__ bool mbar_try(uint32_t bar, uint32_t parity) {
    uint32_t ok;
    asm volatile("{\n.reg .pred p;\nmbarrier.try_wait.parity.shared::cta.b64 p, [%1], %2;\nselp.u32 %0, 1, 0, p;\n}"
                 : "=r"(ok) : "r"(bar), "r"(parity) : "memory");
    return ok;
}
constexpr int SPIN_LIMIT = 1 << 20;
__device__ __forceinline__ void mbar_wait(uint32_t bar, uint32_t parity) {
    int n = 0;
    while (!mbar_try(bar, parity)) { if (++n > SPIN_LIMIT) __trap(); }
}
__device__ __forceinline__ void mbar_wait_u(uint32_t bar, uint32_t parity) {
    asm volatile("{\n.reg .pred p;\n.reg .u32 n;\n"
                 "mbarrier.try_wait.parity.shared::cta.b64 p, [%0], %1;\n@p bra.uni DONE;\nmov.u32 n, 0;\n"
                 "AGAIN:\nmbarrier.try_wait.parity.shared::cta.b64 p, [%0], %1;\n@p bra.uni DONE;\n"
                 "add.u32 n, n, 1;\nsetp.lt.u32 p, n, 0x100000;\n@p bra.uni AGAIN;\ntrap;\nDONE:\n}"
                 ::"r"(bar), "r"(parity) : "memory");
}
__device__ __forceinline__ void tma2d(uint32_t dst, const CUtensorMap* m, int c0, int c1, uint32_t bar) {
    asm volatile("cp.async.bulk.tensor.2d.shared::cluster.global.mbarrier::complete_tx::bytes [%0], [%1, {%3, %4}], [%2];"
                 ::"r"(dst), "l"(m), "r"(bar), "r"(c0), "r"(c1) : "memory");
}
__device__ __forceinline__ void tma3d(uint32_t dst, const CUtensorMap* m, int c0, int c1, int c2, uint32_t bar) {
    asm volatile("cp.async.bulk.tensor.3d.shared::cluster.global.mbarrier::complete_tx::bytes [%0], [%1, {%3, %4, %5}], [%2];"
                 ::"r"(dst), "l"(m), "r"(bar), "r"(c0), "r"(c1), "r"(c2) : "memory");
}
__device__ __forceinline__ uint32_t pack2(float lo, float hi) {
    uint32_t r;
    asm("cvt.rn.bf16x2.f32 %0, %1, %2;" : "=r"(r) : "f"(hi), "f"(lo));
    return r;
}
__device__ __forceinline__ float bf_lo(uint32_t v) { return __uint_as_float(v << 16); }
__device__ __forceinline__ float bf_hi(uint32_t v) { return __uint_as_float(v & 0xffff0000u); }
__device__ __forceinline__ float bf_round(float x) { return bf_lo(pack2(x, 0.f)); }
__device__ __forceinline__ float ex2(float x) { float y; asm("ex2.approx.ftz.f32 %0, %1;" : "=f"(y) : "f"(x)); return y; }
__device__ __forceinline__ void mma16816(float (&c)[4], uint32_t a0, uint32_t a1, uint32_t a2, uint32_t a3, uint32_t b0, uint32_t b1) {
    asm volatile("mma.sync.aligned.m16n8k16.row.col.f32.bf16.bf16.f32 {%0,%1,%2,%3}, {%4,%5,%6,%7}, {%8,%9}, {%0,%1,%2,%3};"
                 : "+f"(c[0]), "+f"(c[1]), "+f"(c[2]), "+f"(c[3]) : "r"(a0), "r"(a1), "r"(a2), "r"(a3), "r"(b0), "r"(b1));
}
__device__ __forceinline__ void mma1688(float (&c)[4], uint32_t a0, uint32_t a1, uint32_t b0) {
    asm volatile("mma.sync.aligned.m16n8k8.row.col.f32.bf16.bf16.f32 {%0,%1,%2,%3}, {%4,%5}, {%6}, {%0,%1,%2,%3};"
                 : "+f"(c[0]), "+f"(c[1]), "+f"(c[2]), "+f"(c[3]) : "r"(a0), "r"(a1), "r"(b0));
}
__device__ __forceinline__ void ldsm4(uint32_t (&r)[4], uint32_t a) {
    asm volatile("ldmatrix.sync.aligned.m8n8.x4.shared.b16 {%0,%1,%2,%3}, [%4];"
                 : "=r"(r[0]), "=r"(r[1]), "=r"(r[2]), "=r"(r[3]) : "r"(a) : "memory");
}
__device__ __forceinline__ void ldsm4t(uint32_t (&r)[4], uint32_t a) {
    asm volatile("ldmatrix.sync.aligned.m8n8.x4.trans.shared.b16 {%0,%1,%2,%3}, [%4];"
                 : "=r"(r[0]), "=r"(r[1]), "=r"(r[2]), "=r"(r[3]) : "r"(a) : "memory");
}
__device__ __forceinline__ void stsm4t(uint32_t a, uint32_t r0, uint32_t r1, uint32_t r2, uint32_t r3) {
    asm volatile("stmatrix.sync.aligned.m8n8.x4.trans.shared.b16 [%0], {%1,%2,%3,%4};"
                 ::"r"(a), "r"(r0), "r"(r1), "r"(r2), "r"(r3) : "memory");
}
__device__ __forceinline__ void lds128(uint32_t (&r)[4], uint32_t a) {
    asm volatile("ld.shared.v4.u32 {%0,%1,%2,%3}, [%4];" : "=r"(r[0]), "=r"(r[1]), "=r"(r[2]), "=r"(r[3]) : "r"(a) : "memory");
}
__device__ __forceinline__ float4 lds128f(uint32_t a) {
    float4 v;
    asm volatile("ld.shared.v4.f32 {%0,%1,%2,%3}, [%4];" : "=f"(v.x), "=f"(v.y), "=f"(v.z), "=f"(v.w) : "r"(a) : "memory");
    return v;
}
__device__ __forceinline__ float2 lds64f(uint32_t a) {
    float2 v;
    asm volatile("ld.shared.v2.f32 {%0,%1}, [%2];" : "=f"(v.x), "=f"(v.y) : "r"(a) : "memory");
    return v;
}
__device__ __forceinline__ uint32_t lds32(uint32_t a) {
    uint32_t v;
    asm volatile("ld.shared.u32 %0, [%1];" : "=r"(v) : "r"(a) : "memory");
    return v;
}
__device__ __forceinline__ void sts128(uint32_t a, uint32_t r0, uint32_t r1, uint32_t r2, uint32_t r3) {
    asm volatile("st.shared.v4.u32 [%0], {%1,%2,%3,%4};" ::"r"(a), "r"(r0), "r"(r1), "r"(r2), "r"(r3) : "memory");
}
__device__ __forceinline__ void sts64(uint32_t a, uint32_t r0, uint32_t r1) {
    asm volatile("st.shared.v2.u32 [%0], {%1,%2};" ::"r"(a), "r"(r0), "r"(r1) : "memory");
}
__device__ __forceinline__ void sts32f(uint32_t a, float r0) {
    asm volatile("st.shared.f32 [%0], %1;" ::"r"(a), "f"(r0) : "memory");
}
__device__ __forceinline__ void st_rlx64(uint2* p, uint32_t x, uint32_t y) {
    asm volatile("{\n.reg .b64 t;\nmov.b64 t, {%1,%2};\nst.relaxed.gpu.global.b64 [%0], t;\n}" ::"l"(p), "r"(x), "r"(y) : "memory");
}
__device__ __forceinline__ uint32_t ld_acq32(const uint32_t* p) {
    uint32_t v;
    asm volatile("ld.acquire.gpu.global.u32 %0, [%1];" : "=r"(v) : "l"(p) : "memory");
    return v;
}
__device__ __forceinline__ void wait_flag(const uint32_t* p, uint32_t need) {
    int n = 0;
    while (ld_acq32(p) < need) { __nanosleep(200); if (++n > SPIN_LIMIT) __trap(); }
}
__device__ __forceinline__ void bar_sync(int id, int n) { asm volatile("bar.sync %0, %1;" ::"r"(id), "r"(n) : "memory"); }
__device__ __forceinline__ void wg_fence() { asm volatile("wgmma.fence.sync.aligned;" ::: "memory"); }
__device__ __forceinline__ void wg_commit() { asm volatile("wgmma.commit_group.sync.aligned;" ::: "memory"); }
template <int N> __device__ __forceinline__ void wg_wait() { asm volatile("wgmma.wait_group.sync.aligned %0;" ::"n"(N) : "memory"); }
__device__ __forceinline__ uint64_t desc_sw128(uint32_t addr, uint32_t lbo, uint32_t sbo) {
    return (uint64_t)((addr & 0x3FFFF) >> 4) | ((uint64_t)(lbo >> 4) << 16) | ((uint64_t)(sbo >> 4) << 32) | (1ull << 62);
}
__device__ __forceinline__ void quad_transpose(uint32_t& r0, uint32_t& r1, uint32_t& r2, uint32_t& r3, int t) {
    const bool o = t & 1, h = t & 2;
    uint32_t s0 = __shfl_xor_sync(~0u, o ? r0 : r1, 1), s1 = __shfl_xor_sync(~0u, o ? r2 : r3, 1);
    uint32_t a0 = o ? s0 : r0, a1 = o ? r1 : s0, a2 = o ? s1 : r2, a3 = o ? r3 : s1;
    s0 = __shfl_xor_sync(~0u, h ? a0 : a2, 2); s1 = __shfl_xor_sync(~0u, h ? a1 : a3, 2);
    r0 = h ? s0 : a0; r1 = h ? s1 : a1; r2 = h ? a2 : s0; r3 = h ? a3 : s1;
}

__device__ __forceinline__ void wgmma_n256(float (&d)[128], uint64_t da, uint64_t db, int sd) {
    asm volatile("{\n.reg .pred p;\nsetp.ne.b32 p, %130, 0;\n"
        "wgmma.mma_async.sync.aligned.m64n256k16.f32.bf16.bf16 "
        "{%0,%1,%2,%3,%4,%5,%6,%7,%8,%9,%10,%11,%12,%13,%14,%15,"
        "%16,%17,%18,%19,%20,%21,%22,%23,%24,%25,%26,%27,%28,%29,%30,%31,"
        "%32,%33,%34,%35,%36,%37,%38,%39,%40,%41,%42,%43,%44,%45,%46,%47,"
        "%48,%49,%50,%51,%52,%53,%54,%55,%56,%57,%58,%59,%60,%61,%62,%63,"
        "%64,%65,%66,%67,%68,%69,%70,%71,%72,%73,%74,%75,%76,%77,%78,%79,"
        "%80,%81,%82,%83,%84,%85,%86,%87,%88,%89,%90,%91,%92,%93,%94,%95,"
        "%96,%97,%98,%99,%100,%101,%102,%103,%104,%105,%106,%107,%108,%109,%110,%111,"
        "%112,%113,%114,%115,%116,%117,%118,%119,%120,%121,%122,%123,%124,%125,%126,%127}, %128, %129, p, 1, 1, 0, 1;\n}\n"
        : "+f"(d[0]), "+f"(d[1]), "+f"(d[2]), "+f"(d[3]), "+f"(d[4]), "+f"(d[5]), "+f"(d[6]), "+f"(d[7]),
          "+f"(d[8]), "+f"(d[9]), "+f"(d[10]), "+f"(d[11]), "+f"(d[12]), "+f"(d[13]), "+f"(d[14]), "+f"(d[15]),
          "+f"(d[16]), "+f"(d[17]), "+f"(d[18]), "+f"(d[19]), "+f"(d[20]), "+f"(d[21]), "+f"(d[22]), "+f"(d[23]),
          "+f"(d[24]), "+f"(d[25]), "+f"(d[26]), "+f"(d[27]), "+f"(d[28]), "+f"(d[29]), "+f"(d[30]), "+f"(d[31]),
          "+f"(d[32]), "+f"(d[33]), "+f"(d[34]), "+f"(d[35]), "+f"(d[36]), "+f"(d[37]), "+f"(d[38]), "+f"(d[39]),
          "+f"(d[40]), "+f"(d[41]), "+f"(d[42]), "+f"(d[43]), "+f"(d[44]), "+f"(d[45]), "+f"(d[46]), "+f"(d[47]),
          "+f"(d[48]), "+f"(d[49]), "+f"(d[50]), "+f"(d[51]), "+f"(d[52]), "+f"(d[53]), "+f"(d[54]), "+f"(d[55]),
          "+f"(d[56]), "+f"(d[57]), "+f"(d[58]), "+f"(d[59]), "+f"(d[60]), "+f"(d[61]), "+f"(d[62]), "+f"(d[63]),
          "+f"(d[64]), "+f"(d[65]), "+f"(d[66]), "+f"(d[67]), "+f"(d[68]), "+f"(d[69]), "+f"(d[70]), "+f"(d[71]),
          "+f"(d[72]), "+f"(d[73]), "+f"(d[74]), "+f"(d[75]), "+f"(d[76]), "+f"(d[77]), "+f"(d[78]), "+f"(d[79]),
          "+f"(d[80]), "+f"(d[81]), "+f"(d[82]), "+f"(d[83]), "+f"(d[84]), "+f"(d[85]), "+f"(d[86]), "+f"(d[87]),
          "+f"(d[88]), "+f"(d[89]), "+f"(d[90]), "+f"(d[91]), "+f"(d[92]), "+f"(d[93]), "+f"(d[94]), "+f"(d[95]),
          "+f"(d[96]), "+f"(d[97]), "+f"(d[98]), "+f"(d[99]), "+f"(d[100]), "+f"(d[101]), "+f"(d[102]), "+f"(d[103]),
          "+f"(d[104]), "+f"(d[105]), "+f"(d[106]), "+f"(d[107]), "+f"(d[108]), "+f"(d[109]), "+f"(d[110]), "+f"(d[111]),
          "+f"(d[112]), "+f"(d[113]), "+f"(d[114]), "+f"(d[115]), "+f"(d[116]), "+f"(d[117]), "+f"(d[118]), "+f"(d[119]),
          "+f"(d[120]), "+f"(d[121]), "+f"(d[122]), "+f"(d[123]), "+f"(d[124]), "+f"(d[125]), "+f"(d[126]), "+f"(d[127])
        : "l"(da), "l"(db), "r"(sd));
}

__device__ __forceinline__ void wgmma_n128(float (&d)[64], uint64_t da, uint64_t db, int sd) {
    asm volatile("{\n.reg .pred p;\nsetp.ne.b32 p, %66, 0;\n"
        "wgmma.mma_async.sync.aligned.m64n128k16.f32.bf16.bf16 "
        "{%0,%1,%2,%3,%4,%5,%6,%7,%8,%9,%10,%11,%12,%13,%14,%15,"
        "%16,%17,%18,%19,%20,%21,%22,%23,%24,%25,%26,%27,%28,%29,%30,%31,"
        "%32,%33,%34,%35,%36,%37,%38,%39,%40,%41,%42,%43,%44,%45,%46,%47,"
        "%48,%49,%50,%51,%52,%53,%54,%55,%56,%57,%58,%59,%60,%61,%62,%63}, %64, %65, p, 1, 1, 0, 1;\n}\n"
        : "+f"(d[0]), "+f"(d[1]), "+f"(d[2]), "+f"(d[3]), "+f"(d[4]), "+f"(d[5]), "+f"(d[6]), "+f"(d[7]),
          "+f"(d[8]), "+f"(d[9]), "+f"(d[10]), "+f"(d[11]), "+f"(d[12]), "+f"(d[13]), "+f"(d[14]), "+f"(d[15]),
          "+f"(d[16]), "+f"(d[17]), "+f"(d[18]), "+f"(d[19]), "+f"(d[20]), "+f"(d[21]), "+f"(d[22]), "+f"(d[23]),
          "+f"(d[24]), "+f"(d[25]), "+f"(d[26]), "+f"(d[27]), "+f"(d[28]), "+f"(d[29]), "+f"(d[30]), "+f"(d[31]),
          "+f"(d[32]), "+f"(d[33]), "+f"(d[34]), "+f"(d[35]), "+f"(d[36]), "+f"(d[37]), "+f"(d[38]), "+f"(d[39]),
          "+f"(d[40]), "+f"(d[41]), "+f"(d[42]), "+f"(d[43]), "+f"(d[44]), "+f"(d[45]), "+f"(d[46]), "+f"(d[47]),
          "+f"(d[48]), "+f"(d[49]), "+f"(d[50]), "+f"(d[51]), "+f"(d[52]), "+f"(d[53]), "+f"(d[54]), "+f"(d[55]),
          "+f"(d[56]), "+f"(d[57]), "+f"(d[58]), "+f"(d[59]), "+f"(d[60]), "+f"(d[61]), "+f"(d[62]), "+f"(d[63])
        : "l"(da), "l"(db), "r"(sd));
}

__device__ __forceinline__ void wgmma_n64(float (&d)[32], uint64_t da, uint64_t db, int sd) {
    asm volatile("{\n.reg .pred p;\nsetp.ne.b32 p, %34, 0;\n"
        "wgmma.mma_async.sync.aligned.m64n64k16.f32.bf16.bf16 "
        "{%0,%1,%2,%3,%4,%5,%6,%7,%8,%9,%10,%11,%12,%13,%14,%15,"
        "%16,%17,%18,%19,%20,%21,%22,%23,%24,%25,%26,%27,%28,%29,%30,%31}, %32, %33, p, 1, 1, 0, 1;\n}\n"
        : "+f"(d[0]), "+f"(d[1]), "+f"(d[2]), "+f"(d[3]), "+f"(d[4]), "+f"(d[5]), "+f"(d[6]), "+f"(d[7]),
          "+f"(d[8]), "+f"(d[9]), "+f"(d[10]), "+f"(d[11]), "+f"(d[12]), "+f"(d[13]), "+f"(d[14]), "+f"(d[15]),
          "+f"(d[16]), "+f"(d[17]), "+f"(d[18]), "+f"(d[19]), "+f"(d[20]), "+f"(d[21]), "+f"(d[22]), "+f"(d[23]),
          "+f"(d[24]), "+f"(d[25]), "+f"(d[26]), "+f"(d[27]), "+f"(d[28]), "+f"(d[29]), "+f"(d[30]), "+f"(d[31])
        : "l"(da), "l"(db), "r"(sd));
}

constexpr int STAGE_BYTES = 49152, NSTAGE = 4;
constexpr int GEMM_SMEM = NSTAGE * STAGE_BYTES + 128;

struct GemmSmem { uint32_t st, full, empty; };
__device__ __forceinline__ GemmSmem gemm_setup(uint8_t* raw, int releases) {
    GemmSmem g;
    g.st = smem_u32(raw);
    if (g.st & 1023) __trap();
    g.full = g.st + NSTAGE * STAGE_BYTES; g.empty = g.full + 64;
    if (threadIdx.x == 0) {
        for (int s = 0; s < NSTAGE; s++) { mbar_init(g.full + 8 * s, 1); mbar_init(g.empty + 8 * s, releases); }
        asm volatile("fence.mbarrier_init.release.cluster;" ::: "memory");
        asm volatile("fence.proxy.async.shared::cta;" ::: "memory");
    }
    __syncthreads();
    return g;
}
__device__ __forceinline__ void mbar_arrive_one(uint32_t bar, uint32_t who) {
    asm volatile("{\n.reg .pred p;\nsetp.eq.u32 p, %1, 0;\n@p mbarrier.arrive.shared::cta.b64 _, [%0];\n}" ::"r"(bar), "r"(who) : "memory");
}
template <int BM, int BN, int KPS, typename ACC>
__device__ __forceinline__ void gemm_stage(ACC& acc, uint32_t stage, int wg, bool first) {
    const uint64_t da = desc_sw128(stage + wg * 8192, 16, 1024);
    const uint64_t db = desc_sw128(stage + KPS * BM * 128, 8192, 1024);
    wg_fence();
#pragma unroll
    for (int k = 0; k < 4 * KPS; k++) {
        const uint64_t a = da + (k >> 2) * (BM * 8) + (k & 3) * 2, b = db + k * 128;
        if constexpr (BN == 256) wgmma_n256(acc, a, b, first && k == 0 ? 0 : 1);
        else if constexpr (BN == 128) wgmma_n128(acc, a, b, first && k == 0 ? 0 : 1);
        else wgmma_n64(acc, a, b, first && k == 0 ? 0 : 1);
    }
    wg_commit();
}

__device__ __forceinline__ void kv_store_unit(const uint32_t (&pk)[64], int u, bf16* dst, int t) {
    const int G = (u >> 2) * 2 + (u & 1), hh = (u >> 1) & 1;
    uint32_t r0 = pk[(4 * G + 0) * 2 + hh], r1 = pk[(4 * G + 1) * 2 + hh], r2 = pk[(4 * G + 2) * 2 + hh], r3 = pk[(4 * G + 3) * 2 + hh];
    quad_transpose(r0, r1, r2, r3, t);
#define KVST ".cs"
    asm volatile("st.global" KVST ".v4.u32 [%0], {%1,%2,%3,%4};" ::"l"(dst + (size_t)hh * 8 * PW + G * 32), "r"(r0), "r"(r1), "r"(r2), "r"(r3) : "memory");
}

__device__ __forceinline__ uint32_t near_page(int pair, int line) {
    uint32_t best[2] = {~0u, ~0u};
    for (int i = 0; i < 4; i++)
        reinterpret_cast<uint4*>(g_x + pair * 1024 + (i >> 1) * 512 + line * 16)[i & 1] = make_uint4(~0u, ~0u, ~0u, ~0u);
#pragma unroll 1
#define PMIN 8
#define PMAX 16
    for (int i = 0; i < PMAX; i++) {
        if (i >= PMIN && max(best[0], best[1]) - min(best[0], best[1]) > 110 && max(best[0], best[1]) - min(best[0], best[1]) < 300) break;
        uint32_t t0, t1, v;
        asm volatile("mov.u32 %0, %%clock;" : "=r"(t0)::"memory");
        asm volatile("atom.relaxed.gpu.global.or.b32 %0, [%1], -1;" : "=r"(v) : "l"(g_x + pair * 1024 + (i & 1) * 512 + line * 16) : "memory");
        asm volatile("{\n.reg .pred p;\nsetp.ne.u32 p, %1, 0x12345;\nmov.u32 %0, -1;\n@p mov.u32 %0, %%clock;\n}" : "=r"(t1) : "r"(v) : "memory");
        if (i & 1) best[1] = min(best[1], t1 - t0); else best[0] = min(best[0], t1 - t0);
    }
    return best[1] < best[0];
}
__device__ __forceinline__ void map_pages(int c) {
    uint32_t smid;
    asm("mov.u32 %0, %%smid;" : "=r"(smid));
    const uint32_t side = near_page(0, c & 31);
    g_side[smid & 255] = side;
    for (int p = c; p < XPAIRS; p += 132) g_home[p] = near_page(p, 0) ^ side;
}

__device__ __forceinline__ void kv_tile(int c, int n, int& m, int& nb) {
    if (c < 96) { m = (c & 3) + 4 * n; nb = c >> 2; }
    else {
        const int i = ((c - 96) >> 1) + 18 * n, j = i - 48 * NTA, p = j < 0 ? i / 24 : 2 * NTA + j / 48;
        m = 2 * p + (c & 1); nb = j < 0 ? 24 + i % 24 : j % 48;
    }
}

__global__ void __launch_bounds__(384, 1)
k_kv(const __grid_constant__ CUtensorMap mx, const __grid_constant__ CUtensorMap mwk, const __grid_constant__ CUtensorMap mwv,
     const __grid_constant__ CUtensorMap mwq, const bf16* __restrict__ Wo, int c0) {
    extern __shared__ __align__(1024) uint8_t smem_gemm[];
    const int c = c0 + blockIdx.x, ntile = c < 96 ? NTA : (384 - 48 * NTA + 17 - ((c - 96) >> 1)) / 18;
    if (c != 96) asm volatile("griddepcontrol.launch_dependents;");
    const uint32_t bar_done = smem_u32(smem_gemm) + NSTAGE * STAGE_BYTES + 96;
    if (threadIdx.x == 0) { mbar_init(bar_done, 8); mbar_init(bar_done + 8, 8); }
    GemmSmem g = gemm_setup(smem_gemm, 4);
    uint32_t rank, peer_empty;
    asm("mov.u32 %0, %%cluster_ctarank;" : "=r"(rank));
    asm("mapa.shared::cluster.u32 %0, %1, %2;" : "=r"(peer_empty) : "r"(g.empty), "r"(rank ^ 1));
    asm volatile("barrier.cluster.arrive.relaxed.aligned;\nbarrier.cluster.wait.aligned;" ::: "memory");
    auto release = [&](int s) {
        asm volatile("{\n.reg .pred p;\nsetp.eq.u32 p, %2, 0;\n@p mbarrier.arrive.relaxed.cta.shared::cta.b64 _, [%0];\n"
                     "@p mbarrier.arrive.relaxed.cluster.shared::cluster.b64 _, [%1];\n}"
                     ::"r"(g.empty + 8 * s), "r"(peer_empty + 8 * s), "r"(threadIdx.x & 127) : "memory");
    };
    const int wg = __shfl_sync(~0u, threadIdx.x >> 7, 0);
    if (wg == 0) {
        asm volatile("setmaxnreg.dec.sync.aligned.u32 40;");
        if (threadIdx.x == 0) {
            for (int it = 0; it < ntile * 16; it++) {
                const int s = it & 3, kb = it & 15;
                int m, nb;
                kv_tile(c, it >> 4, m, nb);
                mbar_wait(g.empty + 8 * s, ((it >> 2) & 1) ^ 1);
                mbar_expect_tx(g.full + 8 * s, STAGE_BYTES);
                tma2d(g.st + s * STAGE_BYTES, &mx, kb * 64, m * 128, g.full + 8 * s);
                asm volatile("cp.async.bulk.tensor.3d.shared::cluster.global.mbarrier::complete_tx::bytes.multicast::cluster "
                             "[%0], [%1, {%3, %4, %5}], [%2], %6;"
                             ::"r"(g.st + s * STAGE_BYTES + 16384 + (c & 1) * 16384), "l"(nb < 16 ? &mwk : nb < 32 ? &mwv : &mwq), "r"(g.full + 8 * s),
                               "r"(0), "r"(kb * 64), "r"((nb & 15) * 4 + (c & 1) * 2), "h"((uint16_t)(3u << (rank & ~1u))) : "memory");
#define PF0 (16 * NTA - 22)
                if (c < 96 && it >= PF0 && (it - PF0) * 96 + c < 2048)
                    asm volatile("cp.async.bulk.prefetch.L2.global [%0], 4096;" ::"l"((const char*)Wo + ((it - PF0) * 96 + c) * 4096) : "memory");
            }
        } else if (threadIdx.x == 32) {
            if (c == 96) {
                for (int i = 4; i < 64; i++) reinterpret_cast<uint4*>(g_flag)[i] = make_uint4(0, 0, 0, 0);
                asm volatile("fence.acq_rel.gpu;\ngriddepcontrol.launch_dependents;\ngriddepcontrol.wait;\n"
                             "fence.acq_rel.gpu;\nred.relaxed.gpu.global.add.u32 [%0], 1;" ::"l"(g_flag + 8) : "memory");
            }
        } else if (threadIdx.x == 64) {
            for (int n = 0; n < (c < 96 ? 0 : ntile); n++) {
                int m, nb;
                kv_tile(c, n, m, nb);
                mbar_wait(bar_done + (n & 1) * 8, (n >> 1) & 1);
                asm volatile("fence.acq_rel.gpu;\nred.relaxed.gpu.global.add.u32 [%0], 1;" ::"l"(g_flag + (m >> 1)) : "memory");
            }
        } else if (threadIdx.x >= 96) {
            mbar_wait(g.full + 24, 0);
            const uint4 ones = make_uint4(~0u, ~0u, ~0u, ~0u);
            for (int i = c * 32 + threadIdx.x - 96; i < XPAIRS * 512; i += 132 * 32) reinterpret_cast<uint4*>(g_x)[i] = ones;
            __syncwarp();
            if (threadIdx.x == 96) {
                map_pages(c);
                if (c >= 96) asm volatile("fence.acq_rel.gpu;\nred.relaxed.gpu.global.add.u32 [%0], 1;" ::"l"(g_flag + 8) : "memory");
            }
        }
    } else {
        asm volatile("setmaxnreg.inc.sync.aligned.u32 232;");
        const int cw = wg - 1, lane = threadIdx.x & 31, t = lane & 3;
        bf16* const dst0 = g_kv + (size_t)(cw * 64 + ((threadIdx.x >> 5) & 3) * 16 + (lane >> 2)) * PW + t * 8;
        bf16* dst = dst0;
        float acc[128];
        uint32_t pk[64];
#pragma unroll 1
        for (int tile = 0; tile < ntile; tile++) {
#pragma unroll
            for (int kb = 0; kb < 16; kb++) {
                mbar_wait_u(g.full + 8 * (kb & 3), (kb >> 2) & 1);
                gemm_stage<128, 256, 1>(acc, g.st + (kb & 3) * STAGE_BYTES, cw, kb == 0);
                if (tile > 0) {
                    kv_store_unit(pk, kb, dst, t);
                    if (kb == 15) { __syncwarp(); mbar_arrive_one(bar_done + (~tile & 1) * 8, lane); }
                }
                if (kb > 0) {
                    wg_wait<1>();
                    if (kb <= 12 || tile < ntile - 1) release((kb - 1) & 3);
                }
            }
            wg_wait<0>();
            if (tile < ntile - 1) release(3);
#pragma unroll
            for (int i = 0; i < 64; i++) pk[i] = pack2(acc[2 * i], acc[2 * i + 1]);
            int m, nb;
            kv_tile(c, tile, m, nb);
            dst = dst0 + (size_t)m * 128 * PW + nb * 256;
        }
#pragma unroll
        for (int u = 0; u < 16; u++) kv_store_unit(pk, u, dst, t);
        __syncwarp();
        mbar_arrive_one(bar_done + (~ntile & 1) * 8, lane);
    }
}

constexpr int NS1 = 31;
#define RB1 4
#define PFC 4
constexpr int C_W1 = 0;
constexpr int C_W2 = C_W1 + 8 * NS1 * 512;
constexpr int C_KV = C_W2 + 14 * 8 * 512;
constexpr int C_RED = C_KV + 16384;
constexpr int C_QKV = C_RED + 64 * 272;
constexpr int QKV_SZ = 3 * 8 * 272;
constexpr int C_SC = C_RED;
constexpr int C_OB = C_SC + 2 * 8 * 52 * 4;
constexpr int C_BAR = C_QKV + 2 * QKV_SZ;
__host__ __device__ constexpr int smem_idx(int ks, int j) {
    return ks == 0 ? j : ks < 3 ? (j < 4 ? 4 + 4 * ks + j : -1) : (j < 3 ? 7 + 3 * ks + j : -1);
}
constexpr int CHAIN_SMEM = C_BAR + 64;

#define DLY3 10
#define DLY1 4
#define DLY0 4
#define DLY1A 11
#define DLY0A 0
#define DLY1B 4
#define PFD 3
#define DLYW 4
#define DLYQ 3
template <int N> __device__ __forceinline__ uint32_t delayed(uint32_t x, uint32_t self) {
    uint32_t p = self;
#pragma unroll
    for (int i = 0; i < N; i++) asm volatile("ld.volatile.shared.u32 %0, [%0];" : "+r"(p)::"memory");
    return x + (p - self);
}
__device__ __forceinline__ int fresh(int x) { asm volatile("mov.b32 %0, %0;" : "+r"(x)); return x; }
__device__ __forceinline__ void lds128v(uint32_t (&r)[4], uint32_t a) {
    asm volatile("ld.volatile.shared.v4.u32 {%0,%1,%2,%3}, [%4];" : "=r"(r[0]), "=r"(r[1]), "=r"(r[2]), "=r"(r[3]) : "r"(a) : "memory");
}
__device__ __forceinline__ uint2 lds64(uint32_t a) {
    uint2 v;
    asm volatile("ld.shared.v2.u32 {%0,%1}, [%2];" : "=r"(v.x), "=r"(v.y) : "r"(a) : "memory");
    return v;
}
#define LDQ ".L1::no_allocate"
__device__ __forceinline__ uint4 ldw128(const void* p) {
    uint4 v;
    asm volatile("ld.global.nc" LDQ ".v4.u32 {%0,%1,%2,%3}, [%4];" : "=r"(v.x), "=r"(v.y), "=r"(v.z), "=r"(v.w) : "l"(p));
    return v;
}
#define P8_LD(i) "ld.relaxed.gpu.global.b64 d" #i ", [src + " #i " * 256];\n"
#define P8_X(i) "mov.b64 {x" #i ", y" #i "}, d" #i ";\n"
#define P8_HEAD(SRC) "{\n.reg .pred p, q;\n.reg .b64 src, d<8>;\n.reg .b32 n, x<8>, y<8>, m0, m1;\nmov.b64 src, " SRC ";\n"         \
                P8_LD(0) P8_LD(1) P8_LD(2) P8_LD(3) P8_LD(4) P8_LD(5) P8_LD(6) P8_LD(7) "mov.u32 n, 0;\nCHECK:\n" \
                P8_X(0) P8_X(1) P8_X(2) P8_X(3) P8_X(4) P8_X(5) P8_X(6) P8_X(7)
#define P8_VOTE "vote.sync.all.pred p, p, -1;\n@p bra.uni DONE;\n"
#define P8_TAIL "add.u32 n, n, 1;\nsetp.lt.u32 p, n, 0x100000;\n@p bra.uni CHECK;\ntrap;\nDONE:\n"
#define S8_LD(i) "ld.relaxed.gpu.global.b64 %" #i ", [%8 + " #i " * 256];\n"
__device__ __forceinline__ void fetch_state(uint64_t (&d)[8], const void* src) {
    asm volatile(S8_LD(0) S8_LD(1) S8_LD(2) S8_LD(3) S8_LD(4) S8_LD(5) S8_LD(6) S8_LD(7)
                 : "=&l"(d[0]), "=&l"(d[1]), "=&l"(d[2]), "=&l"(d[3]), "=&l"(d[4]), "=&l"(d[5]), "=&l"(d[6]), "=&l"(d[7]) : "l"(src) : "memory");
}
__device__ __forceinline__ void settle_state(uint64_t (&d)[8], const void* src) {
#define S8_X(i) "mov.b64 {x" #i ", _}, %" #i ";\n"
#define S8_R(i) "setp.eq.u32 q, x" #i ", 0xffffffff;\n@q " S8_LD(i)
    asm volatile("{\n.reg .pred p, q;\n.reg .b32 n, x<8>, m0, m1;\nmov.u32 n, 0;\nCHECK:\n"
                 S8_X(0) S8_X(1) S8_X(2) S8_X(3) S8_X(4) S8_X(5) S8_X(6) S8_X(7)
                 "max.u32 m0, x0, x1;\nmax.u32 m0, m0, x2;\nmax.u32 m1, x3, x4;\nmax.u32 m1, m1, x5;\nmax.u32 m0, m0, x6;\n"
                 "max.u32 m0, m0, x7;\nmax.u32 m0, m0, m1;\nsetp.ne.u32 p, m0, 0xffffffff;\n" P8_VOTE
                 S8_R(0) S8_R(1) S8_R(2) S8_R(3) S8_R(4) S8_R(5) S8_R(6) S8_R(7) P8_TAIL "}"
                 : "+l"(d[0]), "+l"(d[1]), "+l"(d[2]), "+l"(d[3]), "+l"(d[4]), "+l"(d[5]), "+l"(d[6]), "+l"(d[7]) : "l"(src) : "memory");
}
__device__ __forceinline__ uint64_t poll_sum(const void* src, uint32_t tag, uint32_t sel) {
#define P8_RT(i) "lop3.b32 m0, x" #i ", %2, 1, 0x28;\nsetp.ne.u32 q, m0, 0;\n@q " P8_LD(i)
#define P8_MMA(c, i, z) "mma.sync.aligned.m16n8k8.row.col.f32.bf16.bf16.f32 {" #c "0," #c "1," #c "2," #c "3}, {x" #i ", y" #i "}, {%3}, {" #z "0," #z "1," #z "2," #z "3};\n"
    uint64_t r;
    asm volatile(P8_HEAD("%1") "{\n.reg .f32 a<4>, b<4>, z<4>;\nmov.f32 z0, 0f00000000;\nmov.f32 z1, z0;\nmov.f32 z2, z0;\nmov.f32 z3, z0;\n"
                 P8_MMA(a, 0, z) P8_MMA(b, 1, z) P8_MMA(a, 2, a) P8_MMA(b, 3, b) P8_MMA(a, 4, a) P8_MMA(b, 5, b) P8_MMA(a, 6, a) P8_MMA(b, 7, b)
                 "add.f32 a0, a0, b0;\nadd.f32 a1, a1, b1;\nadd.f32 a2, a2, b2;\nadd.f32 a3, a3, b3;\n"
                 "cvt.rn.bf16x2.f32 m0, a1, a0;\ncvt.rn.bf16x2.f32 m1, a3, a2;\nmov.b64 %0, {m0, m1};\n}\n"
                 "lop3.b32 m0, x0, x1, %2, 0x7e;\nlop3.b32 m1, x2, x3, %2, 0x7e;\nlop3.b32 m0, m0, x4, %2, 0xf6;\n"
                 "lop3.b32 m1, m1, x5, %2, 0xf6;\nlop3.b32 m0, m0, x6, %2, 0xf6;\nlop3.b32 m1, m1, x7, %2, 0xf6;\n"
                 "lop3.b32 m0, m0, m1, 1, 0xa8;\nsetp.eq.u32 p, m0, 0;\n" P8_VOTE
                 P8_RT(0) P8_RT(1) P8_RT(2) P8_RT(3) P8_RT(4) P8_RT(5) P8_RT(6) P8_RT(7) P8_TAIL "}"
                 : "=&l"(r) : "l"(src), "r"(tag), "r"(sel) : "memory");
    return r;
}
__device__ __forceinline__ uint32_t wait_count_u(const uint32_t* p, uint32_t need) {
    uint32_t v;
    asm volatile("{\n.reg .pred p;\n.reg .u32 n;\nmov.u32 n, 0;\nAGAIN:\nld.acquire.gpu.global.u32 %0, [%1];\nsetp.ge.u32 p, %0, %2;\n"
                 "vote.sync.all.pred p, p, -1;\n@p bra.uni DONE;\nadd.u32 n, n, 1;\nsetp.lt.u32 p, n, 0x100000;\n@p bra.uni AGAIN;\ntrap;\n"
                 "DONE:\nfence.proxy.async.global;\n}" : "=&r"(v) : "l"(p), "r"(need) : "memory");
    return v;
}
__device__ __forceinline__ uint32_t movm(uint32_t x) { asm volatile("movmatrix.sync.aligned.m8n8.trans.b16 %0, %0;" : "+r"(x)); return x; }
template <int NK, typename F>
__device__ __forceinline__ void attend(uint32_t sb, uint32_t lm, uint32_t qs, uint32_t xq, int i8, int lane, bf16* dst, F mid) {
    const int r8 = lane & 7, m4 = lane >> 3;
    const float sl2e = 0.08838834764831845f * 1.4426950408889634f;
    const uint32_t lk = sb + C_KV + ((m4 & 1) * 8 + r8) * 128 + (((m4 >> 1) ^ r8) << 4);
    const uint32_t lkm = sb + xq + (8 + r8) * 272 + (m4 & 1) * 32 + (m4 >> 1) * 16;
    asm volatile("cp.async.wait_all;" ::: "memory");
    __syncwarp();
    float x[4][4];
#pragma unroll
    for (int i = 0; i < 4; i++) x[i][0] = x[i][1] = x[i][2] = x[i][3] = 0.f;
#pragma unroll
    for (int kp = 0; kp < 4; kp++) {
        uint32_t q[4], a[4];
        ldsm4(q, lm + qs + kp * 64);
        ldsm4(a, lkm + kp * 64);
        mma16816(x[2], a[0], a[1], a[2], a[3], q[0], q[1]);
        mma16816(x[3], a[0], a[1], a[2], a[3], q[2], q[3]);
#pragma unroll
        for (int u = 0; u < 4; u++) {
            if ((u & 1) >= NK) continue;
            ldsm4(a, (lk ^ (((kp & 1) * 2 + (u >> 1)) << 5)) + (kp >> 1) * 4096 + (u & 1) * 2048);
            mma16816(x[u & 1], a[0], a[1], a[2], a[3], q[u & 2], q[(u & 2) + 1]);
        }
    }
    x[2][0] += x[3][2]; x[2][1] += x[3][3];
    const int lim = i8 + 2 * (lane & 3) - (lane >> 2);
    uint32_t p[5];
    {
        float m[2], e[5][2];
#pragma unroll
        for (int b = 0; b < 2; b++) {
            e[4][b] = m[b] = x[2][b];
#pragma unroll
            for (int j = 0; j < 2 * NK; j++) {
                e[j][b] = j < 2 * NK - 2 || 8 * j - b <= lim ? x[j >> 1][(j & 1) * 2 + b] : -3.0e38f;
                m[b] = fmaxf(m[b], e[j][b]);
            }
        }
#pragma unroll
        for (int o = 4; o < 32; o <<= 1) {
            m[0] = fmaxf(m[0], __shfl_xor_sync(~0u, m[0], o));
            m[1] = fmaxf(m[1], __shfl_xor_sync(~0u, m[1], o));
        }
        m[0] *= sl2e; m[1] *= sl2e;
#pragma unroll
        for (int j = 0; j < 5; j++)
            if (j < 2 * NK || j == 4) p[j] = movm(pack2(ex2(fmaf(e[j][0], sl2e, -m[0])), ex2(fmaf(e[j][1], sl2e, -m[1]))));
    }
    const uint32_t lvt = sb + C_KV + 8192 + ((m4 >> 1) * 8 + r8) * 128 + (((m4 & 1) ^ r8) << 4), one = 0x3f803f80u;
    float sm[4] = {0.f, 0.f, 0.f, 0.f}, c[8][4];
    mma16816(sm, one, one, one, one, p[0], p[1]);
    if (NK == 2) mma16816(sm, one, one, one, one, p[2], p[3]);
    mma1688(sm, one, one, p[4]);
#pragma unroll
    for (int j = 0; j < 8; j++) c[j][0] = c[j][1] = c[j][2] = c[j][3] = 0.f;
#pragma unroll
    for (int kk = 0; kk < NK; kk++)
#pragma unroll
        for (int j = 0; j < 8; j++) {
            uint32_t a[4];
            ldsm4t(a, (lvt ^ ((j & 3) << 5)) + (j >> 2) * 4096 + kk * 2048);
            mma16816(c[j], a[0], a[1], a[2], a[3], p[2 * kk], p[2 * kk + 1]);
        }
    float i0, i1;
    asm("rcp.approx.ftz.f32 %0, %1;" : "=f"(i0) : "f"(sm[0]));
    asm("rcp.approx.ftz.f32 %0, %1;" : "=f"(i1) : "f"(sm[1]));
    uint32_t o[4][4];
#pragma unroll
    for (int j = 0; j < 4; j++) {
        uint32_t a[4];
        ldsm4t(a, lm + xq + 16 * 272 + j * 64);
        mma1688(c[2 * j], a[0], a[1], p[4]);
        mma1688(c[2 * j + 1], a[2], a[3], p[4]);
#pragma unroll
        for (int u = 0; u < 4; u++) o[j][u] = pack2(c[2 * j + (u >> 1)][(u & 1) * 2] * i0, c[2 * j + (u >> 1)][(u & 1) * 2 + 1] * i1);
    }
#pragma unroll
    for (int j = 0; j < 4; j++) stsm4t(lm + qs + j * 64, o[j][0], o[j][1], o[j][2], o[j][3]);
    mid();
    __syncwarp();
#pragma unroll
    for (int j = 0; j < 4; j++) lds128(o[j], sb + qs + ((lane >> 4) + 2 * j) * 272 + (lane & 15) * 16);
#pragma unroll
    for (int j = 0; j < 4; j++)
        asm volatile("st.global.v4.u32 [%0], {%1,%2,%3,%4};" ::"l"(dst + (size_t)2 * j * HD), "r"(o[j][0]), "r"(o[j][1]), "r"(o[j][2]), "r"(o[j][3]) : "memory");
}
__device__ __forceinline__ void sum8(float (&c)[4], const uint2 (&v)[8], uint32_t idn) {
    float d[4] = {0.f, 0.f, 0.f, 0.f};
    c[0] = c[1] = c[2] = c[3] = 0.f;
    mma16816(c, v[0].x, v[0].y, v[1].x, v[1].y, idn, idn);
    mma16816(d, v[2].x, v[2].y, v[3].x, v[3].y, idn, idn);
    mma16816(c, v[4].x, v[4].y, v[5].x, v[5].y, idn, idn);
    mma16816(d, v[6].x, v[6].y, v[7].x, v[7].y, idn, idn);
    c[0] += d[0]; c[1] += d[1]; c[2] += d[2]; c[3] += d[3];
}

#define CLS 6
__global__ void __cluster_dims__(CLS, 1, 1) __launch_bounds__(256, 1)
k_chain(const bf16* __restrict__ mem0, const bf16* __restrict__ Wq, const bf16* __restrict__ Wk, const bf16* __restrict__ Wv,
        const bf16* __restrict__ Wo, const __grid_constant__ CUtensorMap mkv) {
    extern __shared__ __align__(1024) uint8_t smem_chain[];
    const uint32_t sb = smem_u32(smem_chain);
    if (sb & 1023) __trap();
    const int w = __shfl_sync(~0u, threadIdx.x >> 5, 0), lane = __shfl_sync(~0u, threadIdx.x & 31, threadIdx.x & 31);
    const int tid = w * 32 + lane, g = lane >> 2, t = lane & 3;
    auto pin = [&](uint32_t x) { asm volatile("shfl.sync.idx.b32 %0, %0, %1, 31, -1;" : "+r"(x) : "r"(lane) : "memory"); return x; };
    const int h = blockIdx.x / 3, r = blockIdx.x - 3 * h;
    const uint32_t bar_x = sb + C_BAR, bar_kv = sb + C_BAR + 8, bar_go = sb + C_BAR + 16, bar_w = sb + C_BAR + 24, self = sb + C_BAR + 60;
    asm volatile("griddepcontrol.launch_dependents;");
    const int tbase = r == 0 ? 0 : 1 + 21 * r, ntile = r == 0 ? 22 : 21;
    uint32_t side;
    if (tid == 0) {
        mbar_init(bar_x, 8); mbar_init(bar_kv, 1); mbar_init(bar_go, 1); mbar_init(bar_w, 1);
        asm volatile("st.shared.u32 [%0], %0;" ::"r"(self) : "memory");
        asm volatile("fence.mbarrier_init.release.cluster;" ::: "memory");
        asm volatile("fence.proxy.async.shared::cta;" ::: "memory");
        mbar_expect_tx(bar_w, 128 * 32 * ntile);
    }
    __syncthreads();
    asm volatile("barrier.cluster.arrive.relaxed.aligned;" ::: "memory");
    asm("mov.u32 %0, %%smid;" : "=r"(side));
    asm volatile("ld.relaxed.gpu.global.u32 %0, [%1];" : "=r"(side) : "l"(g_side + (side & 255)) : "memory");
    if (tid < 128)
        asm volatile("cp.async.bulk.shared::cluster.global.mbarrier::complete_tx::bytes [%0], [%1], %2, [%3];"
                     ::"r"(sb + C_W1 + tid * 720), "l"(Wo + (size_t)(h * 128 + tid) * DM + tbase * 16), "r"(32 * ntile), "r"(bar_w) : "memory");
    const int tile0 = tbase + 7 - w;
    const bool three = w >= (r == 0 ? 2 : 3);
    const uint32_t wa = pin(sb + tid * 16);
#define W1A(i) (wa + C_W1 + (i) * 4096)
#define W2A(x) (wa + C_W2 + ((x) < 8 ? (x) * 4096 : 32768 - 1024 + ((x) - 8) * 3072))
    uint32_t wo0[8][4], wr[64][4];
    {
        const bf16* W = (r == 0 ? Wq : r == 1 ? Wk : Wv) + (size_t)(128 * w + (lane >> 4)) * HD + h * 128 + 8 * (lane & 15);
        uint4 raw[8][8];
        auto fetch = [&](int ks) {
#pragma unroll
            for (int i = 0; i < 8; i++) raw[ks][i] = ldw128(W + (size_t)(16 * ks + 2 * i) * HD);
        };
        fetch(0); fetch(1); fetch(2); fetch(3);
        mbar_wait_u(bar_w, 0);
        const uint32_t p = sb + C_W1 + ((lane & 7) + (lane >> 4) * 8) * 720 + (7 - w) * 32 + ((lane >> 3) & 1) * 16;
#pragma unroll
        for (int ks = 0; ks < 8; ks++) {
            uint32_t a[4];
            ldsm4t(wo0[ks], p + ks * 16 * 720);
            ldsm4t(a, p + ks * 16 * 720 + 256);
            sts128(W2A(ks), a[0], a[1], a[2], a[3]);
            if (three) { ldsm4t(a, p + ks * 16 * 720 + 512); sts128(W2A(8 + ks), a[0], a[1], a[2], a[3]); }
        }
        __syncthreads();
        side &= 1;
        if (w == 7 && r > 0) asm volatile("st.relaxed.gpu.global.u32 [%0], %1;" ::"l"(g_flag + 128 + 2 * h + r - 1), "r"(2 | side) : "memory");
        const uint32_t stg = sb + C_KV + w * 4096;
        const uint32_t rd = stg + ((lane & 7) + 8 * (lane >> 4)) * 256 + ((((lane >> 3) & 1) ^ (lane & 7)) << 4);
#pragma unroll
        for (int ks = 0; ks < 8; ks++) {
#pragma unroll
            for (int i = 0; i < 8; i++)
                sts128(stg + (2 * i + (lane >> 4)) * 256 + (((lane & 15) ^ (((2 * i) & 6) | (lane >> 4))) << 4),
                       raw[ks][i].x, raw[ks][i].y, raw[ks][i].z, raw[ks][i].w);
            if (ks < 2) fetch(ks + 4);
            if (ks == 3 || ks == 5) fetch(ks / 2 + 5);
            __syncwarp();
#pragma unroll
            for (int j = 0; j < 8; j++) {
                if (smem_idx(ks, j) >= 0) {
                    uint32_t a[4];
                    ldsm4t(a, rd ^ (j << 5));
                    sts128(W1A(smem_idx(ks, j)), a[0], a[1], a[2], a[3]);
                } else ldsm4t(wr[8 * ks + j], rd ^ (j << 5));
            }
            __syncwarp();
        }
    }
    uint2 bm[8];
#pragma unroll
    for (int ks = 0; ks < 8; ks++) {
        const uint32_t* p = (const uint32_t*)(mem0 + g * DM + (8 * w + ks) * 16) + t;
        asm volatile("ld.global.nc.u32 %0, [%2];\nld.global.nc.u32 %1, [%2 + 16];" : "=r"(bm[ks].x), "=r"(bm[ks].y) : "l"(p));
    }
    uint32_t psel, msel0, msel1;
    {
        const int j = r > 0 ? 2 * h + r - 1 : 0, tl = min(tile0 + 8 * (lane >> 1), 63);
        const uint32_t b = wait_count_u(lane < 8 ? g_flag + 128 + tl : g_flag + (lane & 8), lane < 8 ? 2 : lane & 8 ? 37 : 48);
        psel = __ballot_sync(~0u, (g_home[lane == 6 ? j * 2 + ((w >> 1) & 1) : tl * 2 + (lane & 1)] ^ (lane == 6 ? side : b)) & 1);
        msel0 = __ballot_sync(~0u, (g_home[128 + lane * 4 + (w >> 1)] ^ side) & 1);
        msel1 = __ballot_sync(~0u, (g_home[256 + lane * 4 + (w >> 1)] ^ side) & 1);
        if (r > 0) {
            if (w < 4) asm volatile("prefetch.global.L2 [%0];" ::"l"(g_x + (128 + (1 + (w >> 1)) * 4 + (j >> 4)) * 1024 + (w & 1) * 512 + (j & 15) * 32 + lane) : "memory");
            if (w < 4) asm volatile("prefetch.global.L2 [%0];" ::"l"(g_x + j * 2048 + tid * 16) : "memory");
        }
    }
    asm volatile("fence.proxy.async.shared::cta;" ::: "memory");
    __syncthreads();
    if (tid == 0) {
        mbar_expect_tx(bar_kv, 16384);
        tma3d(sb + C_KV, &mkv, 0, 0, 2 * h, bar_kv);
        tma3d(sb + C_KV + 8192, &mkv, 0, 0, 64 + 2 * h, bar_kv);
    }
    asm volatile("barrier.cluster.wait.aligned;" ::: "memory");

    auto load_kv = [&](int s) {
        asm volatile("{\n.reg .pred p;\nelect.sync _|p, -1;\n@p mbarrier.arrive.expect_tx.shared::cta.b64 _, [%2], 16384;\n"
                     "@p cp.async.bulk.tensor.3d.shared::cluster.global.mbarrier::complete_tx::bytes [%0], [%1, {%3, %4, %5}], [%2];\n"
                     "@p cp.async.bulk.tensor.3d.shared::cluster.global.mbarrier::complete_tx::bytes [%6], [%1, {%3, %4, %7}], [%2];\n}"
                     ::"r"(sb + C_KV), "l"(&mkv), "r"(bar_kv), "r"(0), "r"(s * 32), "r"(2 * h), "r"(sb + C_KV + 8192), "r"(64 + 2 * h) : "memory");
    };
    const bool attends = w == 7 || (w == 6 && r == 0);
    const int i8 = r == 0 ? (w - 4) * 8 : (r - 1) * 8;
    auto load_q = [&](int s) {
        const int l = fresh(lane);
        const bf16* p = g_kv + (size_t)(s * 32 + i8 + (l >> 4)) * PW + 2 * HD + h * 128 + (l & 15) * 8;
#pragma unroll
        for (int j = 0; j < 4; j++)
            asm volatile("cp.async.cg.shared.global [%0], [%1], 16;"
                         ::"r"(sb + C_RED + w * 2176 + ((l >> 4) + 2 * j) * 272 + (l & 15) * 16), "l"(p + (size_t)2 * j * PW) : "memory");
    };
    auto report = [&](int blk) {
        asm volatile("{\n.reg .pred p;\nelect.sync _|p, -1;\nfence.acq_rel.gpu;\n@p red.relaxed.gpu.global.add.u32 [%0], 1;\n}"
                     ::"l"(g_flag + 64 + blk) : "memory");
    };
    const float sl2e = 0.08838834764831845f * 1.4426950408889634f;
    const uint32_t idn = pin(g == 2 * t ? 0x00003f80u : g == 2 * t + 1 ? 0x3f800000u : 0u);
    const uint32_t lm = pin(sb + (lane & 7) * 272 + (lane >> 3) * 16);
    const uint32_t sa = pin(sb + C_SC + (w & 1) * (8 * 52 * 4) + (2 * t * 52 + (w < 4 ? 32 : (w & 2) * 8) + g) * 4);
    const uint32_t sr = pin(sb + C_SC + (g * 52 + 8 * t) * 4), sr2 = pin(sb + C_SC + (g * 52 + 32 + 2 * t) * 4);
    uint32_t kva;
    {
        const int pos = (w & 2) * 8 + (lane & 15), row = (pos & 24) + ((pos + (pos >> 2 & 6)) & 7);
        const int key = 4 * (lane & 6) + (((lane & 7) + 2 * (lane >> 4)) & 7);
        kva = pin(w >= 4 ? sb + C_KV + (w & 1) * 4096 + row * 128 + (((lane >> 4) ^ (row & 7)) << 4)
                         : sb + C_KV + 8192 + (w >> 1) * 4096 + key * 128 + ((((w & 1) * 4 + ((lane >> 3) & 1)) ^ (key & 7)) << 4));
    }
#define ATTEND(NK, s, mid) do {                                                                                       \
        const int l_ = fresh(lane);                                                                                      \
        attend<NK>(sb, lm, C_RED + w * 2176, C_QKV + ((s) & 1) * QKV_SZ, i8, l_,                                         \
                   g_o + (size_t)((s) * 32 + i8 + (l_ >> 4)) * HD + h * 128 + (l_ & 15) * 8, mid);                       \
    } while (0)
    auto chores = [&](int s) {
        if ((s & 3) == 0 && s) report((s >> 2) - 1);
        if ((s & 7) == 6 - PFD && s < NSEG - 8) wait_count_u(g_flag + (s >> 3) + 1, (s >> 3) + 1 < 2 * NTA ? 48 : 96);
    };
    uint32_t buf0[8][4], ring[RB1][4];
    auto stage_w1 = [&]() {
#pragma unroll
        for (int i = 0; i < 8; i++) lds128v(buf0[i], W1A(i));
#pragma unroll
        for (int i = 0; i < RB1; i++) lds128v(ring[i], W1A(8 + i));
    };
    stage_w1();
#pragma unroll 1
    for (int s = 0;; s++) {
        const uint32_t xq = C_QKV + (s & 1) * QKV_SZ;
        {
            float acc[8][4];
#pragma unroll
            for (int ks = 0; ks < 8; ks++) {
#pragma unroll
                for (int j = 0; j < 8; j++) {
                    const int i = smem_idx(ks, j) - 8;
                    if (ks == 0) {
                        acc[j][0] = acc[j][1] = acc[j][2] = acc[j][3] = 0.f;
                        mma16816(acc[j], buf0[j][0], buf0[j][1], buf0[j][2], buf0[j][3], bm[ks].x, bm[ks].y);
                    } else if (i >= 0) {
                        uint32_t(&a)[4] = ring[i % RB1];
                        mma16816(acc[j], a[0], a[1], a[2], a[3], bm[ks].x, bm[ks].y);
                        if (8 + i + RB1 < NS1) lds128v(a, W1A(8 + i + RB1));
                    } else {
                        const uint32_t(&a)[4] = wr[8 * ks + j];
                        mma16816(acc[j], a[0], a[1], a[2], a[3], bm[ks].x, bm[ks].y);
                    }
                }
            }
#pragma unroll
            for (int c = 0; c < 4; c++)
                stsm4t(lm + C_RED + w * 2176 + c * 64, pack2(acc[2 * c][0], acc[2 * c][1]), pack2(acc[2 * c][2], acc[2 * c][3]),
                       pack2(acc[2 * c + 1][0], acc[2 * c + 1][1]), pack2(acc[2 * c + 1][2], acc[2 * c + 1][3]));
        }
        {
            const uint32_t a = sb + C_RED + w * 272 + lane * 8;
            if (w == 3) mbar_wait_u(bar_kv, s & 1);
            __syncthreads();
            uint2 v[8];
#pragma unroll
            for (int i = 0; i < 8; i++) v[i] = lds64(a + i * 2176);
            float c[4];
            sum8(c, v, idn);
            const uint32_t p0 = pack2(c[0], c[1]), p1 = pack2(c[2], c[3]);
            const uint32_t dst = sb + xq + (r * 8 + w) * 272 + lane * 8;
#pragma unroll
            for (int i = 1; i < 3; i++) {
                const uint32_t peer = (h % (CLS / 3)) * 3 + (r + i >= 3 ? r + i - 3 : r + i);
                uint32_t rd, rb;
                asm("mapa.shared::cluster.u32 %0, %1, %2;" : "=r"(rd) : "r"(dst), "r"(peer));
                asm("mapa.shared::cluster.u32 %0, %1, %2;" : "=r"(rb) : "r"(bar_x), "r"(peer));
                asm volatile("st.async.weak.shared::cluster.mbarrier::complete_tx::bytes.v2.b32 [%0], {%1,%2}, [%3];"
                             ::"r"(rd), "r"(p0), "r"(p1), "r"(rb) : "memory");
            }
            sts64(dst, p0, p1);
            __syncwarp();
            asm volatile("{\n.reg .pred p;\nsetp.eq.u32 p, %1, 0;\n@p mbarrier.arrive.expect_tx.shared::cta.b64 _, [%0], 512;\n}"
                         ::"r"(bar_x), "r"(lane) : "memory");
        }
        if (s == NSEG - 1) break;
        uint32_t wb[8][4], wc[8][4];
        const uint32_t po = (tile0 * 2 + (lane >> 4)) * 8192 + ((lane >> 3) & 1) * 2048 + h * 64 + (lane & 7) * 8;
        const uint32_t tag = s & 1;
        auto project = [&](const uint32_t(&wt)[8][4], const uint32_t(&ob)[4][4], int i) {
            float c0[4] = {0.f, 0.f, 0.f, 0.f}, c1[4] = {0.f, 0.f, 0.f, 0.f};
#pragma unroll
            for (int ks = 0; ks < 8; ks++)
                mma16816((ks & 1) ? c1 : c0, wt[ks][0], wt[ks][1], wt[ks][2], wt[ks][3], ob[ks >> 1][(ks & 1) * 2], ob[ks >> 1][(ks & 1) * 2 + 1]);
            uint32_t p0 = pack2(c0[0] + c1[0], c0[1] + c1[1]), p1 = pack2(c0[2] + c1[2], c0[3] + c1[3]);
            asm volatile("movmatrix.sync.aligned.m8n8.trans.b16 %0, %0;\nmovmatrix.sync.aligned.m8n8.trans.b16 %1, %1;" : "+r"(p0), "+r"(p1));
            st_rlx64((uint2*)((char*)g_x + po + i * 131072 + ((psel >> (2 * i + (lane >> 4))) & 1) * 4096), (p0 & ~1u) | tag, p1);
        };
        if (w >= 4) {
            uint32_t ka[4][4];
#pragma unroll
            for (int ks = 0; ks < 4; ks++) ldsm4(ka[ks], kva ^ (ks << 5));
            const uint32_t qa = lm + xq + (w & 1) * 128;
            mbar_wait_u(bar_x, s & 1);
            {
                uint32_t qb[2][4];
                ldsm4(qb[0], qa);
                ldsm4(qb[1], qa + 64);
                float c0[4] = {0.f, 0.f, 0.f, 0.f}, c1[4] = {0.f, 0.f, 0.f, 0.f};
                mma16816(c0, ka[0][0], ka[0][1], ka[0][2], ka[0][3], qb[0][0], qb[0][1]);
                mma16816(c1, ka[1][0], ka[1][1], ka[1][2], ka[1][3], qb[0][2], qb[0][3]);
                mma16816(c0, ka[2][0], ka[2][1], ka[2][2], ka[2][3], qb[1][0], qb[1][1]);
                mma16816(c1, ka[3][0], ka[3][1], ka[3][2], ka[3][3], qb[1][2], qb[1][3]);
                sts32f(sa, c0[0] + c1[0]);
                sts32f(sa + 208, c0[1] + c1[1]);
                sts32f(sa + 32, c0[2] + c1[2]);
                sts32f(sa + 240, c0[3] + c1[3]);
            }
            __syncthreads();
            uint32_t wd;
            if (attends) { load_q(s); wd = delayed<DLYQ>(wa, self); } else wd = delayed<DLYW>(wa, self);
#pragma unroll
            for (int i = 0; i < 8; i++) lds128(wb[i], wd + C_W2 + i * 4096);
#pragma unroll
            for (int i = 0; i < PFC; i++) lds128(wc[i], wd + C_W2 + 32768 - 1024 + i * 3072);
            __syncthreads();
            uint32_t ob[4][4];
#pragma unroll
            for (int i = 0; i < 4; i++) ldsm4(ob[i], lm + C_OB + i * 64);
#pragma unroll
            for (int i = PFC; i < 8; i++) lds128(wc[i], W2A(8 + i));
            project(wb, ob, 1);
            project(wo0, ob, 0);
            project(wc, ob, 2);
        } else {
            uint32_t va[4][4];
#pragma unroll
            for (int i = 0; i < 4; i++) ldsm4t(va[i], kva ^ (((i >> 1) << 5) | ((i & 1) * 0x240)));
#pragma unroll
            for (int i = 0; i < 8; i++) lds128(wb[i], W2A(i));
            const uint32_t qa = lm + xq + (w & 1) * 128, oa = lm + w * 64;
            mbar_wait_u(bar_x, s & 1);
            if (w < 2) {
                uint32_t qb[2][4], km[2][4];
                ldsm4(qb[0], qa);
                ldsm4(km[0], qa + 8 * 272);
                ldsm4(qb[1], qa + 64);
                ldsm4(km[1], qa + 8 * 272 + 64);
                float c0[4] = {0.f, 0.f, 0.f, 0.f}, c1[4] = {0.f, 0.f, 0.f, 0.f};
                mma16816(c0, km[0][0], km[0][1], km[0][2], km[0][3], qb[0][0], qb[0][2]);
                mma16816(c1, km[0][0], km[0][1], km[0][2], km[0][3], qb[0][1], qb[0][3]);
                mma16816(c0, km[1][0], km[1][1], km[1][2], km[1][3], qb[1][0], qb[1][2]);
                mma16816(c1, km[1][0], km[1][1], km[1][2], km[1][3], qb[1][1], qb[1][3]);
                sts32f(sa, c0[0] + c1[2]);
                sts32f(sa + 208, c0[1] + c1[3]);
            }
            __syncthreads();
            {
                float4 x0 = lds128f(sr), y0 = lds128f(sr + 1664), x1 = lds128f(sr + 16), y1 = lds128f(sr + 1680);
                float2 x2 = lds64f(sr2), y2 = lds64f(sr2 + 1664);
                float p[10] = {x0.x + y0.x, x0.y + y0.y, x0.z + y0.z, x0.w + y0.w, x1.x + y1.x,
                               x1.y + y1.y, x1.z + y1.z, x1.w + y1.w, x2.x + y2.x, x2.y + y2.y};
                float m = fmaxf(fmaxf(fmaxf(p[0], p[1]), fmaxf(p[2], p[3])), fmaxf(fmaxf(fmaxf(p[4], p[5]), fmaxf(p[6], p[7])), fmaxf(p[8], p[9])));
                const float m1 = __shfl_xor_sync(~0u, m, 1), m2 = __shfl_xor_sync(~0u, m, 2), m3 = __shfl_xor_sync(~0u, m, 3);
                uint32_t vm[4];
                ldsm4t(vm, oa + xq + 16 * 272);
                m = fmaxf(fmaxf(m, m1), fmaxf(m2, m3));
                const float ms = m * sl2e;
#pragma unroll
                for (int i = 0; i < 10; i++) p[i] = ex2(fmaf(p[i], sl2e, -ms));
                const uint32_t b0 = pack2(p[0], p[1]), b1 = pack2(p[2], p[3]), b2 = pack2(p[4], p[5]), b3 = pack2(p[6], p[7]), b4 = pack2(p[8], p[9]);
                const uint32_t one = 0x3f803f80u;
                float o0[4] = {0.f, 0.f, 0.f, 0.f}, o1[4] = {0.f, 0.f, 0.f, 0.f}, sm[4] = {0.f, 0.f, 0.f, 0.f};
                mma16816(sm, one, one, one, one, b0, b1);
                mma16816(o0, va[0][0], va[0][1], va[0][2], va[0][3], b0, b1);
                mma16816(o1, va[2][0], va[2][1], va[2][2], va[2][3], b0, b1);
                mma16816(sm, one, one, one, one, b2, b3);
                mma16816(o0, va[1][0], va[1][1], va[1][2], va[1][3], b2, b3);
                mma16816(o1, va[3][0], va[3][1], va[3][2], va[3][3], b2, b3);
                mma1688(sm, one, one, b4);
                mma1688(o0, vm[0], vm[1], b4);
                mma1688(o1, vm[2], vm[3], b4);
                float i0, i1;
                asm("rcp.approx.ftz.f32 %0, %1;" : "=f"(i0) : "f"(sm[0]));
                asm("rcp.approx.ftz.f32 %0, %1;" : "=f"(i1) : "f"(sm[1]));
                stsm4t(oa + C_OB, pack2(o0[0] * i0, o0[1] * i1), pack2(o0[2] * i0, o0[3] * i1),
                       pack2(o1[0] * i0, o1[1] * i1), pack2(o1[2] * i0, o1[3] * i1));
            }
            __syncthreads();
            uint32_t ob[4][4];
#pragma unroll
            for (int i = 0; i < 4; i++) ldsm4(ob[i], lm + C_OB + i * 64);
            if (three) {
#pragma unroll
                for (int i = 0; i < 8; i++) lds128(wc[i], W2A(8 + i));
                project(wb, ob, 1);
                project(wo0, ob, 0);
                project(wc, ob, 2);
            } else {
                project(wb, ob, 1);
                project(wo0, ob, 0);
            }
        }
        __syncthreads();
        uint32_t eo = (128 + (s + 1) * 4 + (w >> 1)) * 8192 + (((s < 31 ? msel0 : msel1) >> ((s + 1) & 31)) & 1) * 4096 + (w & 1) * 2048 + lane * 8;
        uint64_t d[8];
        if (r == 0) {
            if (w >= 6) {
                auto mid = [&]() {
                    bar_sync(2, 64);
                    mbar_wait_u(bar_go, s & 1);
                    eo = delayed<DLY0A>(eo, self);
                    fetch_state(d, (const char*)g_x + eo);
                };
                ATTEND(2, s, mid);
                stage_w1();
            } else {
                if (w < 3 && s + PFD < NSEG) {
                    const bf16* p = g_kv + (size_t)((s + PFD) * 32 + fresh(lane)) * PW + w * HD + h * 128;
                    asm volatile("prefetch.global.L2 [%0];\nprefetch.global.L2 [%0 + 128];" ::"l"(p) : "memory");
                }
                stage_w1();
                if (w == 5) {
                    chores(s);
                    if (h == 0) asm volatile("st.relaxed.gpu.global.u32 [%0], %1;" ::"l"(g_flag + 98), "r"(s + 1) : "memory");
                }
                mbar_wait_u(bar_go, s & 1);
                eo = delayed<DLY0>(eo, self);
                fetch_state(d, (const char*)g_x + eo);
            }
        } else {
            const int j = 2 * h + r - 1;
            if (w < 4) {
                const int l = fresh(lane), g = l >> 2, t = l & 3;
                const char* src = (const char*)g_x + delayed<DLY3>((j * 2 + (w >> 1)) * 8192 + (psel & 64) * 64 + (w & 1) * 2048 + t * 64 + g * 8, self);
                const char* dst = (const char*)g_x + pin((128 + (s + 1) * 4 + (j >> 4)) * 8192 + (j & 15) * 256 + w * 64 + (t & 1) * 4096 + g * 8);
                const uint64_t v = poll_sum(src, tag, (lane & 4) ? 0x3f800000u : 0x00003f80u);
                asm volatile("st.relaxed.gpu.global.b64 [%0], %1;" ::"l"(dst), "l"(v) : "memory");
                asm volatile("bar.arrive 1, 256;" ::: "memory");
                stage_w1();
                eo = delayed<DLY1>(eo, self);
                fetch_state(d, (const char*)g_x + eo);
            } else if (w == 7) {
                auto mid = [&]() {
                    bar_sync(1, 256);
                    eo = delayed<DLY1B>(eo, self);
                    fetch_state(d, (const char*)g_x + eo);
                };
                ATTEND(1, s, mid);
                stage_w1();
            } else {
                if (w >= 5 && s + 3 < NSEG)
                    asm volatile("prefetch.global.L2 [%0];" ::"l"(g_x + (128 + (s + 3) * 4 + (j >> 4)) * 1024 + (w & 1) * 512 + (j & 15) * 32 + lane) : "memory");
                stage_w1();
                if (w == 5) chores(s);
                bar_sync(1, 256);
                if (w == 4 && r == 1)
                    asm volatile("{\n.reg .pred p;\n.reg .u32 a;\nelect.sync _|p, -1;\nmapa.shared::cluster.u32 a, %0, %1;\n"
                                 "@p mbarrier.arrive.relaxed.cluster.shared::cluster.b64 _, [a];\n}" ::"r"(bar_go), "r"((h % (CLS / 3)) * 3) : "memory");
                eo = delayed<DLY1A>(eo, self);
                fetch_state(d, (const char*)g_x + eo);
            }
        }
        if (w == 7) load_kv(s + 1);
        settle_state(d, (const char*)g_x + eo);
#pragma unroll
        for (int i = 0; i < 8; i++) { bm[i].x = (uint32_t)d[i]; bm[i].y = (uint32_t)(d[i] >> 32); }
    }
    mbar_wait_u(bar_x, (NSEG - 1) & 1);
    if (attends) {
        auto nothing = []() {};
        load_q(NSEG - 1);
        if (r == 0) { ATTEND(2, NSEG - 1, nothing); bar_sync(2, 64); } else { ATTEND(1, NSEG - 1, nothing); __syncwarp(); }
        if (w == 7) report(15);
    }
}

constexpr int S4_US = 4368;
constexpr int S4_RS = 8848;
constexpr int S4_KS = 1296;
constexpr int S4_U = 0, S4_R = 16 * S4_US, S4_K = S4_R + 16 * S4_RS;
constexpr int S4_SMEM = S4_K + 16 * S4_KS;
constexpr int S4_SIG = 3104, S4_PK = 2 * S4_SIG;

struct cf { float r, i; };
__device__ __forceinline__ cf cmul(cf a, cf b) { return {fmaf(a.r, b.r, -a.i * b.i), fmaf(a.r, b.i, a.i * b.r)}; }
__device__ __forceinline__ cf cmulc(cf a, cf b) { return {fmaf(a.r, b.r, a.i * b.i), fmaf(a.i, b.r, -a.r * b.i)}; }
__device__ __forceinline__ cf csq(cf a) { const float t = a.r * a.i; return {fmaf(a.r, a.r, -a.i * a.i), t + t}; }
__device__ __forceinline__ cf cexp(float l2, float turns) {
    const float mag = ex2(l2), fr = (turns - rintf(turns)) * 6.283185307179586f;
    return {mag * __cosf(fr), mag * __sinf(fr)};
}
__device__ __forceinline__ void sts32(uint32_t a, uint32_t v) { asm volatile("st.shared.u32 [%0], %1;" ::"r"(a), "r"(v) : "memory"); }
__device__ __forceinline__ uint32_t lds16(uint32_t a) {
    uint32_t v;
    asm volatile("ld.shared.u16 %0, [%1];" : "=r"(v) : "r"(a) : "memory");
    return v;
}

template <int M0, int NQ>
__device__ __forceinline__ void s4_class(float (&acc)[16][4], uint32_t sig, uint32_t taps, int x0) {
    constexpr int D0 = M0 / 8, D1 = M0 == 32 ? 9 : 15;
    uint32_t R[D1 - D0 + 2];
#pragma unroll
    for (int D = D0 - 1; D <= D1; D++) {
        if (D < D0 || 8 * D - 7 >= 2 * M0) { R[D - D0 + 1] = 0; continue; }
        const int m = 8 * D + x0;
        uint32_t lo = lds16(taps + m * (2 * NQ)), hi = lds16(taps + (m - 1) * (2 * NQ));
        if (D == D0) { lo = m >= M0 ? lo : 0; hi = m > M0 ? hi : 0; }
        if (D == 2 * D0) { lo = m < 2 * M0 ? lo : 0; hi = m <= 2 * M0 ? hi : 0; }
        R[D - D0 + 1] = lo | (hi << 16);
    }
#pragma unroll
    for (int J = 0; 2 * J + D0 < 16; J++) {
        uint32_t a[4];
        ldsm4t(a, sig + J * 512);
#pragma unroll
        for (int D = D0; D <= D1; D++)
            if (2 * J + D < 16) mma16816(acc[2 * J + D], a[0], a[1], a[2], a[3], R[D - D0 + 1], R[D - D0]);
    }
}

__global__ void __launch_bounds__(512, 1)
k_s4(const bf16* __restrict__ u, const bf16* __restrict__ Are, const bf16* __restrict__ Aim, const bf16* __restrict__ Bre,
     const bf16* __restrict__ Bim, const bf16* __restrict__ Cre, const bf16* __restrict__ Cim, const bf16* __restrict__ logdt,
     const bf16* __restrict__ Dsk, bf16* __restrict__ out) {
    extern __shared__ __align__(16) uint8_t smem_s4[];
    const uint32_t sb = smem_u32(smem_s4);
    asm volatile("griddepcontrol.launch_dependents;");
    const int tid = threadIdx.x, w = __shfl_sync(~0u, tid >> 5, 0), lane = tid & 31, g = lane >> 2, t = lane & 3;
    const int dw = (w & 1) + ((w >> 1) & 3) * 4 + (w >> 3) * 2;
    uint2 ar, ai, br, bi, cr, ci;
    bf16 ldt;
    auto load_params = [&](int item) {
        const int d = item * 16 + dw, o = d * 128 + lane * 4;
        ar = __ldg((const uint2*)(Are + o)); ai = __ldg((const uint2*)(Aim + o)); br = __ldg((const uint2*)(Bre + o));
        bi = __ldg((const uint2*)(Bim + o)); cr = __ldg((const uint2*)(Cre + o)); ci = __ldg((const uint2*)(Cim + o));
        ldt = logdt[d];
    };
    load_params(blockIdx.x);
#pragma unroll 1
    for (int item = blockIdx.x; item < 64; item += gridDim.x) {
    const int d0 = item * 16;
    const uint32_t tr_off = (lane & 15), tr_l = (lane >> 4) * 16;
    const uint32_t ur = sb + S4_U + w * S4_US, rs = sb + S4_R + w * S4_RS, kd = sb + S4_K + w * S4_KS;
    if (lane < 16) sts128(ur + lane * 16, 0, 0, 0, 0);
    {
        const float dt = bf_round(expf(__bfloat162float(ldt)));
        const bf16* src = u + (size_t)(w * 128 + g) * DM + d0 + 4 * t;
        float T[5][4];
#pragma unroll
        for (int i = 0; i < 5; i++) T[i][0] = T[i][1] = T[i][2] = T[i][3] = 0.f;
        float klast = 0.f;
        const uint32_t wr_ = rs + lane * 272, rd_ = rs + t * 544 + g * 16;
#pragma unroll 1
        for (int c = 0; c < 4; c++) {
            uint2 v[4];
#pragma unroll
            for (int i = 0; i < 4; i++) v[i] = __ldg((const uint2*)(src + (size_t)(c * 32 + i * 8) * DM));
            auto pick = [&](const uint2& x) { const uint32_t y = c < 2 ? x.x : x.y; return (c & 1) ? bf_hi(y) : bf_lo(y); };
            auto pk2 = [](cf x) { return pack2(x.r, x.i); };
            const float l2 = dt * pick(ar) * 1.4426950408889634f, tu = dt * pick(ai) * 0.15915494309189535f;
            const cf z1 = cexp(l2, tu), z2 = csq(z1), z4 = csq(z2), z8 = csq(z4);
            const cf z64 = cexp(l2 * 64.f, tu * 64.f), z128 = csq(z64), z256 = csq(z128), z512 = csq(z256);
            cf a0 = {1.f, 0.f}, a1 = z64;
            cf b0 = cmul({pick(cr), pick(ci)}, {dt * pick(br), dt * pick(bi)});
            b0.i = -b0.i;
            cf b1 = cmulc(b0, z128), b2 = cmulc(b0, z256), y3 = cmulc(b0, z512), b4 = cmulc(y3, z512), b3 = y3;
            const cf y2 = cmulc(b2, z128);
#pragma unroll
            for (int i = 0; i < 8; i++) {
                sts128(wr_ + i * 16, pk2(a0), pk2(a1), pk2(b0), pk2(b1));
                sts128(wr_ + i * 16 + 128, pk2(b2), pk2(b3), pk2(b4), 0);
                b4 = cmulc(b4, z128);
                if (i < 7) {
                    a0 = i == 0 ? z8 : cmul(a0, z8); a1 = cmul(a1, z8);
                    b0 = cmulc(b0, z1); b1 = cmulc(b1, z1);
                    b2 = i == 3 ? y2 : cmulc(b2, z2);
                    if (i & 1) { y3 = cmulc(y3, z128); b3 = y3; } else b3 = cmulc(y3, z4);
                }
            }
            klast += b4.r;
            __syncwarp();
#pragma unroll
            for (int k = 0; k < 8; k++) {
                uint32_t x[4], y[4];
                lds128(x, rd_ + (8 * (k >> 1) + (k & 1)) * 272);
                lds128(y, rd_ + (8 * (k >> 1) + (k & 1)) * 272 + 128);
                mma1688(T[0], x[0], x[1], x[2]);
                mma1688(T[1], x[0], x[1], x[3]);
                mma1688(T[2], x[0], x[1], y[0]);
                mma1688(T[3], x[0], x[1], y[1]);
                mma1688(T[4], x[0], x[1], y[2]);
            }
#pragma unroll
            for (int i = 0; i < 2; i++)
                stsm4t(sb + S4_U + tr_off * S4_US + 256 + (w * 128 + c * 32 + i * 16) * 2 + tr_l, v[2 * i].x, v[2 * i].y, v[2 * i + 1].x, v[2 * i + 1].y);
            __syncwarp();
        }
#pragma unroll
        for (int o2 = 16; o2; o2 >>= 1) klast += __shfl_xor_sync(~0u, klast, o2);
#pragma unroll
        for (int hh = 0; hh < 2; hh++) {
            const int i = g + 8 * hh;
            sts32(kd + (8 * i + 2 * t) * 2, pack2(T[0][2 * hh], T[0][2 * hh + 1]));
            sts32(kd + (128 + 8 * i + 2 * t) * 2, pack2(T[1][2 * hh], T[1][2 * hh + 1]));
            sts32(kd + (256 + 4 * i + 2 * (t & 1) + 64 * (t >> 1)) * 2, pack2(T[2][2 * hh], T[2][2 * hh + 1]));
            sts32(kd + (384 + 2 * i + 32 * t) * 2, pack2(T[3][2 * hh], T[3][2 * hh + 1]));
        }
        asm volatile("stmatrix.sync.aligned.m8n8.x2.trans.shared.b16 [%0], {%1,%2};"
                     ::"r"(kd + 1024 + (lane & 7) * 32 + ((lane >> 3) & 1) * 16), "r"(pack2(T[4][0], T[4][1])), "r"(pack2(T[4][2], T[4][3])) : "memory");
        if (lane == 0) sts32(kd + 1280, pack2(klast, 0.f));
    }
    __syncwarp();
    const uint32_t pk = rs + S4_PK + 64;
    {
#pragma unroll
        for (int i = 0; i < 2; i++) {
            const int x = i * 128 + lane * 4;
            const uint2 c = lds64(kd + x * 2);
            uint32_t p = lds16(kd + x * 2 - 2);
            if (x == 0) p = 0;
            sts128(pk + x * 4, __byte_perm(c.x, p, 0x5410), __byte_perm(c.x, 0, 0x1032), __byte_perm(c.y, c.x, 0x7610), __byte_perm(c.y, 0, 0x1032));
        }
#pragma unroll
        for (int i = 2; i < 4; i++) {
            const int x = i * 128 + lane * 4;
            const uint32_t ab = lds32(kd + 256 + x), c = lds16(kd + 256 + x + 4);
            const uint32_t p = x == 256 ? lds16(kd + 510) : ab;
            sts128(pk + x * 4, __byte_perm(ab, p, 0x5410), __byte_perm(ab, 0, 0x1010), __byte_perm(ab, 0, 0x1032), __byte_perm(c, ab, 0x7610));
        }
        const uint32_t v = lds16(kd + 768), v2 = lds16(kd + 1024);
        if (lane < 24) {
            uint32_t x0 = 0, x1 = 0, x2 = 0, x3 = 0;
            if (lane == 0) { x0 = x1 = x2 = v | (v << 16); x3 = v << 16; }
            if (lane == 12) x3 = v2;
            if (lane == 13) { x0 = v2 | (v2 << 16); x1 = v2 << 16; }
            sts128(lane < 20 ? pk + 2048 + lane * 16 : pk - 64 + (lane - 20) * 16, x0, x1, x2, x3);
        }
        if (lane < 4) sts128(rs + (lane >> 1) * S4_SIG + (lane & 1) * 16, 0, 0, 0, 0);
    }
    __syncthreads();
    float acc[16][4];
#pragma unroll
    for (int i = 0; i < 16; i++) acc[i][0] = acc[i][1] = acc[i][2] = acc[i][3] = 0.f;
    const uint32_t lf = (lane & 7) * 32 + ((lane >> 3) & 1) * 16 + (lane >> 4) * 256;
#pragma unroll 1
    for (int ph = 0; ph < 2; ph++) {
    if (((w >> 2) ^ ph) & 1) {
#pragma unroll
    for (int rg = 3; rg >= 2; rg--) {
#pragma unroll 1
        for (int it = 0; it < (rg == 3 ? 4 : 6); it++) {
            const int n = it * 32 + lane;
            uint32_t x[2][4];
            lds128(x[0], ur + 256 + n * 16 - 16);
            lds128(x[1], ur + 256 + n * 16);
            float e[16], p[15], s[11];
#pragma unroll
            for (int i = 0; i < 8; i++) { e[2 * i] = bf_lo(x[i >> 2][i & 3]); e[2 * i + 1] = bf_hi(x[i >> 2][i & 3]); }
#pragma unroll
            for (int i = 0; i < 15; i++) p[i] = e[i] + e[i + 1];
#pragma unroll
            for (int i = 0; i < 11; i++) s[i] = p[i + 3] + e[i + 5];
            const uint32_t o = rs + 16 + n * 16;
            if (rg == 2) sts128(o, pack2(s[0], s[1]), pack2(s[2], s[3]), pack2(s[4], s[5]), pack2(s[6], s[7]));
#pragma unroll
            for (int i = 0; i < 10; i++) s[i] = p[i + 2] + s[i + 1];
            if (rg == 2) {
                sts64(o + S4_SIG + 8, pack2(s[0], s[1]), pack2(s[2], s[3]));
                sts64(o + S4_SIG + 16, pack2(s[4], s[5]), pack2(s[6], s[7]));
            } else {
#pragma unroll
                for (int i = 0; i < 9; i++) s[i] = p[i + 1] + s[i + 1];
                sts64(o + 8, pack2(s[0], s[1]), pack2(s[2], s[3]));
                sts64(o + 16, pack2(s[4], s[5]), pack2(s[6], s[7]));
#pragma unroll
                for (int i = 0; i < 8; i++) s[i] = p[i] + s[i + 1];
                sts64(o + S4_SIG + 8, pack2(s[0], s[1]), pack2(s[2], s[3]));
                sts64(o + S4_SIG + 16, pack2(s[4], s[5]), pack2(s[6], s[7]));
            }
        }
        __syncwarp();
        if (rg == 3) {
#pragma unroll 1
            for (int q = 1; q <= 2; q++) s4_class<64, 2>(acc, rs + lf + (q == 1 ? 16 : S4_SIG), kd + (384 + q) * 2, g - 2 * t);
        } else {
#pragma unroll 1
            for (int q = 1; q <= 4; q++) s4_class<32, 4>(acc, rs + lf + ((q & 1) ? 0 : S4_SIG) + (q < 3 ? 16 : 0), kd + (256 + q) * 2, g - 2 * t);
        }
        __syncwarp();
    }
    } else
    {
        const uint32_t ub = ur + 256 + lf, kb = pk + (g - 2 * t) * 4;
#pragma unroll 1
        for (int j0 = 0; j0 < 8; j0++) {
            uint32_t B[8][4];
#pragma unroll
            for (int i = 0; i < 8; i++) ldsm4(B[i], ub + i * 512 - j0 * 32);
            auto block = [&](int J, uint32_t a) {
                const uint32_t r0 = lds32(a), rp = lds32(a + 32), rm = lds32(a - 32);
                uint32_t r3;
                asm volatile("ld.volatile.shared.u32 %0, [%1];" : "=r"(r3) : "r"(a) : "memory");
#pragma unroll
                for (int I = J; I < 16; I++)
                    mma16816(acc[I], r0, rp, rm, r3, B[(I - J) >> 1][((I - J) & 1) * 2], B[(I - J) >> 1][((I - J) & 1) * 2 + 1]);
            };
#pragma unroll
            for (int J = 0; J < 4; J++) block(J, kb + j0 * 64 + J * 512);
            if (j0 < 2) { block(4, kb + j0 * 64 + 2048); block(8, kb + j0 * 64 + (544 + 16) * 4); }
        }
    }
    }
    {
        __syncwarp();
#pragma unroll
        for (int i = 0; i < 8; i++)
            stsm4t(rs + lf + i * 512, pack2(acc[2 * i][0], acc[2 * i][1]), pack2(acc[2 * i][2], acc[2 * i][3]),
                   pack2(acc[2 * i + 1][0], acc[2 * i + 1][1]), pack2(acc[2 * i + 1][2], acc[2 * i + 1][3]));
    }
    __syncthreads();
    {
        const uint2 dv = __ldg((const uint2*)(Dsk + d0 + 4 * t));
        load_params(min(item + (int)gridDim.x, 63));
        bf16* dst = out + (size_t)(w * 128 + g) * 2048 + 1024 + d0 + 4 * t;
        uint32_t o[8][4];
#pragma unroll
        for (int i = 0; i < 8; i++) {
            uint32_t y[4], x[4];
            ldsm4t(y, sb + S4_R + tr_off * S4_RS + (w * 128 + i * 16) * 2 + tr_l);
            ldsm4t(x, sb + S4_U + tr_off * S4_US + 256 + (w * 128 + i * 16) * 2 + tr_l);
#pragma unroll
            for (int j = 0; j < 4; j++)
                asm("{\n.reg .b32 s;\nmul.rn.bf16x2 s, %2, %3;\nadd.rn.bf16x2 %0, %1, s;\n}" : "=r"(o[i][j]) : "r"(y[j]), "r"(x[j]), "r"((j & 1) ? dv.y : dv.x));
        }
        __syncthreads();
#pragma unroll
        for (int i = 0; i < 8; i++) {
            *reinterpret_cast<uint2*>(dst + (size_t)(i * 16) * 2048) = make_uint2(o[i][0], o[i][1]);
            *reinterpret_cast<uint2*>(dst + (size_t)(i * 16 + 8) * 2048) = make_uint2(o[i][2], o[i][3]);
        }
    }
    }
}

enum { IT_W256 = 1, IT_W128 = 2, IT_W64 = 3, IT_END = 7 };
struct BgParams { CUtensorMap mo, mo2, mwo4, mwo2, mwo1; };
#define NBT 10
#define P256 56
#define P128 62
struct Sched { uint32_t w0, w1; };
__device__ __forceinline__ int next_item(Sched& z) {
    if (z.w0 >= z.w1) {
        uint32_t prog;
        asm volatile("ld.relaxed.gpu.global.u32 %0, [%1];" : "=r"(prog) : "l"(g_flag + 98) : "memory");
        const uint32_t k = prog <= P256 ? 4 : prog <= P128 ? 2 : 1;
        z.w0 = 4 * gridDim.x + atomicAdd(g_flag + 97, k);
        z.w1 = min(z.w0 + k, NBT * 16u);
        if (z.w0 >= z.w1) return IT_END;
    }
    const uint32_t i = z.w0, k = z.w1 - i >= 4 && !(i & 3) ? 4 : z.w1 - i >= 2 && !(i & 1) ? 2 : 1;
    z.w0 += k;
    return (k == 4 ? IT_W256 : k == 2 ? IT_W128 : IT_W64) | (i >> 4) << 3 | ((i & 15) / k) << 7;
}
constexpr int B_OST = NSTAGE * STAGE_BYTES + 1024;
constexpr int BG_SMEM = B_OST + 32768;

template <int BM, int BN, int KPS, typename ACC>
__device__ __forceinline__ void gemm_mainloop(ACC& acc, const GemmSmem& g, int cw, int rounds, uint32_t& round) {
#pragma unroll
    for (int i = 0; i < BN / 2; i++) acc[i] = 0.f;
#pragma unroll 1
    for (int k0 = 0; k0 < rounds; k0++, round++) {
#pragma unroll
        for (int s = 0; s < 4; s++) {
            mbar_wait_u(g.full + 8 * s, round & 1);
            gemm_stage<BM, BN, KPS>(acc, g.st + s * STAGE_BYTES, cw, false);
            wg_wait<1>();
            if (s > 0 || k0 > 0) mbar_arrive_one(g.empty + 8 * ((s + 3) & 3), threadIdx.x & 31);
        }
    }
    wg_wait<0>();
    mbar_arrive_one(g.empty + 8 * 3, threadIdx.x & 31);
}

template <int BN>
__device__ __forceinline__ void store_tile(const float (&acc)[BN / 2], bf16* dst, int t) {
#pragma unroll
    for (int G = 0; G < BN / 32; G++)
#pragma unroll
        for (int rr = 0; rr < 2; rr++) {
            uint32_t r0 = pack2(acc[16 * G + 2 * rr], acc[16 * G + 2 * rr + 1]), r1 = pack2(acc[16 * G + 4 + 2 * rr], acc[16 * G + 5 + 2 * rr]);
            uint32_t r2 = pack2(acc[16 * G + 8 + 2 * rr], acc[16 * G + 9 + 2 * rr]), r3 = pack2(acc[16 * G + 12 + 2 * rr], acc[16 * G + 13 + 2 * rr]);
            quad_transpose(r0, r1, r2, r3, t);
            *reinterpret_cast<uint4*>(dst + (size_t)rr * 8 * 2048 + G * 32) = make_uint4(r0, r1, r2, r3);
        }
}

template <int BN, int KPS>
__device__ __forceinline__ void wo_item(const GemmSmem& g, int cw, uint32_t& round, bf16* dst, int t) {
    float acc[BN / 2];
    gemm_mainloop<128, BN, KPS>(acc, g, cw, 16 / KPS, round);
    store_tile<BN>(acc, dst, t);
}

__global__ void __launch_bounds__(384, 1) k_bg(const __grid_constant__ BgParams P, bf16* __restrict__ out) {
    extern __shared__ __align__(1024) uint8_t smem_gemm[];
    asm volatile("griddepcontrol.launch_dependents;");
    const uint32_t bar_item = smem_u32(smem_gemm) + NSTAGE * STAGE_BYTES + 128, slot = bar_item + 16;
    if (threadIdx.x == 0) { mbar_init(bar_item, 1); mbar_init(bar_item + 8, 1); }
    if (threadIdx.x == 32) asm volatile("prefetch.tensormap [%0];\nprefetch.tensormap [%1];" ::"l"(&P.mo), "l"(&P.mwo4) : "memory");
    GemmSmem g = gemm_setup(smem_gemm, 8);
    const int wg = __shfl_sync(~0u, threadIdx.x >> 7, 0);
    if (wg == 0) {
        asm volatile("setmaxnreg.dec.sync.aligned.u32 40;");
        if (threadIdx.x == 0) {
            uint32_t it = 0;
            Sched z = {4 * blockIdx.x, 4 * blockIdx.x + 4};
            for (int n = 0;; n++) {
                const int code = next_item(z);
                sts32(slot + (n & 1) * 4, code);
                mbar_arrive(bar_item + (n & 1) * 8);
                const int type = code & 7, blk = (code >> 3) & 15, idx = code >> 7;
                if (type == IT_END) break;
                wait_flag(g_flag + 64 + blk, 96);
                asm volatile("fence.proxy.async.global;" ::: "memory");
                for (int k = 0; k < (type == IT_W64 ? 32 : 64); k++, it++) {
                    const int s = it & 3;
                    const uint32_t st = g.st + s * STAGE_BYTES, fb = g.full + 8 * s;
                    mbar_wait(g.empty + 8 * s, ((it >> 2) & 1) ^ 1);
                    mbar_expect_tx(fb, type == IT_W128 ? 32768 : 49152);
                    if (type == IT_W64) {
                        tma3d(st, &P.mo2, 0, blk * 128, k * 2, fb);
                        tma3d(st + 32768, &P.mwo1, 0, k * 128, idx, fb);
                    } else {
                        tma2d(st, &P.mo, k * 64, blk * 128, fb);
                        tma3d(st + 16384, type == IT_W256 ? &P.mwo4 : &P.mwo2, 0, k * 64, idx * (type == IT_W256 ? 4 : 2), fb);
                    }
                }
            }
        }
    } else {
        asm volatile("setmaxnreg.inc.sync.aligned.u32 232;");
        const int cw = wg - 1, lane = threadIdx.x & 31;
        uint32_t round = 0;
#pragma unroll 1
        for (int n = 0;; n++) {
            mbar_wait_u(bar_item + (n & 1) * 8, (n >> 1) & 1);
            const int code = __shfl_sync(~0u, lds32(slot + (n & 1) * 4), 0);
            const int type = code & 7, blk = (code >> 3) & 15, idx = (code >> 7) & 31;
            if (type == IT_END) break;
            bf16* dst = out + (size_t)(blk * 128 + cw * 64 + ((threadIdx.x >> 5) & 3) * 16 + (lane >> 2)) * 2048 + (lane & 3) * 8;
            if (type == IT_W256) wo_item<256, 1>(g, cw, round, dst + idx * 256, lane & 3);
            else if (type == IT_W128) wo_item<128, 1>(g, cw, round, dst + idx * 128, lane & 3);
            else wo_item<64, 2>(g, cw, round, dst + idx * 64, lane & 3);
        }
    }
}

static_assert(NBT == 10, "k_tail covers blocks 10..15");
__global__ void __cluster_dims__(6, 1, 1) __launch_bounds__(384, 1)
k_tail(const __grid_constant__ BgParams P, bf16* __restrict__ out) {
    extern __shared__ __align__(1024) uint8_t smem_gemm[];
    const int cl = blockIdx.x / 6, rank = blockIdx.x - 6 * cl, half = rank & 1, pr = rank >> 1;
    const int blk = NBT + (cl >> 3) * 3 + pr, idx = cl & 7;
    const uint32_t st = smem_u32(smem_gemm), full = st + 6 * 32768, empty = full + 64, emptyb = full + 128, bar_s = full + 192;
    if (threadIdx.x == 0) {
        for (int s = 0; s < 6; s++) { mbar_init(full + 8 * s, 1); mbar_init(empty + 8 * s, 2); mbar_init(emptyb + 8 * s, 6); }
        mbar_init(bar_s, 1); mbar_expect_tx(bar_s, 32768);
        asm volatile("fence.mbarrier_init.release.cluster;\nfence.proxy.async.shared::cta;" ::: "memory");
    }
    if (threadIdx.x == 32) asm volatile("prefetch.tensormap [%0];\nprefetch.tensormap [%1];" ::"l"(&P.mo), "l"(&P.mwo2) : "memory");
    __syncthreads();
    asm volatile("barrier.cluster.arrive.relaxed.aligned;\nbarrier.cluster.wait.aligned;" ::: "memory");
    const int wg = __shfl_sync(~0u, threadIdx.x >> 7, 0);
    if (wg == 0) {
        if (threadIdx.x == 0) {
            wait_flag(g_flag + 64 + blk, 96);
            asm volatile("fence.proxy.async.global;" ::: "memory");
            if (blockIdx.x == 95)
                for (int i = 0; i < 4; i++) reinterpret_cast<uint4*>(g_flag)[i] = make_uint4(0, 0, 0, 0);
            for (int k = 0, s = 0, ph = 1; k < 32; k++) {
                mbar_wait(empty + 8 * s, ph);
                mbar_expect_tx(full + 8 * s, 32768);
                tma2d(st + s * 32768, &P.mo, (half * 32 + k) * 64, blk * 128, full + 8 * s);
                if (++s == 6) { s = 0; ph ^= 1; }
            }
        } else if (threadIdx.x == 32) {
            for (int k = pr, s = pr, ph = 1; k < 32; k += 3) {
                mbar_wait(emptyb + 8 * s, ph);
                asm volatile("cp.async.bulk.tensor.3d.shared::cluster.global.mbarrier::complete_tx::bytes.multicast::cluster "
                             "[%0], [%1, {%3, %4, %5}], [%2], %6;"
                             ::"r"(st + s * 32768 + 16384), "l"(&P.mwo2), "r"(full + 8 * s), "r"(0), "r"((half * 32 + k) * 64), "r"(idx * 2),
                               "h"((uint16_t)(0x15 << half)) : "memory");
                s += 3;
                if (s >= 6) { s -= 6; ph ^= 1; }
            }
        }
    } else {
        const int cw = wg - 1, lane = threadIdx.x & 31, t = lane & 3;
        float acc[64], fin[32];
#pragma unroll
        for (int i = 0; i < 64; i++) acc[i] = 0.f;
#pragma unroll 1
        for (int k = 0, s = 0, ph = 0, sp = 0; k < 32; k++) {
            mbar_wait_u(full + 8 * s, ph);
            gemm_stage<128, 128, 1>(acc, st + s * 32768, cw, false);
            wg_wait<1>();
            if (k > 0 && k <= 26)
                asm volatile("{\n.reg .pred p;\n.reg .u32 a;\nsetp.eq.u32 p, %3, 0;\nmapa.shared::cluster.u32 a, %1, %2;\n"
                             "@p mbarrier.arrive.relaxed.cta.shared::cta.b64 _, [%0];\n@p mbarrier.arrive.relaxed.cluster.shared::cluster.b64 _, [a];\n}"
                             ::"r"(empty + 8 * sp), "r"(emptyb + 8 * sp), "r"((sp >= 3 ? sp - 3 : sp) * 2 + half), "r"(threadIdx.x & 127) : "memory");
            sp = s;
            if (++s == 6) { s = 0; ph ^= 1; }
        }
        wg_wait<0>();
        const uint32_t xa = st + B_OST + (threadIdx.x - 128) * 16;
        uint32_t ra, rb;
        asm("mapa.shared::cluster.u32 %0, %1, %2;" : "=r"(ra) : "r"(xa), "r"(rank ^ 1));
        asm("mapa.shared::cluster.u32 %0, %1, %2;" : "=r"(rb) : "r"(bar_s), "r"(rank ^ 1));
#pragma unroll
        for (int i = 0; i < 8; i++) {
            float v[4];
#pragma unroll
            for (int j = 0; j < 4; j++) {
                v[j] = half ? acc[4 * i + j] : acc[32 + 4 * i + j];
                fin[4 * i + j] = half ? acc[32 + 4 * i + j] : acc[4 * i + j];
            }
            asm volatile("st.async.weak.shared::cluster.mbarrier::complete_tx::bytes.v4.f32 [%0], {%1,%2,%3,%4}, [%5];"
                         ::"r"(ra + i * 4096), "f"(v[0]), "f"(v[1]), "f"(v[2]), "f"(v[3]), "r"(rb) : "memory");
        }
        mbar_wait_u(bar_s, 0);
#pragma unroll
        for (int i = 0; i < 8; i++) {
            const float4 v = lds128f(xa + i * 4096);
            fin[4 * i] += v.x; fin[4 * i + 1] += v.y; fin[4 * i + 2] += v.z; fin[4 * i + 3] += v.w;
        }
        store_tile<64>(fin, out + (size_t)(blk * 128 + cw * 64 + ((threadIdx.x >> 5) & 3) * 16 + (lane >> 2)) * 2048 + idx * 128 + half * 64 + t * 8, t);
    }
}

typedef CUresult (*EncodeFn)(CUtensorMap*, CUtensorMapDataType, cuuint32_t, void*, const cuuint64_t*, const cuuint64_t*,
                             const cuuint32_t*, const cuuint32_t*, CUtensorMapInterleave, CUtensorMapSwizzle,
                             CUtensorMapL2promotion, CUtensorMapFloatOOBfill);

static void map2d(EncodeFn enc, CUtensorMap* m, const void* p, int rows, int cols, int box_rows) {
    cuuint64_t dim[2] = {(cuuint64_t)cols, (cuuint64_t)rows}, str[1] = {(cuuint64_t)cols * 2};
    cuuint32_t box[2] = {64, (cuuint32_t)box_rows}, es[2] = {1, 1};
    enc(m, CU_TENSOR_MAP_DATA_TYPE_BFLOAT16, 2, (void*)p, dim, str, box, es, CU_TENSOR_MAP_INTERLEAVE_NONE,
        CU_TENSOR_MAP_SWIZZLE_128B, CU_TENSOR_MAP_L2_PROMOTION_L2_256B, CU_TENSOR_MAP_FLOAT_OOB_FILL_NONE);
}
static void map3d(EncodeFn enc, CUtensorMap* m, const void* p, int rows, int cols, int box_rows, int nblk) {
    cuuint64_t dim[3] = {64, (cuuint64_t)rows, (cuuint64_t)cols / 64}, str[2] = {(cuuint64_t)cols * 2, 128};
    cuuint32_t box[3] = {64, (cuuint32_t)box_rows, (cuuint32_t)nblk}, es[3] = {1, 1, 1};
    enc(m, CU_TENSOR_MAP_DATA_TYPE_BFLOAT16, 3, (void*)p, dim, str, box, es, CU_TENSOR_MAP_INTERLEAVE_NONE,
        CU_TENSOR_MAP_SWIZZLE_128B, CU_TENSOR_MAP_L2_PROMOTION_L2_256B, CU_TENSOR_MAP_FLOAT_OOB_FILL_NONE);
}

#define USE_PDL 1

extern "C" void kernel_launch(void* const* d_in, const int* in_sizes, int n_in, void* d_out, int out_size) {
    const bf16 *x = (const bf16*)d_in[0], *mem0 = (const bf16*)d_in[1], *Wq = (const bf16*)d_in[2], *Wk = (const bf16*)d_in[3];
    const bf16 *Wv = (const bf16*)d_in[4], *Wo = (const bf16*)d_in[5];
    const bf16 *u = (const bf16*)d_in[7], *Are = (const bf16*)d_in[8], *Aim = (const bf16*)d_in[9], *Bre = (const bf16*)d_in[10];
    const bf16 *Bim = (const bf16*)d_in[11], *Cre = (const bf16*)d_in[12], *Cim = (const bf16*)d_in[13];
    const bf16 *logdt = (const bf16*)d_in[14], *Dsk = (const bf16*)d_in[15];
    bf16* out = (bf16*)d_out;

    void* fn = nullptr;
    cudaDriverEntryPointQueryResult qr;
    cudaGetDriverEntryPoint("cuTensorMapEncodeTiled", &fn, cudaEnableDefault, &qr);
    EncodeFn enc = (EncodeFn)fn;
    void *kv, *o;
    cudaGetSymbolAddress(&kv, g_kv);
    cudaGetSymbolAddress(&o, g_o);
    CUtensorMap mx, mwq, mwk, mwv, mkv2;
    BgParams P;
    map2d(enc, &mx, x, SEQ, DM, 128);
    map2d(enc, &P.mo, o, SEQ, HD, 128);
    map3d(enc, &P.mo2, o, SEQ, HD, 128, 2);
    map3d(enc, &mwq, Wq, DM, HD, 64, 2);
    map3d(enc, &mwk, Wk, DM, HD, 64, 2);
    map3d(enc, &mwv, Wv, DM, HD, 64, 2);
    map3d(enc, &P.mwo4, Wo, HD, DM, 64, 4);
    map3d(enc, &P.mwo2, Wo, HD, DM, 64, 2);
    map3d(enc, &P.mwo1, Wo, HD, DM, 128, 1);
    map3d(enc, &mkv2, kv, SEQ, PW, 32, 2);
    cudaFuncSetAttribute(k_kv, cudaFuncAttributeMaxDynamicSharedMemorySize, GEMM_SMEM);
    cudaFuncSetAttribute(k_bg, cudaFuncAttributeMaxDynamicSharedMemorySize, BG_SMEM);
    cudaFuncSetAttribute(k_tail, cudaFuncAttributeMaxDynamicSharedMemorySize, BG_SMEM);
    cudaFuncSetAttribute(k_chain, cudaFuncAttributeMaxDynamicSharedMemorySize, CHAIN_SMEM);
    cudaFuncSetAttribute(k_s4, cudaFuncAttributeMaxDynamicSharedMemorySize, S4_SMEM);

    cudaStream_t st = cudaStreamPerThread;
    cudaLaunchAttribute pdl[2], cls[1];
    pdl[0].id = cudaLaunchAttributeProgrammaticStreamSerialization;
    pdl[0].val.programmaticStreamSerializationAllowed = 1;
    cls[0].id = cudaLaunchAttributeClusterDimension;
    cls[0].val.clusterDim.x = CLS; cls[0].val.clusterDim.y = 1; cls[0].val.clusterDim.z = 1;
    cudaLaunchConfig_t cfg = {};
    cfg.stream = st; cfg.attrs = cls; cfg.numAttrs = 1;
    cfg.gridDim = dim3(96); cfg.blockDim = dim3(384); cfg.dynamicSmemBytes = GEMM_SMEM;
    cudaLaunchKernelEx(&cfg, k_kv, mx, mwk, mwv, mwq, Wo, 0);
    pdl[1] = cls[0]; pdl[1].val.clusterDim.x = 2;
    cfg.attrs = pdl; cfg.numAttrs = 2;
    cfg.gridDim = dim3(36);
    cudaLaunchKernelEx(&cfg, k_kv, mx, mwk, mwv, mwq, Wo, 96);
    cfg.numAttrs = 1;
    cfg.gridDim = dim3(96); cfg.blockDim = dim3(256); cfg.dynamicSmemBytes = CHAIN_SMEM;
    cudaLaunchKernelEx(&cfg, k_chain, mem0, Wq, Wk, Wv, Wo, mkv2);
    cfg.numAttrs = USE_PDL;
    cfg.gridDim = dim3(36); cfg.blockDim = dim3(512); cfg.dynamicSmemBytes = S4_SMEM;
    cudaLaunchKernelEx(&cfg, k_s4, u, Are, Aim, Bre, Bim, Cre, Cim, logdt, Dsk, out);
    cfg.gridDim = dim3(36); cfg.blockDim = dim3(384); cfg.dynamicSmemBytes = BG_SMEM;
    cudaLaunchKernelEx(&cfg, k_bg, P, out);
    cfg.gridDim = dim3(96);
    cudaLaunchKernelEx(&cfg, k_tail, P, out);
}
```

```cpp
#include <cuda_runtime.h>
#include <cuda_bf16.h>
#include <cuda.h>
#include <stdint.h>

typedef __nv_bfloat16 bf16;

constexpr int SEQ = 2048, DM = 1024, HD = 4096, NSEG = 64;

constexpr int PW = 3 * HD;
#define NTA 3
constexpr int NBT = 10;
__device__ __align__(1024) bf16 g_kv[(size_t)SEQ * PW];
__device__ __align__(1024) bf16 g_o[(size_t)SEQ * HD];
constexpr int XPAIRS = 128 + NSEG * 4;
__device__ __align__(8192) uint2 g_x[XPAIRS * 1024];
__device__ uint32_t g_home[XPAIRS];
__device__ uint32_t g_side[256];
__device__ __align__(1024) uint32_t g_flag[256];

__device__ __forceinline__ uint32_t smem_u32(const void* p) { return (uint32_t)__cvta_generic_to_shared(p); }
__device__ __forceinline__ void mbar_init(uint32_t bar, uint32_t cnt) {
    asm volatile("mbarrier.init.shared::cta.b64 [%0], %1;" ::"r"(bar), "r"(cnt) : "memory");
}
__device__ __forceinline__ void mbar_expect_tx(uint32_t bar, uint32_t bytes) {
    asm volatile("mbarrier.arrive.expect_tx.shared::cta.b64 _, [%0], %1;" ::"r"(bar), "r"(bytes) : "memory");
}
__device__ __forceinline__ void mbar_arrive(uint32_t bar) {
    asm volatile("mbarrier.arrive.shared::cta.b64 _, [%0];" ::"r"(bar) : "memory");
}
__device__ __forceinline__ bool mbar_try(uint32_t bar, uint32_t parity) {
    uint32_t ok;
    asm volatile("{\n.reg .pred p;\nmbarrier.try_wait.parity.shared::cta.b64 p, [%1], %2;\nselp.u32 %0, 1, 0, p;\n}"
                 : "=r"(ok) : "r"(bar), "r"(parity) : "memory");
    return ok;
}
constexpr int SPIN_LIMIT = 1 << 20;
__device__ __forceinline__ void mbar_wait(uint32_t bar, uint32_t parity) {
    int n = 0;
    while (!mbar_try(bar, parity)) { if (++n > SPIN_LIMIT) __trap(); }
}
__device__ __forceinline__ void mbar_wait_u(uint32_t bar, uint32_t parity) {
    asm volatile("{\n.reg .pred p;\n.reg .u32 n;\n"
                 "mbarrier.try_wait.parity.shared::cta.b64 p, [%0], %1;\n@p bra.uni DONE;\nmov.u32 n, 0;\n"
                 "AGAIN:\nmbarrier.try_wait.parity.shared::cta.b64 p, [%0], %1;\n@p bra.uni DONE;\n"
                 "add.u32 n, n, 1;\nsetp.lt.u32 p, n, 0x100000;\n@p bra.uni AGAIN;\ntrap;\nDONE:\n}"
                 ::"r"(bar), "r"(parity) : "memory");
}
__device__ __forceinline__ void tma2d(uint32_t dst, const CUtensorMap* m, int c0, int c1, uint32_t bar) {
    asm volatile("cp.async.bulk.tensor.2d.shared::cluster.global.mbarrier::complete_tx::bytes [%0], [%1, {%3, %4}], [%2];"
                 ::"r"(dst), "l"(m), "r"(bar), "r"(c0), "r"(c1) : "memory");
}
__device__ __forceinline__ void tma3d(uint32_t dst, const CUtensorMap* m, int c0, int c1, int c2, uint32_t bar) {
    asm volatile("cp.async.bulk.tensor.3d.shared::cluster.global.mbarrier::complete_tx::bytes [%0], [%1, {%3, %4, %5}], [%2];"
                 ::"r"(dst), "l"(m), "r"(bar), "r"(c0), "r"(c1), "r"(c2) : "memory");
}
__device__ __forceinline__ uint32_t pack2(float lo, float hi) {
    uint32_t r;
    asm("cvt.rn.bf16x2.f32 %0, %1, %2;" : "=r"(r) : "f"(hi), "f"(lo));
    return r;
}
__device__ __forceinline__ float bf_lo(uint32_t v) { return __uint_as_float(v << 16); }
__device__ __forceinline__ float bf_hi(uint32_t v) { return __uint_as_float(v & 0xffff0000u); }
__device__ __forceinline__ float bf_round(float x) { return bf_lo(pack2(x, 0.f)); }
__device__ __forceinline__ float ex2(float x) { float y; asm("ex2.approx.ftz.f32 %0, %1;" : "=f"(y) : "f"(x)); return y; }
__device__ __forceinline__ void mma16816(float (&c)[4], uint32_t a0, uint32_t a1, uint32_t a2, uint32_t a3, uint32_t b0, uint32_t b1) {
    asm volatile("mma.sync.aligned.m16n8k16.row.col.f32.bf16.bf16.f32 {%0,%1,%2,%3}, {%4,%5,%6,%7}, {%8,%9}, {%0,%1,%2,%3};"
                 : "+f"(c[0]), "+f"(c[1]), "+f"(c[2]), "+f"(c[3]) : "r"(a0), "r"(a1), "r"(a2), "r"(a3), "r"(b0), "r"(b1));
}
__device__ __forceinline__ void mma1688(float (&c)[4], uint32_t a0, uint32_t a1, uint32_t b0) {
    asm volatile("mma.sync.aligned.m16n8k8.row.col.f32.bf16.bf16.f32 {%0,%1,%2,%3}, {%4,%5}, {%6}, {%0,%1,%2,%3};"
                 : "+f"(c[0]), "+f"(c[1]), "+f"(c[2]), "+f"(c[3]) : "r"(a0), "r"(a1), "r"(b0));
}
__device__ __forceinline__ void ldsm4(uint32_t (&r)[4], uint32_t a) {
    asm volatile("ldmatrix.sync.aligned.m8n8.x4.shared.b16 {%0,%1,%2,%3}, [%4];"
                 : "=r"(r[0]), "=r"(r[1]), "=r"(r[2]), "=r"(r[3]) : "r"(a) : "memory");
}
__device__ __forceinline__ void ldsm4t(uint32_t (&r)[4], uint32_t a) {
    asm volatile("ldmatrix.sync.aligned.m8n8.x4.trans.shared.b16 {%0,%1,%2,%3}, [%4];"
                 : "=r"(r[0]), "=r"(r[1]), "=r"(r[2]), "=r"(r[3]) : "r"(a) : "memory");
}
__device__ __forceinline__ void stsm4t(uint32_t a, uint32_t r0, uint32_t r1, uint32_t r2, uint32_t r3) {
    asm volatile("stmatrix.sync.aligned.m8n8.x4.trans.shared.b16 [%0], {%1,%2,%3,%4};"
                 ::"r"(a), "r"(r0), "r"(r1), "r"(r2), "r"(r3) : "memory");
}
__device__ __forceinline__ void lds128(uint32_t (&r)[4], uint32_t a) {
    asm volatile("ld.shared.v4.u32 {%0,%1,%2,%3}, [%4];" : "=r"(r[0]), "=r"(r[1]), "=r"(r[2]), "=r"(r[3]) : "r"(a) : "memory");
}
__device__ __forceinline__ float4 lds128f(uint32_t a) {
    float4 v;
    asm volatile("ld.shared.v4.f32 {%0,%1,%2,%3}, [%4];" : "=f"(v.x), "=f"(v.y), "=f"(v.z), "=f"(v.w) : "r"(a) : "memory");
    return v;
}
__device__ __forceinline__ float2 lds64f(uint32_t a) {
    float2 v;
    asm volatile("ld.shared.v2.f32 {%0,%1}, [%2];" : "=f"(v.x), "=f"(v.y) : "r"(a) : "memory");
    return v;
}
__device__ __forceinline__ uint32_t lds32(uint32_t a) {
    uint32_t v;
    asm volatile("ld.shared.u32 %0, [%1];" : "=r"(v) : "r"(a) : "memory");
    return v;
}
__device__ __forceinline__ void sts128(uint32_t a, uint32_t r0, uint32_t r1, uint32_t r2, uint32_t r3) {
    asm volatile("st.shared.v4.u32 [%0], {%1,%2,%3,%4};" ::"r"(a), "r"(r0), "r"(r1), "r"(r2), "r"(r3) : "memory");
}
__device__ __forceinline__ void sts64(uint32_t a, uint32_t r0, uint32_t r1) {
    asm volatile("st.shared.v2.u32 [%0], {%1,%2};" ::"r"(a), "r"(r0), "r"(r1) : "memory");
}
__device__ __forceinline__ void sts32f(uint32_t a, float r0) {
    asm volatile("st.shared.f32 [%0], %1;" ::"r"(a), "f"(r0) : "memory");
}
__device__ __forceinline__ void st_rlx64(uint2* p, uint32_t x, uint32_t y) {
    asm volatile("{\n.reg .b64 t;\nmov.b64 t, {%1,%2};\nst.relaxed.gpu.global.b64 [%0], t;\n}" ::"l"(p), "r"(x), "r"(y) : "memory");
}
__device__ __forceinline__ uint32_t ld_acq32(const uint32_t* p) {
    uint32_t v;
    asm volatile("ld.acquire.gpu.global.u32 %0, [%1];" : "=r"(v) : "l"(p) : "memory");
    return v;
}
__device__ __forceinline__ void wait_flag(const uint32_t* p, uint32_t need) {
    int n = 0;
    while (ld_acq32(p) < need) { __nanosleep(200); if (++n > SPIN_LIMIT) __trap(); }
}
__device__ __forceinline__ void bar_sync(int id, int n) { asm volatile("bar.sync %0, %1;" ::"r"(id), "r"(n) : "memory"); }
__device__ __forceinline__ void wg_fence() { asm volatile("wgmma.fence.sync.aligned;" ::: "memory"); }
__device__ __forceinline__ void wg_commit() { asm volatile("wgmma.commit_group.sync.aligned;" ::: "memory"); }
template <int N> __device__ __forceinline__ void wg_wait() { asm volatile("wgmma.wait_group.sync.aligned %0;" ::"n"(N) : "memory"); }
__device__ __forceinline__ uint64_t desc_sw128(uint32_t addr, uint32_t lbo, uint32_t sbo) {
    return (uint64_t)((addr & 0x3FFFF) >> 4) | ((uint64_t)(lbo >> 4) << 16) | ((uint64_t)(sbo >> 4) << 32) | (1ull << 62);
}
__device__ __forceinline__ void quad_transpose(uint32_t& r0, uint32_t& r1, uint32_t& r2, uint32_t& r3, int t) {
    const bool o = t & 1, h = t & 2;
    uint32_t s0 = __shfl_xor_sync(~0u, o ? r0 : r1, 1), s1 = __shfl_xor_sync(~0u, o ? r2 : r3, 1);
    uint32_t a0 = o ? s0 : r0, a1 = o ? r1 : s0, a2 = o ? s1 : r2, a3 = o ? r3 : s1;
    s0 = __shfl_xor_sync(~0u, h ? a0 : a2, 2); s1 = __shfl_xor_sync(~0u, h ? a1 : a3, 2);
    r0 = h ? s0 : a0; r1 = h ? s1 : a1; r2 = h ? a2 : s0; r3 = h ? a3 : s1;
}

__device__ __forceinline__ void wgmma_n256(float (&d)[128], uint64_t da, uint64_t db, int sd) {
    asm volatile("{\n.reg .pred p;\nsetp.ne.b32 p, %130, 0;\n"
        "wgmma.mma_async.sync.aligned.m64n256k16.f32.bf16.bf16 "
        "{%0,%1,%2,%3,%4,%5,%6,%7,%8,%9,%10,%11,%12,%13,%14,%15,"
        "%16,%17,%18,%19,%20,%21,%22,%23,%24,%25,%26,%27,%28,%29,%30,%31,"
        "%32,%33,%34,%35,%36,%37,%38,%39,%40,%41,%42,%43,%44,%45,%46,%47,"
        "%48,%49,%50,%51,%52,%53,%54,%55,%56,%57,%58,%59,%60,%61,%62,%63,"
        "%64,%65,%66,%67,%68,%69,%70,%71,%72,%73,%74,%75,%76,%77,%78,%79,"
        "%80,%81,%82,%83,%84,%85,%86,%87,%88,%89,%90,%91,%92,%93,%94,%95,"
        "%96,%97,%98,%99,%100,%101,%102,%103,%104,%105,%106,%107,%108,%109,%110,%111,"
        "%112,%113,%114,%115,%116,%117,%118,%119,%120,%121,%122,%123,%124,%125,%126,%127}, %128, %129, p, 1, 1, 0, 1;\n}\n"
        : "+f"(d[0]), "+f"(d[1]), "+f"(d[2]), "+f"(d[3]), "+f"(d[4]), "+f"(d[5]), "+f"(d[6]), "+f"(d[7]),
          "+f"(d[8]), "+f"(d[9]), "+f"(d[10]), "+f"(d[11]), "+f"(d[12]), "+f"(d[13]), "+f"(d[14]), "+f"(d[15]),
          "+f"(d[16]), "+f"(d[17]), "+f"(d[18]), "+f"(d[19]), "+f"(d[20]), "+f"(d[21]), "+f"(d[22]), "+f"(d[23]),
          "+f"(d[24]), "+f"(d[25]), "+f"(d[26]), "+f"(d[27]), "+f"(d[28]), "+f"(d[29]), "+f"(d[30]), "+f"(d[31]),
          "+f"(d[32]), "+f"(d[33]), "+f"(d[34]), "+f"(d[35]), "+f"(d[36]), "+f"(d[37]), "+f"(d[38]), "+f"(d[39]),
          "+f"(d[40]), "+f"(d[41]), "+f"(d[42]), "+f"(d[43]), "+f"(d[44]), "+f"(d[45]), "+f"(d[46]), "+f"(d[47]),
          "+f"(d[48]), "+f"(d[49]), "+f"(d[50]), "+f"(d[51]), "+f"(d[52]), "+f"(d[53]), "+f"(d[54]), "+f"(d[55]),
          "+f"(d[56]), "+f"(d[57]), "+f"(d[58]), "+f"(d[59]), "+f"(d[60]), "+f"(d[61]), "+f"(d[62]), "+f"(d[63]),
          "+f"(d[64]), "+f"(d[65]), "+f"(d[66]), "+f"(d[67]), "+f"(d[68]), "+f"(d[69]), "+f"(d[70]), "+f"(d[71]),
          "+f"(d[72]), "+f"(d[73]), "+f"(d[74]), "+f"(d[75]), "+f"(d[76]), "+f"(d[77]), "+f"(d[78]), "+f"(d[79]),
          "+f"(d[80]), "+f"(d[81]), "+f"(d[82]), "+f"(d[83]), "+f"(d[84]), "+f"(d[85]), "+f"(d[86]), "+f"(d[87]),
          "+f"(d[88]), "+f"(d[89]), "+f"(d[90]), "+f"(d[91]), "+f"(d[92]), "+f"(d[93]), "+f"(d[94]), "+f"(d[95]),
          "+f"(d[96]), "+f"(d[97]), "+f"(d[98]), "+f"(d[99]), "+f"(d[100]), "+f"(d[101]), "+f"(d[102]), "+f"(d[103]),
          "+f"(d[104]), "+f"(d[105]), "+f"(d[106]), "+f"(d[107]), "+f"(d[108]), "+f"(d[109]), "+f"(d[110]), "+f"(d[111]),
          "+f"(d[112]), "+f"(d[113]), "+f"(d[114]), "+f"(d[115]), "+f"(d[116]), "+f"(d[117]), "+f"(d[118]), "+f"(d[119]),
          "+f"(d[120]), "+f"(d[121]), "+f"(d[122]), "+f"(d[123]), "+f"(d[124]), "+f"(d[125]), "+f"(d[126]), "+f"(d[127])
        : "l"(da), "l"(db), "r"(sd));
}

__device__ __forceinline__ void wgmma_n128(float (&d)[64], uint64_t da, uint64_t db, int sd) {
    asm volatile("{\n.reg .pred p;\nsetp.ne.b32 p, %66, 0;\n"
        "wgmma.mma_async.sync.aligned.m64n128k16.f32.bf16.bf16 "
        "{%0,%1,%2,%3,%4,%5,%6,%7,%8,%9,%10,%11,%12,%13,%14,%15,"
        "%16,%17,%18,%19,%20,%21,%22,%23,%24,%25,%26,%27,%28,%29,%30,%31,"
        "%32,%33,%34,%35,%36,%37,%38,%39,%40,%41,%42,%43,%44,%45,%46,%47,"
        "%48,%49,%50,%51,%52,%53,%54,%55,%56,%57,%58,%59,%60,%61,%62,%63}, %64, %65, p, 1, 1, 0, 1;\n}\n"
        : "+f"(d[0]), "+f"(d[1]), "+f"(d[2]), "+f"(d[3]), "+f"(d[4]), "+f"(d[5]), "+f"(d[6]), "+f"(d[7]),
          "+f"(d[8]), "+f"(d[9]), "+f"(d[10]), "+f"(d[11]), "+f"(d[12]), "+f"(d[13]), "+f"(d[14]), "+f"(d[15]),
          "+f"(d[16]), "+f"(d[17]), "+f"(d[18]), "+f"(d[19]), "+f"(d[20]), "+f"(d[21]), "+f"(d[22]), "+f"(d[23]),
          "+f"(d[24]), "+f"(d[25]), "+f"(d[26]), "+f"(d[27]), "+f"(d[28]), "+f"(d[29]), "+f"(d[30]), "+f"(d[31]),
          "+f"(d[32]), "+f"(d[33]), "+f"(d[34]), "+f"(d[35]), "+f"(d[36]), "+f"(d[37]), "+f"(d[38]), "+f"(d[39]),
          "+f"(d[40]), "+f"(d[41]), "+f"(d[42]), "+f"(d[43]), "+f"(d[44]), "+f"(d[45]), "+f"(d[46]), "+f"(d[47]),
          "+f"(d[48]), "+f"(d[49]), "+f"(d[50]), "+f"(d[51]), "+f"(d[52]), "+f"(d[53]), "+f"(d[54]), "+f"(d[55]),
          "+f"(d[56]), "+f"(d[57]), "+f"(d[58]), "+f"(d[59]), "+f"(d[60]), "+f"(d[61]), "+f"(d[62]), "+f"(d[63])
        : "l"(da), "l"(db), "r"(sd));
}

__device__ __forceinline__ void wgmma_n64(float (&d)[32], uint64_t da, uint64_t db, int sd) {
    asm volatile("{\n.reg .pred p;\nsetp.ne.b32 p, %34, 0;\n"
        "wgmma.mma_async.sync.aligned.m64n64k16.f32.bf16.bf16 "
        "{%0,%1,%2,%3,%4,%5,%6,%7,%8,%9,%10,%11,%12,%13,%14,%15,"
        "%16,%17,%18,%19,%20,%21,%22,%23,%24,%25,%26,%27,%28,%29,%30,%31}, %32, %33, p, 1, 1, 0, 1;\n}\n"
        : "+f"(d[0]), "+f"(d[1]), "+f"(d[2]), "+f"(d[3]), "+f"(d[4]), "+f"(d[5]), "+f"(d[6]), "+f"(d[7]),
          "+f"(d[8]), "+f"(d[9]), "+f"(d[10]), "+f"(d[11]), "+f"(d[12]), "+f"(d[13]), "+f"(d[14]), "+f"(d[15]),
          "+f"(d[16]), "+f"(d[17]), "+f"(d[18]), "+f"(d[19]), "+f"(d[20]), "+f"(d[21]), "+f"(d[22]), "+f"(d[23]),
          "+f"(d[24]), "+f"(d[25]), "+f"(d[26]), "+f"(d[27]), "+f"(d[28]), "+f"(d[29]), "+f"(d[30]), "+f"(d[31])
        : "l"(da), "l"(db), "r"(sd));
}

constexpr int STAGE_BYTES = 49152, NSTAGE = 4;
constexpr int GEMM_SMEM = NSTAGE * STAGE_BYTES + 128;

struct GemmSmem { uint32_t st, full, empty; };
__device__ __forceinline__ GemmSmem gemm_setup(uint8_t* raw, int releases) {
    GemmSmem g;
    g.st = smem_u32(raw);
    if (g.st & 1023) __trap();
    g.full = g.st + NSTAGE * STAGE_BYTES; g.empty = g.full + 64;
    if (threadIdx.x == 0) {
        for (int s = 0; s < NSTAGE; s++) { mbar_init(g.full + 8 * s, 1); mbar_init(g.empty + 8 * s, releases); }
        asm volatile("fence.mbarrier_init.release.cluster;" ::: "memory");
        asm volatile("fence.proxy.async.shared::cta;" ::: "memory");
    }
    __syncthreads();
    return g;
}
__device__ __forceinline__ void mbar_arrive_one(uint32_t bar, uint32_t who) {
    asm volatile("{\n.reg .pred p;\nsetp.eq.u32 p, %1, 0;\n@p mbarrier.arrive.shared::cta.b64 _, [%0];\n}" ::"r"(bar), "r"(who) : "memory");
}
template <int BM, int BN, int KPS, typename ACC>
__device__ __forceinline__ void gemm_stage(ACC& acc, uint32_t stage, int wg, bool first) {
    const uint64_t da = desc_sw128(stage + wg * 8192, 16, 1024);
    const uint64_t db = desc_sw128(stage + KPS * BM * 128, 8192, 1024);
    wg_fence();
#pragma unroll
    for (int k = 0; k < 4 * KPS; k++) {
        const uint64_t a = da + (k >> 2) * (BM * 8) + (k & 3) * 2, b = db + k * 128;
        if constexpr (BN == 256) wgmma_n256(acc, a, b, first && k == 0 ? 0 : 1);
        else if constexpr (BN == 128) wgmma_n128(acc, a, b, first && k == 0 ? 0 : 1);
        else wgmma_n64(acc, a, b, first && k == 0 ? 0 : 1);
    }
    wg_commit();
}

__device__ __forceinline__ void kv_store_unit(const uint32_t (&pk)[64], int u, bf16* dst, int t) {
    const int G = (u >> 2) * 2 + (u & 1), hh = (u >> 1) & 1;
    uint32_t r0 = pk[(4 * G + 0) * 2 + hh], r1 = pk[(4 * G + 1) * 2 + hh], r2 = pk[(4 * G + 2) * 2 + hh], r3 = pk[(4 * G + 3) * 2 + hh];
    quad_transpose(r0, r1, r2, r3, t);
#define KVST ".cs"
    asm volatile("st.global" KVST ".v4.u32 [%0], {%1,%2,%3,%4};" ::"l"(dst + (size_t)hh * 8 * PW + G * 32), "r"(r0), "r"(r1), "r"(r2), "r"(r3) : "memory");
}

__device__ __forceinline__ uint32_t near_page(int pair, int line) {
    uint32_t best[2] = {~0u, ~0u};
    for (int i = 0; i < 4; i++)
        reinterpret_cast<uint4*>(g_x + pair * 1024 + (i >> 1) * 512 + line * 16)[i & 1] = make_uint4(~0u, ~0u, ~0u, ~0u);
#pragma unroll 1
#define PMIN 8
#define PMAX 16
    for (int i = 0; i < PMAX; i++) {
        if (i >= PMIN && max(best[0], best[1]) - min(best[0], best[1]) > 110 && max(best[0], best[1]) - min(best[0], best[1]) < 300) break;
        uint32_t t0, t1, v;
        asm volatile("mov.u32 %0, %%clock;" : "=r"(t0)::"memory");
        asm volatile("atom.relaxed.gpu.global.or.b32 %0, [%1], -1;" : "=r"(v) : "l"(g_x + pair * 1024 + (i & 1) * 512 + line * 16) : "memory");
        asm volatile("{\n.reg .pred p;\nsetp.ne.u32 p, %1, 0x12345;\nmov.u32 %0, -1;\n@p mov.u32 %0, %%clock;\n}" : "=r"(t1) : "r"(v) : "memory");
        if (i & 1) best[1] = min(best[1], t1 - t0); else best[0] = min(best[0], t1 - t0);
    }
    return best[1] < best[0];
}
__device__ __forceinline__ void map_pages(int c) {
    uint32_t smid;
    asm("mov.u32 %0, %%smid;" : "=r"(smid));
    const uint32_t side = near_page(0, c & 31);
    g_side[smid & 255] = side;
    for (int p = c; p < XPAIRS; p += 132) g_home[p] = near_page(p, 0) ^ side;
}

__device__ __forceinline__ void kv_tile(int c, int n, int& m, int& nb) {
    if (c < 96) { m = (c & 3) + 4 * n; nb = c >> 2; }
    else {
        const int i = ((c - 96) >> 1) + 18 * n, j = i - 48 * NTA, p = j < 0 ? i / 24 : 2 * NTA + j / 48;
        m = 2 * p + (c & 1); nb = j < 0 ? 24 + i % 24 : j % 48;
    }
}

__global__ void __launch_bounds__(384, 1)
k_kv(const __grid_constant__ CUtensorMap mx, const __grid_constant__ CUtensorMap mwk, const __grid_constant__ CUtensorMap mwv,
     const __grid_constant__ CUtensorMap mwq, const __grid_constant__ CUtensorMap mwq1, const bf16* __restrict__ Wo, int c0) {
    extern __shared__ __align__(1024) uint8_t smem_gemm[];
    const int c = c0 + blockIdx.x, ntile = c < 96 ? NTA : 13;
    static_assert(NTA == 3, "round counts");
    const bool extra = c >= 96 && c < 120;
    const int xcol = 40 + ((c - 96) & ~1);
    if (c != 96) asm volatile("griddepcontrol.launch_dependents;");
    const uint32_t bar_done = smem_u32(smem_gemm) + NSTAGE * STAGE_BYTES + 96;
    if (threadIdx.x == 0) { mbar_init(bar_done, 8); mbar_init(bar_done + 8, 8); }
    GemmSmem g = gemm_setup(smem_gemm, 4);
    uint32_t rank, peer_empty;
    asm("mov.u32 %0, %%cluster_ctarank;" : "=r"(rank));
    asm("mapa.shared::cluster.u32 %0, %1, %2;" : "=r"(peer_empty) : "r"(g.empty), "r"(rank ^ 1));
    asm volatile("barrier.cluster.arrive.relaxed.aligned;\nbarrier.cluster.wait.aligned;" ::: "memory");
    auto release = [&](int s) {
        asm volatile("{\n.reg .pred p;\nsetp.eq.u32 p, %2, 0;\n@p mbarrier.arrive.relaxed.cta.shared::cta.b64 _, [%0];\n"
                     "@p mbarrier.arrive.relaxed.cluster.shared::cluster.b64 _, [%1];\n}"
                     ::"r"(g.empty + 8 * s), "r"(peer_empty + 8 * s), "r"(threadIdx.x & 127) : "memory");
    };
    const int wg = __shfl_sync(~0u, threadIdx.x >> 7, 0);
    if (wg == 0) {
        asm volatile("setmaxnreg.dec.sync.aligned.u32 40;");
        if (threadIdx.x == 0) {
            for (int it = 0; it < ntile * 16; it++) {
                const int s = it & 3, kb = it & 15;
                int m, nb;
                kv_tile(c, it >> 4, m, nb);
                mbar_wait(g.empty + 8 * s, ((it >> 2) & 1) ^ 1);
                mbar_expect_tx(g.full + 8 * s, STAGE_BYTES);
                tma2d(g.st + s * STAGE_BYTES, &mx, kb * 64, m * 128, g.full + 8 * s);
                asm volatile("cp.async.bulk.tensor.3d.shared::cluster.global.mbarrier::complete_tx::bytes.multicast::cluster "
                             "[%0], [%1, {%3, %4, %5}], [%2], %6;"
                             ::"r"(g.st + s * STAGE_BYTES + 16384 + (c & 1) * 16384), "l"(nb < 16 ? &mwk : nb < 32 ? &mwv : &mwq), "r"(g.full + 8 * s),
                               "r"(0), "r"(kb * 64), "r"((nb & 15) * 4 + (c & 1) * 2), "h"((uint16_t)(3u << (rank & ~1u))) : "memory");
#define PF0 (16 * NTA - 22)
                if (c < 96 && it >= PF0 && (it - PF0) * 96 + c < 2048)
                    asm volatile("cp.async.bulk.prefetch.L2.global [%0], 4096;" ::"l"((const char*)Wo + ((it - PF0) * 96 + c) * 4096) : "memory");
            }
            for (int kb = 0; kb < (extra ? 16 : 0); kb++) {
                const int s = kb & 3;
                mbar_wait(g.empty + 8 * s, ((kb >> 2) & 1) ^ 1);
                mbar_expect_tx(g.full + 8 * s, 32768);
                tma2d(g.st + s * STAGE_BYTES, &mx, kb * 64, (14 + (c & 1)) * 128, g.full + 8 * s);
                asm volatile("cp.async.bulk.tensor.3d.shared::cluster.global.mbarrier::complete_tx::bytes.multicast::cluster "
                             "[%0], [%1, {%3, %4, %5}], [%2], %6;"
                             ::"r"(g.st + s * STAGE_BYTES + 16384 + (c & 1) * 8192), "l"(&mwq1), "r"(g.full + 8 * s),
                               "r"(0), "r"(kb * 64), "r"(xcol + (c & 1)), "h"((uint16_t)3) : "memory");
            }
        } else if (threadIdx.x == 32) {
            if (c == 96) {
                for (int i = 4; i < 64; i++) reinterpret_cast<uint4*>(g_flag)[i] = make_uint4(0, 0, 0, 0);
                asm volatile("fence.acq_rel.gpu;\ngriddepcontrol.launch_dependents;\ngriddepcontrol.wait;\n"
                             "fence.acq_rel.gpu;\nred.relaxed.gpu.global.add.u32 [%0], 1;" ::"l"(g_flag + 8) : "memory");
            }
        } else if (threadIdx.x == 64) {
            for (int n = 0; n < (c < 96 ? 0 : ntile + extra); n++) {
                int m, nb;
                kv_tile(c, n, m, nb);
                mbar_wait(bar_done + (n & 1) * 8, (n >> 1) & 1);
                asm volatile("fence.acq_rel.gpu;\nred.relaxed.gpu.global.add.u32 [%0], 1;" ::"l"(g_flag + min(m >> 1, 7)) : "memory");
            }
        } else if (threadIdx.x >= 96) {
            mbar_wait(g.full + 24, 0);
            const uint4 ones = make_uint4(~0u, ~0u, ~0u, ~0u);
            for (int i = c * 32 + threadIdx.x - 96; i < XPAIRS * 512; i += 132 * 32) reinterpret_cast<uint4*>(g_x)[i] = ones;
            __syncwarp();
            if (threadIdx.x == 96) {
                map_pages(c);
                if (c >= 96) asm volatile("fence.acq_rel.gpu;\nred.relaxed.gpu.global.add.u32 [%0], 1;" ::"l"(g_flag + 8) : "memory");
            }
        }
    } else {
        asm volatile("setmaxnreg.inc.sync.aligned.u32 232;");
        const int cw = wg - 1, lane = threadIdx.x & 31, t = lane & 3;
        bf16* const dst0 = g_kv + (size_t)(cw * 64 + ((threadIdx.x >> 5) & 3) * 16 + (lane >> 2)) * PW + t * 8;
        bf16* dst = dst0;
        float acc[128];
        uint32_t pk[64];
#pragma unroll 1
        for (int tile = 0; tile < ntile; tile++) {
#pragma unroll
            for (int kb = 0; kb < 16; kb++) {
                mbar_wait_u(g.full + 8 * (kb & 3), (kb >> 2) & 1);
                gemm_stage<128, 256, 1>(acc, g.st + (kb & 3) * STAGE_BYTES, cw, kb == 0);
                if (tile > 0) {
                    kv_store_unit(pk, kb, dst, t);
                    if (kb == 15) { __syncwarp(); mbar_arrive_one(bar_done + (~tile & 1) * 8, lane); }
                }
                if (kb > 0) {
                    wg_wait<1>();
                    if (kb <= 12 || tile < ntile - 1 || extra) release((kb - 1) & 3);
                }
            }
            wg_wait<0>();
            if (tile < ntile - 1 || extra) release(3);
#pragma unroll
            for (int i = 0; i < 64; i++) pk[i] = pack2(acc[2 * i], acc[2 * i + 1]);
            int m, nb;
            kv_tile(c, tile, m, nb);
            dst = dst0 + (size_t)m * 128 * PW + nb * 256;
        }
        if (extra) {
            float acc2[64];
#pragma unroll
            for (int i = 0; i < 64; i++) acc2[i] = 0.f;
#pragma unroll
            for (int kb = 0; kb < 16; kb++) {
                mbar_wait_u(g.full + 8 * (kb & 3), (kb >> 2) & 1);
                gemm_stage<128, 128, 1>(acc2, g.st + (kb & 3) * STAGE_BYTES, cw, false);
                kv_store_unit(pk, kb, dst, t);
                wg_wait<1>();
                if (kb > 0 && kb <= 12) release((kb - 1) & 3);
            }
            __syncwarp();
            mbar_arrive_one(bar_done, lane);
            wg_wait<0>();
#pragma unroll
            for (int i = 0; i < 32; i++) pk[i] = pack2(acc2[2 * i], acc2[2 * i + 1]);
            dst = dst0 + (size_t)(14 + (c & 1)) * 128 * PW + 2 * HD + xcol * 64;
#pragma unroll
            for (int u = 0; u < 8; u++) kv_store_unit(pk, u, dst, t);
        } else {
#pragma unroll
            for (int u = 0; u < 16; u++) kv_store_unit(pk, u, dst, t);
        }
        __syncwarp();
        mbar_arrive_one(bar_done + (extra ? 8 : 0), lane);
    }
}

constexpr int NS1 = 31;
#define RB1 4
#define PFC 4
constexpr int C_W1 = 0;
constexpr int C_W2 = C_W1 + 8 * NS1 * 512;
constexpr int C_KV = C_W2 + 14 * 8 * 512;
constexpr int C_RED = C_KV + 16384;
constexpr int C_QKV = C_RED + 64 * 272;
constexpr int QKV_SZ = 3 * 8 * 272;
constexpr int C_SC = C_RED;
constexpr int C_OB = C_SC + 2 * 8 * 52 * 4;
constexpr int C_BAR = C_QKV + 2 * QKV_SZ;
__host__ __device__ constexpr int smem_idx(int ks, int j) {
    return ks == 0 ? j : ks < 3 ? (j < 4 ? 4 + 4 * ks + j : -1) : (j < 3 ? 7 + 3 * ks + j : -1);
}
constexpr int CHAIN_SMEM = C_BAR + 64;

#define DLY3 10
#define DLY1 4
#define DLY0 4
#define DLY1A 11
#define DLY0A 0
#define DLY1B 4
#define PFD 3
#define DLYW 4
#define DLYQ 3
template <int N> __device__ __forceinline__ uint32_t delayed(uint32_t x, uint32_t self) {
    uint32_t p = self;
#pragma unroll
    for (int i = 0; i < N; i++) asm volatile("ld.volatile.shared.u32 %0, [%0];" : "+r"(p)::"memory");
    return x + (p - self);
}
__device__ __forceinline__ int fresh(int x) { asm volatile("mov.b32 %0, %0;" : "+r"(x)); return x; }
__device__ __forceinline__ void lds128v(uint32_t (&r)[4], uint32_t a) {
    asm volatile("ld.volatile.shared.v4.u32 {%0,%1,%2,%3}, [%4];" : "=r"(r[0]), "=r"(r[1]), "=r"(r[2]), "=r"(r[3]) : "r"(a) : "memory");
}
__device__ __forceinline__ uint2 lds64(uint32_t a) {
    uint2 v;
    asm volatile("ld.shared.v2.u32 {%0,%1}, [%2];" : "=r"(v.x), "=r"(v.y) : "r"(a) : "memory");
    return v;
}
#define LDQ ".L1::no_allocate"
__device__ __forceinline__ uint4 ldw128(const void* p) {
    uint4 v;
    asm volatile("ld.global.nc" LDQ ".v4.u32 {%0,%1,%2,%3}, [%4];" : "=r"(v.x), "=r"(v.y), "=r"(v.z), "=r"(v.w) : "l"(p));
    return v;
}
#define P8_LD(i) "ld.relaxed.gpu.global.b64 d" #i ", [src + " #i " * 256];\n"
#define P8_X(i) "mov.b64 {x" #i ", y" #i "}, d" #i ";\n"
#define P8_HEAD(SRC) "{\n.reg .pred p, q;\n.reg .b64 src, d<8>;\n.reg .b32 n, x<8>, y<8>, m0, m1;\nmov.b64 src, " SRC ";\n"         \
                P8_LD(0) P8_LD(1) P8_LD(2) P8_LD(3) P8_LD(4) P8_LD(5) P8_LD(6) P8_LD(7) "mov.u32 n, 0;\nCHECK:\n" \
                P8_X(0) P8_X(1) P8_X(2) P8_X(3) P8_X(4) P8_X(5) P8_X(6) P8_X(7)
#define P8_VOTE "vote.sync.all.pred p, p, -1;\n@p bra.uni DONE;\n"
#define P8_TAIL "add.u32 n, n, 1;\nsetp.lt.u32 p, n, 0x100000;\n@p bra.uni CHECK;\ntrap;\nDONE:\n"
#define S8_LD(i) "ld.relaxed.gpu.global.b64 %" #i ", [%8 + " #i " * 256];\n"
__device__ __forceinline__ void fetch_state(uint64_t (&d)[8], const void* src) {
    asm volatile(S8_LD(0) S8_LD(1) S8_LD(2) S8_LD(3) S8_LD(4) S8_LD(5) S8_LD(6) S8_LD(7)
                 : "=&l"(d[0]), "=&l"(d[1]), "=&l"(d[2]), "=&l"(d[3]), "=&l"(d[4]), "=&l"(d[5]), "=&l"(d[6]), "=&l"(d[7]) : "l"(src) : "memory");
}
__device__ __forceinline__ void settle_state(uint64_t (&d)[8], const void* src) {
#define S8_X(i) "mov.b64 {x" #i ", _}, %" #i ";\n"
#define S8_R(i) "setp.eq.u32 q, x" #i ", 0xffffffff;\n@q " S8_LD(i)
    asm volatile("{\n.reg .pred p, q;\n.reg .b32 n, x<8>, m0, m1;\nmov.u32 n, 0;\nCHECK:\n"
                 S8_X(0) S8_X(1) S8_X(2) S8_X(3) S8_X(4) S8_X(5) S8_X(6) S8_X(7)
                 "max.u32 m0, x0, x1;\nmax.u32 m0, m0, x2;\nmax.u32 m1, x3, x4;\nmax.u32 m1, m1, x5;\nmax.u32 m0, m0, x6;\n"
                 "max.u32 m0, m0, x7;\nmax.u32 m0, m0, m1;\nsetp.ne.u32 p, m0, 0xffffffff;\n" P8_VOTE
                 S8_R(0) S8_R(1) S8_R(2) S8_R(3) S8_R(4) S8_R(5) S8_R(6) S8_R(7) P8_TAIL "}"
                 : "+l"(d[0]), "+l"(d[1]), "+l"(d[2]), "+l"(d[3]), "+l"(d[4]), "+l"(d[5]), "+l"(d[6]), "+l"(d[7]) : "l"(src) : "memory");
}
__device__ __forceinline__ uint64_t poll_sum(const void* src, uint32_t tag, uint32_t sel) {
#define P8_RT(i) "lop3.b32 m0, x" #i ", %2, 1, 0x28;\nsetp.ne.u32 q, m0, 0;\n@q " P8_LD(i)
#define P8_MMA(c, i, z) "mma.sync.aligned.m16n8k8.row.col.f32.bf16.bf16.f32 {" #c "0," #c "1," #c "2," #c "3}, {x" #i ", y" #i "}, {%3}, {" #z "0," #z "1," #z "2," #z "3};\n"
    uint64_t r;
    asm volatile(P8_HEAD("%1") "{\n.reg .f32 a<4>, b<4>, z<4>;\nmov.f32 z0, 0f00000000;\nmov.f32 z1, z0;\nmov.f32 z2, z0;\nmov.f32 z3, z0;\n"
                 P8_MMA(a, 0, z) P8_MMA(b, 1, z) P8_MMA(a, 2, a) P8_MMA(b, 3, b) P8_MMA(a, 4, a) P8_MMA(b, 5, b) P8_MMA(a, 6, a) P8_MMA(b, 7, b)
                 "add.f32 a0, a0, b0;\nadd.f32 a1, a1, b1;\nadd.f32 a2, a2, b2;\nadd.f32 a3, a3, b3;\n"
                 "cvt.rn.bf16x2.f32 m0, a1, a0;\ncvt.rn.bf16x2.f32 m1, a3, a2;\nmov.b64 %0, {m0, m1};\n}\n"
                 "lop3.b32 m0, x0, x1, %2, 0x7e;\nlop3.b32 m1, x2, x3, %2, 0x7e;\nlop3.b32 m0, m0, x4, %2, 0xf6;\n"
                 "lop3.b32 m1, m1, x5, %2, 0xf6;\nlop3.b32 m0, m0, x6, %2, 0xf6;\nlop3.b32 m1, m1, x7, %2, 0xf6;\n"
                 "lop3.b32 m0, m0, m1, 1, 0xa8;\nsetp.eq.u32 p, m0, 0;\n" P8_VOTE
                 P8_RT(0) P8_RT(1) P8_RT(2) P8_RT(3) P8_RT(4) P8_RT(5) P8_RT(6) P8_RT(7) P8_TAIL "}"
                 : "=&l"(r) : "l"(src), "r"(tag), "r"(sel) : "memory");
    return r;
}
__device__ __forceinline__ uint32_t wait_count_u(const uint32_t* p, uint32_t need) {
    uint32_t v;
    asm volatile("{\n.reg .pred p;\n.reg .u32 n;\nmov.u32 n, 0;\nAGAIN:\nld.acquire.gpu.global.u32 %0, [%1];\nsetp.ge.u32 p, %0, %2;\n"
                 "vote.sync.all.pred p, p, -1;\n@p bra.uni DONE;\nadd.u32 n, n, 1;\nsetp.lt.u32 p, n, 0x100000;\n@p bra.uni AGAIN;\ntrap;\n"
                 "DONE:\nfence.proxy.async.global;\n}" : "=&r"(v) : "l"(p), "r"(need) : "memory");
    return v;
}
__device__ __forceinline__ uint32_t movm(uint32_t x) { asm volatile("movmatrix.sync.aligned.m8n8.trans.b16 %0, %0;" : "+r"(x)); return x; }
template <int NK, typename F>
__device__ __forceinline__ void attend(uint32_t sb, uint32_t lm, uint32_t qs, uint32_t xq, int i8, int lane, bf16* dst, F mid) {
    const int r8 = lane & 7, m4 = lane >> 3;
    const float sl2e = 0.08838834764831845f * 1.4426950408889634f;
    const uint32_t lk = sb + C_KV + ((m4 & 1) * 8 + r8) * 128 + (((m4 >> 1) ^ r8) << 4);
    const uint32_t lkm = sb + xq + (8 + r8) * 272 + (m4 & 1) * 32 + (m4 >> 1) * 16;
    asm volatile("cp.async.wait_all;" ::: "memory");
    __syncwarp();
    float x[4][4];
#pragma unroll
    for (int i = 0; i < 4; i++) x[i][0] = x[i][1] = x[i][2] = x[i][3] = 0.f;
#pragma unroll
    for (int kp = 0; kp < 4; kp++) {
        uint32_t q[4], a[4];
        ldsm4(q, lm + qs + kp * 64);
        ldsm4(a, lkm + kp * 64);
        mma16816(x[2], a[0], a[1], a[2], a[3], q[0], q[1]);
        mma16816(x[3], a[0], a[1], a[2], a[3], q[2], q[3]);
#pragma unroll
        for (int u = 0; u < 4; u++) {
            if ((u & 1) >= NK) continue;
            ldsm4(a, (lk ^ (((kp & 1) * 2 + (u >> 1)) << 5)) + (kp >> 1) * 4096 + (u & 1) * 2048);
            mma16816(x[u & 1], a[0], a[1], a[2], a[3], q[u & 2], q[(u & 2) + 1]);
        }
    }
    x[2][0] += x[3][2]; x[2][1] += x[3][3];
    const int lim = i8 + 2 * (lane & 3) - (lane >> 2);
    uint32_t p[5];
    {
        float m[2], e[5][2];
#pragma unroll
        for (int b = 0; b < 2; b++) {
            e[4][b] = m[b] = x[2][b];
#pragma unroll
            for (int j = 0; j < 2 * NK; j++) {
                e[j][b] = j < 2 * NK - 2 || 8 * j - b <= lim ? x[j >> 1][(j & 1) * 2 + b] : -3.0e38f;
                m[b] = fmaxf(m[b], e[j][b]);
            }
        }
#pragma unroll
        for (int o = 4; o < 32; o <<= 1) {
            m[0] = fmaxf(m[0], __shfl_xor_sync(~0u, m[0], o));
            m[1] = fmaxf(m[1], __shfl_xor_sync(~0u, m[1], o));
        }
        m[0] *= sl2e; m[1] *= sl2e;
#pragma unroll
        for (int j = 0; j < 5; j++)
            if (j < 2 * NK || j == 4) p[j] = movm(pack2(ex2(fmaf(e[j][0], sl2e, -m[0])), ex2(fmaf(e[j][1], sl2e, -m[1]))));
    }
    const uint32_t lvt = sb + C_KV + 8192 + ((m4 >> 1) * 8 + r8) * 128 + (((m4 & 1) ^ r8) << 4), one = 0x3f803f80u;
    float sm[4] = {0.f, 0.f, 0.f, 0.f}, c[8][4];
    mma16816(sm, one, one, one, one, p[0], p[1]);
    if (NK == 2) mma16816(sm, one, one, one, one, p[2], p[3]);
    mma1688(sm, one, one, p[4]);
#pragma unroll
    for (int j = 0; j < 8; j++) c[j][0] = c[j][1] = c[j][2] = c[j][3] = 0.f;
#pragma unroll
    for (int kk = 0; kk < NK; kk++)
#pragma unroll
        for (int j = 0; j < 8; j++) {
            uint32_t a[4];
            ldsm4t(a, (lvt ^ ((j & 3) << 5)) + (j >> 2) * 4096 + kk * 2048);
            mma16816(c[j], a[0], a[1], a[2], a[3], p[2 * kk], p[2 * kk + 1]);
        }
    float i0, i1;
    asm("rcp.approx.ftz.f32 %0, %1;" : "=f"(i0) : "f"(sm[0]));
    asm("rcp.approx.ftz.f32 %0, %1;" : "=f"(i1) : "f"(sm[1]));
    uint32_t o[4][4];
#pragma unroll
    for (int j = 0; j < 4; j++) {
        uint32_t a[4];
        ldsm4t(a, lm + xq + 16 * 272 + j * 64);
        mma1688(c[2 * j], a[0], a[1], p[4]);
        mma1688(c[2 * j + 1], a[2], a[3], p[4]);
#pragma unroll
        for (int u = 0; u < 4; u++) o[j][u] = pack2(c[2 * j + (u >> 1)][(u & 1) * 2] * i0, c[2 * j + (u >> 1)][(u & 1) * 2 + 1] * i1);
    }
#pragma unroll
    for (int j = 0; j < 4; j++) stsm4t(lm + qs + j * 64, o[j][0], o[j][1], o[j][2], o[j][3]);
    mid();
    __syncwarp();
#pragma unroll
    for (int j = 0; j < 4; j++) lds128(o[j], sb + qs + ((lane >> 4) + 2 * j) * 272 + (lane & 15) * 16);
#pragma unroll
    for (int j = 0; j < 4; j++)
        asm volatile("st.global.v4.u32 [%0], {%1,%2,%3,%4};" ::"l"(dst + (size_t)2 * j * HD), "r"(o[j][0]), "r"(o[j][1]), "r"(o[j][2]), "r"(o[j][3]) : "memory");
}
__device__ __forceinline__ void sum8(float (&c)[4], const uint2 (&v)[8], uint32_t idn) {
    float d[4] = {0.f, 0.f, 0.f, 0.f};
    c[0] = c[1] = c[2] = c[3] = 0.f;
    mma16816(c, v[0].x, v[0].y, v[1].x, v[1].y, idn, idn);
    mma16816(d, v[2].x, v[2].y, v[3].x, v[3].y, idn, idn);
    mma16816(c, v[4].x, v[4].y, v[5].x, v[5].y, idn, idn);
    mma16816(d, v[6].x, v[6].y, v[7].x, v[7].y, idn, idn);
    c[0] += d[0]; c[1] += d[1]; c[2] += d[2]; c[3] += d[3];
}

#define CLS 6
__global__ void __cluster_dims__(CLS, 1, 1) __launch_bounds__(256, 1)
k_chain(const bf16* __restrict__ mem0, const bf16* __restrict__ Wq, const bf16* __restrict__ Wk, const bf16* __restrict__ Wv,
        const bf16* __restrict__ Wo, const __grid_constant__ CUtensorMap mkv) {
    extern __shared__ __align__(1024) uint8_t smem_chain[];
    const uint32_t sb = smem_u32(smem_chain);
    if (sb & 1023) __trap();
    const int w = __shfl_sync(~0u, threadIdx.x >> 5, 0), lane = __shfl_sync(~0u, threadIdx.x & 31, threadIdx.x & 31);
    const int tid = w * 32 + lane, g = lane >> 2, t = lane & 3;
    auto pin = [&](uint32_t x) { asm volatile("shfl.sync.idx.b32 %0, %0, %1, 31, -1;" : "+r"(x) : "r"(lane) : "memory"); return x; };
    const int h = blockIdx.x / 3, r = blockIdx.x - 3 * h;
    const uint32_t bar_x = sb + C_BAR, bar_kv = sb + C_BAR + 8, bar_go = sb + C_BAR + 16, bar_w = sb + C_BAR + 24, self = sb + C_BAR + 60;
    asm volatile("griddepcontrol.launch_dependents;");
    const int tbase = r == 0 ? 0 : 1 + 21 * r, ntile = r == 0 ? 22 : 21;
    uint32_t side;
    if (tid == 0) {
        mbar_init(bar_x, 8); mbar_init(bar_kv, 1); mbar_init(bar_go, 1); mbar_init(bar_w, 1);
        asm volatile("st.shared.u32 [%0], %0;" ::"r"(self) : "memory");
        asm volatile("fence.mbarrier_init.release.cluster;" ::: "memory");
        asm volatile("fence.proxy.async.shared::cta;" ::: "memory");
        mbar_expect_tx(bar_w, 128 * 32 * ntile);
    }
    __syncthreads();
    asm volatile("barrier.cluster.arrive.relaxed.aligned;" ::: "memory");
    asm("mov.u32 %0, %%smid;" : "=r"(side));
    asm volatile("ld.relaxed.gpu.global.u32 %0, [%1];" : "=r"(side) : "l"(g_side + (side & 255)) : "memory");
    if (tid < 128)
        asm volatile("cp.async.bulk.shared::cluster.global.mbarrier::complete_tx::bytes [%0], [%1], %2, [%3];"
                     ::"r"(sb + C_W1 + tid * 720), "l"(Wo + (size_t)(h * 128 + tid) * DM + tbase * 16), "r"(32 * ntile), "r"(bar_w) : "memory");
    const int tile0 = tbase + 7 - w;
    const bool three = w >= (r == 0 ? 2 : 3);
    const uint32_t wa = pin(sb + tid * 16);
#define W1A(i) (wa + C_W1 + (i) * 4096)
#define W2A(x) (wa + C_W2 + ((x) < 8 ? (x) * 4096 : 32768 - 1024 + ((x) - 8) * 3072))
    uint32_t wo0[8][4], wr[64][4];
    {
        const bf16* W = (r == 0 ? Wq : r == 1 ? Wk : Wv) + (size_t)(128 * w + (lane >> 4)) * HD + h * 128 + 8 * (lane & 15);
        uint4 raw[8][8];
        auto fetch = [&](int ks) {
#pragma unroll
            for (int i = 0; i < 8; i++) raw[ks][i] = ldw128(W + (size_t)(16 * ks + 2 * i) * HD);
        };
        fetch(0); fetch(1); fetch(2); fetch(3);
        mbar_wait_u(bar_w, 0);
        const uint32_t p = sb + C_W1 + ((lane & 7) + (lane >> 4) * 8) * 720 + (7 - w) * 32 + ((lane >> 3) & 1) * 16;
#pragma unroll
        for (int ks = 0; ks < 8; ks++) {
            uint32_t a[4];
            ldsm4t(wo0[ks], p + ks * 16 * 720);
            ldsm4t(a, p + ks * 16 * 720 + 256);
            sts128(W2A(ks), a[0], a[1], a[2], a[3]);
            if (three) { ldsm4t(a, p + ks * 16 * 720 + 512); sts128(W2A(8 + ks), a[0], a[1], a[2], a[3]); }
        }
        __syncthreads();
        side &= 1;
        if (w == 7 && r > 0) asm volatile("st.relaxed.gpu.global.u32 [%0], %1;" ::"l"(g_flag + 128 + 2 * h + r - 1), "r"(2 | side) : "memory");
        const uint32_t stg = sb + C_KV + w * 4096;
        const uint32_t rd = stg + ((lane & 7) + 8 * (lane >> 4)) * 256 + ((((lane >> 3) & 1) ^ (lane & 7)) << 4);
#pragma unroll
        for (int ks = 0; ks < 8; ks++) {
#pragma unroll
            for (int i = 0; i < 8; i++)
                sts128(stg + (2 * i + (lane >> 4)) * 256 + (((lane & 15) ^ (((2 * i) & 6) | (lane >> 4))) << 4),
                       raw[ks][i].x, raw[ks][i].y, raw[ks][i].z, raw[ks][i].w);
            if (ks < 2) fetch(ks + 4);
            if (ks == 3 || ks == 5) fetch(ks / 2 + 5);
            __syncwarp();
#pragma unroll
            for (int j = 0; j < 8; j++) {
                if (smem_idx(ks, j) >= 0) {
                    uint32_t a[4];
                    ldsm4t(a, rd ^ (j << 5));
                    sts128(W1A(smem_idx(ks, j)), a[0], a[1], a[2], a[3]);
                } else ldsm4t(wr[8 * ks + j], rd ^ (j << 5));
            }
            __syncwarp();
        }
    }
    uint2 bm[8];
#pragma unroll
    for (int ks = 0; ks < 8; ks++) {
        const uint32_t* p = (const uint32_t*)(mem0 + g * DM + (8 * w + ks) * 16) + t;
        asm volatile("ld.global.nc.u32 %0, [%2];\nld.global.nc.u32 %1, [%2 + 16];" : "=r"(bm[ks].x), "=r"(bm[ks].y) : "l"(p));
    }
    uint32_t psel, msel0, msel1;
    {
        const int j = r > 0 ? 2 * h + r - 1 : 0, tl = min(tile0 + 8 * (lane >> 1), 63);
        const uint32_t b = wait_count_u(lane < 8 ? g_flag + 128 + tl : g_flag + (lane & 8), lane < 8 ? 2 : lane & 8 ? 37 : 48);
        psel = __ballot_sync(~0u, (g_home[lane == 6 ? j * 2 + ((w >> 1) & 1) : tl * 2 + (lane & 1)] ^ (lane == 6 ? side : b)) & 1);
        msel0 = __ballot_sync(~0u, (g_home[128 + lane * 4 + (w >> 1)] ^ side) & 1);
        msel1 = __ballot_sync(~0u, (g_home[256 + lane * 4 + (w >> 1)] ^ side) & 1);
        if (r > 0) {
            if (w < 4) asm volatile("prefetch.global.L2 [%0];" ::"l"(g_x + (128 + (1 + (w >> 1)) * 4 + (j >> 4)) * 1024 + (w & 1) * 512 + (j & 15) * 32 + lane) : "memory");
            if (w < 4) asm volatile("prefetch.global.L2 [%0];" ::"l"(g_x + j * 2048 + tid * 16) : "memory");
        }
    }
    asm volatile("fence.proxy.async.shared::cta;" ::: "memory");
    __syncthreads();
    if (tid == 0) {
        mbar_expect_tx(bar_kv, 16384);
        tma3d(sb + C_KV, &mkv, 0, 0, 2 * h, bar_kv);
        tma3d(sb + C_KV + 8192, &mkv, 0, 0, 64 + 2 * h, bar_kv);
    }
    asm volatile("barrier.cluster.wait.aligned;" ::: "memory");

    auto load_kv = [&](int s) {
        asm volatile("{\n.reg .pred p;\nelect.sync _|p, -1;\n@p mbarrier.arrive.expect_tx.shared::cta.b64 _, [%2], 16384;\n"
                     "@p cp.async.bulk.tensor.3d.shared::cluster.global.mbarrier::complete_tx::bytes [%0], [%1, {%3, %4, %5}], [%2];\n"
                     "@p cp.async.bulk.tensor.3d.shared::cluster.global.mbarrier::complete_tx::bytes [%6], [%1, {%3, %4, %7}], [%2];\n}"
                     ::"r"(sb + C_KV), "l"(&mkv), "r"(bar_kv), "r"(0), "r"(s * 32), "r"(2 * h), "r"(sb + C_KV + 8192), "r"(64 + 2 * h) : "memory");
    };
    const bool attends = w == 7 || (w == 6 && r == 0);
    const int i8 = r == 0 ? (w - 4) * 8 : (r - 1) * 8;
    auto load_q = [&](int s) {
        const int l = fresh(lane);
        const bf16* p = g_kv + (size_t)(s * 32 + i8 + (l >> 4)) * PW + 2 * HD + h * 128 + (l & 15) * 8;
#pragma unroll
        for (int j = 0; j < 4; j++)
            asm volatile("cp.async.cg.shared.global [%0], [%1], 16;"
                         ::"r"(sb + C_RED + w * 2176 + ((l >> 4) + 2 * j) * 272 + (l & 15) * 16), "l"(p + (size_t)2 * j * PW) : "memory");
    };
    auto report = [&](int part) {
        asm volatile("{\n.reg .pred p;\nelect.sync _|p, -1;\nfence.acq_rel.gpu;\n@p red.relaxed.gpu.global.add.u32 [%0], 1;\n}"
                     ::"l"(g_flag + 64 + part) : "memory");
    };
    const float sl2e = 0.08838834764831845f * 1.4426950408889634f;
    const uint32_t idn = pin(g == 2 * t ? 0x00003f80u : g == 2 * t + 1 ? 0x3f800000u : 0u);
    const uint32_t lm = pin(sb + (lane & 7) * 272 + (lane >> 3) * 16);
    const uint32_t sa = pin(sb + C_SC + (w & 1) * (8 * 52 * 4) + (2 * t * 52 + (w < 4 ? 32 : (w & 2) * 8) + g) * 4);
    const uint32_t sr = pin(sb + C_SC + (g * 52 + 8 * t) * 4), sr2 = pin(sb + C_SC + (g * 52 + 32 + 2 * t) * 4);
    uint32_t kva;
    {
        const int pos = (w & 2) * 8 + (lane & 15), row = (pos & 24) + ((pos + (pos >> 2 & 6)) & 7);
        const int key = 4 * (lane & 6) + (((lane & 7) + 2 * (lane >> 4)) & 7);
        kva = pin(w >= 4 ? sb + C_KV + (w & 1) * 4096 + row * 128 + (((lane >> 4) ^ (row & 7)) << 4)
                         : sb + C_KV + 8192 + (w >> 1) * 4096 + key * 128 + ((((w & 1) * 4 + ((lane >> 3) & 1)) ^ (key & 7)) << 4));
    }
#define ATTEND(NK, s, mid) do {                                                                                       \
        const int l_ = fresh(lane);                                                                                      \
        attend<NK>(sb, lm, C_RED + w * 2176, C_QKV + ((s) & 1) * QKV_SZ, i8, l_,                                         \
                   g_o + (size_t)((s) * 32 + i8 + (l_ >> 4)) * HD + h * 128 + (l_ & 15) * 8, mid);                       \
    } while (0)
    auto chores = [&](int s) {
        if (s == 4 * NBT) report(0);
        if ((s & 7) == 6 - PFD && s < NSEG - 8) wait_count_u(g_flag + (s >> 3) + 1, (s >> 3) + 1 < 2 * NTA ? 48 : s < 48 ? 96 : 108);
    };
    uint32_t buf0[8][4], ring[RB1][4];
    auto stage_w1 = [&]() {
#pragma unroll
        for (int i = 0; i < 8; i++) lds128v(buf0[i], W1A(i));
#pragma unroll
        for (int i = 0; i < RB1; i++) lds128v(ring[i], W1A(8 + i));
    };
    stage_w1();
#pragma unroll 1
    for (int s = 0;; s++) {
        const uint32_t xq = C_QKV + (s & 1) * QKV_SZ;
        {
            float acc[8][4];
#pragma unroll
            for (int ks = 0; ks < 8; ks++) {
#pragma unroll
                for (int j = 0; j < 8; j++) {
                    const int i = smem_idx(ks, j) - 8;
                    if (ks == 0) {
                        acc[j][0] = acc[j][1] = acc[j][2] = acc[j][3] = 0.f;
                        mma16816(acc[j], buf0[j][0], buf0[j][1], buf0[j][2], buf0[j][3], bm[ks].x, bm[ks].y);
                    } else if (i >= 0) {
                        uint32_t(&a)[4] = ring[i % RB1];
                        mma16816(acc[j], a[0], a[1], a[2], a[3], bm[ks].x, bm[ks].y);
                        if (8 + i + RB1 < NS1) lds128v(a, W1A(8 + i + RB1));
                    } else {
                        const uint32_t(&a)[4] = wr[8 * ks + j];
                        mma16816(acc[j], a[0], a[1], a[2], a[3], bm[ks].x, bm[ks].y);
                    }
                }
            }
#pragma unroll
            for (int c = 0; c < 4; c++)
                stsm4t(lm + C_RED + w * 2176 + c * 64, pack2(acc[2 * c][0], acc[2 * c][1]), pack2(acc[2 * c][2], acc[2 * c][3]),
                       pack2(acc[2 * c + 1][0], acc[2 * c + 1][1]), pack2(acc[2 * c + 1][2], acc[2 * c + 1][3]));
        }
        {
            const uint32_t a = sb + C_RED + w * 272 + lane * 8;
            if (w == 3) mbar_wait_u(bar_kv, s & 1);
            __syncthreads();
            uint2 v[8];
#pragma unroll
            for (int i = 0; i < 8; i++) v[i] = lds64(a + i * 2176);
            float c[4];
            sum8(c, v, idn);
            const uint32_t p0 = pack2(c[0], c[1]), p1 = pack2(c[2], c[3]);
            const uint32_t dst = sb + xq + (r * 8 + w) * 272 + lane * 8;
#pragma unroll
            for (int i = 1; i < 3; i++) {
                const uint32_t peer = (h % (CLS / 3)) * 3 + (r + i >= 3 ? r + i - 3 : r + i);
                uint32_t rd, rb;
                asm("mapa.shared::cluster.u32 %0, %1, %2;" : "=r"(rd) : "r"(dst), "r"(peer));
                asm("mapa.shared::cluster.u32 %0, %1, %2;" : "=r"(rb) : "r"(bar_x), "r"(peer));
                asm volatile("st.async.weak.shared::cluster.mbarrier::complete_tx::bytes.v2.b32 [%0], {%1,%2}, [%3];"
                             ::"r"(rd), "r"(p0), "r"(p1), "r"(rb) : "memory");
            }
            sts64(dst, p0, p1);
            __syncwarp();
            asm volatile("{\n.reg .pred p;\nsetp.eq.u32 p, %1, 0;\n@p mbarrier.arrive.expect_tx.shared::cta.b64 _, [%0], 512;\n}"
                         ::"r"(bar_x), "r"(lane) : "memory");
        }
        if (s == NSEG - 1) break;
        uint32_t wb[8][4], wc[8][4];
        const uint32_t po = (tile0 * 2 + (lane >> 4)) * 8192 + ((lane >> 3) & 1) * 2048 + h * 64 + (lane & 7) * 8;
        const uint32_t tag = s & 1;
        auto project = [&](const uint32_t(&wt)[8][4], const uint32_t(&ob)[4][4], int i) {
            float c0[4] = {0.f, 0.f, 0.f, 0.f}, c1[4] = {0.f, 0.f, 0.f, 0.f};
#pragma unroll
            for (int ks = 0; ks < 8; ks++)
                mma16816((ks & 1) ? c1 : c0, wt[ks][0], wt[ks][1], wt[ks][2], wt[ks][3], ob[ks >> 1][(ks & 1) * 2], ob[ks >> 1][(ks & 1) * 2 + 1]);
            uint32_t p0 = pack2(c0[0] + c1[0], c0[1] + c1[1]), p1 = pack2(c0[2] + c1[2], c0[3] + c1[3]);
            asm volatile("movmatrix.sync.aligned.m8n8.trans.b16 %0, %0;\nmovmatrix.sync.aligned.m8n8.trans.b16 %1, %1;" : "+r"(p0), "+r"(p1));
            st_rlx64((uint2*)((char*)g_x + po + i * 131072 + ((psel >> (2 * i + (lane >> 4))) & 1) * 4096), (p0 & ~1u) | tag, p1);
        };
        if (w >= 4) {
            uint32_t ka[4][4];
#pragma unroll
            for (int ks = 0; ks < 4; ks++) ldsm4(ka[ks], kva ^ (ks << 5));
            const uint32_t qa = lm + xq + (w & 1) * 128;
            mbar_wait_u(bar_x, s & 1);
            {
                uint32_t qb[2][4];
                ldsm4(qb[0], qa);
                ldsm4(qb[1], qa + 64);
                float c0[4] = {0.f, 0.f, 0.f, 0.f}, c1[4] = {0.f, 0.f, 0.f, 0.f};
                mma16816(c0, ka[0][0], ka[0][1], ka[0][2], ka[0][3], qb[0][0], qb[0][1]);
                mma16816(c1, ka[1][0], ka[1][1], ka[1][2], ka[1][3], qb[0][2], qb[0][3]);
                mma16816(c0, ka[2][0], ka[2][1], ka[2][2], ka[2][3], qb[1][0], qb[1][1]);
                mma16816(c1, ka[3][0], ka[3][1], ka[3][2], ka[3][3], qb[1][2], qb[1][3]);
                sts32f(sa, c0[0] + c1[0]);
                sts32f(sa + 208, c0[1] + c1[1]);
                sts32f(sa + 32, c0[2] + c1[2]);
                sts32f(sa + 240, c0[3] + c1[3]);
            }
            __syncthreads();
            uint32_t wd;
            if (attends) { load_q(s); wd = delayed<DLYQ>(wa, self); } else wd = delayed<DLYW>(wa, self);
#pragma unroll
            for (int i = 0; i < 8; i++) lds128(wb[i], wd + C_W2 + i * 4096);
#pragma unroll
            for (int i = 0; i < PFC; i++) lds128(wc[i], wd + C_W2 + 32768 - 1024 + i * 3072);
            __syncthreads();
            uint32_t ob[4][4];
#pragma unroll
            for (int i = 0; i < 4; i++) ldsm4(ob[i], lm + C_OB + i * 64);
#pragma unroll
            for (int i = PFC; i < 8; i++) lds128(wc[i], W2A(8 + i));
            project(wb, ob, 1);
            project(wo0, ob, 0);
            project(wc, ob, 2);
        } else {
            uint32_t va[4][4];
#pragma unroll
            for (int i = 0; i < 4; i++) ldsm4t(va[i], kva ^ (((i >> 1) << 5) | ((i & 1) * 0x240)));
#pragma unroll
            for (int i = 0; i < 8; i++) lds128(wb[i], W2A(i));
            const uint32_t qa = lm + xq + (w & 1) * 128, oa = lm + w * 64;
            mbar_wait_u(bar_x, s & 1);
            if (w < 2) {
                uint32_t qb[2][4], km[2][4];
                ldsm4(qb[0], qa);
                ldsm4(km[0], qa + 8 * 272);
                ldsm4(qb[1], qa + 64);
                ldsm4(km[1], qa + 8 * 272 + 64);
                float c0[4] = {0.f, 0.f, 0.f, 0.f}, c1[4] = {0.f, 0.f, 0.f, 0.f};
                mma16816(c0, km[0][0], km[0][1], km[0][2], km[0][3], qb[0][0], qb[0][2]);
                mma16816(c1, km[0][0], km[0][1], km[0][2], km[0][3], qb[0][1], qb[0][3]);
                mma16816(c0, km[1][0], km[1][1], km[1][2], km[1][3], qb[1][0], qb[1][2]);
                mma16816(c1, km[1][0], km[1][1], km[1][2], km[1][3], qb[1][1], qb[1][3]);
                sts32f(sa, c0[0] + c1[2]);
                sts32f(sa + 208, c0[1] + c1[3]);
            }
            __syncthreads();
            {
                float4 x0 = lds128f(sr), y0 = lds128f(sr + 1664), x1 = lds128f(sr + 16), y1 = lds128f(sr + 1680);
                float2 x2 = lds64f(sr2), y2 = lds64f(sr2 + 1664);
                float p[10] = {x0.x + y0.x, x0.y + y0.y, x0.z + y0.z, x0.w + y0.w, x1.x + y1.x,
                               x1.y + y1.y, x1.z + y1.z, x1.w + y1.w, x2.x + y2.x, x2.y + y2.y};
                float m = fmaxf(fmaxf(fmaxf(p[0], p[1]), fmaxf(p[2], p[3])), fmaxf(fmaxf(fmaxf(p[4], p[5]), fmaxf(p[6], p[7])), fmaxf(p[8], p[9])));
                const float m1 = __shfl_xor_sync(~0u, m, 1), m2 = __shfl_xor_sync(~0u, m, 2), m3 = __shfl_xor_sync(~0u, m, 3);
                uint32_t vm[4];
                ldsm4t(vm, oa + xq + 16 * 272);
                m = fmaxf(fmaxf(m, m1), fmaxf(m2, m3));
                const float ms = m * sl2e;
#pragma unroll
                for (int i = 0; i < 10; i++) p[i] = ex2(fmaf(p[i], sl2e, -ms));
                const uint32_t b0 = pack2(p[0], p[1]), b1 = pack2(p[2], p[3]), b2 = pack2(p[4], p[5]), b3 = pack2(p[6], p[7]), b4 = pack2(p[8], p[9]);
                const uint32_t one = 0x3f803f80u;
                float o0[4] = {0.f, 0.f, 0.f, 0.f}, o1[4] = {0.f, 0.f, 0.f, 0.f}, sm[4] = {0.f, 0.f, 0.f, 0.f};
                mma16816(sm, one, one, one, one, b0, b1);
                mma16816(o0, va[0][0], va[0][1], va[0][2], va[0][3], b0, b1);
                mma16816(o1, va[2][0], va[2][1], va[2][2], va[2][3], b0, b1);
                mma16816(sm, one, one, one, one, b2, b3);
                mma16816(o0, va[1][0], va[1][1], va[1][2], va[1][3], b2, b3);
                mma16816(o1, va[3][0], va[3][1], va[3][2], va[3][3], b2, b3);
                mma1688(sm, one, one, b4);
                mma1688(o0, vm[0], vm[1], b4);
                mma1688(o1, vm[2], vm[3], b4);
                float i0, i1;
                asm("rcp.approx.ftz.f32 %0, %1;" : "=f"(i0) : "f"(sm[0]));
                asm("rcp.approx.ftz.f32 %0, %1;" : "=f"(i1) : "f"(sm[1]));
                stsm4t(oa + C_OB, pack2(o0[0] * i0, o0[1] * i1), pack2(o0[2] * i0, o0[3] * i1),
                       pack2(o1[0] * i0, o1[1] * i1), pack2(o1[2] * i0, o1[3] * i1));
            }
            __syncthreads();
            uint32_t ob[4][4];
#pragma unroll
            for (int i = 0; i < 4; i++) ldsm4(ob[i], lm + C_OB + i * 64);
            if (three) {
#pragma unroll
                for (int i = 0; i < 8; i++) lds128(wc[i], W2A(8 + i));
                project(wb, ob, 1);
                project(wo0, ob, 0);
                project(wc, ob, 2);
            } else {
                project(wb, ob, 1);
                project(wo0, ob, 0);
            }
        }
        __syncthreads();
        uint32_t eo = (128 + (s + 1) * 4 + (w >> 1)) * 8192 + (((s < 31 ? msel0 : msel1) >> ((s + 1) & 31)) & 1) * 4096 + (w & 1) * 2048 + lane * 8;
        uint64_t d[8];
        if (r == 0) {
            if (w >= 6) {
                auto mid = [&]() {
                    bar_sync(2, 64);
                    mbar_wait_u(bar_go, s & 1);
                    eo = delayed<DLY0A>(eo, self);
                    fetch_state(d, (const char*)g_x + eo);
                };
                ATTEND(2, s, mid);
                stage_w1();
            } else {
                if (w < 3 && s + PFD < NSEG) {
                    const bf16* p = g_kv + (size_t)((s + PFD) * 32 + fresh(lane)) * PW + w * HD + h * 128;
                    asm volatile("prefetch.global.L2 [%0];\nprefetch.global.L2 [%0 + 128];" ::"l"(p) : "memory");
                }
                stage_w1();
                if (w == 5) {
                    chores(s);
                    if (h == 0) asm volatile("st.relaxed.gpu.global.u32 [%0], %1;" ::"l"(g_flag + 98), "r"(s + 1) : "memory");
                }
                mbar_wait_u(bar_go, s & 1);
                eo = delayed<DLY0>(eo, self);
                fetch_state(d, (const char*)g_x + eo);
            }
        } else {
            const int j = 2 * h + r - 1;
            if (w < 4) {
                const int l = fresh(lane), g = l >> 2, t = l & 3;
                const char* src = (const char*)g_x + delayed<DLY3>((j * 2 + (w >> 1)) * 8192 + (psel & 64) * 64 + (w & 1) * 2048 + t * 64 + g * 8, self);
                const char* dst = (const char*)g_x + pin((128 + (s + 1) * 4 + (j >> 4)) * 8192 + (j & 15) * 256 + w * 64 + (t & 1) * 4096 + g * 8);
                const uint64_t v = poll_sum(src, tag, (lane & 4) ? 0x3f800000u : 0x00003f80u);
                asm volatile("st.relaxed.gpu.global.b64 [%0], %1;" ::"l"(dst), "l"(v) : "memory");
                asm volatile("bar.arrive 1, 256;" ::: "memory");
                stage_w1();
                eo = delayed<DLY1>(eo, self);
                fetch_state(d, (const char*)g_x + eo);
            } else if (w == 7) {
                auto mid = [&]() {
                    bar_sync(1, 256);
                    eo = delayed<DLY1B>(eo, self);
                    fetch_state(d, (const char*)g_x + eo);
                };
                ATTEND(1, s, mid);
                stage_w1();
            } else {
                if (w >= 5 && s + 3 < NSEG)
                    asm volatile("prefetch.global.L2 [%0];" ::"l"(g_x + (128 + (s + 3) * 4 + (j >> 4)) * 1024 + (w & 1) * 512 + (j & 15) * 32 + lane) : "memory");
                stage_w1();
                if (w == 5) chores(s);
                bar_sync(1, 256);
                if (w == 4 && r == 1)
                    asm volatile("{\n.reg .pred p;\n.reg .u32 a;\nelect.sync _|p, -1;\nmapa.shared::cluster.u32 a, %0, %1;\n"
                                 "@p mbarrier.arrive.relaxed.cluster.shared::cluster.b64 _, [a];\n}" ::"r"(bar_go), "r"((h % (CLS / 3)) * 3) : "memory");
                eo = delayed<DLY1A>(eo, self);
                fetch_state(d, (const char*)g_x + eo);
            }
        }
        if (w == 7) load_kv(s + 1);
        settle_state(d, (const char*)g_x + eo);
#pragma unroll
        for (int i = 0; i < 8; i++) { bm[i].x = (uint32_t)d[i]; bm[i].y = (uint32_t)(d[i] >> 32); }
    }
    mbar_wait_u(bar_x, (NSEG - 1) & 1);
    if (attends) {
        auto nothing = []() {};
        load_q(NSEG - 1);
        if (r == 0) { ATTEND(2, NSEG - 1, nothing); bar_sync(2, 64); } else { ATTEND(1, NSEG - 1, nothing); __syncwarp(); }
        if (w == 7) report(1);
    }
}

constexpr int S4_US = 4368;
constexpr int S4_RS = 8848;
constexpr int S4_KS = 1296;
constexpr int S4_U = 0, S4_R = 16 * S4_US, S4_K = S4_R + 16 * S4_RS;
constexpr int S4_SMEM = S4_K + 16 * S4_KS;
constexpr int S4_SIG = 3104, S4_PK = 2 * S4_SIG;

struct cf { float r, i; };
__device__ __forceinline__ cf cmul(cf a, cf b) { return {fmaf(a.r, b.r, -a.i * b.i), fmaf(a.r, b.i, a.i * b.r)}; }
__device__ __forceinline__ cf cmulc(cf a, cf b) { return {fmaf(a.r, b.r, a.i * b.i), fmaf(a.i, b.r, -a.r * b.i)}; }
__device__ __forceinline__ cf csq(cf a) { const float t = a.r * a.i; return {fmaf(a.r, a.r, -a.i * a.i), t + t}; }
__device__ __forceinline__ cf cexp(float l2, float turns) {
    const float mag = ex2(l2), fr = (turns - rintf(turns)) * 6.283185307179586f;
    return {mag * __cosf(fr), mag * __sinf(fr)};
}
__device__ __forceinline__ void sts32(uint32_t a, uint32_t v) { asm volatile("st.shared.u32 [%0], %1;" ::"r"(a), "r"(v) : "memory"); }
__device__ __forceinline__ uint32_t lds16(uint32_t a) {
    uint32_t v;
    asm volatile("ld.shared.u16 %0, [%1];" : "=r"(v) : "r"(a) : "memory");
    return v;
}

template <int M0, int NQ>
__device__ __forceinline__ void s4_class(float (&acc)[16][4], uint32_t sig, uint32_t taps, int x0) {
    constexpr int D0 = M0 / 8, D1 = M0 == 32 ? 9 : 15;
    uint32_t R[D1 - D0 + 2];
#pragma unroll
    for (int D = D0 - 1; D <= D1; D++) {
        if (D < D0 || 8 * D - 7 >= 2 * M0) { R[D - D0 + 1] = 0; continue; }
        const int m = 8 * D + x0;
        uint32_t lo = lds16(taps + m * (2 * NQ)), hi = lds16(taps + (m - 1) * (2 * NQ));
        if (D == D0) { lo = m >= M0 ? lo : 0; hi = m > M0 ? hi : 0; }
        if (D == 2 * D0) { lo = m < 2 * M0 ? lo : 0; hi = m <= 2 * M0 ? hi : 0; }
        R[D - D0 + 1] = lo | (hi << 16);
    }
#pragma unroll
    for (int J = 0; 2 * J + D0 < 16; J++) {
        uint32_t a[4];
        ldsm4t(a, sig + J * 512);
#pragma unroll
        for (int D = D0; D <= D1; D++)
            if (2 * J + D < 16) mma16816(acc[2 * J + D], a[0], a[1], a[2], a[3], R[D - D0 + 1], R[D - D0]);
    }
}

__global__ void __launch_bounds__(512, 1)
k_s4(const bf16* __restrict__ u, const bf16* __restrict__ Are, const bf16* __restrict__ Aim, const bf16* __restrict__ Bre,
     const bf16* __restrict__ Bim, const bf16* __restrict__ Cre, const bf16* __restrict__ Cim, const bf16* __restrict__ logdt,
     const bf16* __restrict__ Dsk, bf16* __restrict__ out) {
    extern __shared__ __align__(16) uint8_t smem_s4[];
    const uint32_t sb = smem_u32(smem_s4);
    asm volatile("griddepcontrol.launch_dependents;");
    const int tid = threadIdx.x, w = __shfl_sync(~0u, tid >> 5, 0), lane = tid & 31, g = lane >> 2, t = lane & 3;
    const int dw = (w & 1) + ((w >> 1) & 3) * 4 + (w >> 3) * 2;
    uint2 ar, ai, br, bi, cr, ci;
    bf16 ldt;
    auto load_params = [&](int item) {
        const int d = item * 16 + dw, o = d * 128 + lane * 4;
        ar = __ldg((const uint2*)(Are + o)); ai = __ldg((const uint2*)(Aim + o)); br = __ldg((const uint2*)(Bre + o));
        bi = __ldg((const uint2*)(Bim + o)); cr = __ldg((const uint2*)(Cre + o)); ci = __ldg((const uint2*)(Cim + o));
        ldt = logdt[d];
    };
    load_params(blockIdx.x);
#pragma unroll 1
    for (int item = blockIdx.x; item < 64; item += gridDim.x) {
    const int d0 = item * 16;
    const uint32_t tr_off = (lane & 15), tr_l = (lane >> 4) * 16;
    const uint32_t ur = sb + S4_U + w * S4_US, rs = sb + S4_R + w * S4_RS, kd = sb + S4_K + w * S4_KS;
    if (lane < 16) sts128(ur + lane * 16, 0, 0, 0, 0);
    {
        const float dt = bf_round(expf(__bfloat162float(ldt)));
        const bf16* src = u + (size_t)(w * 128 + g) * DM + d0 + 4 * t;
        float T[5][4];
#pragma unroll
        for (int i = 0; i < 5; i++) T[i][0] = T[i][1] = T[i][2] = T[i][3] = 0.f;
        float klast = 0.f;
        const uint32_t wr_ = rs + lane * 272, rd_ = rs + t * 544 + g * 16;
#pragma unroll 1
        for (int c = 0; c < 4; c++) {
            uint2 v[4];
#pragma unroll
            for (int i = 0; i < 4; i++) v[i] = __ldg((const uint2*)(src + (size_t)(c * 32 + i * 8) * DM));
            auto pick = [&](const uint2& x) { const uint32_t y = c < 2 ? x.x : x.y; return (c & 1) ? bf_hi(y) : bf_lo(y); };
            auto pk2 = [](cf x) { return pack2(x.r, x.i); };
            const float l2 = dt * pick(ar) * 1.4426950408889634f, tu = dt * pick(ai) * 0.15915494309189535f;
            const cf z1 = cexp(l2, tu), z2 = csq(z1), z4 = csq(z2), z8 = csq(z4);
            const cf z64 = cexp(l2 * 64.f, tu * 64.f), z128 = csq(z64), z256 = csq(z128), z512 = csq(z256);
            cf a0 = {1.f, 0.f}, a1 = z64;
            cf b0 = cmul({pick(cr), pick(ci)}, {dt * pick(br), dt * pick(bi)});
            b0.i = -b0.i;
            cf b1 = cmulc(b0, z128), b2 = cmulc(b0, z256), y3 = cmulc(b0, z512), b4 = cmulc(y3, z512), b3 = y3;
            const cf y2 = cmulc(b2, z128);
#pragma unroll
            for (int i = 0; i < 8; i++) {
                sts128(wr_ + i * 16, pk2(a0), pk2(a1), pk2(b0), pk2(b1));
                sts128(wr_ + i * 16 + 128, pk2(b2), pk2(b3), pk2(b4), 0);
                b4 = cmulc(b4, z128);
                if (i < 7) {
                    a0 = i == 0 ? z8 : cmul(a0, z8); a1 = cmul(a1, z8);
                    b0 = cmulc(b0, z1); b1 = cmulc(b1, z1);
                    b2 = i == 3 ? y2 : cmulc(b2, z2);
                    if (i & 1) { y3 = cmulc(y3, z128); b3 = y3; } else b3 = cmulc(y3, z4);
                }
            }
            klast += b4.r;
            __syncwarp();
#pragma unroll
            for (int k = 0; k < 8; k++) {
                uint32_t x[4], y[4];
                lds128(x, rd_ + (8 * (k >> 1) + (k & 1)) * 272);
                lds128(y, rd_ + (8 * (k >> 1) + (k & 1)) * 272 + 128);
                mma1688(T[0], x[0], x[1], x[2]);
                mma1688(T[1], x[0], x[1], x[3]);
                mma1688(T[2], x[0], x[1], y[0]);
                mma1688(T[3], x[0], x[1], y[1]);
                mma1688(T[4], x[0], x[1], y[2]);
            }
#pragma unroll
            for (int i = 0; i < 2; i++)
                stsm4t(sb + S4_U + tr_off * S4_US + 256 + (w * 128 + c * 32 + i * 16) * 2 + tr_l, v[2 * i].x, v[2 * i].y, v[2 * i + 1].x, v[2 * i + 1].y);
            __syncwarp();
        }
#pragma unroll
        for (int o2 = 16; o2; o2 >>= 1) klast += __shfl_xor_sync(~0u, klast, o2);
#pragma unroll
        for (int hh = 0; hh < 2; hh++) {
            const int i = g + 8 * hh;
            sts32(kd + (8 * i + 2 * t) * 2, pack2(T[0][2 * hh], T[0][2 * hh + 1]));
            sts32(kd + (128 + 8 * i + 2 * t) * 2, pack2(T[1][2 * hh], T[1][2 * hh + 1]));
            sts32(kd + (256 + 4 * i + 2 * (t & 1) + 64 * (t >> 1)) * 2, pack2(T[2][2 * hh], T[2][2 * hh + 1]));
            sts32(kd + (384 + 2 * i + 32 * t) * 2, pack2(T[3][2 * hh], T[3][2 * hh + 1]));
        }
        asm volatile("stmatrix.sync.aligned.m8n8.x2.trans.shared.b16 [%0], {%1,%2};"
                     ::"r"(kd + 1024 + (lane & 7) * 32 + ((lane >> 3) & 1) * 16), "r"(pack2(T[4][0], T[4][1])), "r"(pack2(T[4][2], T[4][3])) : "memory");
        if (lane == 0) sts32(kd + 1280, pack2(klast, 0.f));
    }
    __syncwarp();
    const uint32_t pk = rs + S4_PK + 64;
    {
#pragma unroll
        for (int i = 0; i < 2; i++) {
            const int x = i * 128 + lane * 4;
            const uint2 c = lds64(kd + x * 2);
            uint32_t p = lds16(kd + x * 2 - 2);
            if (x == 0) p = 0;
            sts128(pk + x * 4, __byte_perm(c.x, p, 0x5410), __byte_perm(c.x, 0, 0x1032), __byte_perm(c.y, c.x, 0x7610), __byte_perm(c.y, 0, 0x1032));
        }
#pragma unroll
        for (int i = 2; i < 4; i++) {
            const int x = i * 128 + lane * 4;
            const uint32_t ab = lds32(kd + 256 + x), c = lds16(kd + 256 + x + 4);
            const uint32_t p = x == 256 ? lds16(kd + 510) : ab;
            sts128(pk + x * 4, __byte_perm(ab, p, 0x5410), __byte_perm(ab, 0, 0x1010), __byte_perm(ab, 0, 0x1032), __byte_perm(c, ab, 0x7610));
        }
        const uint32_t v = lds16(kd + 768), v2 = lds16(kd + 1024);
        if (lane < 24) {
            uint32_t x0 = 0, x1 = 0, x2 = 0, x3 = 0;
            if (lane == 0) { x0 = x1 = x2 = v | (v << 16); x3 = v << 16; }
            if (lane == 12) x3 = v2;
            if (lane == 13) { x0 = v2 | (v2 << 16); x1 = v2 << 16; }
            sts128(lane < 20 ? pk + 2048 + lane * 16 : pk - 64 + (lane - 20) * 16, x0, x1, x2, x3);
        }
        if (lane < 4) sts128(rs + (lane >> 1) * S4_SIG + (lane & 1) * 16, 0, 0, 0, 0);
    }
    __syncthreads();
    float acc[16][4];
#pragma unroll
    for (int i = 0; i < 16; i++) acc[i][0] = acc[i][1] = acc[i][2] = acc[i][3] = 0.f;
    const uint32_t lf = (lane & 7) * 32 + ((lane >> 3) & 1) * 16 + (lane >> 4) * 256;
#pragma unroll 1
    for (int ph = 0; ph < 2; ph++) {
    if (((w >> 2) ^ ph) & 1) {
#pragma unroll
    for (int rg = 3; rg >= 2; rg--) {
#pragma unroll 1
        for (int it = 0; it < (rg == 3 ? 4 : 6); it++) {
            const int n = it * 32 + lane;
            uint32_t x[2][4];
            lds128(x[0], ur + 256 + n * 16 - 16);
            lds128(x[1], ur + 256 + n * 16);
            float e[16], p[15], s[11];
#pragma unroll
            for (int i = 0; i < 8; i++) { e[2 * i] = bf_lo(x[i >> 2][i & 3]); e[2 * i + 1] = bf_hi(x[i >> 2][i & 3]); }
#pragma unroll
            for (int i = 0; i < 15; i++) p[i] = e[i] + e[i + 1];
#pragma unroll
            for (int i = 0; i < 11; i++) s[i] = p[i + 3] + e[i + 5];
            const uint32_t o = rs + 16 + n * 16;
            if (rg == 2) sts128(o, pack2(s[0], s[1]), pack2(s[2], s[3]), pack2(s[4], s[5]), pack2(s[6], s[7]));
#pragma unroll
            for (int i = 0; i < 10; i++) s[i] = p[i + 2] + s[i + 1];
            if (rg == 2) {
                sts64(o + S4_SIG + 8, pack2(s[0], s[1]), pack2(s[2], s[3]));
                sts64(o + S4_SIG + 16, pack2(s[4], s[5]), pack2(s[6], s[7]));
            } else {
#pragma unroll
                for (int i = 0; i < 9; i++) s[i] = p[i + 1] + s[i + 1];
                sts64(o + 8, pack2(s[0], s[1]), pack2(s[2], s[3]));
                sts64(o + 16, pack2(s[4], s[5]), pack2(s[6], s[7]));
#pragma unroll
                for (int i = 0; i < 8; i++) s[i] = p[i] + s[i + 1];
                sts64(o + S4_SIG + 8, pack2(s[0], s[1]), pack2(s[2], s[3]));
                sts64(o + S4_SIG + 16, pack2(s[4], s[5]), pack2(s[6], s[7]));
            }
        }
        __syncwarp();
        if (rg == 3) {
#pragma unroll 1
            for (int q = 1; q <= 2; q++) s4_class<64, 2>(acc, rs + lf + (q == 1 ? 16 : S4_SIG), kd + (384 + q) * 2, g - 2 * t);
        } else {
#pragma unroll 1
            for (int q = 1; q <= 4; q++) s4_class<32, 4>(acc, rs + lf + ((q & 1) ? 0 : S4_SIG) + (q < 3 ? 16 : 0), kd + (256 + q) * 2, g - 2 * t);
        }
        __syncwarp();
    }
    } else
    {
        const uint32_t ub = ur + 256 + lf, kb = pk + (g - 2 * t) * 4;
#pragma unroll 1
        for (int j0 = 0; j0 < 8; j0++) {
            uint32_t B[8][4];
#pragma unroll
            for (int i = 0; i < 8; i++) ldsm4(B[i], ub + i * 512 - j0 * 32);
            auto block = [&](int J, uint32_t a) {
                const uint32_t r0 = lds32(a), rp = lds32(a + 32), rm = lds32(a - 32);
                uint32_t r3;
                asm volatile("ld.volatile.shared.u32 %0, [%1];" : "=r"(r3) : "r"(a) : "memory");
#pragma unroll
                for (int I = J; I < 16; I++)
                    mma16816(acc[I], r0, rp, rm, r3, B[(I - J) >> 1][((I - J) & 1) * 2], B[(I - J) >> 1][((I - J) & 1) * 2 + 1]);
            };
#pragma unroll
            for (int J = 0; J < 4; J++) block(J, kb + j0 * 64 + J * 512);
            if (j0 < 2) { block(4, kb + j0 * 64 + 2048); block(8, kb + j0 * 64 + (544 + 16) * 4); }
        }
    }
    }
    {
        __syncwarp();
#pragma unroll
        for (int i = 0; i < 8; i++)
            stsm4t(rs + lf + i * 512, pack2(acc[2 * i][0], acc[2 * i][1]), pack2(acc[2 * i][2], acc[2 * i][3]),
                   pack2(acc[2 * i + 1][0], acc[2 * i + 1][1]), pack2(acc[2 * i + 1][2], acc[2 * i + 1][3]));
    }
    __syncthreads();
    {
        const uint2 dv = __ldg((const uint2*)(Dsk + d0 + 4 * t));
        load_params(min(item + (int)gridDim.x, 63));
        bf16* dst = out + (size_t)(w * 128 + g) * 2048 + 1024 + d0 + 4 * t;
        uint32_t o[8][4];
#pragma unroll
        for (int i = 0; i < 8; i++) {
            uint32_t y[4], x[4];
            ldsm4t(y, sb + S4_R + tr_off * S4_RS + (w * 128 + i * 16) * 2 + tr_l);
            ldsm4t(x, sb + S4_U + tr_off * S4_US + 256 + (w * 128 + i * 16) * 2 + tr_l);
#pragma unroll
            for (int j = 0; j < 4; j++)
                asm("{\n.reg .b32 s;\nmul.rn.bf16x2 s, %2, %3;\nadd.rn.bf16x2 %0, %1, s;\n}" : "=r"(o[i][j]) : "r"(y[j]), "r"(x[j]), "r"((j & 1) ? dv.y : dv.x));
        }
        __syncthreads();
#pragma unroll
        for (int i = 0; i < 8; i++) {
            *reinterpret_cast<uint2*>(dst + (size_t)(i * 16) * 2048) = make_uint2(o[i][0], o[i][1]);
            *reinterpret_cast<uint2*>(dst + (size_t)(i * 16 + 8) * 2048) = make_uint2(o[i][2], o[i][3]);
        }
    }
    }
}

enum { IT_W256 = 1, IT_W128 = 2, IT_W64 = 3, IT_END = 7 };
struct BgParams { CUtensorMap mo, mo2, mwo4, mwo2, mwo1; };
#define P256 56
#define P128 62
struct Sched { uint32_t w0, w1; };
__device__ __forceinline__ int next_item(Sched& z) {
    if (z.w0 >= z.w1) {
        uint32_t prog;
        asm volatile("ld.relaxed.gpu.global.u32 %0, [%1];" : "=r"(prog) : "l"(g_flag + 98) : "memory");
        const uint32_t k = prog <= P256 ? 4 : prog <= P128 ? 2 : 1;
        z.w0 = 4 * gridDim.x + atomicAdd(g_flag + 97, k);
        z.w1 = min(z.w0 + k, NBT * 16u);
        if (z.w0 >= z.w1) return IT_END;
    }
    const uint32_t i = z.w0, k = z.w1 - i >= 4 && !(i & 3) ? 4 : z.w1 - i >= 2 && !(i & 1) ? 2 : 1;
    z.w0 += k;
    return (k == 4 ? IT_W256 : k == 2 ? IT_W128 : IT_W64) | (i >> 4) << 3 | ((i & 15) / k) << 7;
}
constexpr int B_OST = NSTAGE * STAGE_BYTES + 1024;
constexpr int BG_SMEM = B_OST + 32768;

template <int BM, int BN, int KPS, typename ACC>
__device__ __forceinline__ void gemm_mainloop(ACC& acc, const GemmSmem& g, int cw, int rounds, uint32_t& round) {
#pragma unroll
    for (int i = 0; i < BN / 2; i++) acc[i] = 0.f;
#pragma unroll 1
    for (int k0 = 0; k0 < rounds; k0++, round++) {
#pragma unroll
        for (int s = 0; s < 4; s++) {
            mbar_wait_u(g.full + 8 * s, round & 1);
            gemm_stage<BM, BN, KPS>(acc, g.st + s * STAGE_BYTES, cw, false);
            wg_wait<1>();
            if (s > 0 || k0 > 0) mbar_arrive_one(g.empty + 8 * ((s + 3) & 3), threadIdx.x & 31);
        }
    }
    wg_wait<0>();
    mbar_arrive_one(g.empty + 8 * 3, threadIdx.x & 31);
}

template <int BN>
__device__ __forceinline__ void store_tile(const float (&acc)[BN / 2], bf16* dst, int t) {
#pragma unroll
    for (int G = 0; G < BN / 32; G++)
#pragma unroll
        for (int rr = 0; rr < 2; rr++) {
            uint32_t r0 = pack2(acc[16 * G + 2 * rr], acc[16 * G + 2 * rr + 1]), r1 = pack2(acc[16 * G + 4 + 2 * rr], acc[16 * G + 5 + 2 * rr]);
            uint32_t r2 = pack2(acc[16 * G + 8 + 2 * rr], acc[16 * G + 9 + 2 * rr]), r3 = pack2(acc[16 * G + 12 + 2 * rr], acc[16 * G + 13 + 2 * rr]);
            quad_transpose(r0, r1, r2, r3, t);
            *reinterpret_cast<uint4*>(dst + (size_t)rr * 8 * 2048 + G * 32) = make_uint4(r0, r1, r2, r3);
        }
}

template <int BN, int KPS>
__device__ __forceinline__ void wo_item(const GemmSmem& g, int cw, uint32_t& round, bf16* dst, int t) {
    float acc[BN / 2];
    gemm_mainloop<128, BN, KPS>(acc, g, cw, 16 / KPS, round);
    store_tile<BN>(acc, dst, t);
}

__global__ void __launch_bounds__(384, 1) k_bg(const __grid_constant__ BgParams P, bf16* __restrict__ out) {
    extern __shared__ __align__(1024) uint8_t smem_gemm[];
    asm volatile("griddepcontrol.launch_dependents;");
    const uint32_t bar_item = smem_u32(smem_gemm) + NSTAGE * STAGE_BYTES + 128, slot = bar_item + 16;
    if (threadIdx.x == 0) { mbar_init(bar_item, 1); mbar_init(bar_item + 8, 1); }
    if (threadIdx.x == 32) asm volatile("prefetch.tensormap [%0];\nprefetch.tensormap [%1];" ::"l"(&P.mo), "l"(&P.mwo4) : "memory");
    GemmSmem g = gemm_setup(smem_gemm, 8);
    const int wg = __shfl_sync(~0u, threadIdx.x >> 7, 0);
    if (wg == 0) {
        asm volatile("setmaxnreg.dec.sync.aligned.u32 40;");
        if (threadIdx.x == 0) {
            uint32_t it = 0;
            Sched z = {4 * blockIdx.x, 4 * blockIdx.x + 4};
            wait_flag(g_flag + 64, 96);
            asm volatile("fence.proxy.async.global;" ::: "memory");
            for (int n = 0;; n++) {
                const int code = next_item(z);
                sts32(slot + (n & 1) * 4, code);
                mbar_arrive(bar_item + (n & 1) * 8);
                const int type = code & 7, blk = (code >> 3) & 15, idx = code >> 7;
                if (type == IT_END) break;
                for (int k = 0; k < (type == IT_W64 ? 32 : 64); k++, it++) {
                    const int s = it & 3;
                    const uint32_t st = g.st + s * STAGE_BYTES, fb = g.full + 8 * s;
                    mbar_wait(g.empty + 8 * s, ((it >> 2) & 1) ^ 1);
                    mbar_expect_tx(fb, type == IT_W128 ? 32768 : 49152);
                    if (type == IT_W64) {
                        tma3d(st, &P.mo2, 0, blk * 128, k * 2, fb);
                        tma3d(st + 32768, &P.mwo1, 0, k * 128, idx, fb);
                    } else {
                        tma2d(st, &P.mo, k * 64, blk * 128, fb);
                        tma3d(st + 16384, type == IT_W256 ? &P.mwo4 : &P.mwo2, 0, k * 64, idx * (type == IT_W256 ? 4 : 2), fb);
                    }
                }
            }
        }
    } else {
        asm volatile("setmaxnreg.inc.sync.aligned.u32 232;");
        const int cw = wg - 1, lane = threadIdx.x & 31;
        uint32_t round = 0;
#pragma unroll 1
        for (int n = 0;; n++) {
            mbar_wait_u(bar_item + (n & 1) * 8, (n >> 1) & 1);
            const int code = __shfl_sync(~0u, lds32(slot + (n & 1) * 4), 0);
            const int type = code & 7, blk = (code >> 3) & 15, idx = (code >> 7) & 31;
            if (type == IT_END) break;
            bf16* dst = out + (size_t)(blk * 128 + cw * 64 + ((threadIdx.x >> 5) & 3) * 16 + (lane >> 2)) * 2048 + (lane & 3) * 8;
            if (type == IT_W256) wo_item<256, 1>(g, cw, round, dst + idx * 256, lane & 3);
            else if (type == IT_W128) wo_item<128, 1>(g, cw, round, dst + idx * 128, lane & 3);
            else wo_item<64, 2>(g, cw, round, dst + idx * 64, lane & 3);
        }
    }
}

static_assert(NBT == 10, "k_tail covers blocks 10..15");
__global__ void __cluster_dims__(6, 1, 1) __launch_bounds__(384, 1)
k_tail(const __grid_constant__ BgParams P, bf16* __restrict__ out) {
    extern __shared__ __align__(1024) uint8_t smem_gemm[];
    const int cl = blockIdx.x / 6, rank = blockIdx.x - 6 * cl, half = rank & 1, pr = rank >> 1;
    const int blk = NBT + (cl >> 3) * 3 + pr, idx = cl & 7;
    const uint32_t st = smem_u32(smem_gemm), full = st + 6 * 32768, empty = full + 64, emptyb = full + 128, bar_s = full + 192;
    if (threadIdx.x == 0) {
        for (int s = 0; s < 6; s++) { mbar_init(full + 8 * s, 1); mbar_init(empty + 8 * s, 2); mbar_init(emptyb + 8 * s, 6); }
        mbar_init(bar_s, 1); mbar_expect_tx(bar_s, 32768);
        asm volatile("fence.mbarrier_init.release.cluster;\nfence.proxy.async.shared::cta;" ::: "memory");
    }
    if (threadIdx.x == 32) asm volatile("prefetch.tensormap [%0];\nprefetch.tensormap [%1];" ::"l"(&P.mo), "l"(&P.mwo2) : "memory");
    __syncthreads();
    asm volatile("barrier.cluster.arrive.relaxed.aligned;\nbarrier.cluster.wait.aligned;" ::: "memory");
    const int wg = __shfl_sync(~0u, threadIdx.x >> 7, 0);
    if (wg == 0) {
        if (threadIdx.x == 0) {
            wait_flag(g_flag + 65, 96);
            asm volatile("fence.proxy.async.global;" ::: "memory");
            if (blockIdx.x == 95)
                for (int i = 0; i < 4; i++) reinterpret_cast<uint4*>(g_flag)[i] = make_uint4(0, 0, 0, 0);
            for (int k = 0, s = 0, ph = 1; k < 32; k++) {
                mbar_wait(empty + 8 * s, ph);
                mbar_expect_tx(full + 8 * s, 32768);
                tma2d(st + s * 32768, &P.mo, (half * 32 + k) * 64, blk * 128, full + 8 * s);
                if (++s == 6) { s = 0; ph ^= 1; }
            }
        } else if (threadIdx.x == 32) {
            for (int k = pr, s = pr, ph = 1; k < 32; k += 3) {
                mbar_wait(emptyb + 8 * s, ph);
                asm volatile("cp.async.bulk.tensor.3d.shared::cluster.global.mbarrier::complete_tx::bytes.multicast::cluster "
                             "[%0], [%1, {%3, %4, %5}], [%2], %6;"
                             ::"r"(st + s * 32768 + 16384), "l"(&P.mwo2), "r"(full + 8 * s), "r"(0), "r"((half * 32 + k) * 64), "r"(idx * 2),
                               "h"((uint16_t)(0x15 << half)) : "memory");
                s += 3;
                if (s >= 6) { s -= 6; ph ^= 1; }
            }
        }
    } else {
        const int cw = wg - 1, lane = threadIdx.x & 31, t = lane & 3;
        float acc[64], fin[32];
#pragma unroll
        for (int i = 0; i < 64; i++) acc[i] = 0.f;
#pragma unroll 1
        for (int k = 0, s = 0, ph = 0, sp = 0; k < 32; k++) {
            mbar_wait_u(full + 8 * s, ph);
            gemm_stage<128, 128, 1>(acc, st + s * 32768, cw, false);
            wg_wait<1>();
            if (k > 0 && k <= 26)
                asm volatile("{\n.reg .pred p;\n.reg .u32 a;\nsetp.eq.u32 p, %3, 0;\nmapa.shared::cluster.u32 a, %1, %2;\n"
                             "@p mbarrier.arrive.relaxed.cta.shared::cta.b64 _, [%0];\n@p mbarrier.arrive.relaxed.cluster.shared::cluster.b64 _, [a];\n}"
                             ::"r"(empty + 8 * sp), "r"(emptyb + 8 * sp), "r"((sp >= 3 ? sp - 3 : sp) * 2 + half), "r"(threadIdx.x & 127) : "memory");
            sp = s;
            if (++s == 6) { s = 0; ph ^= 1; }
        }
        wg_wait<0>();
        const uint32_t xa = st + B_OST + (threadIdx.x - 128) * 16;
        uint32_t ra, rb;
        asm("mapa.shared::cluster.u32 %0, %1, %2;" : "=r"(ra) : "r"(xa), "r"(rank ^ 1));
        asm("mapa.shared::cluster.u32 %0, %1, %2;" : "=r"(rb) : "r"(bar_s), "r"(rank ^ 1));
#pragma unroll
        for (int i = 0; i < 8; i++) {
            float v[4];
#pragma unroll
            for (int j = 0; j < 4; j++) {
                v[j] = half ? acc[4 * i + j] : acc[32 + 4 * i + j];
                fin[4 * i + j] = half ? acc[32 + 4 * i + j] : acc[4 * i + j];
            }
            asm volatile("st.async.weak.shared::cluster.mbarrier::complete_tx::bytes.v4.f32 [%0], {%1,%2,%3,%4}, [%5];"
                         ::"r"(ra + i * 4096), "f"(v[0]), "f"(v[1]), "f"(v[2]), "f"(v[3]), "r"(rb) : "memory");
        }
        mbar_wait_u(bar_s, 0);
#pragma unroll
        for (int i = 0; i < 8; i++) {
            const float4 v = lds128f(xa + i * 4096);
            fin[4 * i] += v.x; fin[4 * i + 1] += v.y; fin[4 * i + 2] += v.z; fin[4 * i + 3] += v.w;
        }
        store_tile<64>(fin, out + (size_t)(blk * 128 + cw * 64 + ((threadIdx.x >> 5) & 3) * 16 + (lane >> 2)) * 2048 + idx * 128 + half * 64 + t * 8, t);
    }
}

typedef CUresult (*EncodeFn)(CUtensorMap*, CUtensorMapDataType, cuuint32_t, void*, const cuuint64_t*, const cuuint64_t*,
                             const cuuint32_t*, const cuuint32_t*, CUtensorMapInterleave, CUtensorMapSwizzle,
                             CUtensorMapL2promotion, CUtensorMapFloatOOBfill);

static void map2d(EncodeFn enc, CUtensorMap* m, const void* p, int rows, int cols, int box_rows) {
    cuuint64_t dim[2] = {(cuuint64_t)cols, (cuuint64_t)rows}, str[1] = {(cuuint64_t)cols * 2};
    cuuint32_t box[2] = {64, (cuuint32_t)box_rows}, es[2] = {1, 1};
    enc(m, CU_TENSOR_MAP_DATA_TYPE_BFLOAT16, 2, (void*)p, dim, str, box, es, CU_TENSOR_MAP_INTERLEAVE_NONE,
        CU_TENSOR_MAP_SWIZZLE_128B, CU_TENSOR_MAP_L2_PROMOTION_L2_256B, CU_TENSOR_MAP_FLOAT_OOB_FILL_NONE);
}
static void map3d(EncodeFn enc, CUtensorMap* m, const void* p, int rows, int cols, int box_rows, int nblk) {
    cuuint64_t dim[3] = {64, (cuuint64_t)rows, (cuuint64_t)cols / 64}, str[2] = {(cuuint64_t)cols * 2, 128};
    cuuint32_t box[3] = {64, (cuuint32_t)box_rows, (cuuint32_t)nblk}, es[3] = {1, 1, 1};
    enc(m, CU_TENSOR_MAP_DATA_TYPE_BFLOAT16, 3, (void*)p, dim, str, box, es, CU_TENSOR_MAP_INTERLEAVE_NONE,
        CU_TENSOR_MAP_SWIZZLE_128B, CU_TENSOR_MAP_L2_PROMOTION_L2_256B, CU_TENSOR_MAP_FLOAT_OOB_FILL_NONE);
}

#define USE_PDL 1

extern "C" void kernel_launch(void* const* d_in, const int* in_sizes, int n_in, void* d_out, int out_size) {
    const bf16 *x = (const bf16*)d_in[0], *mem0 = (const bf16*)d_in[1], *Wq = (const bf16*)d_in[2], *Wk = (const bf16*)d_in[3];
    const bf16 *Wv = (const bf16*)d_in[4], *Wo = (const bf16*)d_in[5];
    const bf16 *u = (const bf16*)d_in[7], *Are = (const bf16*)d_in[8], *Aim = (const bf16*)d_in[9], *Bre = (const bf16*)d_in[10];
    const bf16 *Bim = (const bf16*)d_in[11], *Cre = (const bf16*)d_in[12], *Cim = (const bf16*)d_in[13];
    const bf16 *logdt = (const bf16*)d_in[14], *Dsk = (const bf16*)d_in[15];
    bf16* out = (bf16*)d_out;

    void* fn = nullptr;
    cudaDriverEntryPointQueryResult qr;
    cudaGetDriverEntryPoint("cuTensorMapEncodeTiled", &fn, cudaEnableDefault, &qr);
    EncodeFn enc = (EncodeFn)fn;
    void *kv, *o;
    cudaGetSymbolAddress(&kv, g_kv);
    cudaGetSymbolAddress(&o, g_o);
    CUtensorMap mx, mwq, mwq1, mwk, mwv, mkv2;
    BgParams P;
    map2d(enc, &mx, x, SEQ, DM, 128);
    map2d(enc, &P.mo, o, SEQ, HD, 128);
    map3d(enc, &P.mo2, o, SEQ, HD, 128, 2);
    map3d(enc, &mwq, Wq, DM, HD, 64, 2);
    map3d(enc, &mwq1, Wq, DM, HD, 64, 1);
    map3d(enc, &mwk, Wk, DM, HD, 64, 2);
    map3d(enc, &mwv, Wv, DM, HD, 64, 2);
    map3d(enc, &P.mwo4, Wo, HD, DM, 64, 4);
    map3d(enc, &P.mwo2, Wo, HD, DM, 64, 2);
    map3d(enc, &P.mwo1, Wo, HD, DM, 128, 1);
    map3d(enc, &mkv2, kv, SEQ, PW, 32, 2);
    cudaFuncSetAttribute(k_kv, cudaFuncAttributeMaxDynamicSharedMemorySize, GEMM_SMEM);
    cudaFuncSetAttribute(k_bg, cudaFuncAttributeMaxDynamicSharedMemorySize, BG_SMEM);
    cudaFuncSetAttribute(k_tail, cudaFuncAttributeMaxDynamicSharedMemorySize, BG_SMEM);
    cudaFuncSetAttribute(k_chain, cudaFuncAttributeMaxDynamicSharedMemorySize, CHAIN_SMEM);
    cudaFuncSetAttribute(k_s4, cudaFuncAttributeMaxDynamicSharedMemorySize, S4_SMEM);

    cudaStream_t st = cudaStreamPerThread;
    cudaLaunchAttribute pdl[2], cls[1];
    pdl[0].id = cudaLaunchAttributeProgrammaticStreamSerialization;
    pdl[0].val.programmaticStreamSerializationAllowed = 1;
    cls[0].id = cudaLaunchAttributeClusterDimension;
    cls[0].val.clusterDim.x = CLS; cls[0].val.clusterDim.y = 1; cls[0].val.clusterDim.z = 1;
    cudaLaunchConfig_t cfg = {};
    cfg.stream = st; cfg.attrs = cls; cfg.numAttrs = 1;
    cfg.gridDim = dim3(96); cfg.blockDim = dim3(384); cfg.dynamicSmemBytes = GEMM_SMEM;
    cudaLaunchKernelEx(&cfg, k_kv, mx, mwk, mwv, mwq, mwq1, Wo, 0);
    pdl[1] = cls[0]; pdl[1].val.clusterDim.x = 2;
    cfg.attrs = pdl; cfg.numAttrs = 2;
    cfg.gridDim = dim3(36);
    cudaLaunchKernelEx(&cfg, k_kv, mx, mwk, mwv, mwq, mwq1, Wo, 96);
    cfg.numAttrs = 1;
    cfg.gridDim = dim3(96); cfg.blockDim = dim3(256); cfg.dynamicSmemBytes = CHAIN_SMEM;
    cudaLaunchKernelEx(&cfg, k_chain, mem0, Wq, Wk, Wv, Wo, mkv2);
    cfg.numAttrs = USE_PDL;
    cfg.gridDim = dim3(36); cfg.blockDim = dim3(512); cfg.dynamicSmemBytes = S4_SMEM;
    cudaLaunchKernelEx(&cfg, k_s4, u, Are, Aim, Bre, Bim, Cre, Cim, logdt, Dsk, out);
    cfg.gridDim = dim3(36); cfg.blockDim = dim3(384); cfg.dynamicSmemBytes = BG_SMEM;
    cudaLaunchKernelEx(&cfg, k_bg, P, out);
    cfg.gridDim = dim3(96);
    cudaLaunchKernelEx(&cfg, k_tail, P, out);
}
```

```cpp
#include <cuda_runtime.h>
#include <cuda_bf16.h>
#include <cuda.h>
#include <stdint.h>

typedef __nv_bfloat16 bf16;

constexpr int SEQ = 2048, DM = 1024, HD = 4096, NSEG = 64;

constexpr int PW = 3 * HD;
#define NTA 3
constexpr int NBT = 10;
__device__ __align__(1024) bf16 g_kv[(size_t)SEQ * PW];
__device__ __align__(1024) bf16 g_o[(size_t)SEQ * HD];
constexpr int XPAIRS = 128 + NSEG * 4;
__device__ __align__(8192) uint2 g_x[XPAIRS * 1024];
__device__ uint32_t g_home[XPAIRS];
__device__ uint32_t g_side[256];
__device__ __align__(1024) uint32_t g_flag[256];

__device__ __forceinline__ uint32_t smem_u32(const void* p) { return (uint32_t)__cvta_generic_to_shared(p); }
__device__ __forceinline__ void mbar_init(uint32_t bar, uint32_t cnt) {
    asm volatile("mbarrier.init.shared::cta.b64 [%0], %1;" ::"r"(bar), "r"(cnt) : "memory");
}
__device__ __forceinline__ void mbar_expect_tx(uint32_t bar, uint32_t bytes) {
    asm volatile("mbarrier.arrive.expect_tx.shared::cta.b64 _, [%0], %1;" ::"r"(bar), "r"(bytes) : "memory");
}
__device__ __forceinline__ void mbar_arrive(uint32_t bar) {
    asm volatile("mbarrier.arrive.shared::cta.b64 _, [%0];" ::"r"(bar) : "memory");
}
__device__ __forceinline__ bool mbar_try(uint32_t bar, uint32_t parity) {
    uint32_t ok;
    asm volatile("{\n.reg .pred p;\nmbarrier.try_wait.parity.shared::cta.b64 p, [%1], %2;\nselp.u32 %0, 1, 0, p;\n}"
                 : "=r"(ok) : "r"(bar), "r"(parity) : "memory");
    return ok;
}
constexpr int SPIN_LIMIT = 1 << 20;
__device__ __forceinline__ void mbar_wait(uint32_t bar, uint32_t parity) {
    int n = 0;
    while (!mbar_try(bar, parity)) { if (++n > SPIN_LIMIT) __trap(); }
}
__device__ __forceinline__ void mbar_wait_u(uint32_t bar, uint32_t parity) {
    asm volatile("{\n.reg .pred p;\n.reg .u32 n;\n"
                 "mbarrier.try_wait.parity.shared::cta.b64 p, [%0], %1;\n@p bra.uni DONE;\nmov.u32 n, 0;\n"
                 "AGAIN:\nmbarrier.try_wait.parity.shared::cta.b64 p, [%0], %1;\n@p bra.uni DONE;\n"
                 "add.u32 n, n, 1;\nsetp.lt.u32 p, n, 0x100000;\n@p bra.uni AGAIN;\ntrap;\nDONE:\n}"
                 ::"r"(bar), "r"(parity) : "memory");
}
__device__ __forceinline__ void tma2d(uint32_t dst, const CUtensorMap* m, int c0, int c1, uint32_t bar) {
    asm volatile("cp.async.bulk.tensor.2d.shared::cluster.global.mbarrier::complete_tx::bytes [%0], [%1, {%3, %4}], [%2];"
                 ::"r"(dst), "l"(m), "r"(bar), "r"(c0), "r"(c1) : "memory");
}
__device__ __forceinline__ void tma3d(uint32_t dst, const CUtensorMap* m, int c0, int c1, int c2, uint32_t bar) {
    asm volatile("cp.async.bulk.tensor.3d.shared::cluster.global.mbarrier::complete_tx::bytes [%0], [%1, {%3, %4, %5}], [%2];"
                 ::"r"(dst), "l"(m), "r"(bar), "r"(c0), "r"(c1), "r"(c2) : "memory");
}
__device__ __forceinline__ uint32_t pack2(float lo, float hi) {
    uint32_t r;
    asm("cvt.rn.bf16x2.f32 %0, %1, %2;" : "=r"(r) : "f"(hi), "f"(lo));
    return r;
}
__device__ __forceinline__ float bf_lo(uint32_t v) { return __uint_as_float(v << 16); }
__device__ __forceinline__ float bf_hi(uint32_t v) { return __uint_as_float(v & 0xffff0000u); }
__device__ __forceinline__ float bf_round(float x) { return bf_lo(pack2(x, 0.f)); }
__device__ __forceinline__ float ex2(float x) { float y; asm("ex2.approx.ftz.f32 %0, %1;" : "=f"(y) : "f"(x)); return y; }
__device__ __forceinline__ void mma16816(float (&c)[4], uint32_t a0, uint32_t a1, uint32_t a2, uint32_t a3, uint32_t b0, uint32_t b1) {
    asm volatile("mma.sync.aligned.m16n8k16.row.col.f32.bf16.bf16.f32 {%0,%1,%2,%3}, {%4,%5,%6,%7}, {%8,%9}, {%0,%1,%2,%3};"
                 : "+f"(c[0]), "+f"(c[1]), "+f"(c[2]), "+f"(c[3]) : "r"(a0), "r"(a1), "r"(a2), "r"(a3), "r"(b0), "r"(b1));
}
__device__ __forceinline__ void mma1688(float (&c)[4], uint32_t a0, uint32_t a1, uint32_t b0) {
    asm volatile("mma.sync.aligned.m16n8k8.row.col.f32.bf16.bf16.f32 {%0,%1,%2,%3}, {%4,%5}, {%6}, {%0,%1,%2,%3};"
                 : "+f"(c[0]), "+f"(c[1]), "+f"(c[2]), "+f"(c[3]) : "r"(a0), "r"(a1), "r"(b0));
}
__device__ __forceinline__ void ldsm4(uint32_t (&r)[4], uint32_t a) {
    asm volatile("ldmatrix.sync.aligned.m8n8.x4.shared.b16 {%0,%1,%2,%3}, [%4];"
                 : "=r"(r[0]), "=r"(r[1]), "=r"(r[2]), "=r"(r[3]) : "r"(a) : "memory");
}
__device__ __forceinline__ void ldsm4t(uint32_t (&r)[4], uint32_t a) {
    asm volatile("ldmatrix.sync.aligned.m8n8.x4.trans.shared.b16 {%0,%1,%2,%3}, [%4];"
                 : "=r"(r[0]), "=r"(r[1]), "=r"(r[2]), "=r"(r[3]) : "r"(a) : "memory");
}
__device__ __forceinline__ void stsm4t(uint32_t a, uint32_t r0, uint32_t r1, uint32_t r2, uint32_t r3) {
    asm volatile("stmatrix.sync.aligned.m8n8.x4.trans.shared.b16 [%0], {%1,%2,%3,%4};"
                 ::"r"(a), "r"(r0), "r"(r1), "r"(r2), "r"(r3) : "memory");
}
__device__ __forceinline__ void lds128(uint32_t (&r)[4], uint32_t a) {
    asm volatile("ld.shared.v4.u32 {%0,%1,%2,%3}, [%4];" : "=r"(r[0]), "=r"(r[1]), "=r"(r[2]), "=r"(r[3]) : "r"(a) : "memory");
}
__device__ __forceinline__ float4 lds128f(uint32_t a) {
    float4 v;
    asm volatile("ld.shared.v4.f32 {%0,%1,%2,%3}, [%4];" : "=f"(v.x), "=f"(v.y), "=f"(v.z), "=f"(v.w) : "r"(a) : "memory");
    return v;
}
__device__ __forceinline__ float2 lds64f(uint32_t a) {
    float2 v;
    asm volatile("ld.shared.v2.f32 {%0,%1}, [%2];" : "=f"(v.x), "=f"(v.y) : "r"(a) : "memory");
    return v;
}
__device__ __forceinline__ uint32_t lds32(uint32_t a) {
    uint32_t v;
    asm volatile("ld.shared.u32 %0, [%1];" : "=r"(v) : "r"(a) : "memory");
    return v;
}
__device__ __forceinline__ void sts128(uint32_t a, uint32_t r0, uint32_t r1, uint32_t r2, uint32_t r3) {
    asm volatile("st.shared.v4.u32 [%0], {%1,%2,%3,%4};" ::"r"(a), "r"(r0), "r"(r1), "r"(r2), "r"(r3) : "memory");
}
__device__ __forceinline__ void sts64(uint32_t a, uint32_t r0, uint32_t r1) {
    asm volatile("st.shared.v2.u32 [%0], {%1,%2};" ::"r"(a), "r"(r0), "r"(r1) : "memory");
}
__device__ __forceinline__ void sts32f(uint32_t a, float r0) {
    asm volatile("st.shared.f32 [%0], %1;" ::"r"(a), "f"(r0) : "memory");
}
__device__ __forceinline__ void st_rlx64(uint2* p, uint32_t x, uint32_t y) {
    asm volatile("{\n.reg .b64 t;\nmov.b64 t, {%1,%2};\nst.relaxed.gpu.global.b64 [%0], t;\n}" ::"l"(p), "r"(x), "r"(y) : "memory");
}
__device__ __forceinline__ uint32_t ld_acq32(const uint32_t* p) {
    uint32_t v;
    asm volatile("ld.acquire.gpu.global.u32 %0, [%1];" : "=r"(v) : "l"(p) : "memory");
    return v;
}
__device__ __forceinline__ void wait_flag(const uint32_t* p, uint32_t need) {
    int n = 0;
    while (ld_acq32(p) < need) { __nanosleep(200); if (++n > SPIN_LIMIT) __trap(); }
}
__device__ __forceinline__ void bar_sync(int id, int n) { asm volatile("bar.sync %0, %1;" ::"r"(id), "r"(n) : "memory"); }
__device__ __forceinline__ void wg_fence() { asm volatile("wgmma.fence.sync.aligned;" ::: "memory"); }
__device__ __forceinline__ void wg_commit() { asm volatile("wgmma.commit_group.sync.aligned;" ::: "memory"); }
template <int N> __device__ __forceinline__ void wg_wait() { asm volatile("wgmma.wait_group.sync.aligned %0;" ::"n"(N) : "memory"); }
__device__ __forceinline__ uint64_t desc_sw128(uint32_t addr, uint32_t lbo, uint32_t sbo) {
    return (uint64_t)((addr & 0x3FFFF) >> 4) | ((uint64_t)(lbo >> 4) << 16) | ((uint64_t)(sbo >> 4) << 32) | (1ull << 62);
}
__device__ __forceinline__ void quad_transpose(uint32_t& r0, uint32_t& r1, uint32_t& r2, uint32_t& r3, int t) {
    const bool o = t & 1, h = t & 2;
    uint32_t s0 = __shfl_xor_sync(~0u, o ? r0 : r1, 1), s1 = __shfl_xor_sync(~0u, o ? r2 : r3, 1);
    uint32_t a0 = o ? s0 : r0, a1 = o ? r1 : s0, a2 = o ? s1 : r2, a3 = o ? r3 : s1;
    s0 = __shfl_xor_sync(~0u, h ? a0 : a2, 2); s1 = __shfl_xor_sync(~0u, h ? a1 : a3, 2);
    r0 = h ? s0 : a0; r1 = h ? s1 : a1; r2 = h ? a2 : s0; r3 = h ? a3 : s1;
}

__device__ __forceinline__ void wgmma_n256(float (&d)[128], uint64_t da, uint64_t db, int sd) {
    asm volatile("{\n.reg .pred p;\nsetp.ne.b32 p, %130, 0;\n"
        "wgmma.mma_async.sync.aligned.m64n256k16.f32.bf16.bf16 "
        "{%0,%1,%2,%3,%4,%5,%6,%7,%8,%9,%10,%11,%12,%13,%14,%15,"
        "%16,%17,%18,%19,%20,%21,%22,%23,%24,%25,%26,%27,%28,%29,%30,%31,"
        "%32,%33,%34,%35,%36,%37,%38,%39,%40,%41,%42,%43,%44,%45,%46,%47,"
        "%48,%49,%50,%51,%52,%53,%54,%55,%56,%57,%58,%59,%60,%61,%62,%63,"
        "%64,%65,%66,%67,%68,%69,%70,%71,%72,%73,%74,%75,%76,%77,%78,%79,"
        "%80,%81,%82,%83,%84,%85,%86,%87,%88,%89,%90,%91,%92,%93,%94,%95,"
        "%96,%97,%98,%99,%100,%101,%102,%103,%104,%105,%106,%107,%108,%109,%110,%111,"
        "%112,%113,%114,%115,%116,%117,%118,%119,%120,%121,%122,%123,%124,%125,%126,%127}, %128, %129, p, 1, 1, 0, 1;\n}\n"
        : "+f"(d[0]), "+f"(d[1]), "+f"(d[2]), "+f"(d[3]), "+f"(d[4]), "+f"(d[5]), "+f"(d[6]), "+f"(d[7]),
          "+f"(d[8]), "+f"(d[9]), "+f"(d[10]), "+f"(d[11]), "+f"(d[12]), "+f"(d[13]), "+f"(d[14]), "+f"(d[15]),
          "+f"(d[16]), "+f"(d[17]), "+f"(d[18]), "+f"(d[19]), "+f"(d[20]), "+f"(d[21]), "+f"(d[22]), "+f"(d[23]),
          "+f"(d[24]), "+f"(d[25]), "+f"(d[26]), "+f"(d[27]), "+f"(d[28]), "+f"(d[29]), "+f"(d[30]), "+f"(d[31]),
          "+f"(d[32]), "+f"(d[33]), "+f"(d[34]), "+f"(d[35]), "+f"(d[36]), "+f"(d[37]), "+f"(d[38]), "+f"(d[39]),
          "+f"(d[40]), "+f"(d[41]), "+f"(d[42]), "+f"(d[43]), "+f"(d[44]), "+f"(d[45]), "+f"(d[46]), "+f"(d[47]),
          "+f"(d[48]), "+f"(d[49]), "+f"(d[50]), "+f"(d[51]), "+f"(d[52]), "+f"(d[53]), "+f"(d[54]), "+f"(d[55]),
          "+f"(d[56]), "+f"(d[57]), "+f"(d[58]), "+f"(d[59]), "+f"(d[60]), "+f"(d[61]), "+f"(d[62]), "+f"(d[63]),
          "+f"(d[64]), "+f"(d[65]), "+f"(d[66]), "+f"(d[67]), "+f"(d[68]), "+f"(d[69]), "+f"(d[70]), "+f"(d[71]),
          "+f"(d[72]), "+f"(d[73]), "+f"(d[74]), "+f"(d[75]), "+f"(d[76]), "+f"(d[77]), "+f"(d[78]), "+f"(d[79]),
          "+f"(d[80]), "+f"(d[81]), "+f"(d[82]), "+f"(d[83]), "+f"(d[84]), "+f"(d[85]), "+f"(d[86]), "+f"(d[87]),
          "+f"(d[88]), "+f"(d[89]), "+f"(d[90]), "+f"(d[91]), "+f"(d[92]), "+f"(d[93]), "+f"(d[94]), "+f"(d[95]),
          "+f"(d[96]), "+f"(d[97]), "+f"(d[98]), "+f"(d[99]), "+f"(d[100]), "+f"(d[101]), "+f"(d[102]), "+f"(d[103]),
          "+f"(d[104]), "+f"(d[105]), "+f"(d[106]), "+f"(d[107]), "+f"(d[108]), "+f"(d[109]), "+f"(d[110]), "+f"(d[111]),
          "+f"(d[112]), "+f"(d[113]), "+f"(d[114]), "+f"(d[115]), "+f"(d[116]), "+f"(d[117]), "+f"(d[118]), "+f"(d[119]),
          "+f"(d[120]), "+f"(d[121]), "+f"(d[122]), "+f"(d[123]), "+f"(d[124]), "+f"(d[125]), "+f"(d[126]), "+f"(d[127])
        : "l"(da), "l"(db), "r"(sd));
}

__device__ __forceinline__ void wgmma_n128(float (&d)[64], uint64_t da, uint64_t db, int sd) {
    asm volatile("{\n.reg .pred p;\nsetp.ne.b32 p, %66, 0;\n"
        "wgmma.mma_async.sync.aligned.m64n128k16.f32.bf16.bf16 "
        "{%0,%1,%2,%3,%4,%5,%6,%7,%8,%9,%10,%11,%12,%13,%14,%15,"
        "%16,%17,%18,%19,%20,%21,%22,%23,%24,%25,%26,%27,%28,%29,%30,%31,"
        "%32,%33,%34,%35,%36,%37,%38,%39,%40,%41,%42,%43,%44,%45,%46,%47,"
        "%48,%49,%50,%51,%52,%53,%54,%55,%56,%57,%58,%59,%60,%61,%62,%63}, %64, %65, p, 1, 1, 0, 1;\n}\n"
        : "+f"(d[0]), "+f"(d[1]), "+f"(d[2]), "+f"(d[3]), "+f"(d[4]), "+f"(d[5]), "+f"(d[6]), "+f"(d[7]),
          "+f"(d[8]), "+f"(d[9]), "+f"(d[10]), "+f"(d[11]), "+f"(d[12]), "+f"(d[13]), "+f"(d[14]), "+f"(d[15]),
          "+f"(d[16]), "+f"(d[17]), "+f"(d[18]), "+f"(d[19]), "+f"(d[20]), "+f"(d[21]), "+f"(d[22]), "+f"(d[23]),
          "+f"(d[24]), "+f"(d[25]), "+f"(d[26]), "+f"(d[27]), "+f"(d[28]), "+f"(d[29]), "+f"(d[30]), "+f"(d[31]),
          "+f"(d[32]), "+f"(d[33]), "+f"(d[34]), "+f"(d[35]), "+f"(d[36]), "+f"(d[37]), "+f"(d[38]), "+f"(d[39]),
          "+f"(d[40]), "+f"(d[41]), "+f"(d[42]), "+f"(d[43]), "+f"(d[44]), "+f"(d[45]), "+f"(d[46]), "+f"(d[47]),
          "+f"(d[48]), "+f"(d[49]), "+f"(d[50]), "+f"(d[51]), "+f"(d[52]), "+f"(d[53]), "+f"(d[54]), "+f"(d[55]),
          "+f"(d[56]), "+f"(d[57]), "+f"(d[58]), "+f"(d[59]), "+f"(d[60]), "+f"(d[61]), "+f"(d[62]), "+f"(d[63])
        : "l"(da), "l"(db), "r"(sd));
}

__device__ __forceinline__ void wgmma_n64(float (&d)[32], uint64_t da, uint64_t db, int sd) {
    asm volatile("{\n.reg .pred p;\nsetp.ne.b32 p, %34, 0;\n"
        "wgmma.mma_async.sync.aligned.m64n64k16.f32.bf16.bf16 "
        "{%0,%1,%2,%3,%4,%5,%6,%7,%8,%9,%10,%11,%12,%13,%14,%15,"
        "%16,%17,%18,%19,%20,%21,%22,%23,%24,%25,%26,%27,%28,%29,%30,%31}, %32, %33, p, 1, 1, 0, 1;\n}\n"
        : "+f"(d[0]), "+f"(d[1]), "+f"(d[2]), "+f"(d[3]), "+f"(d[4]), "+f"(d[5]), "+f"(d[6]), "+f"(d[7]),
          "+f"(d[8]), "+f"(d[9]), "+f"(d[10]), "+f"(d[11]), "+f"(d[12]), "+f"(d[13]), "+f"(d[14]), "+f"(d[15]),
          "+f"(d[16]), "+f"(d[17]), "+f"(d[18]), "+f"(d[19]), "+f"(d[20]), "+f"(d[21]), "+f"(d[22]), "+f"(d[23]),
          "+f"(d[24]), "+f"(d[25]), "+f"(d[26]), "+f"(d[27]), "+f"(d[28]), "+f"(d[29]), "+f"(d[30]), "+f"(d[31])
        : "l"(da), "l"(db), "r"(sd));
}

constexpr int STAGE_BYTES = 49152, NSTAGE = 4;
constexpr int GEMM_SMEM = NSTAGE * STAGE_BYTES + 128;

struct GemmSmem { uint32_t st, full, empty; };
__device__ __forceinline__ GemmSmem gemm_setup(uint8_t* raw, int releases) {
    GemmSmem g;
    g.st = smem_u32(raw);
    if (g.st & 1023) __trap();
    g.full = g.st + NSTAGE * STAGE_BYTES; g.empty = g.full + 64;
    if (threadIdx.x == 0) {
        for (int s = 0; s < NSTAGE; s++) { mbar_init(g.full + 8 * s, 1); mbar_init(g.empty + 8 * s, releases); }
        asm volatile("fence.mbarrier_init.release.cluster;" ::: "memory");
        asm volatile("fence.proxy.async.shared::cta;" ::: "memory");
    }
    __syncthreads();
    return g;
}
__device__ __forceinline__ void mbar_arrive_one(uint32_t bar, uint32_t who) {
    asm volatile("{\n.reg .pred p;\nsetp.eq.u32 p, %1, 0;\n@p mbarrier.arrive.shared::cta.b64 _, [%0];\n}" ::"r"(bar), "r"(who) : "memory");
}
template <int BM, int BN, int KPS, typename ACC>
__device__ __forceinline__ void gemm_stage(ACC& acc, uint32_t stage, int wg, bool first) {
    const uint64_t da = desc_sw128(stage + wg * 8192, 16, 1024);
    const uint64_t db = desc_sw128(stage + KPS * BM * 128, 8192, 1024);
    wg_fence();
#pragma unroll
    for (int k = 0; k < 4 * KPS; k++) {
        const uint64_t a = da + (k >> 2) * (BM * 8) + (k & 3) * 2, b = db + k * 128;
        if constexpr (BN == 256) wgmma_n256(acc, a, b, first && k == 0 ? 0 : 1);
        else if constexpr (BN == 128) wgmma_n128(acc, a, b, first && k == 0 ? 0 : 1);
        else wgmma_n64(acc, a, b, first && k == 0 ? 0 : 1);
    }
    wg_commit();
}

__device__ __forceinline__ void kv_store_unit(const uint32_t (&pk)[64], int u, bf16* dst, int t) {
    const int G = (u >> 2) * 2 + (u & 1), hh = (u >> 1) & 1;
    uint32_t r0 = pk[(4 * G + 0) * 2 + hh], r1 = pk[(4 * G + 1) * 2 + hh], r2 = pk[(4 * G + 2) * 2 + hh], r3 = pk[(4 * G + 3) * 2 + hh];
    quad_transpose(r0, r1, r2, r3, t);
#define KVST ".cs"
    asm volatile("st.global" KVST ".v4.u32 [%0], {%1,%2,%3,%4};" ::"l"(dst + (size_t)hh * 8 * PW + G * 32), "r"(r0), "r"(r1), "r"(r2), "r"(r3) : "memory");
}

__device__ __forceinline__ uint32_t near_page(int pair, int line) {
    uint32_t best[2] = {~0u, ~0u};
    for (int i = 0; i < 4; i++)
        reinterpret_cast<uint4*>(g_x + pair * 1024 + (i >> 1) * 512 + line * 16)[i & 1] = make_uint4(~0u, ~0u, ~0u, ~0u);
#pragma unroll 1
#define PMIN 8
#define PMAX 16
    for (int i = 0; i < PMAX; i++) {
        if (i >= PMIN && max(best[0], best[1]) - min(best[0], best[1]) > 110 && max(best[0], best[1]) - min(best[0], best[1]) < 300) break;
        uint32_t t0, t1, v;
        asm volatile("mov.u32 %0, %%clock;" : "=r"(t0)::"memory");
        asm volatile("atom.relaxed.gpu.global.or.b32 %0, [%1], -1;" : "=r"(v) : "l"(g_x + pair * 1024 + (i & 1) * 512 + line * 16) : "memory");
        asm volatile("{\n.reg .pred p;\nsetp.ne.u32 p, %1, 0x12345;\nmov.u32 %0, -1;\n@p mov.u32 %0, %%clock;\n}" : "=r"(t1) : "r"(v) : "memory");
        if (i & 1) best[1] = min(best[1], t1 - t0); else best[0] = min(best[0], t1 - t0);
    }
    return best[1] < best[0];
}
__device__ __forceinline__ void map_pages(int c) {
    uint32_t smid;
    asm("mov.u32 %0, %%smid;" : "=r"(smid));
    const uint32_t side = near_page(0, c & 31);
    g_side[smid & 255] = side;
    for (int p = c; p < XPAIRS; p += 132) g_home[p] = near_page(p, 0) ^ side;
}

__device__ __forceinline__ void kv_tile(int c, int n, int& m, int& nb) {
    if (c < 96) { m = (c & 3) + 4 * n; nb = c >> 2; }
    else {
        const int i = ((c - 96) >> 1) + 18 * n, j = i - 48 * NTA, p = j < 0 ? i / 24 : 2 * NTA + j / 48;
        m = 2 * p + (c & 1); nb = j < 0 ? 24 + i % 24 : j % 48;
    }
}

__global__ void __launch_bounds__(384, 1)
k_kv(const __grid_constant__ CUtensorMap mx, const __grid_constant__ CUtensorMap mwk, const __grid_constant__ CUtensorMap mwv,
     const __grid_constant__ CUtensorMap mwq, const __grid_constant__ CUtensorMap mwq1, const bf16* __restrict__ Wo, int c0) {
    extern __shared__ __align__(1024) uint8_t smem_gemm[];
    const int c = c0 + blockIdx.x, ntile = c < 96 ? NTA : 13;
    static_assert(NTA == 3, "round counts");
    const bool extra = c >= 96 && c < 120;
    const int xcol = 40 + ((c - 96) & ~1);
    if (c != 96) asm volatile("griddepcontrol.launch_dependents;");
    const uint32_t bar_done = smem_u32(smem_gemm) + NSTAGE * STAGE_BYTES + 96;
    if (threadIdx.x == 0) { mbar_init(bar_done, 8); mbar_init(bar_done + 8, 8); }
    GemmSmem g = gemm_setup(smem_gemm, 4);
    uint32_t rank, peer_empty;
    asm("mov.u32 %0, %%cluster_ctarank;" : "=r"(rank));
    asm("mapa.shared::cluster.u32 %0, %1, %2;" : "=r"(peer_empty) : "r"(g.empty), "r"(rank ^ 1));
    asm volatile("barrier.cluster.arrive.relaxed.aligned;\nbarrier.cluster.wait.aligned;" ::: "memory");
    auto release = [&](int s) {
        asm volatile("{\n.reg .pred p;\nsetp.eq.u32 p, %2, 0;\n@p mbarrier.arrive.relaxed.cta.shared::cta.b64 _, [%0];\n"
                     "@p mbarrier.arrive.relaxed.cluster.shared::cluster.b64 _, [%1];\n}"
                     ::"r"(g.empty + 8 * s), "r"(peer_empty + 8 * s), "r"(threadIdx.x & 127) : "memory");
    };
    const int wg = __shfl_sync(~0u, threadIdx.x >> 7, 0);
    if (wg == 0) {
        asm volatile("setmaxnreg.dec.sync.aligned.u32 40;");
        if (threadIdx.x == 0) {
            for (int it = 0; it < ntile * 16; it++) {
                const int s = it & 3, kb = it & 15;
                int m, nb;
                kv_tile(c, it >> 4, m, nb);
                mbar_wait(g.empty + 8 * s, ((it >> 2) & 1) ^ 1);
                mbar_expect_tx(g.full + 8 * s, STAGE_BYTES);
                tma2d(g.st + s * STAGE_BYTES, &mx, kb * 64, m * 128, g.full + 8 * s);
                asm volatile("cp.async.bulk.tensor.3d.shared::cluster.global.mbarrier::complete_tx::bytes.multicast::cluster "
                             "[%0], [%1, {%3, %4, %5}], [%2], %6;"
                             ::"r"(g.st + s * STAGE_BYTES + 16384 + (c & 1) * 16384), "l"(nb < 16 ? &mwk : nb < 32 ? &mwv : &mwq), "r"(g.full + 8 * s),
                               "r"(0), "r"(kb * 64), "r"((nb & 15) * 4 + (c & 1) * 2), "h"((uint16_t)(3u << (rank & ~1u))) : "memory");
#define PF0 (16 * NTA - 22)
                if (c < 96 && it >= PF0 && (it - PF0) * 96 + c < 2048)
                    asm volatile("cp.async.bulk.prefetch.L2.global [%0], 4096;" ::"l"((const char*)Wo + ((it - PF0) * 96 + c) * 4096) : "memory");
            }
            for (int kb = 0; kb < (extra ? 16 : 0); kb++) {
                const int s = kb & 3;
                mbar_wait(g.empty + 8 * s, ((kb >> 2) & 1) ^ 1);
                mbar_expect_tx(g.full + 8 * s, 32768);
                tma2d(g.st + s * STAGE_BYTES, &mx, kb * 64, (14 + (c & 1)) * 128, g.full + 8 * s);
                asm volatile("cp.async.bulk.tensor.3d.shared::cluster.global.mbarrier::complete_tx::bytes.multicast::cluster "
                             "[%0], [%1, {%3, %4, %5}], [%2], %6;"
                             ::"r"(g.st + s * STAGE_BYTES + 16384 + (c & 1) * 8192), "l"(&mwq1), "r"(g.full + 8 * s),
                               "r"(0), "r"(kb * 64), "r"(xcol + (c & 1)), "h"((uint16_t)3) : "memory");
            }
        } else if (threadIdx.x == 32) {
            if (c == 96) {
                for (int i = 4; i < 64; i++) reinterpret_cast<uint4*>(g_flag)[i] = make_uint4(0, 0, 0, 0);
                asm volatile("fence.acq_rel.gpu;\ngriddepcontrol.launch_dependents;\ngriddepcontrol.wait;\n"
                             "fence.acq_rel.gpu;\nred.relaxed.gpu.global.add.u32 [%0], 1;" ::"l"(g_flag + 8) : "memory");
            }
        } else if (threadIdx.x == 64) {
            for (int n = 0; n < (c < 96 ? 0 : ntile + extra); n++) {
                int m, nb;
                kv_tile(c, n, m, nb);
                mbar_wait(bar_done + (n & 1) * 8, (n >> 1) & 1);
                asm volatile("fence.acq_rel.gpu;\nred.relaxed.gpu.global.add.u32 [%0], 1;" ::"l"(g_flag + min(m >> 1, 7)) : "memory");
            }
        } else if (threadIdx.x >= 96) {
            mbar_wait(g.full + 24, 0);
            const uint4 ones = make_uint4(~0u, ~0u, ~0u, ~0u);
            for (int i = c * 32 + threadIdx.x - 96; i < XPAIRS * 512; i += 132 * 32) reinterpret_cast<uint4*>(g_x)[i] = ones;
            __syncwarp();
            if (threadIdx.x == 96) {
                map_pages(c);
                if (c >= 96) asm volatile("fence.acq_rel.gpu;\nred.relaxed.gpu.global.add.u32 [%0], 1;" ::"l"(g_flag + 8) : "memory");
            }
        }
    } else {
        asm volatile("setmaxnreg.inc.sync.aligned.u32 232;");
        const int cw = wg - 1, lane = threadIdx.x & 31, t = lane & 3;
        bf16* const dst0 = g_kv + (size_t)(cw * 64 + ((threadIdx.x >> 5) & 3) * 16 + (lane >> 2)) * PW + t * 8;
        bf16* dst = dst0;
        float acc[128];
        uint32_t pk[64];
#pragma unroll 1
        for (int tile = 0; tile < ntile; tile++) {
#pragma unroll
            for (int kb = 0; kb < 16; kb++) {
                mbar_wait_u(g.full + 8 * (kb & 3), (kb >> 2) & 1);
                gemm_stage<128, 256, 1>(acc, g.st + (kb & 3) * STAGE_BYTES, cw, kb == 0);
                if (tile > 0) {
                    kv_store_unit(pk, kb, dst, t);
                    if (kb == 15) { __syncwarp(); mbar_arrive_one(bar_done + (~tile & 1) * 8, lane); }
                }
                if (kb > 0) {
                    wg_wait<1>();
                    if (kb <= 12 || tile < ntile - 1 || extra) release((kb - 1) & 3);
                }
            }
            wg_wait<0>();
            if (tile < ntile - 1 || extra) release(3);
#pragma unroll
            for (int i = 0; i < 64; i++) pk[i] = pack2(acc[2 * i], acc[2 * i + 1]);
            int m, nb;
            kv_tile(c, tile, m, nb);
            dst = dst0 + (size_t)m * 128 * PW + nb * 256;
        }
        if (extra) {
            float acc2[64];
#pragma unroll
            for (int i = 0; i < 64; i++) acc2[i] = 0.f;
#pragma unroll
            for (int kb = 0; kb < 16; kb++) {
                mbar_wait_u(g.full + 8 * (kb & 3), (kb >> 2) & 1);
                gemm_stage<128, 128, 1>(acc2, g.st + (kb & 3) * STAGE_BYTES, cw, false);
                kv_store_unit(pk, kb, dst, t);
                wg_wait<1>();
                if (kb > 0 && kb <= 12) release((kb - 1) & 3);
            }
            __syncwarp();
            mbar_arrive_one(bar_done, lane);
            wg_wait<0>();
#pragma unroll
            for (int i = 0; i < 32; i++) pk[i] = pack2(acc2[2 * i], acc2[2 * i + 1]);
            dst = dst0 + (size_t)(14 + (c & 1)) * 128 * PW + 2 * HD + xcol * 64;
#pragma unroll
            for (int u = 0; u < 8; u++) kv_store_unit(pk, u, dst, t);
        } else {
#pragma unroll
            for (int u = 0; u < 16; u++) kv_store_unit(pk, u, dst, t);
        }
        __syncwarp();
        mbar_arrive_one(bar_done + (extra ? 8 : 0), lane);
    }
}

constexpr int NS1 = 31;
#define RB1 4
#define PFC 4
constexpr int C_W1 = 0;
constexpr int C_W2 = C_W1 + 8 * NS1 * 512;
constexpr int C_KV = C_W2 + 14 * 8 * 512;
constexpr int C_RED = C_KV + 16384;
constexpr int C_QKV = C_RED + 64 * 272;
constexpr int QKV_SZ = 3 * 8 * 272;
constexpr int C_SC = C_RED;
constexpr int C_OB = C_SC + 2 * 8 * 52 * 4;
constexpr int C_BAR = C_QKV + 2 * QKV_SZ;
__host__ __device__ constexpr int smem_idx(int ks, int j) {
    return ks == 0 ? j : ks < 3 ? (j < 4 ? 4 + 4 * ks + j : -1) : (j < 3 ? 7 + 3 * ks + j : -1);
}
constexpr int CHAIN_SMEM = C_BAR + 64;

#define DLY3 10
#define DLY1 6
#define DLY0 4
#define DLY1A 11
#define DLY0A 0
#define DLY0B 8
#define DLY1B 8
#define PFD 3
#define DLYW 6
#define DLYQ 4
template <int N> __device__ __forceinline__ uint32_t delayed(uint32_t x, uint32_t self) {
    uint32_t p = self;
#pragma unroll
    for (int i = 0; i < N; i++) asm volatile("ld.volatile.shared.u32 %0, [%0];" : "+r"(p)::"memory");
    return x + (p - self);
}
__device__ __forceinline__ uint32_t hold(uint32_t x) { asm volatile("mov.b32 %0, %0;" : "+r"(x)::"memory"); return x; }
__device__ __forceinline__ int fresh(int x) { asm volatile("mov.b32 %0, %0;" : "+r"(x)); return x; }
__device__ __forceinline__ void lds128v(uint32_t (&r)[4], uint32_t a) {
    asm volatile("ld.volatile.shared.v4.u32 {%0,%1,%2,%3}, [%4];" : "=r"(r[0]), "=r"(r[1]), "=r"(r[2]), "=r"(r[3]) : "r"(a) : "memory");
}
__device__ __forceinline__ uint2 lds64(uint32_t a) {
    uint2 v;
    asm volatile("ld.shared.v2.u32 {%0,%1}, [%2];" : "=r"(v.x), "=r"(v.y) : "r"(a) : "memory");
    return v;
}
#define LDQ ".L1::no_allocate"
__device__ __forceinline__ uint4 ldw128(const void* p) {
    uint4 v;
    asm volatile("ld.global.nc" LDQ ".v4.u32 {%0,%1,%2,%3}, [%4];" : "=r"(v.x), "=r"(v.y), "=r"(v.z), "=r"(v.w) : "l"(p));
    return v;
}
#define P8_LD(i) "ld.relaxed.gpu.global.b64 d" #i ", [src + " #i " * 256];\n"
#define P8_X(i) "mov.b64 {x" #i ", y" #i "}, d" #i ";\n"
#define P8_HEAD(SRC) "{\n.reg .pred p, q;\n.reg .b64 src, d<8>;\n.reg .b32 n, x<8>, y<8>, m0, m1;\nmov.b64 src, " SRC ";\n"         \
                P8_LD(0) P8_LD(1) P8_LD(2) P8_LD(3) P8_LD(4) P8_LD(5) P8_LD(6) P8_LD(7) "mov.u32 n, 0;\nCHECK:\n" \
                P8_X(0) P8_X(1) P8_X(2) P8_X(3) P8_X(4) P8_X(5) P8_X(6) P8_X(7)
#define P8_VOTE "vote.sync.all.pred p, p, -1;\n@p bra.uni DONE;\n"
#define P8_TAIL "add.u32 n, n, 1;\nsetp.lt.u32 p, n, 0x100000;\n@p bra.uni CHECK;\ntrap;\nDONE:\n"
#define S8_LD(i) "ld.relaxed.gpu.global.b64 %" #i ", [%8 + " #i " * 256];\n"
__device__ __forceinline__ void fetch_state(uint64_t (&d)[8], const void* src) {
    asm volatile(S8_LD(0) S8_LD(1) S8_LD(2) S8_LD(3) S8_LD(4) S8_LD(5) S8_LD(6) S8_LD(7)
                 : "=&l"(d[0]), "=&l"(d[1]), "=&l"(d[2]), "=&l"(d[3]), "=&l"(d[4]), "=&l"(d[5]), "=&l"(d[6]), "=&l"(d[7]) : "l"(src) : "memory");
}
__device__ __forceinline__ void settle_state(uint64_t (&d)[8], const void* src) {
#define S8_X(i) "mov.b64 {x" #i ", _}, %" #i ";\n"
#define S8_R(i) "setp.eq.u32 q, x" #i ", 0xffffffff;\n@q " S8_LD(i)
    asm volatile("{\n.reg .pred p, q;\n.reg .b32 n, x<8>, m0, m1;\nmov.u32 n, 0;\nCHECK:\n"
                 S8_X(0) S8_X(1) S8_X(2) S8_X(3) S8_X(4) S8_X(5) S8_X(6) S8_X(7)
                 "max.u32 m0, x0, x1;\nmax.u32 m0, m0, x2;\nmax.u32 m1, x3, x4;\nmax.u32 m1, m1, x5;\nmax.u32 m0, m0, x6;\n"
                 "max.u32 m0, m0, x7;\nmax.u32 m0, m0, m1;\nsetp.ne.u32 p, m0, 0xffffffff;\n" P8_VOTE
                 S8_R(0) S8_R(1) S8_R(2) S8_R(3) S8_R(4) S8_R(5) S8_R(6) S8_R(7) P8_TAIL "}"
                 : "+l"(d[0]), "+l"(d[1]), "+l"(d[2]), "+l"(d[3]), "+l"(d[4]), "+l"(d[5]), "+l"(d[6]), "+l"(d[7]) : "l"(src) : "memory");
}
__device__ __forceinline__ uint64_t poll_sum(const void* src, uint32_t tag, uint32_t sel) {
#define P8_RT(i) "lop3.b32 m0, x" #i ", %2, 1, 0x28;\nsetp.ne.u32 q, m0, 0;\n@q " P8_LD(i)
#define P8_MMA(c, i, z) "mma.sync.aligned.m16n8k8.row.col.f32.bf16.bf16.f32 {" #c "0," #c "1," #c "2," #c "3}, {x" #i ", y" #i "}, {%3}, {" #z "0," #z "1," #z "2," #z "3};\n"
    uint64_t r;
    asm volatile(P8_HEAD("%1") "{\n.reg .f32 a<4>, b<4>, z<4>;\nmov.f32 z0, 0f00000000;\nmov.f32 z1, z0;\nmov.f32 z2, z0;\nmov.f32 z3, z0;\n"
                 P8_MMA(a, 0, z) P8_MMA(b, 1, z) P8_MMA(a, 2, a) P8_MMA(b, 3, b) P8_MMA(a, 4, a) P8_MMA(b, 5, b) P8_MMA(a, 6, a) P8_MMA(b, 7, b)
                 "add.f32 a0, a0, b0;\nadd.f32 a1, a1, b1;\nadd.f32 a2, a2, b2;\nadd.f32 a3, a3, b3;\n"
                 "cvt.rn.bf16x2.f32 m0, a1, a0;\ncvt.rn.bf16x2.f32 m1, a3, a2;\nmov.b64 %0, {m0, m1};\n}\n"
                 "lop3.b32 m0, x0, x1, %2, 0x7e;\nlop3.b32 m1, x2, x3, %2, 0x7e;\nlop3.b32 m0, m0, x4, %2, 0xf6;\n"
                 "lop3.b32 m1, m1, x5, %2, 0xf6;\nlop3.b32 m0, m0, x6, %2, 0xf6;\nlop3.b32 m1, m1, x7, %2, 0xf6;\n"
                 "lop3.b32 m0, m0, m1, 1, 0xa8;\nsetp.eq.u32 p, m0, 0;\n" P8_VOTE
                 P8_RT(0) P8_RT(1) P8_RT(2) P8_RT(3) P8_RT(4) P8_RT(5) P8_RT(6) P8_RT(7) P8_TAIL "}"
                 : "=&l"(r) : "l"(src), "r"(tag), "r"(sel) : "memory");
    return r;
}
__device__ __forceinline__ uint32_t wait_count_u(const uint32_t* p, uint32_t need) {
    uint32_t v;
    asm volatile("{\n.reg .pred p;\n.reg .u32 n;\nmov.u32 n, 0;\nAGAIN:\nld.acquire.gpu.global.u32 %0, [%1];\nsetp.ge.u32 p, %0, %2;\n"
                 "vote.sync.all.pred p, p, -1;\n@p bra.uni DONE;\nadd.u32 n, n, 1;\nsetp.lt.u32 p, n, 0x100000;\n@p bra.uni AGAIN;\ntrap;\n"
                 "DONE:\nfence.proxy.async.global;\n}" : "=&r"(v) : "l"(p), "r"(need) : "memory");
    return v;
}
__device__ __forceinline__ uint32_t movm(uint32_t x) { asm volatile("movmatrix.sync.aligned.m8n8.trans.b16 %0, %0;" : "+r"(x)); return x; }
template <int NK, typename F>
__device__ __forceinline__ void attend(uint32_t sb, uint32_t lm, uint32_t qs, uint32_t xq, int i8, int lane, bf16* dst, F mid) {
    const int r8 = lane & 7, m4 = lane >> 3;
    const float sl2e = 0.08838834764831845f * 1.4426950408889634f;
    const uint32_t lk = sb + C_KV + ((m4 & 1) * 8 + r8) * 128 + (((m4 >> 1) ^ r8) << 4);
    const uint32_t lkm = sb + xq + (8 + r8) * 272 + (m4 & 1) * 32 + (m4 >> 1) * 16;
    asm volatile("cp.async.wait_all;" ::: "memory");
    __syncwarp();
    float x[4][4];
#pragma unroll
    for (int i = 0; i < 4; i++) x[i][0] = x[i][1] = x[i][2] = x[i][3] = 0.f;
#pragma unroll
    for (int kp = 0; kp < 4; kp++) {
        uint32_t q[4], a[4];
        ldsm4(q, lm + qs + kp * 64);
        ldsm4(a, lkm + kp * 64);
        mma16816(x[2], a[0], a[1], a[2], a[3], q[0], q[1]);
        mma16816(x[3], a[0], a[1], a[2], a[3], q[2], q[3]);
#pragma unroll
        for (int u = 0; u < 4; u++) {
            if ((u & 1) >= NK) continue;
            ldsm4(a, (lk ^ (((kp & 1) * 2 + (u >> 1)) << 5)) + (kp >> 1) * 4096 + (u & 1) * 2048);
            mma16816(x[u & 1], a[0], a[1], a[2], a[3], q[u & 2], q[(u & 2) + 1]);
        }
    }
    x[2][0] += x[3][2]; x[2][1] += x[3][3];
    const int lim = i8 + 2 * (lane & 3) - (lane >> 2);
    uint32_t p[5];
    {
        float m[2], e[5][2];
#pragma unroll
        for (int b = 0; b < 2; b++) {
            e[4][b] = m[b] = x[2][b];
#pragma unroll
            for (int j = 0; j < 2 * NK; j++) {
                e[j][b] = j < 2 * NK - 2 || 8 * j - b <= lim ? x[j >> 1][(j & 1) * 2 + b] : -3.0e38f;
                m[b] = fmaxf(m[b], e[j][b]);
            }
        }
#pragma unroll
        for (int o = 4; o < 32; o <<= 1) {
            m[0] = fmaxf(m[0], __shfl_xor_sync(~0u, m[0], o));
            m[1] = fmaxf(m[1], __shfl_xor_sync(~0u, m[1], o));
        }
        m[0] *= sl2e; m[1] *= sl2e;
#pragma unroll
        for (int j = 0; j < 5; j++)
            if (j < 2 * NK || j == 4) p[j] = movm(pack2(ex2(fmaf(e[j][0], sl2e, -m[0])), ex2(fmaf(e[j][1], sl2e, -m[1]))));
    }
    const uint32_t lvt = sb + C_KV + 8192 + ((m4 >> 1) * 8 + r8) * 128 + (((m4 & 1) ^ r8) << 4), one = 0x3f803f80u;
    float sm[4] = {0.f, 0.f, 0.f, 0.f}, c[8][4];
    mma16816(sm, one, one, one, one, p[0], p[1]);
    if (NK == 2) mma16816(sm, one, one, one, one, p[2], p[3]);
    mma1688(sm, one, one, p[4]);
#pragma unroll
    for (int j = 0; j < 8; j++) c[j][0] = c[j][1] = c[j][2] = c[j][3] = 0.f;
#pragma unroll
    for (int kk = 0; kk < NK; kk++)
#pragma unroll
        for (int j = 0; j < 8; j++) {
            uint32_t a[4];
            ldsm4t(a, (lvt ^ ((j & 3) << 5)) + (j >> 2) * 4096 + kk * 2048);
            mma16816(c[j], a[0], a[1], a[2], a[3], p[2 * kk], p[2 * kk + 1]);
        }
    float i0, i1;
    asm("rcp.approx.ftz.f32 %0, %1;" : "=f"(i0) : "f"(sm[0]));
    asm("rcp.approx.ftz.f32 %0, %1;" : "=f"(i1) : "f"(sm[1]));
    uint32_t o[4][4];
#pragma unroll
    for (int j = 0; j < 4; j++) {
        uint32_t a[4];
        ldsm4t(a, lm + xq + 16 * 272 + j * 64);
        mma1688(c[2 * j], a[0], a[1], p[4]);
        mma1688(c[2 * j + 1], a[2], a[3], p[4]);
#pragma unroll
        for (int u = 0; u < 4; u++) o[j][u] = pack2(c[2 * j + (u >> 1)][(u & 1) * 2] * i0, c[2 * j + (u >> 1)][(u & 1) * 2 + 1] * i1);
    }
#pragma unroll
    for (int j = 0; j < 4; j++) stsm4t(lm + qs + j * 64, o[j][0], o[j][1], o[j][2], o[j][3]);
    mid();
    __syncwarp();
#pragma unroll
    for (int j = 0; j < 4; j++) lds128(o[j], sb + qs + ((lane >> 4) + 2 * j) * 272 + (lane & 15) * 16);
#pragma unroll
    for (int j = 0; j < 4; j++)
        asm volatile("st.global.v4.u32 [%0], {%1,%2,%3,%4};" ::"l"(dst + (size_t)2 * j * HD), "r"(o[j][0]), "r"(o[j][1]), "r"(o[j][2]), "r"(o[j][3]) : "memory");
}
__device__ __forceinline__ void sum8(float (&c)[4], const uint2 (&v)[8], uint32_t idn) {
    float d[4] = {0.f, 0.f, 0.f, 0.f};
    c[0] = c[1] = c[2] = c[3] = 0.f;
    mma16816(c, v[0].x, v[0].y, v[1].x, v[1].y, idn, idn);
    mma16816(d, v[2].x, v[2].y, v[3].x, v[3].y, idn, idn);
    mma16816(c, v[4].x, v[4].y, v[5].x, v[5].y, idn, idn);
    mma16816(d, v[6].x, v[6].y, v[7].x, v[7].y, idn, idn);
    c[0] += d[0]; c[1] += d[1]; c[2] += d[2]; c[3] += d[3];
}

#define CLS 6
__global__ void __cluster_dims__(CLS, 1, 1) __launch_bounds__(256, 1)
k_chain(const bf16* __restrict__ mem0, const bf16* __restrict__ Wq, const bf16* __restrict__ Wk, const bf16* __restrict__ Wv,
        const bf16* __restrict__ Wo, const __grid_constant__ CUtensorMap mkv) {
    extern __shared__ __align__(1024) uint8_t smem_chain[];
    const uint32_t sb = smem_u32(smem_chain);
    if (sb & 1023) __trap();
    const int w = __shfl_sync(~0u, threadIdx.x >> 5, 0), lane = __shfl_sync(~0u, threadIdx.x & 31, threadIdx.x & 31);
    const int tid = w * 32 + lane, g = lane >> 2, t = lane & 3;
    auto pin = [&](uint32_t x) { asm volatile("shfl.sync.idx.b32 %0, %0, %1, 31, -1;" : "+r"(x) : "r"(lane) : "memory"); return x; };
    const int h = blockIdx.x / 3, r = blockIdx.x - 3 * h;
    const uint32_t bar_x = sb + C_BAR, bar_kv = sb + C_BAR + 8, bar_go = sb + C_BAR + 16, bar_w = sb + C_BAR + 24, self = sb + C_BAR + 60;
    asm volatile("griddepcontrol.launch_dependents;");
    const int tbase = r == 0 ? 0 : 1 + 21 * r, ntile = r == 0 ? 22 : 21;
    uint32_t side;
    if (tid == 0) {
        mbar_init(bar_x, 8); mbar_init(bar_kv, 1); mbar_init(bar_go, 1); mbar_init(bar_w, 1);
        asm volatile("st.shared.u32 [%0], %0;" ::"r"(self) : "memory");
        asm volatile("fence.mbarrier_init.release.cluster;" ::: "memory");
        asm volatile("fence.proxy.async.shared::cta;" ::: "memory");
        mbar_expect_tx(bar_w, 128 * 32 * ntile);
    }
    __syncthreads();
    asm volatile("barrier.cluster.arrive.relaxed.aligned;" ::: "memory");
    asm("mov.u32 %0, %%smid;" : "=r"(side));
    asm volatile("ld.relaxed.gpu.global.u32 %0, [%1];" : "=r"(side) : "l"(g_side + (side & 255)) : "memory");
    if (tid < 128)
        asm volatile("cp.async.bulk.shared::cluster.global.mbarrier::complete_tx::bytes [%0], [%1], %2, [%3];"
                     ::"r"(sb + C_W1 + tid * 720), "l"(Wo + (size_t)(h * 128 + tid) * DM + tbase * 16), "r"(32 * ntile), "r"(bar_w) : "memory");
    const int tile0 = tbase + 7 - w;
    const bool three = w >= (r == 0 ? 2 : 3);
    const uint32_t wa = pin(sb + tid * 16);
#define W1A(i) (wa + C_W1 + (i) * 4096)
#define W2A(x) (wa + C_W2 + ((x) < 8 ? (x) * 4096 : 32768 - 1024 + ((x) - 8) * 3072))
    uint32_t wo0[8][4], wr[64][4];
    {
        const bf16* W = (r == 0 ? Wq : r == 1 ? Wk : Wv) + (size_t)(128 * w + (lane >> 4)) * HD + h * 128 + 8 * (lane & 15);
        uint4 raw[8][8];
        auto fetch = [&](int ks) {
#pragma unroll
            for (int i = 0; i < 8; i++) raw[ks][i] = ldw128(W + (size_t)(16 * ks + 2 * i) * HD);
        };
        fetch(0); fetch(1); fetch(2); fetch(3);
        mbar_wait_u(bar_w, 0);
        const uint32_t p = sb + C_W1 + ((lane & 7) + (lane >> 4) * 8) * 720 + (7 - w) * 32 + ((lane >> 3) & 1) * 16;
#pragma unroll
        for (int ks = 0; ks < 8; ks++) {
            uint32_t a[4];
            ldsm4t(wo0[ks], p + ks * 16 * 720);
            ldsm4t(a, p + ks * 16 * 720 + 256);
            sts128(W2A(ks), a[0], a[1], a[2], a[3]);
            if (three) { ldsm4t(a, p + ks * 16 * 720 + 512); sts128(W2A(8 + ks), a[0], a[1], a[2], a[3]); }
        }
        __syncthreads();
        side &= 1;
        if (w == 7 && r > 0) asm volatile("st.relaxed.gpu.global.u32 [%0], %1;" ::"l"(g_flag + 128 + 2 * h + r - 1), "r"(2 | side) : "memory");
        const uint32_t stg = sb + C_KV + w * 4096;
        const uint32_t rd = stg + ((lane & 7) + 8 * (lane >> 4)) * 256 + ((((lane >> 3) & 1) ^ (lane & 7)) << 4);
#pragma unroll
        for (int ks = 0; ks < 8; ks++) {
#pragma unroll
            for (int i = 0; i < 8; i++)
                sts128(stg + (2 * i + (lane >> 4)) * 256 + (((lane & 15) ^ (((2 * i) & 6) | (lane >> 4))) << 4),
                       raw[ks][i].x, raw[ks][i].y, raw[ks][i].z, raw[ks][i].w);
            if (ks < 2) fetch(ks + 4);
            if (ks == 3 || ks == 5) fetch(ks / 2 + 5);
            __syncwarp();
#pragma unroll
            for (int j = 0; j < 8; j++) {
                if (smem_idx(ks, j) >= 0) {
                    uint32_t a[4];
                    ldsm4t(a, rd ^ (j << 5));
                    sts128(W1A(smem_idx(ks, j)), a[0], a[1], a[2], a[3]);
                } else ldsm4t(wr[8 * ks + j], rd ^ (j << 5));
            }
            __syncwarp();
        }
    }
    uint2 bm[8];
#pragma unroll
    for (int ks = 0; ks < 8; ks++) {
        const uint32_t* p = (const uint32_t*)(mem0 + g * DM + (8 * w + ks) * 16) + t;
        asm volatile("ld.global.nc.u32 %0, [%2];\nld.global.nc.u32 %1, [%2 + 16];" : "=r"(bm[ks].x), "=r"(bm[ks].y) : "l"(p));
    }
    uint32_t psel, msel0, msel1;
    {
        const int j = r > 0 ? 2 * h + r - 1 : 0, tl = min(tile0 + 8 * (lane >> 1), 63);
        const uint32_t b = wait_count_u(lane < 8 ? g_flag + 128 + tl : g_flag + (lane & 8), lane < 8 ? 2 : lane & 8 ? 37 : 48);
        psel = __ballot_sync(~0u, (g_home[lane == 6 ? j * 2 + ((w >> 1) & 1) : tl * 2 + (lane & 1)] ^ (lane == 6 ? side : b)) & 1);
        msel0 = __ballot_sync(~0u, (g_home[128 + lane * 4 + (w >> 1)] ^ side) & 1);
        msel1 = __ballot_sync(~0u, (g_home[256 + lane * 4 + (w >> 1)] ^ side) & 1);
        if (r > 0) {
            if (w < 4) asm volatile("prefetch.global.L2 [%0];" ::"l"(g_x + (128 + (1 + (w >> 1)) * 4 + (j >> 4)) * 1024 + (w & 1) * 512 + (j & 15) * 32 + lane) : "memory");
            if (w < 4) asm volatile("prefetch.global.L2 [%0];" ::"l"(g_x + j * 2048 + tid * 16) : "memory");
        }
    }
    asm volatile("fence.proxy.async.shared::cta;" ::: "memory");
    __syncthreads();
    if (tid == 0) {
        mbar_expect_tx(bar_kv, 16384);
        tma3d(sb + C_KV, &mkv, 0, 0, 2 * h, bar_kv);
        tma3d(sb + C_KV + 8192, &mkv, 0, 0, 64 + 2 * h, bar_kv);
    }
    asm volatile("barrier.cluster.wait.aligned;" ::: "memory");

    auto load_kv = [&](int s) {
        asm volatile("{\n.reg .pred p;\nelect.sync _|p, -1;\n@p mbarrier.arrive.expect_tx.shared::cta.b64 _, [%2], 16384;\n"
                     "@p cp.async.bulk.tensor.3d.shared::cluster.global.mbarrier::complete_tx::bytes [%0], [%1, {%3, %4, %5}], [%2];\n"
                     "@p cp.async.bulk.tensor.3d.shared::cluster.global.mbarrier::complete_tx::bytes [%6], [%1, {%3, %4, %7}], [%2];\n}"
                     ::"r"(sb + C_KV), "l"(&mkv), "r"(bar_kv), "r"(0), "r"(s * 32), "r"(2 * h), "r"(sb + C_KV + 8192), "r"(64 + 2 * h) : "memory");
    };
    const bool attends = w == 7 || (w == 6 && r == 0);
    const int i8 = r == 0 ? (w - 4) * 8 : (r - 1) * 8;
    auto load_q = [&](int s) {
        const int l = fresh(lane);
        const bf16* p = g_kv + (size_t)(s * 32 + i8 + (l >> 4)) * PW + 2 * HD + h * 128 + (l & 15) * 8;
#pragma unroll
        for (int j = 0; j < 4; j++)
            asm volatile("cp.async.cg.shared.global [%0], [%1], 16;"
                         ::"r"(sb + C_RED + w * 2176 + ((l >> 4) + 2 * j) * 272 + (l & 15) * 16), "l"(p + (size_t)2 * j * PW) : "memory");
    };
    auto report = [&](int part) {
        asm volatile("{\n.reg .pred p;\nelect.sync _|p, -1;\nfence.acq_rel.gpu;\n@p red.relaxed.gpu.global.add.u32 [%0], 1;\n}"
                     ::"l"(g_flag + 64 + part) : "memory");
    };
    const float sl2e = 0.08838834764831845f * 1.4426950408889634f;
    const uint32_t idn = pin(g == 2 * t ? 0x00003f80u : g == 2 * t + 1 ? 0x3f800000u : 0u);
    const uint32_t lm = pin(sb + (lane & 7) * 272 + (lane >> 3) * 16);
    const uint32_t sa = pin(sb + C_SC + (w & 1) * (8 * 52 * 4) + (2 * t * 52 + (w < 4 ? 32 : (w & 2) * 8) + g) * 4);
    const uint32_t sr = pin(sb + C_SC + (g * 52 + 8 * t) * 4), sr2 = pin(sb + C_SC + (g * 52 + 32 + 2 * t) * 4);
    uint32_t kva;
    {
        const int pos = (w & 2) * 8 + (lane & 15), row = (pos & 24) + ((pos + (pos >> 2 & 6)) & 7);
        const int key = 4 * (lane & 6) + (((lane & 7) + 2 * (lane >> 4)) & 7);
        kva = pin(w >= 4 ? sb + C_KV + (w & 1) * 4096 + row * 128 + (((lane >> 4) ^ (row & 7)) << 4)
                         : sb + C_KV + 8192 + (w >> 1) * 4096 + key * 128 + ((((w & 1) * 4 + ((lane >> 3) & 1)) ^ (key & 7)) << 4));
    }
#define ATTEND(NK, s, mid) do {                                                                                       \
        const int l_ = fresh(lane);                                                                                      \
        attend<NK>(sb, lm, C_RED + w * 2176, C_QKV + ((s) & 1) * QKV_SZ, i8, l_,                                         \
                   g_o + (size_t)((s) * 32 + i8 + (l_ >> 4)) * HD + h * 128 + (l_ & 15) * 8, mid);                       \
    } while (0)
    auto chores = [&](int s) {
        if (s == 4 * NBT) report(0);
        if ((s & 7) == 6 - PFD && s < NSEG - 8) wait_count_u(g_flag + (s >> 3) + 1, (s >> 3) + 1 < 2 * NTA ? 48 : s < 48 ? 96 : 108);
    };
    uint32_t buf0[8][4], ring[RB1][4];
    auto stage_w1 = [&]() {
#pragma unroll
        for (int i = 0; i < 8; i++) lds128v(buf0[i], W1A(i));
#pragma unroll
        for (int i = 0; i < RB1; i++) lds128v(ring[i], W1A(8 + i));
    };
    stage_w1();
#pragma unroll 1
    for (int s = 0;; s++) {
        const uint32_t xq = C_QKV + (s & 1) * QKV_SZ;
        {
            float acc[8][4];
#pragma unroll
            for (int ks = 0; ks < 8; ks++) {
#pragma unroll
                for (int j = 0; j < 8; j++) {
                    const int i = smem_idx(ks, j) - 8;
                    if (ks == 0) {
                        acc[j][0] = acc[j][1] = acc[j][2] = acc[j][3] = 0.f;
                        mma16816(acc[j], buf0[j][0], buf0[j][1], buf0[j][2], buf0[j][3], bm[ks].x, bm[ks].y);
                    } else if (i >= 0) {
                        uint32_t(&a)[4] = ring[i % RB1];
                        mma16816(acc[j], a[0], a[1], a[2], a[3], bm[ks].x, bm[ks].y);
                        if (8 + i + RB1 < NS1) lds128v(a, W1A(8 + i + RB1));
                    } else {
                        const uint32_t(&a)[4] = wr[8 * ks + j];
                        mma16816(acc[j], a[0], a[1], a[2], a[3], bm[ks].x, bm[ks].y);
                    }
                }
            }
#pragma unroll
            for (int c = 0; c < 4; c++)
                stsm4t(lm + C_RED + w * 2176 + c * 64, pack2(acc[2 * c][0], acc[2 * c][1]), pack2(acc[2 * c][2], acc[2 * c][3]),
                       pack2(acc[2 * c + 1][0], acc[2 * c + 1][1]), pack2(acc[2 * c + 1][2], acc[2 * c + 1][3]));
        }
        {
            const uint32_t a = sb + C_RED + w * 272 + lane * 8;
            if (w == 3) mbar_wait_u(bar_kv, s & 1);
            __syncthreads();
            uint2 v[8];
#pragma unroll
            for (int i = 0; i < 8; i++) v[i] = lds64(a + i * 2176);
            float c[4];
            sum8(c, v, idn);
            const uint32_t p0 = pack2(c[0], c[1]), p1 = pack2(c[2], c[3]);
            const uint32_t dst = sb + xq + (r * 8 + w) * 272 + lane * 8;
#pragma unroll
            for (int i = 1; i < 3; i++) {
                const uint32_t peer = (h % (CLS / 3)) * 3 + (r + i >= 3 ? r + i - 3 : r + i);
                uint32_t rd, rb;
                asm("mapa.shared::cluster.u32 %0, %1, %2;" : "=r"(rd) : "r"(dst), "r"(peer));
                asm("mapa.shared::cluster.u32 %0, %1, %2;" : "=r"(rb) : "r"(bar_x), "r"(peer));
                asm volatile("st.async.weak.shared::cluster.mbarrier::complete_tx::bytes.v2.b32 [%0], {%1,%2}, [%3];"
                             ::"r"(rd), "r"(p0), "r"(p1), "r"(rb) : "memory");
            }
            sts64(dst, p0, p1);
            __syncwarp();
            asm volatile("{\n.reg .pred p;\nsetp.eq.u32 p, %1, 0;\n@p mbarrier.arrive.expect_tx.shared::cta.b64 _, [%0], 512;\n}"
                         ::"r"(bar_x), "r"(lane) : "memory");
        }
        if (s == NSEG - 1) break;
        uint32_t wb[8][4], wc[8][4];
        const uint32_t po = (tile0 * 2 + (lane >> 4)) * 8192 + ((lane >> 3) & 1) * 2048 + h * 64 + (lane & 7) * 8;
        const uint32_t tag = s & 1;
        auto project = [&](const uint32_t(&wt)[8][4], const uint32_t(&ob)[4][4], int i) {
            float c0[4] = {0.f, 0.f, 0.f, 0.f}, c1[4] = {0.f, 0.f, 0.f, 0.f};
#pragma unroll
            for (int ks = 0; ks < 8; ks++)
                mma16816((ks & 1) ? c1 : c0, wt[ks][0], wt[ks][1], wt[ks][2], wt[ks][3], ob[ks >> 1][(ks & 1) * 2], ob[ks >> 1][(ks & 1) * 2 + 1]);
            uint32_t p0 = pack2(c0[0] + c1[0], c0[1] + c1[1]), p1 = pack2(c0[2] + c1[2], c0[3] + c1[3]);
            asm volatile("movmatrix.sync.aligned.m8n8.trans.b16 %0, %0;\nmovmatrix.sync.aligned.m8n8.trans.b16 %1, %1;" : "+r"(p0), "+r"(p1));
            st_rlx64((uint2*)((char*)g_x + po + i * 131072 + ((psel >> (2 * i + (lane >> 4))) & 1) * 4096), (p0 & ~1u) | tag, p1);
        };
        if (w >= 4) {
            uint32_t ka[4][4];
#pragma unroll
            for (int ks = 0; ks < 4; ks++) ldsm4(ka[ks], kva ^ (ks << 5));
            const uint32_t qa = lm + xq + (w & 1) * 128;
            mbar_wait_u(bar_x, s & 1);
            {
                uint32_t qb[2][4];
                ldsm4(qb[0], qa);
                ldsm4(qb[1], qa + 64);
                float c0[4] = {0.f, 0.f, 0.f, 0.f}, c1[4] = {0.f, 0.f, 0.f, 0.f};
                mma16816(c0, ka[0][0], ka[0][1], ka[0][2], ka[0][3], qb[0][0], qb[0][1]);
                mma16816(c1, ka[1][0], ka[1][1], ka[1][2], ka[1][3], qb[0][2], qb[0][3]);
                mma16816(c0, ka[2][0], ka[2][1], ka[2][2], ka[2][3], qb[1][0], qb[1][1]);
                mma16816(c1, ka[3][0], ka[3][1], ka[3][2], ka[3][3], qb[1][2], qb[1][3]);
                sts32f(sa, c0[0] + c1[0]);
                sts32f(sa + 208, c0[1] + c1[1]);
                sts32f(sa + 32, c0[2] + c1[2]);
                sts32f(sa + 240, c0[3] + c1[3]);
            }
            __syncthreads();
            uint32_t wd;
            if (attends) { load_q(s); wd = delayed<DLYQ>(wa, self); } else wd = delayed<DLYW>(wa, self);
#pragma unroll
            for (int i = 0; i < 8; i++) lds128(wb[i], wd + C_W2 + i * 4096);
#pragma unroll
            for (int i = 0; i < PFC; i++) lds128(wc[i], wd + C_W2 + 32768 - 1024 + i * 3072);
            __syncthreads();
            uint32_t ob[4][4];
#pragma unroll
            for (int i = 0; i < 4; i++) ldsm4(ob[i], lm + C_OB + i * 64);
#pragma unroll
            for (int i = PFC; i < 8; i++) lds128(wc[i], W2A(8 + i));
            project(wb, ob, 1);
            project(wo0, ob, 0);
            project(wc, ob, 2);
        } else {
            uint32_t va[4][4];
#pragma unroll
            for (int i = 0; i < 4; i++) ldsm4t(va[i], kva ^ (((i >> 1) << 5) | ((i & 1) * 0x240)));
#pragma unroll
            for (int i = 0; i < 8; i++) lds128(wb[i], W2A(i));
            const uint32_t qa = lm + xq + (w & 1) * 128, oa = lm + w * 64;
            if (w < 2) {
                const uint32_t qp = hold(qa), ka = hold(qa + 8 * 272 + ((lane & 8) << 1) - (lane & 16));
                mbar_wait_u(bar_x, s & 1);
                uint32_t qb[2][4], km[2][4];
                ldsm4(qb[0], qp);
                ldsm4(km[0], ka);
                ldsm4(qb[1], qp + 64);
                ldsm4(km[1], ka + 64);
                float c0[4] = {0.f, 0.f, 0.f, 0.f}, c1[4] = {0.f, 0.f, 0.f, 0.f};
                mma16816(c0, km[0][0], km[0][1], km[0][2], km[0][3], qb[0][0], qb[0][1]);
                mma16816(c1, km[0][0], km[0][1], km[0][2], km[0][3], qb[0][2], qb[0][3]);
                mma16816(c0, km[1][0], km[1][1], km[1][2], km[1][3], qb[1][0], qb[1][1]);
                mma16816(c1, km[1][0], km[1][1], km[1][2], km[1][3], qb[1][2], qb[1][3]);
                sts32f(sa, c0[0] + c1[2]);
                sts32f(sa + 208, c0[1] + c1[3]);
            }
            __syncthreads();
            {
                float4 x0 = lds128f(sr), y0 = lds128f(sr + 1664), x1 = lds128f(sr + 16), y1 = lds128f(sr + 1680);
                float2 x2 = lds64f(sr2), y2 = lds64f(sr2 + 1664);
                uint32_t vm[4];
                ldsm4t(vm, oa + xq + 16 * 272);
                float p[10] = {x0.x + y0.x, x0.y + y0.y, x0.z + y0.z, x0.w + y0.w, x1.x + y1.x,
                               x1.y + y1.y, x1.z + y1.z, x1.w + y1.w, x2.x + y2.x, x2.y + y2.y};
                float m = fmaxf(fmaxf(fmaxf(p[0], p[1]), fmaxf(p[2], p[3])), fmaxf(fmaxf(fmaxf(p[4], p[5]), fmaxf(p[6], p[7])), fmaxf(p[8], p[9])));
                const float m1 = __shfl_xor_sync(~0u, m, 1), m2 = __shfl_xor_sync(~0u, m, 2), m3 = __shfl_xor_sync(~0u, m, 3);
                m = fmaxf(fmaxf(m, m1), fmaxf(m2, m3));
                const float ms = m * sl2e;
#pragma unroll
                for (int i = 0; i < 10; i++) p[i] = ex2(fmaf(p[i], sl2e, -ms));
                const uint32_t b0 = pack2(p[0], p[1]), b1 = pack2(p[2], p[3]), b2 = pack2(p[4], p[5]), b3 = pack2(p[6], p[7]), b4 = pack2(p[8], p[9]);
                const uint32_t one = 0x3f803f80u;
                float o0[4] = {0.f, 0.f, 0.f, 0.f}, o1[4] = {0.f, 0.f, 0.f, 0.f}, sm[4] = {0.f, 0.f, 0.f, 0.f};
                mma1688(sm, one, one, b4);
                mma1688(o0, vm[0], vm[1], b4);
                mma1688(o1, vm[2], vm[3], b4);
                mma16816(sm, one, one, one, one, b0, b1);
                mma16816(o0, va[0][0], va[0][1], va[0][2], va[0][3], b0, b1);
                mma16816(o1, va[2][0], va[2][1], va[2][2], va[2][3], b0, b1);
                mma16816(sm, one, one, one, one, b2, b3);
                mma16816(o0, va[1][0], va[1][1], va[1][2], va[1][3], b2, b3);
                mma16816(o1, va[3][0], va[3][1], va[3][2], va[3][3], b2, b3);
                float i0, i1;
                asm("rcp.approx.ftz.f32 %0, %1;" : "=f"(i0) : "f"(sm[0]));
                asm("rcp.approx.ftz.f32 %0, %1;" : "=f"(i1) : "f"(sm[1]));
                stsm4t(oa + C_OB, pack2(o0[0] * i0, o0[1] * i1), pack2(o0[2] * i0, o0[3] * i1),
                       pack2(o1[0] * i0, o1[1] * i1), pack2(o1[2] * i0, o1[3] * i1));
            }
            __syncthreads();
            uint32_t ob[4][4];
#pragma unroll
            for (int i = 0; i < 4; i++) ldsm4(ob[i], lm + C_OB + i * 64);
            if (three) {
#pragma unroll
                for (int i = 0; i < 8; i++) lds128(wc[i], W2A(8 + i));
                project(wb, ob, 1);
                project(wo0, ob, 0);
                project(wc, ob, 2);
            } else {
                project(wb, ob, 1);
                project(wo0, ob, 0);
            }
        }
        __syncthreads();
        uint32_t eo = (128 + (s + 1) * 4 + (w >> 1)) * 8192 + (((s < 31 ? msel0 : msel1) >> ((s + 1) & 31)) & 1) * 4096 + (w & 1) * 2048 + lane * 8;
        uint64_t d[8];
        if (r == 0) {
            if (w >= 6) {
                auto mid = [&]() {
                    bar_sync(2, 64);
                    mbar_wait_u(bar_go, s & 1);
                    eo = delayed<DLY0A>(eo, self);
                    fetch_state(d, (const char*)g_x + eo);
                };
                ATTEND(2, s, mid);
                stage_w1();
            } else {
                if (w < 3 && s + PFD < NSEG) {
                    const bf16* p = g_kv + (size_t)((s + PFD) * 32 + fresh(lane)) * PW + w * HD + h * 128;
                    asm volatile("prefetch.global.L2 [%0];\nprefetch.global.L2 [%0 + 128];" ::"l"(p) : "memory");
                }
                stage_w1();
                if (w == 5) {
                    chores(s);
                    if (h == 0) asm volatile("st.relaxed.gpu.global.u32 [%0], %1;" ::"l"(g_flag + 98), "r"(s + 1) : "memory");
                }
                mbar_wait_u(bar_go, s & 1);
                if (w < 4) eo = delayed<DLY0>(eo, self); else eo = delayed<DLY0B>(eo, self);
                fetch_state(d, (const char*)g_x + eo);
            }
        } else {
            const int j = 2 * h + r - 1;
            if (w < 4) {
                const int l = fresh(lane), g = l >> 2, t = l & 3;
                const char* src = (const char*)g_x + delayed<DLY3>((j * 2 + (w >> 1)) * 8192 + (psel & 64) * 64 + (w & 1) * 2048 + t * 64 + g * 8, self);
                const char* dst = (const char*)g_x + pin((128 + (s + 1) * 4 + (j >> 4)) * 8192 + (j & 15) * 256 + w * 64 + (t & 1) * 4096 + g * 8);
                const uint64_t v = poll_sum(src, tag, (lane & 4) ? 0x3f800000u : 0x00003f80u);
                asm volatile("st.relaxed.gpu.global.b64 [%0], %1;" ::"l"(dst), "l"(v) : "memory");
                asm volatile("bar.arrive 1, 256;" ::: "memory");
                stage_w1();
                eo = delayed<DLY1>(eo, self);
                fetch_state(d, (const char*)g_x + eo);
            } else if (w == 7) {
                auto mid = [&]() {
                    bar_sync(1, 256);
                    eo = delayed<DLY1B>(eo, self);
                    fetch_state(d, (const char*)g_x + eo);
                };
                ATTEND(1, s, mid);
                stage_w1();
            } else {
                if (w >= 5 && s + 3 < NSEG)
                    asm volatile("prefetch.global.L2 [%0];" ::"l"(g_x + (128 + (s + 3) * 4 + (j >> 4)) * 1024 + (w & 1) * 512 + (j & 15) * 32 + lane) : "memory");
                stage_w1();
                if (w == 5) chores(s);
                bar_sync(1, 256);
                if (w == 4 && r == 1)
                    asm volatile("{\n.reg .pred p;\n.reg .u32 a;\nelect.sync _|p, -1;\nmapa.shared::cluster.u32 a, %0, %1;\n"
                                 "@p mbarrier.arrive.relaxed.cluster.shared::cluster.b64 _, [a];\n}" ::"r"(bar_go), "r"((h % (CLS / 3)) * 3) : "memory");
                eo = delayed<DLY1A>(eo, self);
                fetch_state(d, (const char*)g_x + eo);
            }
        }
        if (w == 7) load_kv(s + 1);
        settle_state(d, (const char*)g_x + eo);
#pragma unroll
        for (int i = 0; i < 8; i++) { bm[i].x = (uint32_t)d[i]; bm[i].y = (uint32_t)(d[i] >> 32); }
    }
    mbar_wait_u(bar_x, (NSEG - 1) & 1);
    if (attends) {
        auto nothing = []() {};
        load_q(NSEG - 1);
        if (r == 0) { ATTEND(2, NSEG - 1, nothing); bar_sync(2, 64); } else { ATTEND(1, NSEG - 1, nothing); __syncwarp(); }
        if (w == 7) report(1);
    }
}

constexpr int S4_US = 4368;
constexpr int S4_RS = 8848;
constexpr int S4_KS = 1296;
constexpr int S4_U = 0, S4_R = 16 * S4_US, S4_K = S4_R + 16 * S4_RS;
constexpr int S4_SMEM = S4_K + 16 * S4_KS;
constexpr int S4_SIG = 3104, S4_PK = 2 * S4_SIG;

struct cf { float r, i; };
__device__ __forceinline__ cf cmul(cf a, cf b) { return {fmaf(a.r, b.r, -a.i * b.i), fmaf(a.r, b.i, a.i * b.r)}; }
__device__ __forceinline__ cf cmulc(cf a, cf b) { return {fmaf(a.r, b.r, a.i * b.i), fmaf(a.i, b.r, -a.r * b.i)}; }
__device__ __forceinline__ cf csq(cf a) { const float t = a.r * a.i; return {fmaf(a.r, a.r, -a.i * a.i), t + t}; }
__device__ __forceinline__ cf cexp(float l2, float turns) {
    const float mag = ex2(l2), fr = (turns - rintf(turns)) * 6.283185307179586f;
    return {mag * __cosf(fr), mag * __sinf(fr)};
}
__device__ __forceinline__ void sts32(uint32_t a, uint32_t v) { asm volatile("st.shared.u32 [%0], %1;" ::"r"(a), "r"(v) : "memory"); }
__device__ __forceinline__ uint32_t lds16(uint32_t a) {
    uint32_t v;
    asm volatile("ld.shared.u16 %0, [%1];" : "=r"(v) : "r"(a) : "memory");
    return v;
}

template <int M0, int NQ>
__device__ __forceinline__ void s4_class(float (&acc)[16][4], uint32_t sig, uint32_t taps, int x0) {
    constexpr int D0 = M0 / 8, D1 = M0 == 32 ? 9 : 15;
    uint32_t R[D1 - D0 + 2];
#pragma unroll
    for (int D = D0 - 1; D <= D1; D++) {
        if (D < D0 || 8 * D - 7 >= 2 * M0) { R[D - D0 + 1] = 0; continue; }
        const int m = 8 * D + x0;
        uint32_t lo = lds16(taps + m * (2 * NQ)), hi = lds16(taps + (m - 1) * (2 * NQ));
        if (D == D0) { lo = m >= M0 ? lo : 0; hi = m > M0 ? hi : 0; }
        if (D == 2 * D0) { lo = m < 2 * M0 ? lo : 0; hi = m <= 2 * M0 ? hi : 0; }
        R[D - D0 + 1] = lo | (hi << 16);
    }
#pragma unroll
    for (int J = 0; 2 * J + D0 < 16; J++) {
        uint32_t a[4];
        ldsm4t(a, sig + J * 512);
#pragma unroll
        for (int D = D0; D <= D1; D++)
            if (2 * J + D < 16) mma16816(acc[2 * J + D], a[0], a[1], a[2], a[3], R[D - D0 + 1], R[D - D0]);
    }
}

__global__ void __launch_bounds__(512, 1)
k_s4(const bf16* __restrict__ u, const bf16* __restrict__ Are, const bf16* __restrict__ Aim, const bf16* __restrict__ Bre,
     const bf16* __restrict__ Bim, const bf16* __restrict__ Cre, const bf16* __restrict__ Cim, const bf16* __restrict__ logdt,
     const bf16* __restrict__ Dsk, bf16* __restrict__ out) {
    extern __shared__ __align__(16) uint8_t smem_s4[];
    const uint32_t sb = smem_u32(smem_s4);
    asm volatile("griddepcontrol.launch_dependents;");
    const int tid = threadIdx.x, w = __shfl_sync(~0u, tid >> 5, 0), lane = tid & 31, g = lane >> 2, t = lane & 3;
    const int dw = (w & 1) + ((w >> 1) & 3) * 4 + (w >> 3) * 2;
    uint2 ar, ai, br, bi, cr, ci;
    bf16 ldt;
    auto load_params = [&](int item) {
        const int d = item * 16 + dw, o = d * 128 + lane * 4;
        ar = __ldg((const uint2*)(Are + o)); ai = __ldg((const uint2*)(Aim + o)); br = __ldg((const uint2*)(Bre + o));
        bi = __ldg((const uint2*)(Bim + o)); cr = __ldg((const uint2*)(Cre + o)); ci = __ldg((const uint2*)(Cim + o));
        ldt = logdt[d];
    };
    load_params(blockIdx.x);
#pragma unroll 1
    for (int item = blockIdx.x; item < 64; item += gridDim.x) {
    const int d0 = item * 16;
    const uint32_t tr_off = (lane & 15), tr_l = (lane >> 4) * 16;
    const uint32_t ur = sb + S4_U + w * S4_US, rs = sb + S4_R + w * S4_RS, kd = sb + S4_K + w * S4_KS;
    if (lane < 16) sts128(ur + lane * 16, 0, 0, 0, 0);
    {
        const float dt = bf_round(expf(__bfloat162float(ldt)));
        const bf16* src = u + (size_t)(w * 128 + g) * DM + d0 + 4 * t;
        float T[5][4];
#pragma unroll
        for (int i = 0; i < 5; i++) T[i][0] = T[i][1] = T[i][2] = T[i][3] = 0.f;
        float klast = 0.f;
        const uint32_t wr_ = rs + lane * 272, rd_ = rs + t * 544 + g * 16;
#pragma unroll 1
        for (int c = 0; c < 4; c++) {
            uint2 v[4];
#pragma unroll
            for (int i = 0; i < 4; i++) v[i] = __ldg((const uint2*)(src + (size_t)(c * 32 + i * 8) * DM));
            auto pick = [&](const uint2& x) { const uint32_t y = c < 2 ? x.x : x.y; return (c & 1) ? bf_hi(y) : bf_lo(y); };
            auto pk2 = [](cf x) { return pack2(x.r, x.i); };
            const float l2 = dt * pick(ar) * 1.4426950408889634f, tu = dt * pick(ai) * 0.15915494309189535f;
            const cf z1 = cexp(l2, tu), z2 = csq(z1), z4 = csq(z2), z8 = csq(z4);
            const cf z64 = cexp(l2 * 64.f, tu * 64.f), z128 = csq(z64), z256 = csq(z128), z512 = csq(z256);
            cf a0 = {1.f, 0.f}, a1 = z64;
            cf b0 = cmul({pick(cr), pick(ci)}, {dt * pick(br), dt * pick(bi)});
            b0.i = -b0.i;
            cf b1 = cmulc(b0, z128), b2 = cmulc(b0, z256), y3 = cmulc(b0, z512), b4 = cmulc(y3, z512), b3 = y3;
            const cf y2 = cmulc(b2, z128);
#pragma unroll
            for (int i = 0; i < 8; i++) {
                sts128(wr_ + i * 16, pk2(a0), pk2(a1), pk2(b0), pk2(b1));
                sts128(wr_ + i * 16 + 128, pk2(b2), pk2(b3), pk2(b4), 0);
                b4 = cmulc(b4, z128);
                if (i < 7) {
                    a0 = i == 0 ? z8 : cmul(a0, z8); a1 = cmul(a1, z8);
                    b0 = cmulc(b0, z1); b1 = cmulc(b1, z1);
                    b2 = i == 3 ? y2 : cmulc(b2, z2);
                    if (i & 1) { y3 = cmulc(y3, z128); b3 = y3; } else b3 = cmulc(y3, z4);
                }
            }
            klast += b4.r;
            __syncwarp();
#pragma unroll
            for (int k = 0; k < 8; k++) {
                uint32_t x[4], y[4];
                lds128(x, rd_ + (8 * (k >> 1) + (k & 1)) * 272);
                lds128(y, rd_ + (8 * (k >> 1) + (k & 1)) * 272 + 128);
                mma1688(T[0], x[0], x[1], x[2]);
                mma1688(T[1], x[0], x[1], x[3]);
                mma1688(T[2], x[0], x[1], y[0]);
                mma1688(T[3], x[0], x[1], y[1]);
                mma1688(T[4], x[0], x[1], y[2]);
            }
#pragma unroll
            for (int i = 0; i < 2; i++)
                stsm4t(sb + S4_U + tr_off * S4_US + 256 + (w * 128 + c * 32 + i * 16) * 2 + tr_l, v[2 * i].x, v[2 * i].y, v[2 * i + 1].x, v[2 * i + 1].y);
            __syncwarp();
        }
#pragma unroll
        for (int o2 = 16; o2; o2 >>= 1) klast += __shfl_xor_sync(~0u, klast, o2);
#pragma unroll
        for (int hh = 0; hh < 2; hh++) {
            const int i = g + 8 * hh;
            sts32(kd + (8 * i + 2 * t) * 2, pack2(T[0][2 * hh], T[0][2 * hh + 1]));
            sts32(kd + (128 + 8 * i + 2 * t) * 2, pack2(T[1][2 * hh], T[1][2 * hh + 1]));
            sts32(kd + (256 + 4 * i + 2 * (t & 1) + 64 * (t >> 1)) * 2, pack2(T[2][2 * hh], T[2][2 * hh + 1]));
            sts32(kd + (384 + 2 * i + 32 * t) * 2, pack2(T[3][2 * hh], T[3][2 * hh + 1]));
        }
        asm volatile("stmatrix.sync.aligned.m8n8.x2.trans.shared.b16 [%0], {%1,%2};"
                     ::"r"(kd + 1024 + (lane & 7) * 32 + ((lane >> 3) & 1) * 16), "r"(pack2(T[4][0], T[4][1])), "r"(pack2(T[4][2], T[4][3])) : "memory");
        if (lane == 0) sts32(kd + 1280, pack2(klast, 0.f));
    }
    __syncwarp();
    const uint32_t pk = rs + S4_PK + 64;
    {
#pragma unroll
        for (int i = 0; i < 2; i++) {
            const int x = i * 128 + lane * 4;
            const uint2 c = lds64(kd + x * 2);
            uint32_t p = lds16(kd + x * 2 - 2);
            if (x == 0) p = 0;
            sts128(pk + x * 4, __byte_perm(c.x, p, 0x5410), __byte_perm(c.x, 0, 0x1032), __byte_perm(c.y, c.x, 0x7610), __byte_perm(c.y, 0, 0x1032));
        }
#pragma unroll
        for (int i = 2; i < 4; i++) {
            const int x = i * 128 + lane * 4;
            const uint32_t ab = lds32(kd + 256 + x), c = lds16(kd + 256 + x + 4);
            const uint32_t p = x == 256 ? lds16(kd + 510) : ab;
            sts128(pk + x * 4, __byte_perm(ab, p, 0x5410), __byte_perm(ab, 0, 0x1010), __byte_perm(ab, 0, 0x1032), __byte_perm(c, ab, 0x7610));
        }
        const uint32_t v = lds16(kd + 768), v2 = lds16(kd + 1024);
        if (lane < 24) {
            uint32_t x0 = 0, x1 = 0, x2 = 0, x3 = 0;
            if (lane == 0) { x0 = x1 = x2 = v | (v << 16); x3 = v << 16; }
            if (lane == 12) x3 = v2;
            if (lane == 13) { x0 = v2 | (v2 << 16); x1 = v2 << 16; }
            sts128(lane < 20 ? pk + 2048 + lane * 16 : pk - 64 + (lane - 20) * 16, x0, x1, x2, x3);
        }
        if (lane < 4) sts128(rs + (lane >> 1) * S4_SIG + (lane & 1) * 16, 0, 0, 0, 0);
    }
    __syncthreads();
    float acc[16][4];
#pragma unroll
    for (int i = 0; i < 16; i++) acc[i][0] = acc[i][1] = acc[i][2] = acc[i][3] = 0.f;
    const uint32_t lf = (lane & 7) * 32 + ((lane >> 3) & 1) * 16 + (lane >> 4) * 256;
#pragma unroll 1
    for (int ph = 0; ph < 2; ph++) {
    if (((w >> 2) ^ ph) & 1) {
#pragma unroll
    for (int rg = 3; rg >= 2; rg--) {
#pragma unroll 1
        for (int it = 0; it < (rg == 3 ? 4 : 6); it++) {
            const int n = it * 32 + lane;
            uint32_t x[2][4];
            lds128(x[0], ur + 256 + n * 16 - 16);
            lds128(x[1], ur + 256 + n * 16);
            float e[16], p[15], s[11];
#pragma unroll
            for (int i = 0; i < 8; i++) { e[2 * i] = bf_lo(x[i >> 2][i & 3]); e[2 * i + 1] = bf_hi(x[i >> 2][i & 3]); }
#pragma unroll
            for (int i = 0; i < 15; i++) p[i] = e[i] + e[i + 1];
#pragma unroll
            for (int i = 0; i < 11; i++) s[i] = p[i + 3] + e[i + 5];
            const uint32_t o = rs + 16 + n * 16;
            if (rg == 2) sts128(o, pack2(s[0], s[1]), pack2(s[2], s[3]), pack2(s[4], s[5]), pack2(s[6], s[7]));
#pragma unroll
            for (int i = 0; i < 10; i++) s[i] = p[i + 2] + s[i + 1];
            if (rg == 2) {
                sts64(o + S4_SIG + 8, pack2(s[0], s[1]), pack2(s[2], s[3]));
                sts64(o + S4_SIG + 16, pack2(s[4], s[5]), pack2(s[6], s[7]));
            } else {
#pragma unroll
                for (int i = 0; i < 9; i++) s[i] = p[i + 1] + s[i + 1];
                sts64(o + 8, pack2(s[0], s[1]), pack2(s[2], s[3]));
                sts64(o + 16, pack2(s[4], s[5]), pack2(s[6], s[7]));
#pragma unroll
                for (int i = 0; i < 8; i++) s[i] = p[i] + s[i + 1];
                sts64(o + S4_SIG + 8, pack2(s[0], s[1]), pack2(s[2], s[3]));
                sts64(o + S4_SIG + 16, pack2(s[4], s[5]), pack2(s[6], s[7]));
            }
        }
        __syncwarp();
        if (rg == 3) {
#pragma unroll 1
            for (int q = 1; q <= 2; q++) s4_class<64, 2>(acc, rs + lf + (q == 1 ? 16 : S4_SIG), kd + (384 + q) * 2, g - 2 * t);
        } else {
#pragma unroll 1
            for (int q = 1; q <= 4; q++) s4_class<32, 4>(acc, rs + lf + ((q & 1) ? 0 : S4_SIG) + (q < 3 ? 16 : 0), kd + (256 + q) * 2, g - 2 * t);
        }
        __syncwarp();
    }
    } else
    {
        const uint32_t ub = ur + 256 + lf, kb = pk + (g - 2 * t) * 4;
#pragma unroll 1
        for (int j0 = 0; j0 < 8; j0++) {
            uint32_t B[8][4];
#pragma unroll
            for (int i = 0; i < 8; i++) ldsm4(B[i], ub + i * 512 - j0 * 32);
            auto block = [&](int J, uint32_t a) {
                const uint32_t r0 = lds32(a), rp = lds32(a + 32), rm = lds32(a - 32);
                uint32_t r3;
                asm volatile("ld.volatile.shared.u32 %0, [%1];" : "=r"(r3) : "r"(a) : "memory");
#pragma unroll
                for (int I = J; I < 16; I++)
                    mma16816(acc[I], r0, rp, rm, r3, B[(I - J) >> 1][((I - J) & 1) * 2], B[(I - J) >> 1][((I - J) & 1) * 2 + 1]);
            };
#pragma unroll
            for (int J = 0; J < 4; J++) block(J, kb + j0 * 64 + J * 512);
            if (j0 < 2) { block(4, kb + j0 * 64 + 2048); block(8, kb + j0 * 64 + (544 + 16) * 4); }
        }
    }
    }
    {
        __syncwarp();
#pragma unroll
        for (int i = 0; i < 8; i++)
            stsm4t(rs + lf + i * 512, pack2(acc[2 * i][0], acc[2 * i][1]), pack2(acc[2 * i][2], acc[2 * i][3]),
                   pack2(acc[2 * i + 1][0], acc[2 * i + 1][1]), pack2(acc[2 * i + 1][2], acc[2 * i + 1][3]));
    }
    __syncthreads();
    {
        const uint2 dv = __ldg((const uint2*)(Dsk + d0 + 4 * t));
        load_params(min(item + (int)gridDim.x, 63));
        bf16* dst = out + (size_t)(w * 128 + g) * 2048 + 1024 + d0 + 4 * t;
        uint32_t o[8][4];
#pragma unroll
        for (int i = 0; i < 8; i++) {
            uint32_t y[4], x[4];
            ldsm4t(y, sb + S4_R + tr_off * S4_RS + (w * 128 + i * 16) * 2 + tr_l);
            ldsm4t(x, sb + S4_U + tr_off * S4_US + 256 + (w * 128 + i * 16) * 2 + tr_l);
#pragma unroll
            for (int j = 0; j < 4; j++)
                asm("{\n.reg .b32 s;\nmul.rn.bf16x2 s, %2, %3;\nadd.rn.bf16x2 %0, %1, s;\n}" : "=r"(o[i][j]) : "r"(y[j]), "r"(x[j]), "r"((j & 1) ? dv.y : dv.x));
        }
        __syncthreads();
#pragma unroll
        for (int i = 0; i < 8; i++) {
            *reinterpret_cast<uint2*>(dst + (size_t)(i * 16) * 2048) = make_uint2(o[i][0], o[i][1]);
            *reinterpret_cast<uint2*>(dst + (size_t)(i * 16 + 8) * 2048) = make_uint2(o[i][2], o[i][3]);
        }
    }
    }
}

enum { IT_W256 = 1, IT_W128 = 2, IT_W64 = 3, IT_END = 7 };
struct BgParams { CUtensorMap mo, mo2, mwo4, mwo2, mwo1; };
#define P256 56
#define P128 62
struct Sched { uint32_t w0, w1; };
__device__ __forceinline__ int next_item(Sched& z) {
    if (z.w0 >= z.w1) {
        uint32_t prog;
        asm volatile("ld.relaxed.gpu.global.u32 %0, [%1];" : "=r"(prog) : "l"(g_flag + 98) : "memory");
        const uint32_t k = prog <= P256 ? 4 : prog <= P128 ? 2 : 1;
        z.w0 = 4 * gridDim.x + atomicAdd(g_flag + 97, k);
        z.w1 = min(z.w0 + k, NBT * 16u);
        if (z.w0 >= z.w1) return IT_END;
    }
    const uint32_t i = z.w0, k = z.w1 - i >= 4 && !(i & 3) ? 4 : z.w1 - i >= 2 && !(i & 1) ? 2 : 1;
    z.w0 += k;
    return (k == 4 ? IT_W256 : k == 2 ? IT_W128 : IT_W64) | (i >> 4) << 3 | ((i & 15) / k) << 7;
}
constexpr int B_OST = NSTAGE * STAGE_BYTES + 1024;
constexpr int BG_SMEM = B_OST + 32768;

template <int BM, int BN, int KPS, typename ACC>
__device__ __forceinline__ void gemm_mainloop(ACC& acc, const GemmSmem& g, int cw, int rounds, uint32_t& round) {
#pragma unroll
    for (int i = 0; i < BN / 2; i++) acc[i] = 0.f;
#pragma unroll 1
    for (int k0 = 0; k0 < rounds; k0++, round++) {
#pragma unroll
        for (int s = 0; s < 4; s++) {
            mbar_wait_u(g.full + 8 * s, round & 1);
            gemm_stage<BM, BN, KPS>(acc, g.st + s * STAGE_BYTES, cw, false);
            wg_wait<1>();
            if (s > 0 || k0 > 0) mbar_arrive_one(g.empty + 8 * ((s + 3) & 3), threadIdx.x & 31);
        }
    }
    wg_wait<0>();
    mbar_arrive_one(g.empty + 8 * 3, threadIdx.x & 31);
}

template <int BN>
__device__ __forceinline__ void store_tile(const float (&acc)[BN / 2], bf16* dst, int t) {
#pragma unroll
    for (int G = 0; G < BN / 32; G++)
#pragma unroll
        for (int rr = 0; rr < 2; rr++) {
            uint32_t r0 = pack2(acc[16 * G + 2 * rr], acc[16 * G + 2 * rr + 1]), r1 = pack2(acc[16 * G + 4 + 2 * rr], acc[16 * G + 5 + 2 * rr]);
            uint32_t r2 = pack2(acc[16 * G + 8 + 2 * rr], acc[16 * G + 9 + 2 * rr]), r3 = pack2(acc[16 * G + 12 + 2 * rr], acc[16 * G + 13 + 2 * rr]);
            quad_transpose(r0, r1, r2, r3, t);
            *reinterpret_cast<uint4*>(dst + (size_t)rr * 8 * 2048 + G * 32) = make_uint4(r0, r1, r2, r3);
        }
}

template <int BN, int KPS>
__device__ __forceinline__ void wo_item(const GemmSmem& g, int cw, uint32_t& round, bf16* dst, int t) {
    float acc[BN / 2];
    gemm_mainloop<128, BN, KPS>(acc, g, cw, 16 / KPS, round);
    store_tile<BN>(acc, dst, t);
}

__global__ void __launch_bounds__(384, 1) k_bg(const __grid_constant__ BgParams P, bf16* __restrict__ out) {
    extern __shared__ __align__(1024) uint8_t smem_gemm[];
    asm volatile("griddepcontrol.launch_dependents;");
    const uint32_t bar_item = smem_u32(smem_gemm) + NSTAGE * STAGE_BYTES + 128, slot = bar_item + 16;
    if (threadIdx.x == 0) { mbar_init(bar_item, 1); mbar_init(bar_item + 8, 1); }
    if (threadIdx.x == 32) asm volatile("prefetch.tensormap [%0];\nprefetch.tensormap [%1];" ::"l"(&P.mo), "l"(&P.mwo4) : "memory");
    GemmSmem g = gemm_setup(smem_gemm, 8);
    const int wg = __shfl_sync(~0u, threadIdx.x >> 7, 0);
    if (wg == 0) {
        asm volatile("setmaxnreg.dec.sync.aligned.u32 40;");
        if (threadIdx.x == 0) {
            uint32_t it = 0;
            Sched z = {4 * blockIdx.x, 4 * blockIdx.x + 4};
            wait_flag(g_flag + 64, 96);
            asm volatile("fence.proxy.async.global;" ::: "memory");
            for (int n = 0;; n++) {
                const int code = next_item(z);
                sts32(slot + (n & 1) * 4, code);
                mbar_arrive(bar_item + (n & 1) * 8);
                const int type = code & 7, blk = (code >> 3) & 15, idx = code >> 7;
                if (type == IT_END) break;
                for (int k = 0; k < (type == IT_W64 ? 32 : 64); k++, it++) {
                    const int s = it & 3;
                    const uint32_t st = g.st + s * STAGE_BYTES, fb = g.full + 8 * s;
                    mbar_wait(g.empty + 8 * s, ((it >> 2) & 1) ^ 1);
                    mbar_expect_tx(fb, type == IT_W128 ? 32768 : 49152);
                    if (type == IT_W64) {
                        tma3d(st, &P.mo2, 0, blk * 128, k * 2, fb);
                        tma3d(st + 32768, &P.mwo1, 0, k * 128, idx, fb);
                    } else {
                        tma2d(st, &P.mo, k * 64, blk * 128, fb);
                        tma3d(st + 16384, type == IT_W256 ? &P.mwo4 : &P.mwo2, 0, k * 64, idx * (type == IT_W256 ? 4 : 2), fb);
                    }
                }
            }
        }
    } else {
        asm volatile("setmaxnreg.inc.sync.aligned.u32 232;");
        const int cw = wg - 1, lane = threadIdx.x & 31;
        uint32_t round = 0;
#pragma unroll 1
        for (int n = 0;; n++) {
            mbar_wait_u(bar_item + (n & 1) * 8, (n >> 1) & 1);
            const int code = __shfl_sync(~0u, lds32(slot + (n & 1) * 4), 0);
            const int type = code & 7, blk = (code >> 3) & 15, idx = (code >> 7) & 31;
            if (type == IT_END) break;
            bf16* dst = out + (size_t)(blk * 128 + cw * 64 + ((threadIdx.x >> 5) & 3) * 16 + (lane >> 2)) * 2048 + (lane & 3) * 8;
            if (type == IT_W256) wo_item<256, 1>(g, cw, round, dst + idx * 256, lane & 3);
            else if (type == IT_W128) wo_item<128, 1>(g, cw, round, dst + idx * 128, lane & 3);
            else wo_item<64, 2>(g, cw, round, dst + idx * 64, lane & 3);
        }
    }
}

static_assert(NBT == 10, "k_tail covers blocks 10..15");
__global__ void __cluster_dims__(6, 1, 1) __launch_bounds__(384, 1)
k_tail(const __grid_constant__ BgParams P, bf16* __restrict__ out) {
    extern __shared__ __align__(1024) uint8_t smem_gemm[];
    const int cl = blockIdx.x / 6, rank = blockIdx.x - 6 * cl, half = rank & 1, pr = rank >> 1;
    const int blk = NBT + (cl >> 3) * 3 + pr, idx = cl & 7;
    const uint32_t st = smem_u32(smem_gemm), full = st + 6 * 32768, empty = full + 64, emptyb = full + 128, bar_s = full + 192;
    if (threadIdx.x == 0) {
        for (int s = 0; s < 6; s++) { mbar_init(full + 8 * s, 1); mbar_init(empty + 8 * s, 2); mbar_init(emptyb + 8 * s, 6); }
        mbar_init(bar_s, 1); mbar_expect_tx(bar_s, 32768);
        asm volatile("fence.mbarrier_init.release.cluster;\nfence.proxy.async.shared::cta;" ::: "memory");
    }
    if (threadIdx.x == 32) asm volatile("prefetch.tensormap [%0];\nprefetch.tensormap [%1];" ::"l"(&P.mo), "l"(&P.mwo2) : "memory");
    __syncthreads();
    asm volatile("barrier.cluster.arrive.relaxed.aligned;\nbarrier.cluster.wait.aligned;" ::: "memory");
    const int wg = __shfl_sync(~0u, threadIdx.x >> 7, 0);
    if (wg == 0) {
        if (threadIdx.x == 0) {
            wait_flag(g_flag + 65, 96);
            asm volatile("fence.proxy.async.global;" ::: "memory");
            if (blockIdx.x == 95)
                for (int i = 0; i < 4; i++) reinterpret_cast<uint4*>(g_flag)[i] = make_uint4(0, 0, 0, 0);
            for (int k = 0, s = 0, ph = 1; k < 32; k++) {
                mbar_wait(empty + 8 * s, ph);
                mbar_expect_tx(full + 8 * s, 32768);
                tma2d(st + s * 32768, &P.mo, (half * 32 + k) * 64, blk * 128, full + 8 * s);
                if (++s == 6) { s = 0; ph ^= 1; }
            }
        } else if (threadIdx.x == 32) {
            for (int k = pr, s = pr, ph = 1; k < 32; k += 3) {
                mbar_wait(emptyb + 8 * s, ph);
                asm volatile("cp.async.bulk.tensor.3d.shared::cluster.global.mbarrier::complete_tx::bytes.multicast::cluster "
                             "[%0], [%1, {%3, %4, %5}], [%2], %6;"
                             ::"r"(st + s * 32768 + 16384), "l"(&P.mwo2), "r"(full + 8 * s), "r"(0), "r"((half * 32 + k) * 64), "r"(idx * 2),
                               "h"((uint16_t)(0x15 << half)) : "memory");
                s += 3;
                if (s >= 6) { s -= 6; ph ^= 1; }
            }
        }
    } else {
        const int cw = wg - 1, lane = threadIdx.x & 31, t = lane & 3;
        float acc[64], fin[32];
#pragma unroll
        for (int i = 0; i < 64; i++) acc[i] = 0.f;
#pragma unroll 1
        for (int k = 0, s = 0, ph = 0, sp = 0; k < 32; k++) {
            mbar_wait_u(full + 8 * s, ph);
            gemm_stage<128, 128, 1>(acc, st + s * 32768, cw, false);
            wg_wait<1>();
            if (k > 0 && k <= 26)
                asm volatile("{\n.reg .pred p;\n.reg .u32 a;\nsetp.eq.u32 p, %3, 0;\nmapa.shared::cluster.u32 a, %1, %2;\n"
                             "@p mbarrier.arrive.relaxed.cta.shared::cta.b64 _, [%0];\n@p mbarrier.arrive.relaxed.cluster.shared::cluster.b64 _, [a];\n}"
                             ::"r"(empty + 8 * sp), "r"(emptyb + 8 * sp), "r"((sp >= 3 ? sp - 3 : sp) * 2 + half), "r"(threadIdx.x & 127) : "memory");
            sp = s;
            if (++s == 6) { s = 0; ph ^= 1; }
        }
        wg_wait<0>();
        const uint32_t xa = st + B_OST + (threadIdx.x - 128) * 16;
        uint32_t ra, rb;
        asm("mapa.shared::cluster.u32 %0, %1, %2;" : "=r"(ra) : "r"(xa), "r"(rank ^ 1));
        asm("mapa.shared::cluster.u32 %0, %1, %2;" : "=r"(rb) : "r"(bar_s), "r"(rank ^ 1));
#pragma unroll
        for (int i = 0; i < 8; i++) {
            float v[4];
#pragma unroll
            for (int j = 0; j < 4; j++) {
                v[j] = half ? acc[4 * i + j] : acc[32 + 4 * i + j];
                fin[4 * i + j] = half ? acc[32 + 4 * i + j] : acc[4 * i + j];
            }
            asm volatile("st.async.weak.shared::cluster.mbarrier::complete_tx::bytes.v4.f32 [%0], {%1,%2,%3,%4}, [%5];"
                         ::"r"(ra + i * 4096), "f"(v[0]), "f"(v[1]), "f"(v[2]), "f"(v[3]), "r"(rb) : "memory");
        }
        mbar_wait_u(bar_s, 0);
#pragma unroll
        for (int i = 0; i < 8; i++) {
            const float4 v = lds128f(xa + i * 4096);
            fin[4 * i] += v.x; fin[4 * i + 1] += v.y; fin[4 * i + 2] += v.z; fin[4 * i + 3] += v.w;
        }
        store_tile<64>(fin, out + (size_t)(blk * 128 + cw * 64 + ((threadIdx.x >> 5) & 3) * 16 + (lane >> 2)) * 2048 + idx * 128 + half * 64 + t * 8, t);
    }
}

typedef CUresult (*EncodeFn)(CUtensorMap*, CUtensorMapDataType, cuuint32_t, void*, const cuuint64_t*, const cuuint64_t*,
                             const cuuint32_t*, const cuuint32_t*, CUtensorMapInterleave, CUtensorMapSwizzle,
                             CUtensorMapL2promotion, CUtensorMapFloatOOBfill);

static void map2d(EncodeFn enc, CUtensorMap* m, const void* p, int rows, int cols, int box_rows) {
    cuuint64_t dim[2] = {(cuuint64_t)cols, (cuuint64_t)rows}, str[1] = {(cuuint64_t)cols * 2};
    cuuint32_t box[2] = {64, (cuuint32_t)box_rows}, es[2] = {1, 1};
    enc(m, CU_TENSOR_MAP_DATA_TYPE_BFLOAT16, 2, (void*)p, dim, str, box, es, CU_TENSOR_MAP_INTERLEAVE_NONE,
        CU_TENSOR_MAP_SWIZZLE_128B, CU_TENSOR_MAP_L2_PROMOTION_L2_256B, CU_TENSOR_MAP_FLOAT_OOB_FILL_NONE);
}
static void map3d(EncodeFn enc, CUtensorMap* m, const void* p, int rows, int cols, int box_rows, int nblk) {
    cuuint64_t dim[3] = {64, (cuuint64_t)rows, (cuuint64_t)cols / 64}, str[2] = {(cuuint64_t)cols * 2, 128};
    cuuint32_t box[3] = {64, (cuuint32_t)box_rows, (cuuint32_t)nblk}, es[3] = {1, 1, 1};
    enc(m, CU_TENSOR_MAP_DATA_TYPE_BFLOAT16, 3, (void*)p, dim, str, box, es, CU_TENSOR_MAP_INTERLEAVE_NONE,
        CU_TENSOR_MAP_SWIZZLE_128B, CU_TENSOR_MAP_L2_PROMOTION_L2_256B, CU_TENSOR_MAP_FLOAT_OOB_FILL_NONE);
}

#define USE_PDL 1

extern "C" void kernel_launch(void* const* d_in, const int* in_sizes, int n_in, void* d_out, int out_size) {
    const bf16 *x = (const bf16*)d_in[0], *mem0 = (const bf16*)d_in[1], *Wq = (const bf16*)d_in[2], *Wk = (const bf16*)d_in[3];
    const bf16 *Wv = (const bf16*)d_in[4], *Wo = (const bf16*)d_in[5];
    const bf16 *u = (const bf16*)d_in[7], *Are = (const bf16*)d_in[8], *Aim = (const bf16*)d_in[9], *Bre = (const bf16*)d_in[10];
    const bf16 *Bim = (const bf16*)d_in[11], *Cre = (const bf16*)d_in[12], *Cim = (const bf16*)d_in[13];
    const bf16 *logdt = (const bf16*)d_in[14], *Dsk = (const bf16*)d_in[15];
    bf16* out = (bf16*)d_out;

    void* fn = nullptr;
    cudaDriverEntryPointQueryResult qr;
    cudaGetDriverEntryPoint("cuTensorMapEncodeTiled", &fn, cudaEnableDefault, &qr);
    EncodeFn enc = (EncodeFn)fn;
    void *kv, *o;
    cudaGetSymbolAddress(&kv, g_kv);
    cudaGetSymbolAddress(&o, g_o);
    CUtensorMap mx, mwq, mwq1, mwk, mwv, mkv2;
    BgParams P;
    map2d(enc, &mx, x, SEQ, DM, 128);
    map2d(enc, &P.mo, o, SEQ, HD, 128);
    map3d(enc, &P.mo2, o, SEQ, HD, 128, 2);
    map3d(enc, &mwq, Wq, DM, HD, 64, 2);
    map3d(enc, &mwq1, Wq, DM, HD, 64, 1);
    map3d(enc, &mwk, Wk, DM, HD, 64, 2);
    map3d(enc, &mwv, Wv, DM, HD, 64, 2);
    map3d(enc, &P.mwo4, Wo, HD, DM, 64, 4);
    map3d(enc, &P.mwo2, Wo, HD, DM, 64, 2);
    map3d(enc, &P.mwo1, Wo, HD, DM, 128, 1);
    map3d(enc, &mkv2, kv, SEQ, PW, 32, 2);
    cudaFuncSetAttribute(k_kv, cudaFuncAttributeMaxDynamicSharedMemorySize, GEMM_SMEM);
    cudaFuncSetAttribute(k_bg, cudaFuncAttributeMaxDynamicSharedMemorySize, BG_SMEM);
    cudaFuncSetAttribute(k_tail, cudaFuncAttributeMaxDynamicSharedMemorySize, BG_SMEM);
    cudaFuncSetAttribute(k_chain, cudaFuncAttributeMaxDynamicSharedMemorySize, CHAIN_SMEM);
    cudaFuncSetAttribute(k_s4, cudaFuncAttributeMaxDynamicSharedMemorySize, S4_SMEM);

    cudaStream_t st = cudaStreamPerThread;
    cudaLaunchAttribute pdl[2], cls[1];
    pdl[0].id = cudaLaunchAttributeProgrammaticStreamSerialization;
    pdl[0].val.programmaticStreamSerializationAllowed = 1;
    cls[0].id = cudaLaunchAttributeClusterDimension;
    cls[0].val.clusterDim.x = CLS; cls[0].val.clusterDim.y = 1; cls[0].val.clusterDim.z = 1;
    cudaLaunchConfig_t cfg = {};
    cfg.stream = st; cfg.attrs = cls; cfg.numAttrs = 1;
    cfg.gridDim = dim3(96); cfg.blockDim = dim3(384); cfg.dynamicSmemBytes = GEMM_SMEM;
    cudaLaunchKernelEx(&cfg, k_kv, mx, mwk, mwv, mwq, mwq1, Wo, 0);
    pdl[1] = cls[0]; pdl[1].val.clusterDim.x = 2;
    cfg.attrs = pdl; cfg.numAttrs = 2;
    cfg.gridDim = dim3(36);
    cudaLaunchKernelEx(&cfg, k_kv, mx, mwk, mwv, mwq, mwq1, Wo, 96);
    cfg.numAttrs = 1;
    cfg.gridDim = dim3(96); cfg.blockDim = dim3(256); cfg.dynamicSmemBytes = CHAIN_SMEM;
    cudaLaunchKernelEx(&cfg, k_chain, mem0, Wq, Wk, Wv, Wo, mkv2);
    cfg.numAttrs = USE_PDL;
    cfg.gridDim = dim3(36); cfg.blockDim = dim3(512); cfg.dynamicSmemBytes = S4_SMEM;
    cudaLaunchKernelEx(&cfg, k_s4, u, Are, Aim, Bre, Bim, Cre, Cim, logdt, Dsk, out);
    cfg.gridDim = dim3(36); cfg.blockDim = dim3(384); cfg.dynamicSmemBytes = BG_SMEM;
    cudaLaunchKernelEx(&cfg, k_bg, P, out);
    cfg.gridDim = dim3(96);
    cudaLaunchKernelEx(&cfg, k_tail, P, out);
}
```
